```python
import torch

def _softmax(x, axis=-1):
    return torch.softmax(x, dim=axis)

def _gelu(x):
    return torch.nn.functional.gelu(x, approximate='tanh')

def _silu(x):
    return torch.nn.functional.silu(x)

def _sigmoid(x):
    return torch.sigmoid(x)

def _layernorm(x, axis=-1, eps=1e-05):
    m = x.mean(dim=axis, keepdim=True)
    v = x.var(dim=axis, keepdim=True, unbiased=False)
    return (x - m) / torch.sqrt(v + eps)

def _scatter_add(tgt, idx, src, axis=0):
    return tgt.clone().index_add_(axis, idx, src)

def _segment_sum(src, seg, n):
    out = torch.zeros((n,) + src.shape[1:], dtype=src.dtype)
    return out.index_add_(0, seg, src)

def _pad(x, pw):
    flat = tuple((v for pair in reversed(pw) for v in pair))
    return torch.nn.functional.pad(x, flat)
kernel_name = 'adaLN_cond__sliding_block_cached__dense_activation_silu__prompt'

def setup_inputs():

    _w = lambda a: (lambda t: t.to(torch.bfloat16) if t.is_floating_point() else t)(torch.as_tensor(a))

    def _A_setup():
        B, Sq, D = (1, 2048, 512)
        Hq, Hkv, Sk, Dh = (32, 8, 2048, 128)
        assert Hq % Hkv == 0, (Hq, Hkv)
        return {'x': _w((lambda *s: torch.randn(*s, dtype=torch.bfloat16) * 0.05)(B, Sq, D)), 'k_cache': _w((lambda *s: torch.randn(*s, dtype=torch.bfloat16) * 1.6)(B, Hkv, Sk, Dh)), 'v_cache': _w((lambda *s: torch.randn(*s, dtype=torch.bfloat16) * 0.8)(B, Hkv, Sk, Dh)), 'wq': _w((lambda *s: torch.randn(*s, dtype=torch.bfloat16) * 1.6)(D, Hq * Dh) * D ** (-0.5)), 'wo': _w((lambda *s: torch.randn(*s, dtype=torch.bfloat16) * 0.8)(Hq * Dh, D) * (Hq * Dh) ** (-0.5))}
    _A_in = _A_setup()

    def _B_setup():
        B, S, D, F = (1, 2048, 512, 1792)
        return {'x': _w((lambda *s: torch.randn(*s, dtype=torch.bfloat16) * 0.05)(B, S, D)), 'w1': _w((lambda *s: torch.randn(*s, dtype=torch.bfloat16) * 1.6)(D, F) * D ** (-0.5)), 'w2': _w((lambda *s: torch.randn(*s, dtype=torch.bfloat16) * 0.2)(F, D) * F ** (-0.5))}
    _B_in = _B_setup()
    return {'A_x': _A_in['x'], 'A_k_cache': _A_in['k_cache'], 'A_v_cache': _A_in['v_cache'], 'A_wq': _A_in['wq'], 'A_wo': _A_in['wo'], 'B_x': _B_in['x'], 'B_w1': _B_in['w1'], 'B_w2': _B_in['w2'], 'c': _w((lambda *s: torch.randn(*s, dtype=torch.bfloat16) * 0.1)(1, 512) * 8.0), 'w_mod': _w((lambda *s: torch.randn(*s, dtype=torch.bfloat16) * 0.1)(512, 6 * 512) * 512 ** (-0.5) * 8.0)}

def reference(A_x, A_k_cache, A_v_cache, A_wq, A_wo, B_x, B_w1, B_w2, c, w_mod):

    def _A_ref(x, k_cache, v_cache, wq, wo):
        B, Sq, D = x.shape
        Hq, Dh = (32, 128)
        Hkv, Sk = (k_cache.shape[1], k_cache.shape[2])
        W = min(4096, max(256, Sk // 4))
        rep = Hq // Hkv
        q = (lambda x, *d: x.permute(*d))((x @ wq).reshape(B, Sq, Hq, Dh), 0, 2, 1, 3)
        k = (lambda x, n, axis: torch.repeat_interleave(x, n, dim=axis))(k_cache[:, :, Sk - W:, :], rep, axis=1)
        v = (lambda x, n, axis: torch.repeat_interleave(x, n, dim=axis))(v_cache[:, :, Sk - W:, :], rep, axis=1)
        scores = torch.einsum('bhqd,bhkd->bhqk', q, k) * Dh ** (-0.5)
        p = _softmax(scores, axis=-1)
        o = torch.einsum('bhqk,bhkd->bhqd', p, v)
        return (lambda x, *d: x.permute(*d))(o, 0, 2, 1, 3).reshape(B, Sq, Hq * Dh) @ wo

    def _B_ref(x, w1, w2):
        h = torch.einsum('bsd,df->bsf', x, w1)
        h = _silu(h)
        out = torch.einsum('bsf,fd->bsd', h, w2)
        return out
    x = A_x
    mod = (_silu(c) @ w_mod).reshape(c.shape[0], 6, 1, -1)
    sa, ca, ga, sb, cb, gb = (mod[:, 0].clone(), mod[:, 1].clone(), mod[:, 2].clone(), mod[:, 3].clone(), mod[:, 4].clone(), mod[:, 5].clone())
    h = _layernorm(x, axis=-1) * (1 + ca) + sa
    x = x + ga * _A_ref(h, A_k_cache, A_v_cache, A_wq, A_wo)
    h = _layernorm(x, axis=-1) * (1 + cb) + sb
    x = x + gb * _B_ref(h, B_w1, B_w2)
    return x
```

```cpp
#include <cuda_runtime.h>
#include <cuda_bf16.h>
#include <cuda.h>
#include <stdint.h>

__device__ __forceinline__ void wgmma_rs_n128_tb0(float (&d)[64], const uint32_t (&a)[4], uint64_t db, int sd) {
  asm volatile("{\n.reg .pred p;\nsetp.ne.b32 p, %69, 0;\n"
    "wgmma.mma_async.sync.aligned.m64n128k16.f32.bf16.bf16 "
    "{%0,%1,%2,%3,%4,%5,%6,%7,%8,%9,%10,%11,%12,%13,%14,%15,"
    "%16,%17,%18,%19,%20,%21,%22,%23,%24,%25,%26,%27,%28,%29,%30,%31,"
    "%32,%33,%34,%35,%36,%37,%38,%39,%40,%41,%42,%43,%44,%45,%46,%47,"
    "%48,%49,%50,%51,%52,%53,%54,%55,%56,%57,%58,%59,%60,%61,%62,%63}, "
    "{%64,%65,%66,%67}, %68, p, 1, 1, 0;\n}\n"
    : "+f"(d[0]), "+f"(d[1]), "+f"(d[2]), "+f"(d[3]), "+f"(d[4]), "+f"(d[5]), "+f"(d[6]), "+f"(d[7]),
      "+f"(d[8]), "+f"(d[9]), "+f"(d[10]), "+f"(d[11]), "+f"(d[12]), "+f"(d[13]), "+f"(d[14]), "+f"(d[15]),
      "+f"(d[16]), "+f"(d[17]), "+f"(d[18]), "+f"(d[19]), "+f"(d[20]), "+f"(d[21]), "+f"(d[22]), "+f"(d[23]),
      "+f"(d[24]), "+f"(d[25]), "+f"(d[26]), "+f"(d[27]), "+f"(d[28]), "+f"(d[29]), "+f"(d[30]), "+f"(d[31]),
      "+f"(d[32]), "+f"(d[33]), "+f"(d[34]), "+f"(d[35]), "+f"(d[36]), "+f"(d[37]), "+f"(d[38]), "+f"(d[39]),
      "+f"(d[40]), "+f"(d[41]), "+f"(d[42]), "+f"(d[43]), "+f"(d[44]), "+f"(d[45]), "+f"(d[46]), "+f"(d[47]),
      "+f"(d[48]), "+f"(d[49]), "+f"(d[50]), "+f"(d[51]), "+f"(d[52]), "+f"(d[53]), "+f"(d[54]), "+f"(d[55]),
      "+f"(d[56]), "+f"(d[57]), "+f"(d[58]), "+f"(d[59]), "+f"(d[60]), "+f"(d[61]), "+f"(d[62]), "+f"(d[63])
    : "r"(a[0]), "r"(a[1]), "r"(a[2]), "r"(a[3]), "l"(db), "r"(sd));
}

__device__ __forceinline__ void wgmma_rs_n128_tb1(float (&d)[64], const uint32_t (&a)[4], uint64_t db, int sd) {
  asm volatile("{\n.reg .pred p;\nsetp.ne.b32 p, %69, 0;\n"
    "wgmma.mma_async.sync.aligned.m64n128k16.f32.bf16.bf16 "
    "{%0,%1,%2,%3,%4,%5,%6,%7,%8,%9,%10,%11,%12,%13,%14,%15,"
    "%16,%17,%18,%19,%20,%21,%22,%23,%24,%25,%26,%27,%28,%29,%30,%31,"
    "%32,%33,%34,%35,%36,%37,%38,%39,%40,%41,%42,%43,%44,%45,%46,%47,"
    "%48,%49,%50,%51,%52,%53,%54,%55,%56,%57,%58,%59,%60,%61,%62,%63}, "
    "{%64,%65,%66,%67}, %68, p, 1, 1, 1;\n}\n"
    : "+f"(d[0]), "+f"(d[1]), "+f"(d[2]), "+f"(d[3]), "+f"(d[4]), "+f"(d[5]), "+f"(d[6]), "+f"(d[7]),
      "+f"(d[8]), "+f"(d[9]), "+f"(d[10]), "+f"(d[11]), "+f"(d[12]), "+f"(d[13]), "+f"(d[14]), "+f"(d[15]),
      "+f"(d[16]), "+f"(d[17]), "+f"(d[18]), "+f"(d[19]), "+f"(d[20]), "+f"(d[21]), "+f"(d[22]), "+f"(d[23]),
      "+f"(d[24]), "+f"(d[25]), "+f"(d[26]), "+f"(d[27]), "+f"(d[28]), "+f"(d[29]), "+f"(d[30]), "+f"(d[31]),
      "+f"(d[32]), "+f"(d[33]), "+f"(d[34]), "+f"(d[35]), "+f"(d[36]), "+f"(d[37]), "+f"(d[38]), "+f"(d[39]),
      "+f"(d[40]), "+f"(d[41]), "+f"(d[42]), "+f"(d[43]), "+f"(d[44]), "+f"(d[45]), "+f"(d[46]), "+f"(d[47]),
      "+f"(d[48]), "+f"(d[49]), "+f"(d[50]), "+f"(d[51]), "+f"(d[52]), "+f"(d[53]), "+f"(d[54]), "+f"(d[55]),
      "+f"(d[56]), "+f"(d[57]), "+f"(d[58]), "+f"(d[59]), "+f"(d[60]), "+f"(d[61]), "+f"(d[62]), "+f"(d[63])
    : "r"(a[0]), "r"(a[1]), "r"(a[2]), "r"(a[3]), "l"(db), "r"(sd));
}

__device__ __forceinline__ void wgmma_rs_n224_tb1(float (&d)[112], const uint32_t (&a)[4], uint64_t db, int sd) {
  asm volatile("{\n.reg .pred p;\nsetp.ne.b32 p, %117, 0;\n"
    "wgmma.mma_async.sync.aligned.m64n224k16.f32.bf16.bf16 "
    "{%0,%1,%2,%3,%4,%5,%6,%7,%8,%9,%10,%11,%12,%13,%14,%15,"
    "%16,%17,%18,%19,%20,%21,%22,%23,%24,%25,%26,%27,%28,%29,%30,%31,"
    "%32,%33,%34,%35,%36,%37,%38,%39,%40,%41,%42,%43,%44,%45,%46,%47,"
    "%48,%49,%50,%51,%52,%53,%54,%55,%56,%57,%58,%59,%60,%61,%62,%63,"
    "%64,%65,%66,%67,%68,%69,%70,%71,%72,%73,%74,%75,%76,%77,%78,%79,"
    "%80,%81,%82,%83,%84,%85,%86,%87,%88,%89,%90,%91,%92,%93,%94,%95,"
    "%96,%97,%98,%99,%100,%101,%102,%103,%104,%105,%106,%107,%108,%109,%110,%111}, "
    "{%112,%113,%114,%115}, %116, p, 1, 1, 1;\n}\n"
    : "+f"(d[0]), "+f"(d[1]), "+f"(d[2]), "+f"(d[3]), "+f"(d[4]), "+f"(d[5]), "+f"(d[6]), "+f"(d[7]),
      "+f"(d[8]), "+f"(d[9]), "+f"(d[10]), "+f"(d[11]), "+f"(d[12]), "+f"(d[13]), "+f"(d[14]), "+f"(d[15]),
      "+f"(d[16]), "+f"(d[17]), "+f"(d[18]), "+f"(d[19]), "+f"(d[20]), "+f"(d[21]), "+f"(d[22]), "+f"(d[23]),
      "+f"(d[24]), "+f"(d[25]), "+f"(d[26]), "+f"(d[27]), "+f"(d[28]), "+f"(d[29]), "+f"(d[30]), "+f"(d[31]),
      "+f"(d[32]), "+f"(d[33]), "+f"(d[34]), "+f"(d[35]), "+f"(d[36]), "+f"(d[37]), "+f"(d[38]), "+f"(d[39]),
      "+f"(d[40]), "+f"(d[41]), "+f"(d[42]), "+f"(d[43]), "+f"(d[44]), "+f"(d[45]), "+f"(d[46]), "+f"(d[47]),
      "+f"(d[48]), "+f"(d[49]), "+f"(d[50]), "+f"(d[51]), "+f"(d[52]), "+f"(d[53]), "+f"(d[54]), "+f"(d[55]),
      "+f"(d[56]), "+f"(d[57]), "+f"(d[58]), "+f"(d[59]), "+f"(d[60]), "+f"(d[61]), "+f"(d[62]), "+f"(d[63]),
      "+f"(d[64]), "+f"(d[65]), "+f"(d[66]), "+f"(d[67]), "+f"(d[68]), "+f"(d[69]), "+f"(d[70]), "+f"(d[71]),
      "+f"(d[72]), "+f"(d[73]), "+f"(d[74]), "+f"(d[75]), "+f"(d[76]), "+f"(d[77]), "+f"(d[78]), "+f"(d[79]),
      "+f"(d[80]), "+f"(d[81]), "+f"(d[82]), "+f"(d[83]), "+f"(d[84]), "+f"(d[85]), "+f"(d[86]), "+f"(d[87]),
      "+f"(d[88]), "+f"(d[89]), "+f"(d[90]), "+f"(d[91]), "+f"(d[92]), "+f"(d[93]), "+f"(d[94]), "+f"(d[95]),
      "+f"(d[96]), "+f"(d[97]), "+f"(d[98]), "+f"(d[99]), "+f"(d[100]), "+f"(d[101]), "+f"(d[102]), "+f"(d[103]),
      "+f"(d[104]), "+f"(d[105]), "+f"(d[106]), "+f"(d[107]), "+f"(d[108]), "+f"(d[109]), "+f"(d[110]), "+f"(d[111])
    : "r"(a[0]), "r"(a[1]), "r"(a[2]), "r"(a[3]), "l"(db), "r"(sd));
}

#define SPIN_LIMIT (1 << 18)

__device__ __forceinline__ uint32_t smem_u32(const void* p) { return (uint32_t)__cvta_generic_to_shared(p); }
__device__ __forceinline__ void mbar_init(uint32_t a, uint32_t c) {
  asm volatile("mbarrier.init.shared::cta.b64 [%0], %1;" ::"r"(a), "r"(c) : "memory");
}
__device__ __forceinline__ void mbar_expect(uint32_t a, uint32_t b) {
  asm volatile("mbarrier.arrive.expect_tx.shared::cta.b64 _, [%0], %1;" ::"r"(a), "r"(b) : "memory");
}
__device__ __forceinline__ void mbar_arrive(uint32_t a) {
  asm volatile("mbarrier.arrive.shared::cta.b64 _, [%0];" ::"r"(a) : "memory");
}
__device__ __forceinline__ void mbar_wait(uint32_t a, uint32_t parity) {
  asm volatile(
      "{\n.reg .pred p;\n.reg .u32 n;\nmov.u32 n, 0;\n"
      "LAB_WAIT:\n"
      "mbarrier.try_wait.parity.shared::cta.b64 p, [%0], %1;\n"
      "@p bra LAB_DONE;\n"
      "add.u32 n, n, 1;\n"
      "setp.lt.u32 p, n, 262144;\n"
      "@p bra LAB_WAIT;\n"
      "LAB_DONE:\n}\n" ::"r"(a), "r"(parity) : "memory");
}
__device__ __forceinline__ void tma3d(uint32_t dst, const CUtensorMap* tm, uint32_t bar, int c0, int c1, int c2) {
  asm volatile(
      "cp.async.bulk.tensor.3d.shared::cluster.global.mbarrier::complete_tx::bytes [%0], [%1, {%3,%4,%5}], [%2];"
      ::"r"(dst), "l"(tm), "r"(bar), "r"(c0), "r"(c1), "r"(c2) : "memory");
}
__device__ __forceinline__ void wg_fence() { asm volatile("wgmma.fence.sync.aligned;" ::: "memory"); }
__device__ __forceinline__ void wg_commit() { asm volatile("wgmma.commit_group.sync.aligned;" ::: "memory"); }
template <int N> __device__ __forceinline__ void wg_wait() {
  asm volatile("wgmma.wait_group.sync.aligned %0;" ::"n"(N) : "memory");
}
template <int N> __device__ __forceinline__ void fence_regs(float (&d)[N]) {
#pragma unroll
  for (int i = 0; i < N; i++) asm volatile("" : "+f"(d[i])::"memory");
}
template <int N> __device__ __forceinline__ void fence_regs(uint32_t (&d)[N][4]) {
#pragma unroll
  for (int i = 0; i < N; i++) asm volatile("" : "+r"(d[i][0]), "+r"(d[i][1]), "+r"(d[i][2]), "+r"(d[i][3])::"memory");
}
template <int N> __device__ __forceinline__ void fence_frags(uint32_t (*d)[4]) {
#pragma unroll
  for (int i = 0; i < N; i++) asm volatile("" : "+r"(d[i][0]), "+r"(d[i][1]), "+r"(d[i][2]), "+r"(d[i][3])::"memory");
}
__device__ __forceinline__ void bar_sync(int id, int n) { asm volatile("bar.sync %0, %1;" ::"r"(id), "r"(n) : "memory"); }
__device__ __forceinline__ void bar_arrive(int id, int n) { asm volatile("bar.arrive %0, %1;" ::"r"(id), "r"(n) : "memory"); }

__host__ __device__ constexpr uint64_t desc_hi(uint32_t lbo, uint32_t sbo, uint32_t swz) {
  return ((uint64_t)(lbo >> 4) << 16) | ((uint64_t)(sbo >> 4) << 32) | ((uint64_t)swz << 62);
}
__device__ __forceinline__ uint64_t mkdesc(uint64_t hi, uint32_t addr) { return hi | (uint64_t)((addr & 0x3FFFF) >> 4); }

__device__ __forceinline__ uint32_t pack_bf16(float lo, float hi) {
  uint32_t r;
  asm("cvt.rn.bf16x2.f32 %0, %1, %2;" : "=r"(r) : "f"(hi), "f"(lo));
  return r;
}
__device__ __forceinline__ float bf_lo(uint32_t w) { return __uint_as_float(w << 16); }
__device__ __forceinline__ float bf_hi(uint32_t w) { return __uint_as_float(w & 0xFFFF0000u); }
__device__ __forceinline__ float round_bf16(float x) { return bf_lo(pack_bf16(x, 0.f)); }
__device__ __forceinline__ uint32_t hfma2_bf16(uint32_t a, uint32_t b, uint32_t c) {
  uint32_t r;
  asm("fma.rn.bf16x2 %0, %1, %2, %3;" : "=r"(r) : "r"(a), "r"(b), "r"(c));
  return r;
}
__device__ __forceinline__ float ex2(float x) {
  float r;
  asm("ex2.approx.ftz.f32 %0, %1;" : "=f"(r) : "f"(x));
  return r;
}
__device__ __forceinline__ float tanh_hw(float x) {
  float r;
  asm("tanh.approx.f32 %0, %1;" : "=f"(r) : "f"(x));
  return r;
}
template <int TAG> __device__ __forceinline__ uint32_t pack_tag(float lo, float hi) {
  uint32_t w = __byte_perm(__float_as_uint(lo), pack_bf16(lo, hi), 0x7632);
  return TAG ? (w | 1u) : (w & ~1u);
}
__device__ __forceinline__ void st_pkt(uint4* p, uint32_t a, uint32_t b, uint32_t c, uint32_t d) {
  asm volatile(
      "{\n.reg .b64 lo, hi;\n.reg .b128 v;\nmov.b64 lo, {%1,%2};\nmov.b64 hi, {%3,%4};\nmov.b128 v, {lo,hi};\n"
      "st.relaxed.gpu.global.b128 [%0], v;\n}\n" ::"l"(p), "r"(a), "r"(b), "r"(c), "r"(d) : "memory");
}
__device__ __forceinline__ void ld_pkt(const uint4* p, uint32_t (&r)[4]) {
  asm volatile(
      "{\n.reg .b64 lo, hi;\n.reg .b128 v;\nld.relaxed.gpu.global.b128 v, [%4];\nmov.b128 {lo,hi}, v;\n"
      "mov.b64 {%0,%1}, lo;\nmov.b64 {%2,%3}, hi;\n}\n"
      : "=r"(r[0]), "=r"(r[1]), "=r"(r[2]), "=r"(r[3]) : "l"(p) : "memory");
}
__device__ __forceinline__ void sts128(uint32_t a, uint32_t x, uint32_t y, uint32_t z, uint32_t w) {
  asm volatile("st.shared.v4.b32 [%0], {%1,%2,%3,%4};" ::"r"(a), "r"(x), "r"(y), "r"(z), "r"(w) : "memory");
}
__device__ __forceinline__ void lds128(uint32_t a, uint32_t (&r)[4]) {
  asm volatile("ld.shared.v4.b32 {%0,%1,%2,%3}, [%4];" : "=r"(r[0]), "=r"(r[1]), "=r"(r[2]), "=r"(r[3]) : "r"(a) : "memory");
}

constexpr int D_MODEL = 512;
constexpr int SK = 2048, WIN = 512;
constexpr int FF = 1792, FSL = 224;
constexpr int NTILES = 80;
constexpr int NSLOT = 4;
constexpr uint32_t SLOT = 32768;
constexpr uint32_t SM_PARK = 0;
constexpr uint32_t SM_RING = 3 * SLOT;
constexpr uint32_t SM_TAB = 7 * SLOT;
constexpr uint32_t SM_RED = SM_TAB + 2048;
constexpr uint32_t SM_BAR = SM_RED + 256;
constexpr uint32_t SM_TOTAL = SM_BAR + 128;

__device__ uint4 g_P[16 * 8 * 8 * 32 * 32];
__device__ uint4 g_G[16 * 8 * 32 * 32];
__device__ uint4 g_mod1[256];
__device__ uint4 g_mod2[512];
__device__ uint32_t g_epoch;

#define TS(i) do { } while (0)

struct Params {
  const __nv_bfloat16* x;
  const __nv_bfloat16* c;
  const __nv_bfloat16* wmod;
  __nv_bfloat16* out;
};

constexpr uint64_t DH_MN128 = desc_hi(16384, 1024, 1);
constexpr uint64_t DH_K128 = desc_hi(16, 1024, 1);
constexpr uint64_t DH_W1 = desc_hi(4096, 512, 2);
constexpr uint64_t DH_W2 = desc_hi(14336, 1024, 1);

struct Ring {
  uint32_t base, bars;
  int t;
  __device__ __forceinline__ uint32_t wait_full(int tt) const {
    mbar_wait(bars + (tt & 3) * 8, (tt >> 2) & 1);
    return base + (tt & 3) * SLOT;
  }
  __device__ __forceinline__ void release(int tt) const {
    if ((threadIdx.x & 31) == 0) mbar_arrive(bars + 32 + (tt & 3) * 8);
  }
};

__device__ __forceinline__ float silu_c(__nv_bfloat16 v) {
  float x = __bfloat162float(v);
  return round_bf16(x / (1.f + __expf(-x)));
}

template <int TAG, int N>
__device__ __forceinline__ void issue_pkts(const uint4* p, int stride, uint32_t (*r)[4]) {
#pragma unroll
  for (int i = 0; i < N; i++) ld_pkt(p + i * stride, r[i]);
}
template <int TAG, int N>
__device__ __forceinline__ void verify_pkts(const uint4* p, int stride, uint32_t (*r)[4]) {
  int spins = 0;
  while (true) {
    uint32_t a = TAG ? 1u : 0u;
#pragma unroll
    for (int i = 0; i < N; i++) a = TAG ? (a & r[i][0]) : (a | r[i][0]);
    bool ok = (a & 1u) == (uint32_t)TAG;
    if (__all_sync(0xffffffffu, ok) || ++spins > SPIN_LIMIT) break;
#pragma unroll
    for (int i = 0; i < N; i++) ld_pkt(p + i * stride, r[i]);
  }
  if (!TAG) {
#pragma unroll
    for (int i = 0; i < N; i++) r[i][0] |= 1u;
  }
}
__device__ __forceinline__ void ld_mod(const uint4* p, uint32_t tag, uint32_t (&r)[4]) {
  int spins = 0;
  ld_pkt(p, r);
  while (r[2] != tag && ++spins < SPIN_LIMIT) ld_pkt(p, r);
}

__global__ void __launch_bounds__(384, 1)
adaln_block_kernel(const __grid_constant__ CUtensorMap tmWq, const __grid_constant__ CUtensorMap tmK,
                   const __grid_constant__ CUtensorMap tmV, const __grid_constant__ CUtensorMap tmWo,
                   const __grid_constant__ CUtensorMap tmW1, const __grid_constant__ CUtensorMap tmW2,
                   const Params p) {
  extern __shared__ __align__(1024) uint8_t smem_raw[];
  const uint32_t sb = smem_u32(smem_raw);
  const int tid = threadIdx.x, lane = tid & 31, warp = tid >> 5;
  const int bid = blockIdx.x, j = bid >> 4, rt = bid & 15;
  const uint32_t bars = sb + SM_BAR;
  if (tid == 256) {
    for (int i = 0; i < NSLOT; i++) { mbar_init(bars + i * 8, 1); mbar_init(bars + 32 + i * 8, 8); }
    asm volatile("fence.mbarrier_init.release.cluster;" ::: "memory");
    asm volatile("fence.proxy.async.shared::cta;" ::: "memory");
    for (int t = 0; t < NSLOT; t++) {
      mbar_expect(bars + t * 8, SLOT);
      tma3d(sb + SM_RING + t * SLOT, &tmWq, bars + t * 8, 0, t * 128, (j * 4 + 1) * 2);
    }
  }
  uint32_t tag;
  asm volatile("ld.relaxed.gpu.global.u32 %0, [%1];" : "=r"(tag) : "l"(&g_epoch) : "memory");
  tag += 1;

  if (warp >= 8) {
    asm volatile("setmaxnreg.dec.sync.aligned.u32 40;");
    const int t = tid - 256;
    {
      uint4 w[4];
      float s[4];
#pragma unroll
      for (int i = 0; i < 4; i++) w[i] = __ldg((const uint4*)(p.wmod + (size_t)(t + 128 * i) * 3072 + bid * 8));
#pragma unroll
      for (int i = 0; i < 4; i++) s[i] = silu_c(p.c[t + 128 * i]);
      float a[8];
#pragma unroll
      for (int k = 0; k < 8; k++) a[k] = 0.f;
#pragma unroll
      for (int i = 0; i < 4; i++) {
        a[0] = fmaf(s[i], bf_lo(w[i].x), a[0]); a[1] = fmaf(s[i], bf_hi(w[i].x), a[1]);
        a[2] = fmaf(s[i], bf_lo(w[i].y), a[2]); a[3] = fmaf(s[i], bf_hi(w[i].y), a[3]);
        a[4] = fmaf(s[i], bf_lo(w[i].z), a[4]); a[5] = fmaf(s[i], bf_hi(w[i].z), a[5]);
        a[6] = fmaf(s[i], bf_lo(w[i].w), a[6]); a[7] = fmaf(s[i], bf_hi(w[i].w), a[7]);
      }
      const bool h16 = lane & 16, h8 = lane & 8, h4 = lane & 4;
#pragma unroll
      for (int k = 0; k < 4; k++) {
        float send = h16 ? a[k] : a[k + 4], keep = h16 ? a[k + 4] : a[k];
        a[k] = keep + __shfl_xor_sync(0xffffffffu, send, 16);
      }
#pragma unroll
      for (int k = 0; k < 2; k++) {
        float send = h8 ? a[k] : a[k + 2], keep = h8 ? a[k + 2] : a[k];
        a[k] = keep + __shfl_xor_sync(0xffffffffu, send, 8);
      }
      {
        float send = h4 ? a[0] : a[1], keep = h4 ? a[1] : a[0];
        a[0] = keep + __shfl_xor_sync(0xffffffffu, send, 4);
      }
      a[0] += __shfl_xor_sync(0xffffffffu, a[0], 2);
      a[0] += __shfl_xor_sync(0xffffffffu, a[0], 1);
      float* red = (float*)(smem_raw + SM_RED);
      if ((lane & 3) == 0) red[(warp - 8) * 8 + (lane >> 2)] = a[0];
      __syncthreads();
      if (warp == 9) {
        const int cl = lane & 7;
        float v = round_bf16(red[cl] + red[8 + cl] + red[16 + cl] + red[24 + cl]);
        if (bid >= 64) v = 1.f + v;
        float vn = __shfl_down_sync(0xffffffffu, v, 1);
        uint32_t wd = pack_bf16(v, vn);
        uint32_t w0 = __shfl_sync(0xffffffffu, wd, (lane & 1) * 4);
        uint32_t w1 = __shfl_sync(0xffffffffu, wd, (lane & 1) * 4 + 2);
        if (lane < 2) st_pkt(&g_mod1[bid * 2 + lane], w0, w1, tag, 0);
      }
    }
    if (warp == 8) {
      if (lane == 0) {
        for (int tt = NSLOT; tt < NTILES; tt++) {
          const int s = tt & 3;
          mbar_wait(bars + 32 + s * 8, ((tt >> 2) & 1) ^ 1);
          const uint32_t dst = sb + SM_RING + s * SLOT, fb = bars + s * 8;
          if (tt < 16) {
            mbar_expect(fb, SLOT);
            tma3d(dst, &tmWq, fb, 0, (tt & 3) * 128, (j * 4 + (((tt >> 2) + 1) & 3)) * 2);
          } else if (tt < 48) {
            const int u = tt - 16;
            const bool isK = (u == 0) || ((u & 1) && u != 31);
            const int n = isK ? ((u + 1) >> 1) : (u == 31 ? 15 : (u >> 1) - 1);
            mbar_expect(fb, SLOT);
            tma3d(dst, isK ? &tmK : &tmV, fb, 0, j * SK + (SK - WIN) + (n & 3) * 128, 0);
          } else if (tt < 64) {
            const int u = tt - 48;
            mbar_expect(fb, SLOT);
            tma3d(dst, &tmWo, fb, 0, j * 512 + (u & 3) * 128, (u >> 2) * 2);
          } else if (tt < 72) {
            mbar_expect(fb, 28672);
            tma3d(dst, &tmW1, fb, 0, (tt - 64) * 64, j * 7);
          } else {
            const int u = tt - 72;
            mbar_expect(fb, 28672);
            tma3d(dst, &tmW2, fb, 0, j * FSL + (u & 1) * 112, (u >> 1) * 2);
          }
        }
      }
    } else if (warp >= 10) {
      const int t2 = tid - 320, hf = t2 & 1, r0 = t2 >> 1;
      float a[8];
#pragma unroll
      for (int k = 0; k < 8; k++) a[k] = 0.f;
#pragma unroll 1
      for (int b = 0; b < 4; b++) {
        uint4 w[4];
        float s[4];
#pragma unroll
        for (int i = 0; i < 4; i++)
          w[i] = __ldg((const uint4*)(p.wmod + (size_t)(r0 + 32 * (4 * b + i)) * 3072 + 1024 + bid * 16 + hf * 8));
#pragma unroll
        for (int i = 0; i < 4; i++) s[i] = silu_c(p.c[r0 + 32 * (4 * b + i)]);
#pragma unroll
        for (int i = 0; i < 4; i++) {
          a[0] = fmaf(s[i], bf_lo(w[i].x), a[0]); a[1] = fmaf(s[i], bf_hi(w[i].x), a[1]);
          a[2] = fmaf(s[i], bf_lo(w[i].y), a[2]); a[3] = fmaf(s[i], bf_hi(w[i].y), a[3]);
          a[4] = fmaf(s[i], bf_lo(w[i].z), a[4]); a[5] = fmaf(s[i], bf_hi(w[i].z), a[5]);
          a[6] = fmaf(s[i], bf_lo(w[i].w), a[6]); a[7] = fmaf(s[i], bf_hi(w[i].w), a[7]);
        }
      }
      const bool h16 = lane & 16, h8 = lane & 8, h4 = lane & 4;
#pragma unroll
      for (int k = 0; k < 4; k++) {
        float send = h16 ? a[k] : a[k + 4], keep = h16 ? a[k + 4] : a[k];
        a[k] = keep + __shfl_xor_sync(0xffffffffu, send, 16);
      }
#pragma unroll
      for (int k = 0; k < 2; k++) {
        float send = h8 ? a[k] : a[k + 2], keep = h8 ? a[k + 2] : a[k];
        a[k] = keep + __shfl_xor_sync(0xffffffffu, send, 8);
      }
      {
        float send = h4 ? a[0] : a[1], keep = h4 ? a[1] : a[0];
        a[0] = keep + __shfl_xor_sync(0xffffffffu, send, 4);
      }
      a[0] += __shfl_xor_sync(0xffffffffu, a[0], 2);
      float* red = (float*)(smem_raw + SM_RED) + 32;
      if ((lane & 2) == 0) red[(warp - 10) * 16 + hf * 8 + (lane >> 2)] = a[0];
      bar_sync(4, 64);
      if (warp == 10) {
        const int cl = lane & 15;
        float v = round_bf16(red[cl] + red[16 + cl]);
        if ((bid >> 5) == 2) v = 1.f + v;
        float vn = __shfl_down_sync(0xffffffffu, v, 1);
        uint32_t wd = pack_bf16(v, vn);
        uint32_t w0 = __shfl_sync(0xffffffffu, wd, (lane & 3) * 2);
        uint32_t w1 = __shfl_sync(0xffffffffu, wd, (lane & 3) * 2 + 8);
        if (lane < 4) st_pkt(&g_mod2[bid * 4 + lane], w0, w1, tag, 0);
      }
    }
  } else {
    asm volatile("setmaxnreg.inc.sync.aligned.u32 232;");
    const int wg = warp >> 2;
    const int q = lane & 3, gq = lane >> 2;
    Ring ring{sb + SM_RING, bars, 0};
    const size_t orow = (size_t)rt * 128 + 16 * j + warp;
    const uint32_t* xo = (const uint32_t*)(p.x + orow * D_MODEL) + gq * 8 + q;
    uint4* const Gown = g_G + ((size_t)(rt * 8 + j) * 32 + gq) * 32 + warp * 4 + q;
    const uint4* const Pown = g_P + ((size_t)(rt * 8 + j) * 8 * 32 + gq) * 32 + warp * 4 + q;
    const uint4* const Gin = g_G + (size_t)(rt * 8 + warp) * 1024 + lane;
    uint4* const Pout = g_P + ((size_t)(rt * 8 + warp) * 8 + j) * 1024 + lane;

    {
      uint32_t xr[4][4];
#pragma unroll
      for (int c = 0; c < 4; c++) {
        xr[c][0] = __ldg(xo + c * 64);
        xr[c][1] = __ldg(xo + c * 64 + 8 * 256);
        xr[c][2] = __ldg(xo + c * 64 + 4);
        xr[c][3] = __ldg(xo + c * 64 + 4 + 8 * 256);
      }
      float s0 = 0.f, s1 = 0.f;
#pragma unroll
      for (int c = 0; c < 4; c++) {
        s0 += (bf_lo(xr[c][0]) + bf_hi(xr[c][0])) + (bf_lo(xr[c][2]) + bf_hi(xr[c][2]));
        s1 += (bf_lo(xr[c][1]) + bf_hi(xr[c][1])) + (bf_lo(xr[c][3]) + bf_hi(xr[c][3]));
      }
#pragma unroll
      for (int o = 16; o > 0; o >>= 1) {
        s0 += __shfl_xor_sync(0xffffffffu, s0, o);
        s1 += __shfl_xor_sync(0xffffffffu, s1, o);
      }
      const float m0 = s0 * (1.f / 512.f), m1 = s1 * (1.f / 512.f);
      float v0 = 0.f, v1 = 0.f;
#pragma unroll
      for (int c = 0; c < 4; c++) {
        float a;
        a = bf_lo(xr[c][0]) - m0; v0 = fmaf(a, a, v0); a = bf_hi(xr[c][0]) - m0; v0 = fmaf(a, a, v0);
        a = bf_lo(xr[c][2]) - m0; v0 = fmaf(a, a, v0); a = bf_hi(xr[c][2]) - m0; v0 = fmaf(a, a, v0);
        a = bf_lo(xr[c][1]) - m1; v1 = fmaf(a, a, v1); a = bf_hi(xr[c][1]) - m1; v1 = fmaf(a, a, v1);
        a = bf_lo(xr[c][3]) - m1; v1 = fmaf(a, a, v1); a = bf_hi(xr[c][3]) - m1; v1 = fmaf(a, a, v1);
      }
#pragma unroll
      for (int o = 16; o > 0; o >>= 1) {
        v0 += __shfl_xor_sync(0xffffffffu, v0, o);
        v1 += __shfl_xor_sync(0xffffffffu, v1, o);
      }
      const float r0 = rsqrtf(v0 * (1.f / 512.f) + 1e-5f), r1 = rsqrtf(v1 * (1.f / 512.f) + 1e-5f);
#pragma unroll
      for (int c = 0; c < 4; c++) {
        st_pkt(Gown + c * 256,
               pack_tag<1>((bf_lo(xr[c][0]) - m0) * r0, (bf_hi(xr[c][0]) - m0) * r0),
               pack_bf16((bf_lo(xr[c][1]) - m1) * r1, (bf_hi(xr[c][1]) - m1) * r1),
               pack_bf16((bf_lo(xr[c][2]) - m0) * r0, (bf_hi(xr[c][2]) - m0) * r0),
               pack_bf16((bf_lo(xr[c][3]) - m1) * r1, (bf_hi(xr[c][3]) - m1) * r1));
      }
    }
    TS(0);
    __syncthreads();
    {
      uint32_t r[4];
      ld_mod(&g_mod1[tid], tag, r);
      const int t2 = tid & 127, g = t2 >> 2, pp = (t2 & 3) * 2;
      const uint32_t a = sb + SM_TAB + (uint32_t)(g * 4 + (pp & 3)) * 16 + (tid < 128 ? 8 : 0) + (pp >> 2) * 4;
      asm volatile("st.shared.b32 [%0], %1;" ::"r"(a), "r"(r[0]) : "memory");
      asm volatile("st.shared.b32 [%0], %1;" ::"r"(a + 16), "r"(r[1]) : "memory");
    }
    TS(1);
    uint32_t qf[8][4];
    {
      uint32_t h[32][4];
      issue_pkts<1, 32>(Gin, 32, h);
      bar_sync(1, 256);
      float acc[64];
#pragma unroll
      for (int c = 0; c < 4; c++) {
        verify_pkts<1, 8>(Gin + c * 256, 32, h + c * 8);
#pragma unroll
        for (int i = 0; i < 8; i++) {
          uint32_t m[4];
          lds128(sb + SM_TAB + (uint32_t)((c * 8 + i) * 4 + q) * 16, m);
          uint32_t* hh = h[c * 8 + i];
          hh[0] = hfma2_bf16(hh[0], m[0], m[2]);
          hh[1] = hfma2_bf16(hh[1], m[0], m[2]);
          hh[2] = hfma2_bf16(hh[2], m[1], m[3]);
          hh[3] = hfma2_bf16(hh[3], m[1], m[3]);
        }
        fence_frags<8>(h + c * 8);
        if (c == 0) TS(2);
        const uint32_t b = ring.wait_full(c);
        wg_fence();
#pragma unroll
        for (int k = 0; k < 8; k++) wgmma_rs_n128_tb1(acc, h[c * 8 + k], mkdesc(DH_MN128, b + k * 2048), (c | k) != 0);
        wg_commit();
        wg_wait<0>();
        ring.release(c);
      }
#pragma unroll 1
      for (int ps = 1; ps < 4; ps++) {
        fence_regs(acc);
#pragma unroll
        for (int i = 0; i < 8; i++)
          sts128(sb + SM_PARK + (ps - 1) * SLOT + i * 4096 + tid * 16, pack_bf16(acc[8 * i], acc[8 * i + 1]),
                 pack_bf16(acc[8 * i + 2], acc[8 * i + 3]), pack_bf16(acc[8 * i + 4], acc[8 * i + 5]),
                 pack_bf16(acc[8 * i + 6], acc[8 * i + 7]));
#pragma unroll
        for (int c = 0; c < 4; c++) {
          const uint32_t b = ring.wait_full(ps * 4 + c);
          wg_fence();
#pragma unroll
          for (int k = 0; k < 8; k++) wgmma_rs_n128_tb1(acc, h[c * 8 + k], mkdesc(DH_MN128, b + k * 2048), (c | k) != 0);
          wg_commit();
          wg_wait<0>();
          ring.release(ps * 4 + c);
        }
      }
      fence_regs(acc);
#pragma unroll
      for (int i = 0; i < 8; i++) {
        qf[i][0] = pack_bf16(acc[8 * i], acc[8 * i + 1]); qf[i][1] = pack_bf16(acc[8 * i + 2], acc[8 * i + 3]);
        qf[i][2] = pack_bf16(acc[8 * i + 4], acc[8 * i + 5]); qf[i][3] = pack_bf16(acc[8 * i + 6], acc[8 * i + 7]);
      }
    }
    fence_regs(qf);
    TS(3);

    float S[64];
    {
      float O[64];
      uint32_t P[8][4];
      const float cs = 0.08838834764831845f * 1.4426950408889634f;
      float m0, m1, l0, l1;
      {
        const uint32_t b = ring.wait_full(16);
        wg_fence();
#pragma unroll
        for (int k = 0; k < 8; k++) wgmma_rs_n128_tb0(S, qf[k], mkdesc(DH_K128, b + (k >> 2) * 16384 + (k & 3) * 32), k != 0);
        wg_commit();
        wg_wait<0>();
        fence_regs(S);
        ring.release(16);
        float a0 = fmaxf(S[0], S[1]), a1 = fmaxf(S[2], S[3]);
#pragma unroll
        for (int i = 1; i < 16; i++) {
          a0 = fmaxf(a0, fmaxf(S[4 * i], S[4 * i + 1]));
          a1 = fmaxf(a1, fmaxf(S[4 * i + 2], S[4 * i + 3]));
        }
        a0 = fmaxf(a0, __shfl_xor_sync(0xffffffffu, a0, 1)); a1 = fmaxf(a1, __shfl_xor_sync(0xffffffffu, a1, 1));
        a0 = fmaxf(a0, __shfl_xor_sync(0xffffffffu, a0, 2)); a1 = fmaxf(a1, __shfl_xor_sync(0xffffffffu, a1, 2));
        m0 = a0 * cs; m1 = a1 * cs;
        l0 = 0.f; l1 = 0.f;
#pragma unroll
        for (int i = 0; i < 16; i++) {
          S[4 * i] = ex2(fmaf(S[4 * i], cs, -m0)); S[4 * i + 1] = ex2(fmaf(S[4 * i + 1], cs, -m0));
          S[4 * i + 2] = ex2(fmaf(S[4 * i + 2], cs, -m1)); S[4 * i + 3] = ex2(fmaf(S[4 * i + 3], cs, -m1));
          l0 += S[4 * i] + S[4 * i + 1]; l1 += S[4 * i + 2] + S[4 * i + 3];
        }
#pragma unroll
        for (int i = 0; i < 8; i++) {
          P[i][0] = pack_bf16(S[8 * i], S[8 * i + 1]); P[i][1] = pack_bf16(S[8 * i + 2], S[8 * i + 3]);
          P[i][2] = pack_bf16(S[8 * i + 4], S[8 * i + 5]); P[i][3] = pack_bf16(S[8 * i + 6], S[8 * i + 7]);
        }
#pragma unroll
        for (int i = 0; i < 64; i++) O[i] = 0.f;
      }
      fence_regs(P);
      fence_regs(O);
      if (wg == 1) bar_arrive(2, 256);
#pragma unroll 1
      for (int n = 1; n < 16; n++) {
        const int tk = 16 + 2 * n - 1, tv = tk + 1;
        const bool newhead = (n & 3) == 0;
        const uint32_t bk = ring.wait_full(tk);
        const uint32_t bv = ring.wait_full(tv);
        bar_sync(2 + wg, 256);
        wg_fence();
#pragma unroll
        for (int k = 0; k < 8; k++) wgmma_rs_n128_tb0(S, qf[k], mkdesc(DH_K128, bk + (k >> 2) * 16384 + (k & 3) * 32), k != 0);
        wg_commit();
#pragma unroll
        for (int k = 0; k < 8; k++) wgmma_rs_n128_tb1(O, P[k], mkdesc(DH_MN128, bv + k * 2048), 1);
        wg_commit();
        bar_arrive(2 + (wg ^ 1), 256);
        wg_wait<1>();
        fence_regs(S);
        ring.release(tk);
        if ((n & 3) == 3 && n != 15) {
          fence_regs(qf);
#pragma unroll
          for (int i = 0; i < 8; i++) lds128(sb + SM_PARK + (n >> 2) * SLOT + i * 4096 + tid * 16, qf[i]);
        }
        float a0 = fmaxf(S[0], S[1]), a1 = fmaxf(S[2], S[3]);
#pragma unroll
        for (int i = 1; i < 16; i++) {
          a0 = fmaxf(a0, fmaxf(S[4 * i], S[4 * i + 1]));
          a1 = fmaxf(a1, fmaxf(S[4 * i + 2], S[4 * i + 3]));
        }
        a0 = fmaxf(a0, __shfl_xor_sync(0xffffffffu, a0, 1)); a1 = fmaxf(a1, __shfl_xor_sync(0xffffffffu, a1, 1));
        a0 = fmaxf(a0, __shfl_xor_sync(0xffffffffu, a0, 2)); a1 = fmaxf(a1, __shfl_xor_sync(0xffffffffu, a1, 2));
        a0 *= cs; a1 *= cs;
        const float n0 = newhead ? a0 : fmaxf(a0, m0), n1 = newhead ? a1 : fmaxf(a1, m1);
        float f0, f1;
        if (newhead) {
          l0 += __shfl_xor_sync(0xffffffffu, l0, 1); l1 += __shfl_xor_sync(0xffffffffu, l1, 1);
          l0 += __shfl_xor_sync(0xffffffffu, l0, 2); l1 += __shfl_xor_sync(0xffffffffu, l1, 2);
          f0 = 1.f / l0; f1 = 1.f / l1;
          l0 = 0.f; l1 = 0.f;
        } else {
          f0 = ex2(m0 - n0); f1 = ex2(m1 - n1);
          l0 *= f0; l1 *= f1;
        }
        m0 = n0; m1 = n1;
#pragma unroll
        for (int i = 0; i < 16; i++) {
          S[4 * i] = ex2(fmaf(S[4 * i], cs, -m0)); S[4 * i + 1] = ex2(fmaf(S[4 * i + 1], cs, -m0));
          S[4 * i + 2] = ex2(fmaf(S[4 * i + 2], cs, -m1)); S[4 * i + 3] = ex2(fmaf(S[4 * i + 3], cs, -m1));
          l0 += S[4 * i] + S[4 * i + 1]; l1 += S[4 * i + 2] + S[4 * i + 3];
        }
        wg_wait<0>();
        fence_regs(O);
        fence_regs(S);
        ring.release(tv);
#pragma unroll
        for (int i = 0; i < 16; i++) {
          O[4 * i] *= f0; O[4 * i + 1] *= f0; O[4 * i + 2] *= f1; O[4 * i + 3] *= f1;
        }
        if (newhead) {
#pragma unroll
          for (int i = 0; i < 8; i++)
            sts128(sb + SM_PARK + ((n >> 2) - 1) * SLOT + i * 4096 + tid * 16, pack_bf16(O[8 * i], O[8 * i + 1]),
                   pack_bf16(O[8 * i + 2], O[8 * i + 3]), pack_bf16(O[8 * i + 4], O[8 * i + 5]),
                   pack_bf16(O[8 * i + 6], O[8 * i + 7]));
#pragma unroll
          for (int i = 0; i < 64; i++) O[i] = 0.f;
        }
#pragma unroll
        for (int i = 0; i < 8; i++) {
          P[i][0] = pack_bf16(S[8 * i], S[8 * i + 1]); P[i][1] = pack_bf16(S[8 * i + 2], S[8 * i + 3]);
          P[i][2] = pack_bf16(S[8 * i + 4], S[8 * i + 5]); P[i][3] = pack_bf16(S[8 * i + 6], S[8 * i + 7]);
        }
        fence_regs(P);
        fence_regs(O);
      }
      {
        const uint32_t bv = ring.wait_full(47);
        if (wg == 0) bar_sync(2, 256);
        wg_fence();
#pragma unroll
        for (int k = 0; k < 8; k++) wgmma_rs_n128_tb1(O, P[k], mkdesc(DH_MN128, bv + k * 2048), 1);
        wg_commit();
        l0 += __shfl_xor_sync(0xffffffffu, l0, 1); l1 += __shfl_xor_sync(0xffffffffu, l1, 1);
        l0 += __shfl_xor_sync(0xffffffffu, l0, 2); l1 += __shfl_xor_sync(0xffffffffu, l1, 2);
        const float f0 = 1.f / l0, f1 = 1.f / l1;
        wg_wait<0>();
        fence_regs(O);
        ring.release(47);
#pragma unroll
        for (int i = 0; i < 8; i++) {
          qf[i][0] = pack_bf16(O[8 * i] * f0, O[8 * i + 1] * f0); qf[i][1] = pack_bf16(O[8 * i + 2] * f1, O[8 * i + 3] * f1);
          qf[i][2] = pack_bf16(O[8 * i + 4] * f0, O[8 * i + 5] * f0); qf[i][3] = pack_bf16(O[8 * i + 6] * f1, O[8 * i + 7] * f1);
        }
      }
    }
    fence_regs(qf);
    TS(4);

#pragma unroll 1
    for (int c = 0; c < 4; c++) {
#pragma unroll
      for (int hh = 0; hh < 4; hh++) {
        uint32_t a[8][4];
        if (hh < 3) {
#pragma unroll
          for (int i = 0; i < 8; i++) lds128(sb + SM_PARK + hh * SLOT + i * 4096 + tid * 16, a[i]);
        }
        const uint32_t b = ring.wait_full(48 + c * 4 + hh);
        wg_fence();
#pragma unroll
        for (int k = 0; k < 8; k++)
          wgmma_rs_n128_tb1(S, hh < 3 ? a[k] : qf[k], mkdesc(DH_MN128, b + k * 2048), (hh | k) != 0);
        wg_commit();
        wg_wait<0>();
        ring.release(48 + c * 4 + hh);
      }
      fence_regs(S);
#pragma unroll
      for (int i = 0; i < 8; i++)
        st_pkt(Pout + (c * 8 + i) * 32, pack_tag<1>(S[8 * i], S[8 * i + 1]), pack_bf16(S[8 * i + 2], S[8 * i + 3]),
               pack_bf16(S[8 * i + 4], S[8 * i + 5]), pack_bf16(S[8 * i + 6], S[8 * i + 7]));
    }
    TS(5);

    float x2[4][8];
    {
#pragma unroll
      for (int c = 0; c < 4; c++) {
        uint32_t r[8][4], ga[4];
        issue_pkts<1, 8>(Pown + c * 256, 1024, r);
        const uint32_t x0 = __ldg(xo + c * 64), x1 = __ldg(xo + c * 64 + 8 * 256), x2_ = __ldg(xo + c * 64 + 4),
                       x3 = __ldg(xo + c * 64 + 4 + 8 * 256);
        ld_mod(&g_mod2[(0 * 32 + c * 8 + gq) * 4 + q], tag, ga);
        verify_pkts<1, 8>(Pown + c * 256, 1024, r);
        float y[8];
#pragma unroll
        for (int e = 0; e < 4; e++) {
          y[2 * e] = bf_lo(r[0][e]); y[2 * e + 1] = bf_hi(r[0][e]);
#pragma unroll
          for (int s = 1; s < 8; s++) { y[2 * e] += bf_lo(r[s][e]); y[2 * e + 1] += bf_hi(r[s][e]); }
        }
        x2[c][0] = fmaf(bf_lo(ga[0]), y[0], bf_lo(x0)); x2[c][1] = fmaf(bf_hi(ga[0]), y[1], bf_hi(x0));
        x2[c][2] = fmaf(bf_lo(ga[0]), y[2], bf_lo(x1)); x2[c][3] = fmaf(bf_hi(ga[0]), y[3], bf_hi(x1));
        x2[c][4] = fmaf(bf_lo(ga[1]), y[4], bf_lo(x2_)); x2[c][5] = fmaf(bf_hi(ga[1]), y[5], bf_hi(x2_));
        x2[c][6] = fmaf(bf_lo(ga[1]), y[6], bf_lo(x3)); x2[c][7] = fmaf(bf_hi(ga[1]), y[7], bf_hi(x3));
      }
      TS(6);
      float s0 = 0.f, s1 = 0.f;
#pragma unroll
      for (int c = 0; c < 4; c++) {
        s0 += (x2[c][0] + x2[c][1]) + (x2[c][4] + x2[c][5]);
        s1 += (x2[c][2] + x2[c][3]) + (x2[c][6] + x2[c][7]);
      }
#pragma unroll
      for (int o = 16; o > 0; o >>= 1) {
        s0 += __shfl_xor_sync(0xffffffffu, s0, o);
        s1 += __shfl_xor_sync(0xffffffffu, s1, o);
      }
      const float m0 = s0 * (1.f / 512.f), m1 = s1 * (1.f / 512.f);
      float v0 = 0.f, v1 = 0.f;
#pragma unroll
      for (int c = 0; c < 4; c++) {
#pragma unroll
        for (int e = 0; e < 8; e++) {
          const float a = x2[c][e] - ((e & 2) ? m1 : m0);
          if (e & 2) v1 = fmaf(a, a, v1); else v0 = fmaf(a, a, v0);
        }
      }
#pragma unroll
      for (int o = 16; o > 0; o >>= 1) {
        v0 += __shfl_xor_sync(0xffffffffu, v0, o);
        v1 += __shfl_xor_sync(0xffffffffu, v1, o);
      }
      const float r0 = rsqrtf(v0 * (1.f / 512.f) + 1e-5f), r1 = rsqrtf(v1 * (1.f / 512.f) + 1e-5f);
#pragma unroll
      for (int c = 0; c < 4; c++) {
        uint32_t sh[4], g2[4];
        ld_mod(&g_mod2[(1 * 32 + c * 8 + gq) * 4 + q], tag, sh);
        ld_mod(&g_mod2[(2 * 32 + c * 8 + gq) * 4 + q], tag, g2);
        float hv[8];
#pragma unroll
        for (int e = 0; e < 8; e++) {
          const float t = (x2[c][e] - ((e & 2) ? m1 : m0)) * ((e & 2) ? r1 : r0);
          const uint32_t gw = g2[e >> 2], sw = sh[e >> 2];
          hv[e] = fmaf(t, (e & 1) ? bf_hi(gw) : bf_lo(gw), (e & 1) ? bf_hi(sw) : bf_lo(sw));
        }
        st_pkt(Gown + c * 256, pack_tag<0>(hv[0], hv[1]), pack_bf16(hv[2], hv[3]), pack_bf16(hv[4], hv[5]),
               pack_bf16(hv[6], hv[7]));
      }
#pragma unroll
      for (int c = 0; c < 4; c++) {
        sts128(sb + SM_PARK + (2 * c) * 4096 + tid * 16, __float_as_uint(x2[c][0]), __float_as_uint(x2[c][1]),
               __float_as_uint(x2[c][2]), __float_as_uint(x2[c][3]));
        sts128(sb + SM_PARK + (2 * c + 1) * 4096 + tid * 16, __float_as_uint(x2[c][4]), __float_as_uint(x2[c][5]),
               __float_as_uint(x2[c][6]), __float_as_uint(x2[c][7]));
      }
    }
    TS(7);

    uint32_t H[14][4];
    {
      float acc[112];
      uint32_t a[2][4][4];
      issue_pkts<0, 4>(Gin, 32, a[0]);
#pragma unroll
      for (int u = 0; u < 8; u++) {
        verify_pkts<0, 4>(Gin + u * 128, 32, a[u & 1]);
        fence_frags<4>(a[u & 1]);
        if (u == 0) TS(8);
        if (u < 7) issue_pkts<0, 4>(Gin + (u + 1) * 128, 32, a[(u + 1) & 1]);
        const uint32_t b = ring.wait_full(64 + u);
        wg_fence();
#pragma unroll
        for (int k = 0; k < 4; k++) wgmma_rs_n224_tb1(acc, a[u & 1][k], mkdesc(DH_W1, b + k * 1024), (u | k) != 0);
        wg_commit();
        wg_wait<0>();
        ring.release(64 + u);
      }
      fence_regs(acc);
      TS(9);
#pragma unroll
      for (int i = 0; i < 14; i++) {
#pragma unroll
        for (int e = 0; e < 4; e++) {
          const float u0 = 0.5f * acc[8 * i + 2 * e], u1 = 0.5f * acc[8 * i + 2 * e + 1];
          H[i][e] = pack_bf16(fmaf(u0, tanh_hw(u0), u0), fmaf(u1, tanh_hw(u1), u1));
        }
      }
    }
    fence_regs(H);
    TS(10);
#pragma unroll 1
    for (int c = 0; c < 4; c++) {
#pragma unroll
      for (int hf = 0; hf < 2; hf++) {
        const uint32_t b = ring.wait_full(72 + c * 2 + hf);
        wg_fence();
#pragma unroll
        for (int k = 0; k < 7; k++) wgmma_rs_n128_tb1(S, H[hf * 7 + k], mkdesc(DH_W2, b + k * 2048), (hf | k) != 0);
        wg_commit();
        wg_wait<0>();
        ring.release(72 + c * 2 + hf);
      }
      fence_regs(S);
#pragma unroll
      for (int i = 0; i < 8; i++)
        st_pkt(Pout + (c * 8 + i) * 32, pack_tag<0>(S[8 * i], S[8 * i + 1]), pack_bf16(S[8 * i + 2], S[8 * i + 3]),
               pack_bf16(S[8 * i + 4], S[8 * i + 5]), pack_bf16(S[8 * i + 6], S[8 * i + 7]));
    }
    TS(11);
    {
      uint32_t* oo = (uint32_t*)(p.out + orow * D_MODEL) + gq * 8 + q;
#pragma unroll
      for (int c = 0; c < 4; c++) {
        uint32_t r[8][4], gb[4], xa[4], xb[4];
        issue_pkts<0, 8>(Pown + c * 256, 1024, r);
        ld_mod(&g_mod2[(3 * 32 + c * 8 + gq) * 4 + q], tag, gb);
        lds128(sb + SM_PARK + (2 * c) * 4096 + tid * 16, xa);
        lds128(sb + SM_PARK + (2 * c + 1) * 4096 + tid * 16, xb);
        verify_pkts<0, 8>(Pown + c * 256, 1024, r);
        float y[8];
#pragma unroll
        for (int e = 0; e < 4; e++) {
          y[2 * e] = bf_lo(r[0][e]); y[2 * e + 1] = bf_hi(r[0][e]);
#pragma unroll
          for (int s = 1; s < 8; s++) { y[2 * e] += bf_lo(r[s][e]); y[2 * e + 1] += bf_hi(r[s][e]); }
        }
        oo[c * 64] = pack_bf16(fmaf(bf_lo(gb[0]), y[0], __uint_as_float(xa[0])), fmaf(bf_hi(gb[0]), y[1], __uint_as_float(xa[1])));
        oo[c * 64 + 8 * 256] = pack_bf16(fmaf(bf_lo(gb[0]), y[2], __uint_as_float(xa[2])), fmaf(bf_hi(gb[0]), y[3], __uint_as_float(xa[3])));
        oo[c * 64 + 4] = pack_bf16(fmaf(bf_lo(gb[1]), y[4], __uint_as_float(xb[0])), fmaf(bf_hi(gb[1]), y[5], __uint_as_float(xb[1])));
        oo[c * 64 + 4 + 8 * 256] = pack_bf16(fmaf(bf_lo(gb[1]), y[6], __uint_as_float(xb[2])), fmaf(bf_hi(gb[1]), y[7], __uint_as_float(xb[3])));
      }
    }
    TS(12);
    if (bid == 0 && tid == 0) asm volatile("st.relaxed.gpu.global.u32 [%0], %1;" ::"l"(&g_epoch), "r"(tag) : "memory");
  }
}

typedef CUresult (*EncodeFn)(CUtensorMap*, CUtensorMapDataType, cuuint32_t, void*, const cuuint64_t*, const cuuint64_t*,
                             const cuuint32_t*, const cuuint32_t*, CUtensorMapInterleave, CUtensorMapSwizzle,
                             CUtensorMapL2promotion, CUtensorMapFloatOOBfill);

static void make_map(EncodeFn fn, CUtensorMap* tm, const void* ptr, int inner, int rows, int cols, int box_rows, int box_outer,
                     CUtensorMapSwizzle swz) {
  cuuint64_t gd[3] = {(cuuint64_t)inner, (cuuint64_t)rows, (cuuint64_t)(cols / inner)};
  cuuint64_t gs[2] = {(cuuint64_t)cols * 2, (cuuint64_t)inner * 2};
  cuuint32_t bx[3] = {(cuuint32_t)inner, (cuuint32_t)box_rows, (cuuint32_t)box_outer};
  cuuint32_t es[3] = {1, 1, 1};
  fn(tm, CU_TENSOR_MAP_DATA_TYPE_BFLOAT16, 3, const_cast<void*>(ptr), gd, gs, bx, es, CU_TENSOR_MAP_INTERLEAVE_NONE, swz,
     CU_TENSOR_MAP_L2_PROMOTION_L2_128B, CU_TENSOR_MAP_FLOAT_OOB_FILL_NONE);
}

extern "C" void kernel_launch(void* const* d_in, const int* in_sizes, int n_in, void* d_out, int out_size) {
  (void)in_sizes; (void)n_in; (void)out_size;
  void* fnp = nullptr;
  cudaDriverEntryPointQueryResult qr;
  cudaGetDriverEntryPoint("cuTensorMapEncodeTiled", &fnp, cudaEnableDefault, &qr);
  EncodeFn fn = (EncodeFn)fnp;
  CUtensorMap tmWq, tmK, tmV, tmWo, tmW1, tmW2;
  make_map(fn, &tmWq, d_in[3], 64, 512, 4096, 128, 2, CU_TENSOR_MAP_SWIZZLE_128B);
  make_map(fn, &tmK, d_in[1], 64, 8 * SK, 128, 128, 2, CU_TENSOR_MAP_SWIZZLE_128B);
  make_map(fn, &tmV, d_in[2], 64, 8 * SK, 128, 128, 2, CU_TENSOR_MAP_SWIZZLE_128B);
  make_map(fn, &tmWo, d_in[4], 64, 4096, 512, 128, 2, CU_TENSOR_MAP_SWIZZLE_128B);
  make_map(fn, &tmW1, d_in[6], 32, 512, FF, 64, 7, CU_TENSOR_MAP_SWIZZLE_64B);
  make_map(fn, &tmW2, d_in[7], 64, FF, 512, 112, 2, CU_TENSOR_MAP_SWIZZLE_128B);
  Params p;
  p.x = (const __nv_bfloat16*)d_in[0];
  p.c = (const __nv_bfloat16*)d_in[8];
  p.wmod = (const __nv_bfloat16*)d_in[9];
  p.out = (__nv_bfloat16*)d_out;
  cudaFuncSetAttribute(adaln_block_kernel, cudaFuncAttributeMaxDynamicSharedMemorySize, SM_TOTAL);
  adaln_block_kernel<<<128, 384, SM_TOTAL>>>(tmWq, tmK, tmV, tmWo, tmW1, tmW2, p);
}
```

```cpp
#include <cuda_runtime.h>
#include <cuda_bf16.h>
#include <cuda.h>
#include <stdint.h>

template <int OFF, uint32_t HI>
__device__ __forceinline__ void wgmma_rs_n128_tb0(float (&d)[64], const uint32_t (&a)[4], uint32_t lo, int sd) {
  asm volatile("{\n.reg .pred p;\n.reg .b32 l;\n.reg .b64 db;\nsetp.ne.b32 p, %69, 0;\n"
    "add.u32 l, %68, %70;\nmov.b64 db, {l, %71};\n"
    "wgmma.mma_async.sync.aligned.m64n128k16.f32.bf16.bf16 "
    "{%0,%1,%2,%3,%4,%5,%6,%7,%8,%9,%10,%11,%12,%13,%14,%15,"
    "%16,%17,%18,%19,%20,%21,%22,%23,%24,%25,%26,%27,%28,%29,%30,%31,"
    "%32,%33,%34,%35,%36,%37,%38,%39,%40,%41,%42,%43,%44,%45,%46,%47,"
    "%48,%49,%50,%51,%52,%53,%54,%55,%56,%57,%58,%59,%60,%61,%62,%63}, "
    "{%64,%65,%66,%67}, db, p, 1, 1, 0;\n}\n"
    : "+f"(d[0]), "+f"(d[1]), "+f"(d[2]), "+f"(d[3]), "+f"(d[4]), "+f"(d[5]), "+f"(d[6]), "+f"(d[7]),
      "+f"(d[8]), "+f"(d[9]), "+f"(d[10]), "+f"(d[11]), "+f"(d[12]), "+f"(d[13]), "+f"(d[14]), "+f"(d[15]),
      "+f"(d[16]), "+f"(d[17]), "+f"(d[18]), "+f"(d[19]), "+f"(d[20]), "+f"(d[21]), "+f"(d[22]), "+f"(d[23]),
      "+f"(d[24]), "+f"(d[25]), "+f"(d[26]), "+f"(d[27]), "+f"(d[28]), "+f"(d[29]), "+f"(d[30]), "+f"(d[31]),
      "+f"(d[32]), "+f"(d[33]), "+f"(d[34]), "+f"(d[35]), "+f"(d[36]), "+f"(d[37]), "+f"(d[38]), "+f"(d[39]),
      "+f"(d[40]), "+f"(d[41]), "+f"(d[42]), "+f"(d[43]), "+f"(d[44]), "+f"(d[45]), "+f"(d[46]), "+f"(d[47]),
      "+f"(d[48]), "+f"(d[49]), "+f"(d[50]), "+f"(d[51]), "+f"(d[52]), "+f"(d[53]), "+f"(d[54]), "+f"(d[55]),
      "+f"(d[56]), "+f"(d[57]), "+f"(d[58]), "+f"(d[59]), "+f"(d[60]), "+f"(d[61]), "+f"(d[62]), "+f"(d[63])
    : "r"(a[0]), "r"(a[1]), "r"(a[2]), "r"(a[3]), "r"(lo), "r"(sd), "n"(OFF), "n"(HI));
}

template <int OFF, uint32_t HI>
__device__ __forceinline__ void wgmma_rs_n128_tb1(float (&d)[64], const uint32_t (&a)[4], uint32_t lo, int sd) {
  asm volatile("{\n.reg .pred p;\n.reg .b32 l;\n.reg .b64 db;\nsetp.ne.b32 p, %69, 0;\n"
    "add.u32 l, %68, %70;\nmov.b64 db, {l, %71};\n"
    "wgmma.mma_async.sync.aligned.m64n128k16.f32.bf16.bf16 "
    "{%0,%1,%2,%3,%4,%5,%6,%7,%8,%9,%10,%11,%12,%13,%14,%15,"
    "%16,%17,%18,%19,%20,%21,%22,%23,%24,%25,%26,%27,%28,%29,%30,%31,"
    "%32,%33,%34,%35,%36,%37,%38,%39,%40,%41,%42,%43,%44,%45,%46,%47,"
    "%48,%49,%50,%51,%52,%53,%54,%55,%56,%57,%58,%59,%60,%61,%62,%63}, "
    "{%64,%65,%66,%67}, db, p, 1, 1, 1;\n}\n"
    : "+f"(d[0]), "+f"(d[1]), "+f"(d[2]), "+f"(d[3]), "+f"(d[4]), "+f"(d[5]), "+f"(d[6]), "+f"(d[7]),
      "+f"(d[8]), "+f"(d[9]), "+f"(d[10]), "+f"(d[11]), "+f"(d[12]), "+f"(d[13]), "+f"(d[14]), "+f"(d[15]),
      "+f"(d[16]), "+f"(d[17]), "+f"(d[18]), "+f"(d[19]), "+f"(d[20]), "+f"(d[21]), "+f"(d[22]), "+f"(d[23]),
      "+f"(d[24]), "+f"(d[25]), "+f"(d[26]), "+f"(d[27]), "+f"(d[28]), "+f"(d[29]), "+f"(d[30]), "+f"(d[31]),
      "+f"(d[32]), "+f"(d[33]), "+f"(d[34]), "+f"(d[35]), "+f"(d[36]), "+f"(d[37]), "+f"(d[38]), "+f"(d[39]),
      "+f"(d[40]), "+f"(d[41]), "+f"(d[42]), "+f"(d[43]), "+f"(d[44]), "+f"(d[45]), "+f"(d[46]), "+f"(d[47]),
      "+f"(d[48]), "+f"(d[49]), "+f"(d[50]), "+f"(d[51]), "+f"(d[52]), "+f"(d[53]), "+f"(d[54]), "+f"(d[55]),
      "+f"(d[56]), "+f"(d[57]), "+f"(d[58]), "+f"(d[59]), "+f"(d[60]), "+f"(d[61]), "+f"(d[62]), "+f"(d[63])
    : "r"(a[0]), "r"(a[1]), "r"(a[2]), "r"(a[3]), "r"(lo), "r"(sd), "n"(OFF), "n"(HI));
}

template <int OFF, uint32_t HI>
__device__ __forceinline__ void wgmma_rs_n224_tb1(float (&d)[112], const uint32_t (&a)[4], uint32_t lo, int sd) {
  asm volatile("{\n.reg .pred p;\n.reg .b32 l;\n.reg .b64 db;\nsetp.ne.b32 p, %117, 0;\n"
    "add.u32 l, %116, %118;\nmov.b64 db, {l, %119};\n"
    "wgmma.mma_async.sync.aligned.m64n224k16.f32.bf16.bf16 "
    "{%0,%1,%2,%3,%4,%5,%6,%7,%8,%9,%10,%11,%12,%13,%14,%15,"
    "%16,%17,%18,%19,%20,%21,%22,%23,%24,%25,%26,%27,%28,%29,%30,%31,"
    "%32,%33,%34,%35,%36,%37,%38,%39,%40,%41,%42,%43,%44,%45,%46,%47,"
    "%48,%49,%50,%51,%52,%53,%54,%55,%56,%57,%58,%59,%60,%61,%62,%63,"
    "%64,%65,%66,%67,%68,%69,%70,%71,%72,%73,%74,%75,%76,%77,%78,%79,"
    "%80,%81,%82,%83,%84,%85,%86,%87,%88,%89,%90,%91,%92,%93,%94,%95,"
    "%96,%97,%98,%99,%100,%101,%102,%103,%104,%105,%106,%107,%108,%109,%110,%111}, "
    "{%112,%113,%114,%115}, db, p, 1, 1, 1;\n}\n"
    : "+f"(d[0]), "+f"(d[1]), "+f"(d[2]), "+f"(d[3]), "+f"(d[4]), "+f"(d[5]), "+f"(d[6]), "+f"(d[7]),
      "+f"(d[8]), "+f"(d[9]), "+f"(d[10]), "+f"(d[11]), "+f"(d[12]), "+f"(d[13]), "+f"(d[14]), "+f"(d[15]),
      "+f"(d[16]), "+f"(d[17]), "+f"(d[18]), "+f"(d[19]), "+f"(d[20]), "+f"(d[21]), "+f"(d[22]), "+f"(d[23]),
      "+f"(d[24]), "+f"(d[25]), "+f"(d[26]), "+f"(d[27]), "+f"(d[28]), "+f"(d[29]), "+f"(d[30]), "+f"(d[31]),
      "+f"(d[32]), "+f"(d[33]), "+f"(d[34]), "+f"(d[35]), "+f"(d[36]), "+f"(d[37]), "+f"(d[38]), "+f"(d[39]),
      "+f"(d[40]), "+f"(d[41]), "+f"(d[42]), "+f"(d[43]), "+f"(d[44]), "+f"(d[45]), "+f"(d[46]), "+f"(d[47]),
      "+f"(d[48]), "+f"(d[49]), "+f"(d[50]), "+f"(d[51]), "+f"(d[52]), "+f"(d[53]), "+f"(d[54]), "+f"(d[55]),
      "+f"(d[56]), "+f"(d[57]), "+f"(d[58]), "+f"(d[59]), "+f"(d[60]), "+f"(d[61]), "+f"(d[62]), "+f"(d[63]),
      "+f"(d[64]), "+f"(d[65]), "+f"(d[66]), "+f"(d[67]), "+f"(d[68]), "+f"(d[69]), "+f"(d[70]), "+f"(d[71]),
      "+f"(d[72]), "+f"(d[73]), "+f"(d[74]), "+f"(d[75]), "+f"(d[76]), "+f"(d[77]), "+f"(d[78]), "+f"(d[79]),
      "+f"(d[80]), "+f"(d[81]), "+f"(d[82]), "+f"(d[83]), "+f"(d[84]), "+f"(d[85]), "+f"(d[86]), "+f"(d[87]),
      "+f"(d[88]), "+f"(d[89]), "+f"(d[90]), "+f"(d[91]), "+f"(d[92]), "+f"(d[93]), "+f"(d[94]), "+f"(d[95]),
      "+f"(d[96]), "+f"(d[97]), "+f"(d[98]), "+f"(d[99]), "+f"(d[100]), "+f"(d[101]), "+f"(d[102]), "+f"(d[103]),
      "+f"(d[104]), "+f"(d[105]), "+f"(d[106]), "+f"(d[107]), "+f"(d[108]), "+f"(d[109]), "+f"(d[110]), "+f"(d[111])
    : "r"(a[0]), "r"(a[1]), "r"(a[2]), "r"(a[3]), "r"(lo), "r"(sd), "n"(OFF), "n"(HI));
}

template <int STR>
__device__ __forceinline__ void verify8_tag1(const uint4* p, uint32_t (*r)[4]) {
  asm volatile("{\n.reg .pred p, q;\n.reg .b32 a, n;\nmov.u32 n, 0;\n"
    "LAB_CHK:\n"
    "and.b32 a, %0, %4;\n"
    "and.b32 a, a, %8;\n"
    "and.b32 a, a, %12;\n"
    "and.b32 a, a, %16;\n"
    "and.b32 a, a, %20;\n"
    "and.b32 a, a, %24;\n"
    "and.b32 a, a, %28;\n"
    "and.b32 a, a, 1;\nsetp.eq.u32 p, a, 1;\nvote.sync.all.pred p, p, 0xffffffff;\n"
    "@p bra.uni LAB_OK;\n"
    "ld.relaxed.gpu.global.v4.b32 {%0,%1,%2,%3}, [%32+%33];\n"
    "ld.relaxed.gpu.global.v4.b32 {%4,%5,%6,%7}, [%32+%34];\n"
    "ld.relaxed.gpu.global.v4.b32 {%8,%9,%10,%11}, [%32+%35];\n"
    "ld.relaxed.gpu.global.v4.b32 {%12,%13,%14,%15}, [%32+%36];\n"
    "ld.relaxed.gpu.global.v4.b32 {%16,%17,%18,%19}, [%32+%37];\n"
    "ld.relaxed.gpu.global.v4.b32 {%20,%21,%22,%23}, [%32+%38];\n"
    "ld.relaxed.gpu.global.v4.b32 {%24,%25,%26,%27}, [%32+%39];\n"
    "ld.relaxed.gpu.global.v4.b32 {%28,%29,%30,%31}, [%32+%40];\n"
    "add.u32 n, n, 1;\nsetp.lt.u32 q, n, 262144;\n@q bra.uni LAB_CHK;\n"
    "LAB_OK:\n"
    "}\n"
    : "+r"(r[0][0]), "+r"(r[0][1]), "+r"(r[0][2]), "+r"(r[0][3]), "+r"(r[1][0]), "+r"(r[1][1]), "+r"(r[1][2]), "+r"(r[1][3]),
      "+r"(r[2][0]), "+r"(r[2][1]), "+r"(r[2][2]), "+r"(r[2][3]), "+r"(r[3][0]), "+r"(r[3][1]), "+r"(r[3][2]), "+r"(r[3][3]),
      "+r"(r[4][0]), "+r"(r[4][1]), "+r"(r[4][2]), "+r"(r[4][3]), "+r"(r[5][0]), "+r"(r[5][1]), "+r"(r[5][2]), "+r"(r[5][3]),
      "+r"(r[6][0]), "+r"(r[6][1]), "+r"(r[6][2]), "+r"(r[6][3]), "+r"(r[7][0]), "+r"(r[7][1]), "+r"(r[7][2]), "+r"(r[7][3])
    : "l"(p), "n"(0 * STR), "n"(1 * STR), "n"(2 * STR), "n"(3 * STR), "n"(4 * STR), "n"(5 * STR), "n"(6 * STR), "n"(7 * STR)
    : "memory");
}

template <int STR>
__device__ __forceinline__ void verify8_tag0(const uint4* p, uint32_t (*r)[4]) {
  asm volatile("{\n.reg .pred p, q;\n.reg .b32 a, n;\nmov.u32 n, 0;\n"
    "LAB_CHK:\n"
    "or.b32 a, %0, %4;\n"
    "or.b32 a, a, %8;\n"
    "or.b32 a, a, %12;\n"
    "or.b32 a, a, %16;\n"
    "or.b32 a, a, %20;\n"
    "or.b32 a, a, %24;\n"
    "or.b32 a, a, %28;\n"
    "and.b32 a, a, 1;\nsetp.eq.u32 p, a, 0;\nvote.sync.all.pred p, p, 0xffffffff;\n"
    "@p bra.uni LAB_OK;\n"
    "ld.relaxed.gpu.global.v4.b32 {%0,%1,%2,%3}, [%32+%33];\n"
    "ld.relaxed.gpu.global.v4.b32 {%4,%5,%6,%7}, [%32+%34];\n"
    "ld.relaxed.gpu.global.v4.b32 {%8,%9,%10,%11}, [%32+%35];\n"
    "ld.relaxed.gpu.global.v4.b32 {%12,%13,%14,%15}, [%32+%36];\n"
    "ld.relaxed.gpu.global.v4.b32 {%16,%17,%18,%19}, [%32+%37];\n"
    "ld.relaxed.gpu.global.v4.b32 {%20,%21,%22,%23}, [%32+%38];\n"
    "ld.relaxed.gpu.global.v4.b32 {%24,%25,%26,%27}, [%32+%39];\n"
    "ld.relaxed.gpu.global.v4.b32 {%28,%29,%30,%31}, [%32+%40];\n"
    "add.u32 n, n, 1;\nsetp.lt.u32 q, n, 262144;\n@q bra.uni LAB_CHK;\n"
    "LAB_OK:\n"
    "or.b32 %0, %0, 1;\n"
    "or.b32 %4, %4, 1;\n"
    "or.b32 %8, %8, 1;\n"
    "or.b32 %12, %12, 1;\n"
    "or.b32 %16, %16, 1;\n"
    "or.b32 %20, %20, 1;\n"
    "or.b32 %24, %24, 1;\n"
    "or.b32 %28, %28, 1;\n"
    "}\n"
    : "+r"(r[0][0]), "+r"(r[0][1]), "+r"(r[0][2]), "+r"(r[0][3]), "+r"(r[1][0]), "+r"(r[1][1]), "+r"(r[1][2]), "+r"(r[1][3]),
      "+r"(r[2][0]), "+r"(r[2][1]), "+r"(r[2][2]), "+r"(r[2][3]), "+r"(r[3][0]), "+r"(r[3][1]), "+r"(r[3][2]), "+r"(r[3][3]),
      "+r"(r[4][0]), "+r"(r[4][1]), "+r"(r[4][2]), "+r"(r[4][3]), "+r"(r[5][0]), "+r"(r[5][1]), "+r"(r[5][2]), "+r"(r[5][3]),
      "+r"(r[6][0]), "+r"(r[6][1]), "+r"(r[6][2]), "+r"(r[6][3]), "+r"(r[7][0]), "+r"(r[7][1]), "+r"(r[7][2]), "+r"(r[7][3])
    : "l"(p), "n"(0 * STR), "n"(1 * STR), "n"(2 * STR), "n"(3 * STR), "n"(4 * STR), "n"(5 * STR), "n"(6 * STR), "n"(7 * STR)
    : "memory");
}

template <int STR>
__device__ __forceinline__ void verify4_tag0(const uint4* p, uint32_t (*r)[4]) {
  asm volatile("{\n.reg .pred p, q;\n.reg .b32 a, n;\nmov.u32 n, 0;\n"
    "LAB_CHK:\n"
    "or.b32 a, %0, %4;\n"
    "or.b32 a, a, %8;\n"
    "or.b32 a, a, %12;\n"
    "and.b32 a, a, 1;\nsetp.eq.u32 p, a, 0;\nvote.sync.all.pred p, p, 0xffffffff;\n"
    "@p bra.uni LAB_OK;\n"
    "ld.relaxed.gpu.global.v4.b32 {%0,%1,%2,%3}, [%16+%17];\n"
    "ld.relaxed.gpu.global.v4.b32 {%4,%5,%6,%7}, [%16+%18];\n"
    "ld.relaxed.gpu.global.v4.b32 {%8,%9,%10,%11}, [%16+%19];\n"
    "ld.relaxed.gpu.global.v4.b32 {%12,%13,%14,%15}, [%16+%20];\n"
    "add.u32 n, n, 1;\nsetp.lt.u32 q, n, 262144;\n@q bra.uni LAB_CHK;\n"
    "LAB_OK:\n"
    "or.b32 %0, %0, 1;\n"
    "or.b32 %4, %4, 1;\n"
    "or.b32 %8, %8, 1;\n"
    "or.b32 %12, %12, 1;\n"
    "}\n"
    : "+r"(r[0][0]), "+r"(r[0][1]), "+r"(r[0][2]), "+r"(r[0][3]), "+r"(r[1][0]), "+r"(r[1][1]), "+r"(r[1][2]), "+r"(r[1][3]),
      "+r"(r[2][0]), "+r"(r[2][1]), "+r"(r[2][2]), "+r"(r[2][3]), "+r"(r[3][0]), "+r"(r[3][1]), "+r"(r[3][2]), "+r"(r[3][3])
    : "l"(p), "n"(0 * STR), "n"(1 * STR), "n"(2 * STR), "n"(3 * STR)
    : "memory");
}

#define SPIN_LIMIT (1 << 18)

__device__ __forceinline__ uint32_t smem_u32(const void* p) { return (uint32_t)__cvta_generic_to_shared(p); }
__device__ __forceinline__ void mbar_init(uint32_t a, uint32_t c) {
  asm volatile("mbarrier.init.shared::cta.b64 [%0], %1;" ::"r"(a), "r"(c) : "memory");
}
__device__ __forceinline__ void mbar_expect(uint32_t a, uint32_t b) {
  asm volatile("mbarrier.arrive.expect_tx.shared::cta.b64 _, [%0], %1;" ::"r"(a), "r"(b) : "memory");
}
__device__ __forceinline__ void mbar_arrive(uint32_t a) {
  asm volatile("mbarrier.arrive.shared::cta.b64 _, [%0];" ::"r"(a) : "memory");
}
__device__ __forceinline__ void mbar_wait(uint32_t a, uint32_t parity) {
  asm volatile(
      "{\n.reg .pred p;\n.reg .u32 n;\nmov.u32 n, 0;\n"
      "LAB_WAIT:\n"
      "mbarrier.try_wait.parity.shared::cta.b64 p, [%0], %1;\n"
      "@p bra LAB_DONE;\n"
      "add.u32 n, n, 1;\n"
      "setp.lt.u32 p, n, 262144;\n"
      "@p bra LAB_WAIT;\n"
      "LAB_DONE:\n}\n" ::"r"(a), "r"(parity) : "memory");
}
__device__ __forceinline__ void tma3d(uint32_t dst, const CUtensorMap* tm, uint32_t bar, int c0, int c1, int c2) {
  asm volatile(
      "cp.async.bulk.tensor.3d.shared::cluster.global.mbarrier::complete_tx::bytes [%0], [%1, {%3,%4,%5}], [%2];"
      ::"r"(dst), "l"(tm), "r"(bar), "r"(c0), "r"(c1), "r"(c2) : "memory");
}
__device__ __forceinline__ void wg_fence() { asm volatile("wgmma.fence.sync.aligned;" ::: "memory"); }
__device__ __forceinline__ void wg_commit() { asm volatile("wgmma.commit_group.sync.aligned;" ::: "memory"); }
template <int N> __device__ __forceinline__ void wg_wait() {
  asm volatile("wgmma.wait_group.sync.aligned %0;" ::"n"(N) : "memory");
}
template <int N> __device__ __forceinline__ void fence_regs(float (&d)[N]) {
#pragma unroll
  for (int i = 0; i < N; i++) asm volatile("" : "+f"(d[i])::"memory");
}
template <int N> __device__ __forceinline__ void fence_regs(uint32_t (&d)[N][4]) {
#pragma unroll
  for (int i = 0; i < N; i++) asm volatile("" : "+r"(d[i][0]), "+r"(d[i][1]), "+r"(d[i][2]), "+r"(d[i][3])::"memory");
}
template <int N> __device__ __forceinline__ void fence_frags(uint32_t (*d)[4]) {
#pragma unroll
  for (int i = 0; i < N; i++) asm volatile("" : "+r"(d[i][0]), "+r"(d[i][1]), "+r"(d[i][2]), "+r"(d[i][3])::"memory");
}
__device__ __forceinline__ void bar_sync(int id, int n) { asm volatile("bar.sync %0, %1;" ::"r"(id), "r"(n) : "memory"); }
__device__ __forceinline__ void bar_arrive(int id, int n) { asm volatile("bar.arrive %0, %1;" ::"r"(id), "r"(n) : "memory"); }

__device__ __forceinline__ uint32_t pack_bf16(float lo, float hi) {
  uint32_t r;
  asm("cvt.rn.bf16x2.f32 %0, %1, %2;" : "=r"(r) : "f"(hi), "f"(lo));
  return r;
}
__device__ __forceinline__ float bf_lo(uint32_t w) { return __uint_as_float(w << 16); }
__device__ __forceinline__ float bf_hi(uint32_t w) { return __uint_as_float(w & 0xFFFF0000u); }
__device__ __forceinline__ float round_bf16(float x) { return bf_lo(pack_bf16(x, 0.f)); }
__device__ __forceinline__ uint32_t hfma2_bf16(uint32_t a, uint32_t b, uint32_t c) {
  uint32_t r;
  asm("fma.rn.bf16x2 %0, %1, %2, %3;" : "=r"(r) : "r"(a), "r"(b), "r"(c));
  return r;
}
__device__ __forceinline__ float ex2(float x) {
  float r;
  asm("ex2.approx.ftz.f32 %0, %1;" : "=f"(r) : "f"(x));
  return r;
}
__device__ __forceinline__ float tanh_hw(float x) {
  float r;
  asm("tanh.approx.f32 %0, %1;" : "=f"(r) : "f"(x));
  return r;
}
template <int TAG> __device__ __forceinline__ uint32_t pack_tag(float lo, float hi) {
  uint32_t w = __byte_perm(__float_as_uint(lo), pack_bf16(lo, hi), 0x7632);
  return TAG ? (w | 1u) : (w & ~1u);
}
__device__ __forceinline__ void st_pkt(uint4* p, uint32_t a, uint32_t b, uint32_t c, uint32_t d) {
  asm volatile(
      "st.relaxed.gpu.global.v4.b32 [%0], {%1,%2,%3,%4};" ::"l"(p), "r"(a), "r"(b), "r"(c), "r"(d) : "memory");
}
__device__ __forceinline__ void ld_pkt(const uint4* p, uint32_t (&r)[4]) {
  asm volatile(
      "ld.relaxed.gpu.global.v4.b32 {%0,%1,%2,%3}, [%4];"
      : "=r"(r[0]), "=r"(r[1]), "=r"(r[2]), "=r"(r[3]) : "l"(p) : "memory");
}
__device__ __forceinline__ uint32_t ldg32(const void* p) {
  uint32_t r;
  asm volatile("ld.global.nc.b32 %0, [%1];" : "=r"(r) : "l"(p));
  return r;
}
__device__ __forceinline__ uint32_t ldg16(const void* p) {
  uint16_t r;
  asm volatile("ld.global.nc.b16 %0, [%1];" : "=h"(r) : "l"(p));
  return r;
}
__device__ __forceinline__ uint4 ldg128(const void* p) {
  uint4 r;
  asm volatile("ld.global.nc.v4.b32 {%0,%1,%2,%3}, [%4];" : "=r"(r.x), "=r"(r.y), "=r"(r.z), "=r"(r.w) : "l"(p));
  return r;
}
__device__ __forceinline__ float rcp_hw(float x) {
  float r;
  asm("rcp.approx.ftz.f32 %0, %1;" : "=f"(r) : "f"(x));
  return r;
}
__device__ __forceinline__ void warp_bulk_store(void* gdst, uint32_t ssrc, uint32_t bytes) {
  asm volatile("fence.proxy.async.shared::cta;" ::: "memory");
  __syncwarp();
  if ((threadIdx.x & 31) == 0) {
    asm volatile("cp.async.bulk.global.shared::cta.bulk_group [%0], [%1], %2;" ::"l"(gdst), "r"(ssrc), "r"(bytes) : "memory");
    asm volatile("cp.async.bulk.commit_group;" ::: "memory");
  }
}
template <int N> __device__ __forceinline__ void warp_bulk_wait_read() {
  if ((threadIdx.x & 31) == 0) asm volatile("cp.async.bulk.wait_group.read %0;" ::"n"(N) : "memory");
  __syncwarp();
}
__device__ __forceinline__ void sts128(uint32_t a, uint32_t x, uint32_t y, uint32_t z, uint32_t w) {
  asm volatile("st.shared.v4.b32 [%0], {%1,%2,%3,%4};" ::"r"(a), "r"(x), "r"(y), "r"(z), "r"(w) : "memory");
}
__device__ __forceinline__ void lds128(uint32_t a, uint32_t (&r)[4]) {
  asm volatile("ld.shared.v4.b32 {%0,%1,%2,%3}, [%4];" : "=r"(r[0]), "=r"(r[1]), "=r"(r[2]), "=r"(r[3]) : "r"(a) : "memory");
}

constexpr int SK = 2048, WIN = 512;
constexpr int FF = 1792, FSL = 224;
constexpr int NTILES = 80;
constexpr int NSLOT = 4;
constexpr uint32_t SLOT = 32768;
constexpr uint32_t SM_PARK = 0;
constexpr uint32_t SM_RING = 3 * SLOT;
constexpr uint32_t SM_TAB = 7 * SLOT;
constexpr uint32_t SM_RED = SM_TAB + 2048;
constexpr uint32_t SM_BAR = SM_RED + 256;
constexpr uint32_t SM_TOTAL = SM_BAR + 128;

__device__ uint4 g_P[16 * 8 * 8 * 32 * 32];
__device__ uint4 g_G[16 * 8 * 32 * 32];
__device__ uint4 g_mod1[8 * 256];
__device__ uint4 g_mod2[512];
__device__ uint32_t g_epoch;

#define TS(i) do { } while (0)

struct Params {
  const __nv_bfloat16* x;
  const __nv_bfloat16* c;
  const __nv_bfloat16* wmod;
  __nv_bfloat16* out;
};

constexpr uint32_t HI128 = (1024 >> 4) | (1u << 30);
constexpr uint32_t HI64 = (512 >> 4) | (2u << 30);
constexpr int LB_MN128 = (16384 >> 4) << 16;
constexpr int LB_K128 = 1 << 16;
constexpr int LB_W1 = (4096 >> 4) << 16;
constexpr int LB_W2 = (14336 >> 4) << 16;

template <int I> struct IC {
  __host__ __device__ constexpr operator int() const { return I; }
};
template <int I, int N, typename F> __device__ __forceinline__ void static_for(F&& f) {
  if constexpr (I < N) {
    f(IC<I>{});
    static_for<I + 1, N>(f);
  }
}

struct Ring {
  uint32_t base16, bars;
  __device__ __forceinline__ uint32_t wait_full(uint32_t slot, uint32_t parity) const {
    mbar_wait(bars + slot * 8, parity);
    return base16 + slot * (SLOT >> 4);
  }
  __device__ __forceinline__ void release(uint32_t slot) const {
    if ((threadIdx.x & 31) == 0) mbar_arrive(bars + 32 + slot * 8);
  }
};

__device__ __forceinline__ float silu_c(uint32_t bits) {
  float x = bf_lo(bits);
  return round_bf16(x * rcp_hw(1.f + ex2(-1.4426950408889634f * x)));
}
__device__ __forceinline__ void pack8(uint32_t (&o)[4], const float* v) {
  o[0] = pack_bf16(v[0], v[1]); o[1] = pack_bf16(v[2], v[3]); o[2] = pack_bf16(v[4], v[5]); o[3] = pack_bf16(v[6], v[7]);
}

template <int TAG, int N>
__device__ __forceinline__ void issue_pkts(const uint4* p, int stride, uint32_t (*r)[4]) {
#pragma unroll
  for (int i = 0; i < N; i++) ld_pkt(p + i * stride, r[i]);
}
__device__ __forceinline__ void ld_mod(const uint4* p, uint32_t tag, uint32_t (&r)[4]) {
  int spins = 0;
  ld_pkt(p, r);
  while (r[2] != tag && ++spins < SPIN_LIMIT) ld_pkt(p, r);
}

#define EARLY_TILES 3

__global__ void __launch_bounds__(384, 1)
adaln_block_kernel(const __grid_constant__ CUtensorMap tmWq, const __grid_constant__ CUtensorMap tmK,
                   const __grid_constant__ CUtensorMap tmV, const __grid_constant__ CUtensorMap tmWo,
                   const __grid_constant__ CUtensorMap tmW1, const __grid_constant__ CUtensorMap tmW2,
                   const Params p) {
  extern __shared__ __align__(1024) uint8_t smem_raw[];
  const uint32_t sb = smem_u32(smem_raw);
  const int tid = threadIdx.x, lane = tid & 31;
  const int warp = __shfl_sync(0xffffffffu, tid >> 5, 0);
  const int bid = blockIdx.x, j = bid >> 4, rt = bid & 15;
  const uint32_t bars = sb + SM_BAR;

  if (warp >= 8) {
    asm volatile("setmaxnreg.dec.sync.aligned.u32 40;");
    const int t = tid - 256;
    uint32_t tag;
    {
      uint4 w[4];
      uint32_t cb[4];
#pragma unroll
      for (int i = 0; i < 4; i++) w[i] = ldg128(p.wmod + (size_t)(t + 128 * i) * 3072 + bid * 8);
#pragma unroll
      for (int i = 0; i < 4; i++) cb[i] = ldg16(p.c + t + 128 * i);
      asm volatile("ld.relaxed.gpu.global.u32 %0, [%1];" : "=r"(tag) : "l"(&g_epoch) : "memory");
      if (t == 0) {
        asm volatile("prefetch.tensormap [%0];" ::"l"(&tmWq) : "memory");
        for (int i = 0; i < NSLOT; i++) { mbar_init(bars + i * 8, 1); mbar_init(bars + 32 + i * 8, 8); }
        asm volatile("fence.mbarrier_init.release.cluster;" ::: "memory");
        asm volatile("fence.proxy.async.shared::cta;" ::: "memory");
      }
      __syncthreads();
      if (t == 0) {
#pragma unroll
        for (int i = 0; i < EARLY_TILES; i++) {
          mbar_expect(bars + i * 8, SLOT);
          tma3d(sb + SM_RING + i * SLOT, &tmWq, bars + i * 8, 0, i * 128, (j * 4 + 1) * 2);
        }
      }
      __syncwarp();
      TS(0);
      tag += 1;
      float a[8];
#pragma unroll
      for (int k = 0; k < 8; k++) a[k] = 0.f;
#pragma unroll
      for (int i = 0; i < 4; i++) {
        const float s = silu_c(cb[i]);
        a[0] = fmaf(s, bf_lo(w[i].x), a[0]); a[1] = fmaf(s, bf_hi(w[i].x), a[1]);
        a[2] = fmaf(s, bf_lo(w[i].y), a[2]); a[3] = fmaf(s, bf_hi(w[i].y), a[3]);
        a[4] = fmaf(s, bf_lo(w[i].z), a[4]); a[5] = fmaf(s, bf_hi(w[i].z), a[5]);
        a[6] = fmaf(s, bf_lo(w[i].w), a[6]); a[7] = fmaf(s, bf_hi(w[i].w), a[7]);
      }
      const bool h16 = lane & 16, h8 = lane & 8, h4 = lane & 4;
#pragma unroll
      for (int k = 0; k < 4; k++) {
        float send = h16 ? a[k] : a[k + 4], keep = h16 ? a[k + 4] : a[k];
        a[k] = keep + __shfl_xor_sync(0xffffffffu, send, 16);
      }
#pragma unroll
      for (int k = 0; k < 2; k++) {
        float send = h8 ? a[k] : a[k + 2], keep = h8 ? a[k + 2] : a[k];
        a[k] = keep + __shfl_xor_sync(0xffffffffu, send, 8);
      }
      {
        float send = h4 ? a[0] : a[1], keep = h4 ? a[1] : a[0];
        a[0] = keep + __shfl_xor_sync(0xffffffffu, send, 4);
      }
      a[0] += __shfl_xor_sync(0xffffffffu, a[0], 2);
      a[0] += __shfl_xor_sync(0xffffffffu, a[0], 1);
      float* red = (float*)(smem_raw + SM_RED);
      if ((lane & 3) == 0) red[(warp - 8) * 8 + (lane >> 2)] = a[0];
      if (t == 0) *(uint32_t*)(smem_raw + SM_BAR + 64) = tag;
      bar_sync(5, 128);
      TS(1);
      if (warp == 9) {
        const int cl = lane & 7;
        float v = round_bf16(red[cl] + red[8 + cl] + red[16 + cl] + red[24 + cl]);
        if (bid >= 64) v = 1.f + v;
        float vn = __shfl_down_sync(0xffffffffu, v, 1);
        uint32_t wd = pack_bf16(v, vn);
        uint32_t w0 = __shfl_sync(0xffffffffu, wd, (lane & 1) * 4);
        uint32_t w1 = __shfl_sync(0xffffffffu, wd, (lane & 1) * 4 + 2);
        if (lane < 16) st_pkt(&g_mod1[(lane >> 1) * 256 + bid * 2 + (lane & 1)], w0, w1, tag, 0);
      }
      uint32_t r0[4], r1[4];
      const uint4* src = &g_mod1[j * 256 + t];
      int spins = 0;
      do {
        ld_pkt(src, r0);
        ld_pkt(src + 128, r1);
      } while ((r0[2] != tag || r1[2] != tag) && ++spins < SPIN_LIMIT);
      const int g = t >> 2, pp = (t & 3) * 2;
      const uint32_t ad = sb + SM_TAB + (uint32_t)(g * 4 + (pp & 3)) * 16 + (pp >> 2) * 4;
      asm volatile("st.shared.b32 [%0], %1;" ::"r"(ad + 8), "r"(r0[0]) : "memory");
      asm volatile("st.shared.b32 [%0], %1;" ::"r"(ad + 24), "r"(r0[1]) : "memory");
      asm volatile("st.shared.b32 [%0], %1;" ::"r"(ad), "r"(r1[0]) : "memory");
      asm volatile("st.shared.b32 [%0], %1;" ::"r"(ad + 16), "r"(r1[1]) : "memory");
      bar_arrive(1, 384);
      TS(2);
    }
    if (warp == 8) {
      if (lane == 0) {
        uint32_t s = EARLY_TILES & 3, ph = 1 ^ (EARLY_TILES >> 2);
#pragma unroll 1
        for (int tt = EARLY_TILES; tt < NTILES; tt++) {
          const CUtensorMap* tm;
          int c1, c2;
          uint32_t bytes = SLOT;
          if (tt < 16) {
            tm = &tmWq; c1 = (tt & 3) * 128; c2 = (j * 4 + (((tt >> 2) + 1) & 3)) * 2;
          } else if (tt < 48) {
            const int u = tt - 16;
            const bool isK = (u == 0) || ((u & 1) && u != 31);
            const int n = isK ? ((u + 1) >> 1) : (u == 31 ? 15 : (u >> 1) - 1);
            tm = isK ? &tmK : &tmV; c1 = j * SK + (SK - WIN) + (n & 3) * 128; c2 = 0;
          } else if (tt < 64) {
            const int u = tt - 48;
            tm = &tmWo; c1 = j * 512 + (u & 3) * 128; c2 = (u >> 2) * 2;
          } else if (tt < 72) {
            tm = &tmW1; c1 = (tt - 64) * 64; c2 = j * 7; bytes = 28672;
          } else {
            const int u = tt - 72;
            tm = &tmW2; c1 = j * FSL + (u & 1) * 112; c2 = (u >> 1) * 2; bytes = 28672;
          }
          mbar_wait(bars + 32 + s * 8, ph);
          mbar_expect(bars + s * 8, bytes);
          tma3d(sb + SM_RING + s * SLOT, tm, bars + s * 8, 0, c1, c2);
          if (++s == (tt < 48 ? 4u : 3u)) { s = 0; ph ^= 1; }
        }
      }
    } else if (warp >= 10) {
      const int t2 = tid - 320, hf = t2 & 1, r0 = t2 >> 1;
      float a[8];
#pragma unroll
      for (int k = 0; k < 8; k++) a[k] = 0.f;
#pragma unroll 1
      for (int b = 0; b < 8; b++) {
        uint4 w[2];
        uint32_t cb[2];
#pragma unroll
        for (int i = 0; i < 2; i++) {
          w[i] = ldg128(p.wmod + (size_t)(r0 + 32 * (2 * b + i)) * 3072 + 1024 + bid * 16 + hf * 8);
          cb[i] = ldg16(p.c + r0 + 32 * (2 * b + i));
        }
#pragma unroll
        for (int i = 0; i < 2; i++) {
          const float s = silu_c(cb[i]);
          a[0] = fmaf(s, bf_lo(w[i].x), a[0]); a[1] = fmaf(s, bf_hi(w[i].x), a[1]);
          a[2] = fmaf(s, bf_lo(w[i].y), a[2]); a[3] = fmaf(s, bf_hi(w[i].y), a[3]);
          a[4] = fmaf(s, bf_lo(w[i].z), a[4]); a[5] = fmaf(s, bf_hi(w[i].z), a[5]);
          a[6] = fmaf(s, bf_lo(w[i].w), a[6]); a[7] = fmaf(s, bf_hi(w[i].w), a[7]);
        }
      }
      const bool h16 = lane & 16, h8 = lane & 8, h4 = lane & 4;
#pragma unroll
      for (int k = 0; k < 4; k++) {
        float send = h16 ? a[k] : a[k + 4], keep = h16 ? a[k + 4] : a[k];
        a[k] = keep + __shfl_xor_sync(0xffffffffu, send, 16);
      }
#pragma unroll
      for (int k = 0; k < 2; k++) {
        float send = h8 ? a[k] : a[k + 2], keep = h8 ? a[k + 2] : a[k];
        a[k] = keep + __shfl_xor_sync(0xffffffffu, send, 8);
      }
      {
        float send = h4 ? a[0] : a[1], keep = h4 ? a[1] : a[0];
        a[0] = keep + __shfl_xor_sync(0xffffffffu, send, 4);
      }
      a[0] += __shfl_xor_sync(0xffffffffu, a[0], 2);
      float* red = (float*)(smem_raw + SM_RED) + 32;
      if ((lane & 2) == 0) red[(warp - 10) * 16 + hf * 8 + (lane >> 2)] = a[0];
      bar_sync(4, 64);
      if (warp == 10) {
        const int cl = lane & 15;
        float v = round_bf16(red[cl] + red[16 + cl]);
        if ((bid >> 5) == 2) v = 1.f + v;
        float vn = __shfl_down_sync(0xffffffffu, v, 1);
        uint32_t wd = pack_bf16(v, vn);
        uint32_t w0 = __shfl_sync(0xffffffffu, wd, (lane & 3) * 2);
        uint32_t w1 = __shfl_sync(0xffffffffu, wd, (lane & 3) * 2 + 8);
        if (lane < 4) st_pkt(&g_mod2[bid * 4 + lane], w0, w1, tag, 0);
      }
    }
  } else {
    const int wg = warp >> 2;
    const int q = lane & 3, gq = lane >> 2;
    const Ring ring{(sb + SM_RING) >> 4, bars};
    const uint32_t xoff = (uint32_t)(rt * 128 + 16 * j + warp) * 256 + gq * 8 + q;
    const uint32_t ooff = ((uint32_t)(rt * 8 + j) * 32 + gq) * 32 + warp * 4 + q;
    const uint32_t goff = (uint32_t)(rt * 8 + warp) * 1024 + lane;

    {
      const uint32_t* xo = (const uint32_t*)p.x + xoff;
      uint32_t xr[4][4];
#pragma unroll
      for (int c = 0; c < 4; c++) {
        xr[c][0] = ldg32(xo + c * 64);
        xr[c][1] = ldg32(xo + c * 64 + 8 * 256);
        xr[c][2] = ldg32(xo + c * 64 + 4);
        xr[c][3] = ldg32(xo + c * 64 + 4 + 8 * 256);
      }
      __syncthreads();
      float s0 = 0.f, s1 = 0.f, v0 = 0.f, v1 = 0.f;
#pragma unroll
      for (int c = 0; c < 4; c++) {
#pragma unroll
        for (int e = 0; e < 4; e++) {
          const float a = bf_lo(xr[c][e]), b = bf_hi(xr[c][e]);
          if (e & 1) { s1 += a + b; v1 = fmaf(a, a, fmaf(b, b, v1)); }
          else { s0 += a + b; v0 = fmaf(a, a, fmaf(b, b, v0)); }
        }
      }
#pragma unroll
      for (int o = 16; o > 0; o >>= 1) {
        s0 += __shfl_xor_sync(0xffffffffu, s0, o);
        s1 += __shfl_xor_sync(0xffffffffu, s1, o);
        v0 += __shfl_xor_sync(0xffffffffu, v0, o);
        v1 += __shfl_xor_sync(0xffffffffu, v1, o);
      }
      const float m0 = s0 * (1.f / 512.f), m1 = s1 * (1.f / 512.f);
      const float r0 = rsqrtf(fmaxf(fmaf(-m0, m0, v0 * (1.f / 512.f)), 0.f) + 1e-5f);
      const float r1 = rsqrtf(fmaxf(fmaf(-m1, m1, v1 * (1.f / 512.f)), 0.f) + 1e-5f);
#pragma unroll
      for (int c = 0; c < 4; c++) {
        st_pkt(g_G + ooff + c * 256,
               pack_tag<1>((bf_lo(xr[c][0]) - m0) * r0, (bf_hi(xr[c][0]) - m0) * r0),
               pack_bf16((bf_lo(xr[c][1]) - m1) * r1, (bf_hi(xr[c][1]) - m1) * r1),
               pack_bf16((bf_lo(xr[c][2]) - m0) * r0, (bf_hi(xr[c][2]) - m0) * r0),
               pack_bf16((bf_lo(xr[c][3]) - m1) * r1, (bf_hi(xr[c][3]) - m1) * r1));
      }
    }
    TS(0);
    asm volatile("setmaxnreg.inc.sync.aligned.u32 232;");
    uint32_t qf[8][4];
    {
      uint32_t h[32][4];
      float acc[64];
      const uint4* Gin = g_G + goff;
      issue_pkts<1, 8>(Gin, 32, h);
      verify8_tag1<512>(Gin, h);
      issue_pkts<1, 8>(Gin + 256, 32, h + 8);
      TS(1);
      bar_sync(1, 384);
#pragma unroll
      for (int c = 0; c < 4; c++) {
        if (c > 0) verify8_tag1<512>(Gin + c * 256, h + c * 8);
        if (c > 0 && c < 3) issue_pkts<1, 8>(Gin + (c + 1) * 256, 32, h + (c + 1) * 8);
#pragma unroll
        for (int i = 0; i < 8; i++) {
          uint32_t m[4];
          lds128(sb + SM_TAB + (uint32_t)((c * 8 + i) * 4 + q) * 16, m);
          uint32_t* hh = h[c * 8 + i];
          hh[0] = hfma2_bf16(hh[0], m[0], m[2]);
          hh[1] = hfma2_bf16(hh[1], m[0], m[2]);
          hh[2] = hfma2_bf16(hh[2], m[1], m[3]);
          hh[3] = hfma2_bf16(hh[3], m[1], m[3]);
        }
        fence_frags<8>(h + c * 8);
        const uint32_t b = ring.wait_full(c, 0);
        if (c > 0) { wg_wait<0>(); ring.release(c - 1); }
        if (c == 0) TS(2);
        wg_fence();
        static_for<0, 8>([&](auto K) { wgmma_rs_n128_tb1<LB_MN128 + K * 128, HI128>(acc, h[c * 8 + K], b, (c | K) != 0); });
        wg_commit();
      }
#pragma unroll 1
      for (int ps = 1; ps < 4; ps++) {
        wg_wait<0>();
        ring.release(3);
        fence_regs(acc);
#pragma unroll
        for (int i = 0; i < 8; i++) {
          uint32_t o[4];
          pack8(o, acc + 8 * i);
          sts128(sb + SM_PARK + (ps - 1) * SLOT + i * 4096 + tid * 16, o[0], o[1], o[2], o[3]);
        }
#pragma unroll
        for (int c = 0; c < 4; c++) {
          const uint32_t b = ring.wait_full(c, ps & 1);
          if (c > 0) { wg_wait<0>(); ring.release(c - 1); }
          wg_fence();
          static_for<0, 8>([&](auto K) { wgmma_rs_n128_tb1<LB_MN128 + K * 128, HI128>(acc, h[c * 8 + K], b, (c | K) != 0); });
          wg_commit();
        }
      }
      wg_wait<0>();
      ring.release(3);
      fence_regs(acc);
#pragma unroll
      for (int i = 0; i < 8; i++) pack8(qf[i], acc + 8 * i);
    }
    fence_regs(qf);
    TS(3);

    float S[64];
    {
      float O[64];
      uint32_t P[8][4];
      const float cs = 0.08838834764831845f * 1.4426950408889634f;
      const int TAU = 0x41800000;
      float m0, m1, l0, l1;

      auto first_block_max = [&]() {
        int a0 = __vimax3_s32(__float_as_int(S[0]), __float_as_int(S[1]), __float_as_int(S[1]));
        int a1 = __vimax3_s32(__float_as_int(S[2]), __float_as_int(S[3]), __float_as_int(S[3]));
#pragma unroll
        for (int i = 1; i < 16; i++) {
          a0 = __vimax3_s32(a0, __float_as_int(S[4 * i]), __float_as_int(S[4 * i + 1]));
          a1 = __vimax3_s32(a1, __float_as_int(S[4 * i + 2]), __float_as_int(S[4 * i + 3]));
        }
        a0 = max(a0, __shfl_xor_sync(0xffffffffu, a0, 1)); a1 = max(a1, __shfl_xor_sync(0xffffffffu, a1, 1));
        a0 = max(a0, __shfl_xor_sync(0xffffffffu, a0, 2)); a1 = max(a1, __shfl_xor_sync(0xffffffffu, a1, 2));
        float b0 = __int_as_float(a0), b1 = __int_as_float(a1);
        if (__any_sync(0xffffffffu, (a0 | a1) < 0)) {
          b0 = fmaxf(S[0], S[1]); b1 = fmaxf(S[2], S[3]);
#pragma unroll
          for (int i = 1; i < 16; i++) {
            b0 = fmaxf(b0, fmaxf(S[4 * i], S[4 * i + 1]));
            b1 = fmaxf(b1, fmaxf(S[4 * i + 2], S[4 * i + 3]));
          }
          b0 = fmaxf(b0, __shfl_xor_sync(0xffffffffu, b0, 1)); b1 = fmaxf(b1, __shfl_xor_sync(0xffffffffu, b1, 1));
          b0 = fmaxf(b0, __shfl_xor_sync(0xffffffffu, b0, 2)); b1 = fmaxf(b1, __shfl_xor_sync(0xffffffffu, b1, 2));
        }
        m0 = b0 * cs; m1 = b1 * cs;
      };
      auto scale_sub = [&]() {
#pragma unroll
        for (int i = 0; i < 16; i++) {
          S[4 * i] = fmaf(S[4 * i], cs, -m0); S[4 * i + 1] = fmaf(S[4 * i + 1], cs, -m0);
          S[4 * i + 2] = fmaf(S[4 * i + 2], cs, -m1); S[4 * i + 3] = fmaf(S[4 * i + 3], cs, -m1);
        }
      };
      auto exps = [&](int i0, int i1) {
#pragma unroll
        for (int i = i0; i < i1; i++) {
          S[4 * i] = ex2(S[4 * i]); S[4 * i + 1] = ex2(S[4 * i + 1]);
          S[4 * i + 2] = ex2(S[4 * i + 2]); S[4 * i + 3] = ex2(S[4 * i + 3]);
          l0 += S[4 * i]; l1 += S[4 * i + 2]; l0 += S[4 * i + 1]; l1 += S[4 * i + 3];
        }
      };
      {
        const uint32_t b = ring.wait_full(0, 0);
        wg_fence();
        static_for<0, 8>([&](auto K) { wgmma_rs_n128_tb0<LB_K128 + (K >> 2) * 1024 + (K & 3) * 2, HI128>(S, qf[K], b, K != 0); });
        wg_commit();
        wg_wait<0>();
        fence_regs(S);
        ring.release(0);
        first_block_max();
        scale_sub();
        l0 = 0.f; l1 = 0.f;
        exps(0, 16);
#pragma unroll
        for (int i = 0; i < 8; i++) pack8(P[i], S + 8 * i);
      }
      fence_regs(P);
      if (wg == 1) bar_arrive(2, 256);
#pragma unroll 1
      for (int n = 1; n < 16; n++) {
        const uint32_t tk = 2 * n - 1, tv = 2 * n;
        const bool newhead = (n & 3) == 0;
        const uint32_t bk = ring.wait_full(tk & 3, (tk >> 2) & 1);
        const uint32_t bv = ring.wait_full(tv & 3, (tv >> 2) & 1);
        bar_sync(2 + wg, 256);
        wg_fence();
        static_for<0, 8>([&](auto K) { wgmma_rs_n128_tb0<LB_K128 + (K >> 2) * 1024 + (K & 3) * 2, HI128>(S, qf[K], bk, K != 0); });
        wg_commit();
        static_for<0, 8>([&](auto K) { wgmma_rs_n128_tb1<LB_MN128 + K * 128, HI128>(O, P[K], bv, K != 0 || (n & 3) != 1); });
        wg_commit();
        bar_arrive(2 + (wg ^ 1), 256);
        wg_wait<1>();
        fence_regs(S);
        ring.release(tk & 3);
        if ((n & 3) == 3 && n != 15) {
          fence_regs(qf);
#pragma unroll
          for (int i = 0; i < 8; i++) lds128(sb + SM_PARK + (n >> 2) * SLOT + i * 4096 + tid * 16, qf[i]);
        }
        float f0 = 1.f, f1 = 1.f;
        bool resc = newhead;
        if (newhead) {
          l0 += __shfl_xor_sync(0xffffffffu, l0, 1); l1 += __shfl_xor_sync(0xffffffffu, l1, 1);
          l0 += __shfl_xor_sync(0xffffffffu, l0, 2); l1 += __shfl_xor_sync(0xffffffffu, l1, 2);
          f0 = rcp_hw(l0); f1 = rcp_hw(l1);
          l0 = 0.f; l1 = 0.f;
          first_block_max();
          scale_sub();
        } else {
          scale_sub();
          int a0 = __vimax3_s32(__float_as_int(S[0]), __float_as_int(S[1]), __float_as_int(S[1]));
          int a1 = __vimax3_s32(__float_as_int(S[2]), __float_as_int(S[3]), __float_as_int(S[3]));
#pragma unroll
          for (int i = 1; i < 16; i++) {
            a0 = __vimax3_s32(a0, __float_as_int(S[4 * i]), __float_as_int(S[4 * i + 1]));
            a1 = __vimax3_s32(a1, __float_as_int(S[4 * i + 2]), __float_as_int(S[4 * i + 3]));
          }
          if (__any_sync(0xffffffffu, max(a0, a1) > TAU)) {
            a0 = max(a0, 0); a1 = max(a1, 0);
            a0 = max(a0, __shfl_xor_sync(0xffffffffu, a0, 1)); a1 = max(a1, __shfl_xor_sync(0xffffffffu, a1, 1));
            a0 = max(a0, __shfl_xor_sync(0xffffffffu, a0, 2)); a1 = max(a1, __shfl_xor_sync(0xffffffffu, a1, 2));
            const float d0 = __int_as_float(a0), d1 = __int_as_float(a1);
#pragma unroll
            for (int i = 0; i < 16; i++) { S[4 * i] -= d0; S[4 * i + 1] -= d0; S[4 * i + 2] -= d1; S[4 * i + 3] -= d1; }
            m0 += d0; m1 += d1;
            f0 = ex2(-d0); f1 = ex2(-d1);
            l0 *= f0; l1 *= f1;
            resc = true;
          }
        }
        exps(0, 4);
        wg_wait<0>();
        fence_regs(O);
        fence_regs(P);
        ring.release(tv & 3);
        if (resc) {
#pragma unroll
          for (int i = 0; i < 16; i++) {
            O[4 * i] *= f0; O[4 * i + 1] *= f0; O[4 * i + 2] *= f1; O[4 * i + 3] *= f1;
          }
          if (newhead) {
#pragma unroll
            for (int i = 0; i < 8; i++) {
              uint32_t o[4];
              pack8(o, O + 8 * i);
              sts128(sb + SM_PARK + ((n >> 2) - 1) * SLOT + i * 4096 + tid * 16, o[0], o[1], o[2], o[3]);
            }
          }
        }
        exps(4, 16);
#pragma unroll
        for (int i = 0; i < 8; i++) pack8(P[i], S + 8 * i);
        fence_regs(P);
        fence_regs(O);
      }
      {
        const uint32_t bv = ring.wait_full(3, 1);
        if (wg == 0) bar_sync(2, 256);
        wg_fence();
        static_for<0, 8>([&](auto K) { wgmma_rs_n128_tb1<LB_MN128 + K * 128, HI128>(O, P[K], bv, 1); });
        wg_commit();
        l0 += __shfl_xor_sync(0xffffffffu, l0, 1); l1 += __shfl_xor_sync(0xffffffffu, l1, 1);
        l0 += __shfl_xor_sync(0xffffffffu, l0, 2); l1 += __shfl_xor_sync(0xffffffffu, l1, 2);
        const float f0 = rcp_hw(l0), f1 = rcp_hw(l1);
        wg_wait<0>();
        fence_regs(O);
#pragma unroll
        for (int i = 0; i < 8; i++) {
          qf[i][0] = pack_bf16(O[8 * i] * f0, O[8 * i + 1] * f0); qf[i][1] = pack_bf16(O[8 * i + 2] * f1, O[8 * i + 3] * f1);
          qf[i][2] = pack_bf16(O[8 * i + 4] * f0, O[8 * i + 5] * f0); qf[i][3] = pack_bf16(O[8 * i + 6] * f1, O[8 * i + 7] * f1);
        }
      }
    }
    fence_regs(qf);
    TS(4);

    uint32_t rs = 0, rp = 0;
    uint4* const Pout = g_P + ((size_t)(rt * 8 + warp) * 8 + j) * 1024;
    const uint32_t stage = sb + SM_RING + 3 * SLOT + warp * 4096;
#pragma unroll 1
    for (int c = 0; c < 4; c++) {
#pragma unroll
      for (int hh = 0; hh < 4; hh++) {
        uint32_t a[8][4];
        if (hh < 3) {
#pragma unroll
          for (int i = 0; i < 8; i++) lds128(sb + SM_PARK + hh * SLOT + i * 4096 + tid * 16, a[i]);
        }
        const uint32_t b = ring.wait_full(rs, rp);
        wg_fence();
        static_for<0, 8>([&](auto K) { wgmma_rs_n128_tb1<LB_MN128 + K * 128, HI128>(S, hh < 3 ? a[K] : qf[K], b, (hh | K) != 0); });
        wg_commit();
        if (hh == 3) warp_bulk_wait_read<0>();
        wg_wait<0>();
        ring.release(rs);
        if (++rs == 3) { rs = 0; rp ^= 1; }
      }
      fence_regs(S);
#pragma unroll
      for (int i = 0; i < 8; i++)
        sts128(stage + i * 512 + lane * 16, pack_tag<1>(S[8 * i], S[8 * i + 1]), pack_bf16(S[8 * i + 2], S[8 * i + 3]),
               pack_bf16(S[8 * i + 4], S[8 * i + 5]), pack_bf16(S[8 * i + 6], S[8 * i + 7]));
      warp_bulk_store(Pout + c * 256, stage, 4096);
    }
    TS(5);

    const uint32_t tag = *(volatile uint32_t*)(smem_raw + SM_BAR + 64);
    const uint4* const Pown = g_P + ((size_t)(rt * 8 + j) * 8 * 32 + gq) * 32 + warp * 4 + q;
    {
      const uint32_t* xo = (const uint32_t*)p.x + xoff;
      float x2[4][8];
      uint32_t r[3][8][4], ga[4][4], sh[4][4], g2[4][4], xr[4][4];
#pragma unroll
      for (int c = 0; c < 3; c++) issue_pkts<1, 8>(Pown + c * 256, 1024, r[c]);
#pragma unroll
      for (int c = 0; c < 4; c++) {
        xr[c][0] = ldg32(xo + c * 64); xr[c][1] = ldg32(xo + c * 64 + 8 * 256);
        xr[c][2] = ldg32(xo + c * 64 + 4); xr[c][3] = ldg32(xo + c * 64 + 4 + 8 * 256);
        ld_pkt(&g_mod2[(0 * 32 + c * 8 + gq) * 4 + q], ga[c]);
        ld_pkt(&g_mod2[(1 * 32 + c * 8 + gq) * 4 + q], sh[c]);
        ld_pkt(&g_mod2[(2 * 32 + c * 8 + gq) * 4 + q], g2[c]);
      }
#pragma unroll
      for (int c = 0; c < 4; c++) {
        if (ga[c][2] != tag) ld_mod(&g_mod2[(0 * 32 + c * 8 + gq) * 4 + q], tag, ga[c]);
        if (sh[c][2] != tag) ld_mod(&g_mod2[(1 * 32 + c * 8 + gq) * 4 + q], tag, sh[c]);
        if (g2[c][2] != tag) ld_mod(&g_mod2[(2 * 32 + c * 8 + gq) * 4 + q], tag, g2[c]);
      }
      float s0 = 0.f, s1 = 0.f, v0 = 0.f, v1 = 0.f;
#pragma unroll
      for (int c = 0; c < 4; c++) {
        uint32_t (*rr)[4] = r[c % 3];
        if (c == 3) issue_pkts<1, 8>(Pown + c * 256, 1024, rr);
        verify8_tag1<16384>(Pown + c * 256, rr);
#pragma unroll
        for (int e = 0; e < 4; e++) {
          float y0 = bf_lo(rr[0][e]), y1 = bf_hi(rr[0][e]);
#pragma unroll
          for (int s = 1; s < 8; s++) { y0 += bf_lo(rr[s][e]); y1 += bf_hi(rr[s][e]); }
          const float a = fmaf(bf_lo(ga[c][e >> 1]), y0, bf_lo(xr[c][e])), b = fmaf(bf_hi(ga[c][e >> 1]), y1, bf_hi(xr[c][e]));
          x2[c][2 * e] = a; x2[c][2 * e + 1] = b;
          if (e & 1) { s1 += a + b; v1 = fmaf(a, a, fmaf(b, b, v1)); }
          else { s0 += a + b; v0 = fmaf(a, a, fmaf(b, b, v0)); }
        }
      }
      TS(6);
#pragma unroll
      for (int o = 16; o > 0; o >>= 1) {
        s0 += __shfl_xor_sync(0xffffffffu, s0, o);
        s1 += __shfl_xor_sync(0xffffffffu, s1, o);
        v0 += __shfl_xor_sync(0xffffffffu, v0, o);
        v1 += __shfl_xor_sync(0xffffffffu, v1, o);
      }
      const float m0 = s0 * (1.f / 512.f), m1 = s1 * (1.f / 512.f);
      const float r0 = rsqrtf(fmaxf(fmaf(-m0, m0, v0 * (1.f / 512.f)), 0.f) + 1e-5f);
      const float r1 = rsqrtf(fmaxf(fmaf(-m1, m1, v1 * (1.f / 512.f)), 0.f) + 1e-5f);
#pragma unroll
      for (int c = 0; c < 4; c++) {
        float hv[8];
#pragma unroll
        for (int e = 0; e < 8; e++) {
          const float t = (x2[c][e] - ((e & 2) ? m1 : m0)) * ((e & 2) ? r1 : r0);
          const uint32_t gw = g2[c][e >> 2], sw = sh[c][e >> 2];
          hv[e] = fmaf(t, (e & 1) ? bf_hi(gw) : bf_lo(gw), (e & 1) ? bf_hi(sw) : bf_lo(sw));
        }
        st_pkt(g_G + ooff + c * 256, pack_tag<0>(hv[0], hv[1]), pack_bf16(hv[2], hv[3]), pack_bf16(hv[4], hv[5]),
               pack_bf16(hv[6], hv[7]));
      }
#pragma unroll
      for (int c = 0; c < 4; c++) {
        sts128(sb + SM_PARK + (2 * c) * 4096 + tid * 16, __float_as_uint(x2[c][0]), __float_as_uint(x2[c][1]),
               __float_as_uint(x2[c][2]), __float_as_uint(x2[c][3]));
        sts128(sb + SM_PARK + (2 * c + 1) * 4096 + tid * 16, __float_as_uint(x2[c][4]), __float_as_uint(x2[c][5]),
               __float_as_uint(x2[c][6]), __float_as_uint(x2[c][7]));
      }
    }
    TS(7);

    uint32_t H[14][4];
    {
      float acc[112];
      uint32_t a[3][4][4];
      const uint4* Gin = g_G + goff;
      issue_pkts<0, 4>(Gin, 32, a[0]);
      verify4_tag0<512>(Gin, a[0]);
      issue_pkts<0, 4>(Gin + 128, 32, a[1]);
#pragma unroll
      for (int u = 0; u < 8; u++) {
        if (u > 0) verify4_tag0<512>(Gin + u * 128, a[u % 3]);
        fence_frags<4>(a[u % 3]);
        if (u == 0) TS(8);
        const uint32_t b = ring.wait_full(rs, rp);
        if (u > 0) { wg_wait<0>(); ring.release(rs == 0 ? 2 : rs - 1); }
        wg_fence();
        static_for<0, 4>([&](auto K) { wgmma_rs_n224_tb1<LB_W1 + K * 64, HI64>(acc, a[u % 3][K], b, (u | K) != 0); });
        wg_commit();
        if (u < 6) issue_pkts<0, 4>(Gin + (u + 2) * 128, 32, a[(u + 2) % 3]);
        if (++rs == 3) { rs = 0; rp ^= 1; }
      }
      wg_wait<0>();
      ring.release(rs == 0 ? 2 : rs - 1);
      fence_regs(acc);
      TS(9);
#pragma unroll
      for (int i = 0; i < 14; i++) {
#pragma unroll
        for (int e = 0; e < 4; e++) {
          const float u0 = 0.5f * acc[8 * i + 2 * e], u1 = 0.5f * acc[8 * i + 2 * e + 1];
          H[i][e] = pack_bf16(fmaf(u0, tanh_hw(u0), u0), fmaf(u1, tanh_hw(u1), u1));
        }
      }
    }
    fence_regs(H);
    TS(10);
#pragma unroll 1
    for (int c = 0; c < 4; c++) {
#pragma unroll
      for (int hf = 0; hf < 2; hf++) {
        const uint32_t b = ring.wait_full(rs, rp);
        wg_fence();
        static_for<0, 7>([&](auto K) { wgmma_rs_n128_tb1<LB_W2 + K * 128, HI128>(S, H[hf * 7 + K], b, (hf | K) != 0); });
        wg_commit();
        if (hf == 1) warp_bulk_wait_read<2>();
        wg_wait<0>();
        ring.release(rs);
        if (++rs == 3) { rs = 0; rp ^= 1; }
      }
      fence_regs(S);
      const uint32_t stg = (c == 2) ? stage : sb + SM_PARK + (c == 1 ? 2 : 1) * SLOT + warp * 4096;
#pragma unroll
      for (int i = 0; i < 8; i++)
        sts128(stg + i * 512 + lane * 16, pack_tag<0>(S[8 * i], S[8 * i + 1]), pack_bf16(S[8 * i + 2], S[8 * i + 3]),
               pack_bf16(S[8 * i + 4], S[8 * i + 5]), pack_bf16(S[8 * i + 6], S[8 * i + 7]));
      warp_bulk_store(Pout + c * 256, stg, 4096);
    }
    TS(11);
    {
      uint32_t* oo = (uint32_t*)p.out + xoff;
      uint32_t r[3][8][4], gb[4][4];
#pragma unroll
      for (int c = 0; c < 3; c++) issue_pkts<0, 8>(Pown + c * 256, 1024, r[c]);
#pragma unroll
      for (int c = 0; c < 4; c++) ld_pkt(&g_mod2[(3 * 32 + c * 8 + gq) * 4 + q], gb[c]);
#pragma unroll
      for (int c = 0; c < 4; c++)
        if (gb[c][2] != tag) ld_mod(&g_mod2[(3 * 32 + c * 8 + gq) * 4 + q], tag, gb[c]);
#pragma unroll
      for (int c = 0; c < 4; c++) {
        uint32_t xa[2][4];
        uint32_t (*rr)[4] = r[c % 3];
        if (c == 3) issue_pkts<0, 8>(Pown + c * 256, 1024, rr);
        lds128(sb + SM_PARK + (2 * c) * 4096 + tid * 16, xa[0]);
        lds128(sb + SM_PARK + (2 * c + 1) * 4096 + tid * 16, xa[1]);
        verify8_tag0<16384>(Pown + c * 256, rr);
#pragma unroll
        for (int e = 0; e < 4; e++) {
          float y0 = bf_lo(rr[0][e]), y1 = bf_hi(rr[0][e]);
#pragma unroll
          for (int s = 1; s < 8; s++) { y0 += bf_lo(rr[s][e]); y1 += bf_hi(rr[s][e]); }
          oo[c * 64 + (e >> 1) * 4 + (e & 1) * 8 * 256] =
              pack_bf16(fmaf(bf_lo(gb[c][e >> 1]), y0, __uint_as_float(xa[e >> 1][(e & 1) * 2])),
                        fmaf(bf_hi(gb[c][e >> 1]), y1, __uint_as_float(xa[e >> 1][(e & 1) * 2 + 1])));
        }
      }
    }
    warp_bulk_wait_read<0>();
    TS(12);
    if (bid == 0 && tid == 0) asm volatile("st.relaxed.gpu.global.u32 [%0], %1;" ::"l"(&g_epoch), "r"(tag) : "memory");
  }
}

typedef CUresult (*EncodeFn)(CUtensorMap*, CUtensorMapDataType, cuuint32_t, void*, const cuuint64_t*, const cuuint64_t*,
                             const cuuint32_t*, const cuuint32_t*, CUtensorMapInterleave, CUtensorMapSwizzle,
                             CUtensorMapL2promotion, CUtensorMapFloatOOBfill);

static void make_map(EncodeFn fn, CUtensorMap* tm, const void* ptr, int inner, int rows, int cols, int box_rows, int box_outer,
                     CUtensorMapSwizzle swz) {
  cuuint64_t gd[3] = {(cuuint64_t)inner, (cuuint64_t)rows, (cuuint64_t)(cols / inner)};
  cuuint64_t gs[2] = {(cuuint64_t)cols * 2, (cuuint64_t)inner * 2};
  cuuint32_t bx[3] = {(cuuint32_t)inner, (cuuint32_t)box_rows, (cuuint32_t)box_outer};
  cuuint32_t es[3] = {1, 1, 1};
  fn(tm, CU_TENSOR_MAP_DATA_TYPE_BFLOAT16, 3, const_cast<void*>(ptr), gd, gs, bx, es, CU_TENSOR_MAP_INTERLEAVE_NONE, swz,
     CU_TENSOR_MAP_L2_PROMOTION_L2_128B, CU_TENSOR_MAP_FLOAT_OOB_FILL_NONE);
}

extern "C" void kernel_launch(void* const* d_in, const int* in_sizes, int n_in, void* d_out, int out_size) {
  (void)in_sizes; (void)n_in; (void)out_size;
  void* fnp = nullptr;
  cudaDriverEntryPointQueryResult qr;
  cudaGetDriverEntryPoint("cuTensorMapEncodeTiled", &fnp, cudaEnableDefault, &qr);
  EncodeFn fn = (EncodeFn)fnp;
  CUtensorMap tmWq, tmK, tmV, tmWo, tmW1, tmW2;
  make_map(fn, &tmWq, d_in[3], 64, 512, 4096, 128, 2, CU_TENSOR_MAP_SWIZZLE_128B);
  make_map(fn, &tmK, d_in[1], 64, 8 * SK, 128, 128, 2, CU_TENSOR_MAP_SWIZZLE_128B);
  make_map(fn, &tmV, d_in[2], 64, 8 * SK, 128, 128, 2, CU_TENSOR_MAP_SWIZZLE_128B);
  make_map(fn, &tmWo, d_in[4], 64, 4096, 512, 128, 2, CU_TENSOR_MAP_SWIZZLE_128B);
  make_map(fn, &tmW1, d_in[6], 32, 512, FF, 64, 7, CU_TENSOR_MAP_SWIZZLE_64B);
  make_map(fn, &tmW2, d_in[7], 64, FF, 512, 112, 2, CU_TENSOR_MAP_SWIZZLE_128B);
  Params p;
  p.x = (const __nv_bfloat16*)d_in[0];
  p.c = (const __nv_bfloat16*)d_in[8];
  p.wmod = (const __nv_bfloat16*)d_in[9];
  p.out = (__nv_bfloat16*)d_out;
  cudaFuncSetAttribute(adaln_block_kernel, cudaFuncAttributeMaxDynamicSharedMemorySize, SM_TOTAL);
  adaln_block_kernel<<<128, 384, SM_TOTAL>>>(tmWq, tmK, tmV, tmWo, tmW1, tmW2, p);
}
```

```cpp
#include <cuda_runtime.h>
#include <cuda_bf16.h>
#include <cuda.h>
#include <stdint.h>

template <int OFF, uint32_t HI>
__device__ __forceinline__ void wgmma_rs_n128_tb0(float (&d)[64], const uint32_t (&a)[4], uint32_t lo, int sd) {
  asm volatile("{\n.reg .pred p;\n.reg .b32 l;\n.reg .b64 db;\nsetp.ne.b32 p, %69, 0;\n"
    "add.u32 l, %68, %70;\nmov.b64 db, {l, %71};\n"
    "wgmma.mma_async.sync.aligned.m64n128k16.f32.bf16.bf16 "
    "{%0,%1,%2,%3,%4,%5,%6,%7,%8,%9,%10,%11,%12,%13,%14,%15,"
    "%16,%17,%18,%19,%20,%21,%22,%23,%24,%25,%26,%27,%28,%29,%30,%31,"
    "%32,%33,%34,%35,%36,%37,%38,%39,%40,%41,%42,%43,%44,%45,%46,%47,"
    "%48,%49,%50,%51,%52,%53,%54,%55,%56,%57,%58,%59,%60,%61,%62,%63}, "
    "{%64,%65,%66,%67}, db, p, 1, 1, 0;\n}\n"
    : "+f"(d[0]), "+f"(d[1]), "+f"(d[2]), "+f"(d[3]), "+f"(d[4]), "+f"(d[5]), "+f"(d[6]), "+f"(d[7]),
      "+f"(d[8]), "+f"(d[9]), "+f"(d[10]), "+f"(d[11]), "+f"(d[12]), "+f"(d[13]), "+f"(d[14]), "+f"(d[15]),
      "+f"(d[16]), "+f"(d[17]), "+f"(d[18]), "+f"(d[19]), "+f"(d[20]), "+f"(d[21]), "+f"(d[22]), "+f"(d[23]),
      "+f"(d[24]), "+f"(d[25]), "+f"(d[26]), "+f"(d[27]), "+f"(d[28]), "+f"(d[29]), "+f"(d[30]), "+f"(d[31]),
      "+f"(d[32]), "+f"(d[33]), "+f"(d[34]), "+f"(d[35]), "+f"(d[36]), "+f"(d[37]), "+f"(d[38]), "+f"(d[39]),
      "+f"(d[40]), "+f"(d[41]), "+f"(d[42]), "+f"(d[43]), "+f"(d[44]), "+f"(d[45]), "+f"(d[46]), "+f"(d[47]),
      "+f"(d[48]), "+f"(d[49]), "+f"(d[50]), "+f"(d[51]), "+f"(d[52]), "+f"(d[53]), "+f"(d[54]), "+f"(d[55]),
      "+f"(d[56]), "+f"(d[57]), "+f"(d[58]), "+f"(d[59]), "+f"(d[60]), "+f"(d[61]), "+f"(d[62]), "+f"(d[63])
    : "r"(a[0]), "r"(a[1]), "r"(a[2]), "r"(a[3]), "r"(lo), "r"(sd), "n"(OFF), "n"(HI));
}

template <int OFF, uint32_t HI>
__device__ __forceinline__ void wgmma_rs_n128_tb1(float (&d)[64], const uint32_t (&a)[4], uint32_t lo, int sd) {
  asm volatile("{\n.reg .pred p;\n.reg .b32 l;\n.reg .b64 db;\nsetp.ne.b32 p, %69, 0;\n"
    "add.u32 l, %68, %70;\nmov.b64 db, {l, %71};\n"
    "wgmma.mma_async.sync.aligned.m64n128k16.f32.bf16.bf16 "
    "{%0,%1,%2,%3,%4,%5,%6,%7,%8,%9,%10,%11,%12,%13,%14,%15,"
    "%16,%17,%18,%19,%20,%21,%22,%23,%24,%25,%26,%27,%28,%29,%30,%31,"
    "%32,%33,%34,%35,%36,%37,%38,%39,%40,%41,%42,%43,%44,%45,%46,%47,"
    "%48,%49,%50,%51,%52,%53,%54,%55,%56,%57,%58,%59,%60,%61,%62,%63}, "
    "{%64,%65,%66,%67}, db, p, 1, 1, 1;\n}\n"
    : "+f"(d[0]), "+f"(d[1]), "+f"(d[2]), "+f"(d[3]), "+f"(d[4]), "+f"(d[5]), "+f"(d[6]), "+f"(d[7]),
      "+f"(d[8]), "+f"(d[9]), "+f"(d[10]), "+f"(d[11]), "+f"(d[12]), "+f"(d[13]), "+f"(d[14]), "+f"(d[15]),
      "+f"(d[16]), "+f"(d[17]), "+f"(d[18]), "+f"(d[19]), "+f"(d[20]), "+f"(d[21]), "+f"(d[22]), "+f"(d[23]),
      "+f"(d[24]), "+f"(d[25]), "+f"(d[26]), "+f"(d[27]), "+f"(d[28]), "+f"(d[29]), "+f"(d[30]), "+f"(d[31]),
      "+f"(d[32]), "+f"(d[33]), "+f"(d[34]), "+f"(d[35]), "+f"(d[36]), "+f"(d[37]), "+f"(d[38]), "+f"(d[39]),
      "+f"(d[40]), "+f"(d[41]), "+f"(d[42]), "+f"(d[43]), "+f"(d[44]), "+f"(d[45]), "+f"(d[46]), "+f"(d[47]),
      "+f"(d[48]), "+f"(d[49]), "+f"(d[50]), "+f"(d[51]), "+f"(d[52]), "+f"(d[53]), "+f"(d[54]), "+f"(d[55]),
      "+f"(d[56]), "+f"(d[57]), "+f"(d[58]), "+f"(d[59]), "+f"(d[60]), "+f"(d[61]), "+f"(d[62]), "+f"(d[63])
    : "r"(a[0]), "r"(a[1]), "r"(a[2]), "r"(a[3]), "r"(lo), "r"(sd), "n"(OFF), "n"(HI));
}

template <int OFF, uint32_t HI>
__device__ __forceinline__ void wgmma_rs_n224_tb1(float (&d)[112], const uint32_t (&a)[4], uint32_t lo, int sd) {
  asm volatile("{\n.reg .pred p;\n.reg .b32 l;\n.reg .b64 db;\nsetp.ne.b32 p, %117, 0;\n"
    "add.u32 l, %116, %118;\nmov.b64 db, {l, %119};\n"
    "wgmma.mma_async.sync.aligned.m64n224k16.f32.bf16.bf16 "
    "{%0,%1,%2,%3,%4,%5,%6,%7,%8,%9,%10,%11,%12,%13,%14,%15,"
    "%16,%17,%18,%19,%20,%21,%22,%23,%24,%25,%26,%27,%28,%29,%30,%31,"
    "%32,%33,%34,%35,%36,%37,%38,%39,%40,%41,%42,%43,%44,%45,%46,%47,"
    "%48,%49,%50,%51,%52,%53,%54,%55,%56,%57,%58,%59,%60,%61,%62,%63,"
    "%64,%65,%66,%67,%68,%69,%70,%71,%72,%73,%74,%75,%76,%77,%78,%79,"
    "%80,%81,%82,%83,%84,%85,%86,%87,%88,%89,%90,%91,%92,%93,%94,%95,"
    "%96,%97,%98,%99,%100,%101,%102,%103,%104,%105,%106,%107,%108,%109,%110,%111}, "
    "{%112,%113,%114,%115}, db, p, 1, 1, 1;\n}\n"
    : "+f"(d[0]), "+f"(d[1]), "+f"(d[2]), "+f"(d[3]), "+f"(d[4]), "+f"(d[5]), "+f"(d[6]), "+f"(d[7]),
      "+f"(d[8]), "+f"(d[9]), "+f"(d[10]), "+f"(d[11]), "+f"(d[12]), "+f"(d[13]), "+f"(d[14]), "+f"(d[15]),
      "+f"(d[16]), "+f"(d[17]), "+f"(d[18]), "+f"(d[19]), "+f"(d[20]), "+f"(d[21]), "+f"(d[22]), "+f"(d[23]),
      "+f"(d[24]), "+f"(d[25]), "+f"(d[26]), "+f"(d[27]), "+f"(d[28]), "+f"(d[29]), "+f"(d[30]), "+f"(d[31]),
      "+f"(d[32]), "+f"(d[33]), "+f"(d[34]), "+f"(d[35]), "+f"(d[36]), "+f"(d[37]), "+f"(d[38]), "+f"(d[39]),
      "+f"(d[40]), "+f"(d[41]), "+f"(d[42]), "+f"(d[43]), "+f"(d[44]), "+f"(d[45]), "+f"(d[46]), "+f"(d[47]),
      "+f"(d[48]), "+f"(d[49]), "+f"(d[50]), "+f"(d[51]), "+f"(d[52]), "+f"(d[53]), "+f"(d[54]), "+f"(d[55]),
      "+f"(d[56]), "+f"(d[57]), "+f"(d[58]), "+f"(d[59]), "+f"(d[60]), "+f"(d[61]), "+f"(d[62]), "+f"(d[63]),
      "+f"(d[64]), "+f"(d[65]), "+f"(d[66]), "+f"(d[67]), "+f"(d[68]), "+f"(d[69]), "+f"(d[70]), "+f"(d[71]),
      "+f"(d[72]), "+f"(d[73]), "+f"(d[74]), "+f"(d[75]), "+f"(d[76]), "+f"(d[77]), "+f"(d[78]), "+f"(d[79]),
      "+f"(d[80]), "+f"(d[81]), "+f"(d[82]), "+f"(d[83]), "+f"(d[84]), "+f"(d[85]), "+f"(d[86]), "+f"(d[87]),
      "+f"(d[88]), "+f"(d[89]), "+f"(d[90]), "+f"(d[91]), "+f"(d[92]), "+f"(d[93]), "+f"(d[94]), "+f"(d[95]),
      "+f"(d[96]), "+f"(d[97]), "+f"(d[98]), "+f"(d[99]), "+f"(d[100]), "+f"(d[101]), "+f"(d[102]), "+f"(d[103]),
      "+f"(d[104]), "+f"(d[105]), "+f"(d[106]), "+f"(d[107]), "+f"(d[108]), "+f"(d[109]), "+f"(d[110]), "+f"(d[111])
    : "r"(a[0]), "r"(a[1]), "r"(a[2]), "r"(a[3]), "r"(lo), "r"(sd), "n"(OFF), "n"(HI));
}

template <int STR>
__device__ __forceinline__ void verify8_tag1(const uint4* p, uint32_t (*r)[4]) {
  asm volatile("{\n.reg .pred p, q;\n.reg .b32 a, n;\nmov.u32 n, 0;\n"
    "LAB_CHK:\n"
    "and.b32 a, %0, %4;\n"
    "and.b32 a, a, %8;\n"
    "and.b32 a, a, %12;\n"
    "and.b32 a, a, %16;\n"
    "and.b32 a, a, %20;\n"
    "and.b32 a, a, %24;\n"
    "and.b32 a, a, %28;\n"
    "and.b32 a, a, 1;\nsetp.eq.u32 p, a, 1;\nvote.sync.all.pred p, p, 0xffffffff;\n"
    "@p bra.uni LAB_OK;\n"
    "ld.relaxed.gpu.global.v4.b32 {%0,%1,%2,%3}, [%32+%33];\n"
    "ld.relaxed.gpu.global.v4.b32 {%4,%5,%6,%7}, [%32+%34];\n"
    "ld.relaxed.gpu.global.v4.b32 {%8,%9,%10,%11}, [%32+%35];\n"
    "ld.relaxed.gpu.global.v4.b32 {%12,%13,%14,%15}, [%32+%36];\n"
    "ld.relaxed.gpu.global.v4.b32 {%16,%17,%18,%19}, [%32+%37];\n"
    "ld.relaxed.gpu.global.v4.b32 {%20,%21,%22,%23}, [%32+%38];\n"
    "ld.relaxed.gpu.global.v4.b32 {%24,%25,%26,%27}, [%32+%39];\n"
    "ld.relaxed.gpu.global.v4.b32 {%28,%29,%30,%31}, [%32+%40];\n"
    "add.u32 n, n, 1;\nsetp.lt.u32 q, n, 262144;\n@q bra.uni LAB_CHK;\n"
    "LAB_OK:\n"
    "}\n"
    : "+r"(r[0][0]), "+r"(r[0][1]), "+r"(r[0][2]), "+r"(r[0][3]), "+r"(r[1][0]), "+r"(r[1][1]), "+r"(r[1][2]), "+r"(r[1][3]),
      "+r"(r[2][0]), "+r"(r[2][1]), "+r"(r[2][2]), "+r"(r[2][3]), "+r"(r[3][0]), "+r"(r[3][1]), "+r"(r[3][2]), "+r"(r[3][3]),
      "+r"(r[4][0]), "+r"(r[4][1]), "+r"(r[4][2]), "+r"(r[4][3]), "+r"(r[5][0]), "+r"(r[5][1]), "+r"(r[5][2]), "+r"(r[5][3]),
      "+r"(r[6][0]), "+r"(r[6][1]), "+r"(r[6][2]), "+r"(r[6][3]), "+r"(r[7][0]), "+r"(r[7][1]), "+r"(r[7][2]), "+r"(r[7][3])
    : "l"(p), "n"(0 * STR), "n"(1 * STR), "n"(2 * STR), "n"(3 * STR), "n"(4 * STR), "n"(5 * STR), "n"(6 * STR), "n"(7 * STR)
    : "memory");
}

template <int STR>
__device__ __forceinline__ void verify8_tag0(const uint4* p, uint32_t (*r)[4]) {
  asm volatile("{\n.reg .pred p, q;\n.reg .b32 a, n;\nmov.u32 n, 0;\n"
    "LAB_CHK:\n"
    "or.b32 a, %0, %4;\n"
    "or.b32 a, a, %8;\n"
    "or.b32 a, a, %12;\n"
    "or.b32 a, a, %16;\n"
    "or.b32 a, a, %20;\n"
    "or.b32 a, a, %24;\n"
    "or.b32 a, a, %28;\n"
    "and.b32 a, a, 1;\nsetp.eq.u32 p, a, 0;\nvote.sync.all.pred p, p, 0xffffffff;\n"
    "@p bra.uni LAB_OK;\n"
    "ld.relaxed.gpu.global.v4.b32 {%0,%1,%2,%3}, [%32+%33];\n"
    "ld.relaxed.gpu.global.v4.b32 {%4,%5,%6,%7}, [%32+%34];\n"
    "ld.relaxed.gpu.global.v4.b32 {%8,%9,%10,%11}, [%32+%35];\n"
    "ld.relaxed.gpu.global.v4.b32 {%12,%13,%14,%15}, [%32+%36];\n"
    "ld.relaxed.gpu.global.v4.b32 {%16,%17,%18,%19}, [%32+%37];\n"
    "ld.relaxed.gpu.global.v4.b32 {%20,%21,%22,%23}, [%32+%38];\n"
    "ld.relaxed.gpu.global.v4.b32 {%24,%25,%26,%27}, [%32+%39];\n"
    "ld.relaxed.gpu.global.v4.b32 {%28,%29,%30,%31}, [%32+%40];\n"
    "add.u32 n, n, 1;\nsetp.lt.u32 q, n, 262144;\n@q bra.uni LAB_CHK;\n"
    "LAB_OK:\n"
    "or.b32 %0, %0, 1;\n"
    "or.b32 %4, %4, 1;\n"
    "or.b32 %8, %8, 1;\n"
    "or.b32 %12, %12, 1;\n"
    "or.b32 %16, %16, 1;\n"
    "or.b32 %20, %20, 1;\n"
    "or.b32 %24, %24, 1;\n"
    "or.b32 %28, %28, 1;\n"
    "}\n"
    : "+r"(r[0][0]), "+r"(r[0][1]), "+r"(r[0][2]), "+r"(r[0][3]), "+r"(r[1][0]), "+r"(r[1][1]), "+r"(r[1][2]), "+r"(r[1][3]),
      "+r"(r[2][0]), "+r"(r[2][1]), "+r"(r[2][2]), "+r"(r[2][3]), "+r"(r[3][0]), "+r"(r[3][1]), "+r"(r[3][2]), "+r"(r[3][3]),
      "+r"(r[4][0]), "+r"(r[4][1]), "+r"(r[4][2]), "+r"(r[4][3]), "+r"(r[5][0]), "+r"(r[5][1]), "+r"(r[5][2]), "+r"(r[5][3]),
      "+r"(r[6][0]), "+r"(r[6][1]), "+r"(r[6][2]), "+r"(r[6][3]), "+r"(r[7][0]), "+r"(r[7][1]), "+r"(r[7][2]), "+r"(r[7][3])
    : "l"(p), "n"(0 * STR), "n"(1 * STR), "n"(2 * STR), "n"(3 * STR), "n"(4 * STR), "n"(5 * STR), "n"(6 * STR), "n"(7 * STR)
    : "memory");
}

template <int STR>
__device__ __forceinline__ void verify4_tag0(const uint4* p, uint32_t (*r)[4]) {
  asm volatile("{\n.reg .pred p, q;\n.reg .b32 a, n;\nmov.u32 n, 0;\n"
    "LAB_CHK:\n"
    "or.b32 a, %0, %4;\n"
    "or.b32 a, a, %8;\n"
    "or.b32 a, a, %12;\n"
    "and.b32 a, a, 1;\nsetp.eq.u32 p, a, 0;\nvote.sync.all.pred p, p, 0xffffffff;\n"
    "@p bra.uni LAB_OK;\n"
    "ld.relaxed.gpu.global.v4.b32 {%0,%1,%2,%3}, [%16+%17];\n"
    "ld.relaxed.gpu.global.v4.b32 {%4,%5,%6,%7}, [%16+%18];\n"
    "ld.relaxed.gpu.global.v4.b32 {%8,%9,%10,%11}, [%16+%19];\n"
    "ld.relaxed.gpu.global.v4.b32 {%12,%13,%14,%15}, [%16+%20];\n"
    "add.u32 n, n, 1;\nsetp.lt.u32 q, n, 262144;\n@q bra.uni LAB_CHK;\n"
    "LAB_OK:\n"
    "or.b32 %0, %0, 1;\n"
    "or.b32 %4, %4, 1;\n"
    "or.b32 %8, %8, 1;\n"
    "or.b32 %12, %12, 1;\n"
    "}\n"
    : "+r"(r[0][0]), "+r"(r[0][1]), "+r"(r[0][2]), "+r"(r[0][3]), "+r"(r[1][0]), "+r"(r[1][1]), "+r"(r[1][2]), "+r"(r[1][3]),
      "+r"(r[2][0]), "+r"(r[2][1]), "+r"(r[2][2]), "+r"(r[2][3]), "+r"(r[3][0]), "+r"(r[3][1]), "+r"(r[3][2]), "+r"(r[3][3])
    : "l"(p), "n"(0 * STR), "n"(1 * STR), "n"(2 * STR), "n"(3 * STR)
    : "memory");
}

#define SPIN_LIMIT (1 << 18)

__device__ __forceinline__ uint32_t smem_u32(const void* p) { return (uint32_t)__cvta_generic_to_shared(p); }
__device__ __forceinline__ void mbar_init(uint32_t a, uint32_t c) {
  asm volatile("mbarrier.init.shared::cta.b64 [%0], %1;" ::"r"(a), "r"(c) : "memory");
}
__device__ __forceinline__ void mbar_expect(uint32_t a, uint32_t b) {
  asm volatile("mbarrier.arrive.expect_tx.shared::cta.b64 _, [%0], %1;" ::"r"(a), "r"(b) : "memory");
}
__device__ __forceinline__ void mbar_arrive(uint32_t a) {
  asm volatile("mbarrier.arrive.shared::cta.b64 _, [%0];" ::"r"(a) : "memory");
}
__device__ __forceinline__ void mbar_wait(uint32_t a, uint32_t parity) {
  asm volatile(
      "{\n.reg .pred p;\n.reg .u32 n;\nmov.u32 n, 0;\n"
      "LAB_WAIT:\n"
      "mbarrier.try_wait.parity.shared::cta.b64 p, [%0], %1;\n"
      "@p bra LAB_DONE;\n"
      "add.u32 n, n, 1;\n"
      "setp.lt.u32 p, n, 262144;\n"
      "@p bra LAB_WAIT;\n"
      "LAB_DONE:\n}\n" ::"r"(a), "r"(parity) : "memory");
}
__device__ __forceinline__ void tma3d(uint32_t dst, const CUtensorMap* tm, uint32_t bar, int c0, int c1, int c2) {
  asm volatile(
      "cp.async.bulk.tensor.3d.shared::cluster.global.mbarrier::complete_tx::bytes [%0], [%1, {%3,%4,%5}], [%2];"
      ::"r"(dst), "l"(tm), "r"(bar), "r"(c0), "r"(c1), "r"(c2) : "memory");
}
__device__ __forceinline__ void wg_fence() { asm volatile("wgmma.fence.sync.aligned;" ::: "memory"); }
__device__ __forceinline__ void wg_commit() { asm volatile("wgmma.commit_group.sync.aligned;" ::: "memory"); }
template <int N> __device__ __forceinline__ void wg_wait() {
  asm volatile("wgmma.wait_group.sync.aligned %0;" ::"n"(N) : "memory");
}
template <int N> __device__ __forceinline__ void fence_regs(float (&d)[N]) {
#pragma unroll
  for (int i = 0; i < N; i++) asm volatile("" : "+f"(d[i])::"memory");
}
template <int N> __device__ __forceinline__ void fence_regs(uint32_t (&d)[N][4]) {
#pragma unroll
  for (int i = 0; i < N; i++) asm volatile("" : "+r"(d[i][0]), "+r"(d[i][1]), "+r"(d[i][2]), "+r"(d[i][3])::"memory");
}
template <int N> __device__ __forceinline__ void fence_frags(uint32_t (*d)[4]) {
#pragma unroll
  for (int i = 0; i < N; i++) asm volatile("" : "+r"(d[i][0]), "+r"(d[i][1]), "+r"(d[i][2]), "+r"(d[i][3])::"memory");
}
__device__ __forceinline__ void bar_sync(int id, int n) { asm volatile("bar.sync %0, %1;" ::"r"(id), "r"(n) : "memory"); }
__device__ __forceinline__ void bar_arrive(int id, int n) { asm volatile("bar.arrive %0, %1;" ::"r"(id), "r"(n) : "memory"); }

__device__ __forceinline__ uint32_t pack_bf16(float lo, float hi) {
  uint32_t r;
  asm("cvt.rn.bf16x2.f32 %0, %1, %2;" : "=r"(r) : "f"(hi), "f"(lo));
  return r;
}
__device__ __forceinline__ float bf_lo(uint32_t w) { return __uint_as_float(w << 16); }
__device__ __forceinline__ float bf_hi(uint32_t w) { return __uint_as_float(w & 0xFFFF0000u); }
__device__ __forceinline__ float round_bf16(float x) { return bf_lo(pack_bf16(x, 0.f)); }
__device__ __forceinline__ uint32_t hfma2_bf16(uint32_t a, uint32_t b, uint32_t c) {
  uint32_t r;
  asm("fma.rn.bf16x2 %0, %1, %2, %3;" : "=r"(r) : "r"(a), "r"(b), "r"(c));
  return r;
}
__device__ __forceinline__ float ex2(float x) {
  float r;
  asm("ex2.approx.ftz.f32 %0, %1;" : "=f"(r) : "f"(x));
  return r;
}
__device__ __forceinline__ float tanh_hw(float x) {
  float r;
  asm("tanh.approx.f32 %0, %1;" : "=f"(r) : "f"(x));
  return r;
}
template <int TAG> __device__ __forceinline__ uint32_t pack_tag(float lo, float hi) {
  uint32_t w = __byte_perm(__float_as_uint(lo), pack_bf16(lo, hi), 0x7632);
  return TAG ? (w | 1u) : (w & ~1u);
}
__device__ __forceinline__ void st_pkt(uint4* p, uint32_t a, uint32_t b, uint32_t c, uint32_t d) {
  asm volatile(
      "st.relaxed.gpu.global.v4.b32 [%0], {%1,%2,%3,%4};" ::"l"(p), "r"(a), "r"(b), "r"(c), "r"(d) : "memory");
}
__device__ __forceinline__ void ld_pkt(const uint4* p, uint32_t (&r)[4]) {
  asm volatile(
      "ld.relaxed.gpu.global.v4.b32 {%0,%1,%2,%3}, [%4];"
      : "=r"(r[0]), "=r"(r[1]), "=r"(r[2]), "=r"(r[3]) : "l"(p) : "memory");
}
__device__ __forceinline__ uint32_t ldg32(const void* p) {
  uint32_t r;
  asm volatile("ld.global.nc.b32 %0, [%1];" : "=r"(r) : "l"(p));
  return r;
}
__device__ __forceinline__ uint32_t ldg16(const void* p) {
  uint16_t r;
  asm volatile("ld.global.nc.b16 %0, [%1];" : "=h"(r) : "l"(p));
  return r;
}
__device__ __forceinline__ uint4 ldg128(const void* p) {
  uint4 r;
  asm volatile("ld.global.nc.v4.b32 {%0,%1,%2,%3}, [%4];" : "=r"(r.x), "=r"(r.y), "=r"(r.z), "=r"(r.w) : "l"(p));
  return r;
}
__device__ __forceinline__ void l2_prefetch(const void* p, uint32_t bytes) {
  asm volatile("cp.async.bulk.prefetch.L2.global [%0], %1;" ::"l"(p), "r"(bytes) : "memory");
}
__device__ __forceinline__ float rcp_hw(float x) {
  float r;
  asm("rcp.approx.ftz.f32 %0, %1;" : "=f"(r) : "f"(x));
  return r;
}
__device__ __forceinline__ void warp_bulk_store(void* gdst, uint32_t ssrc, uint32_t bytes) {
  asm volatile("fence.proxy.async.shared::cta;" ::: "memory");
  __syncwarp();
  if ((threadIdx.x & 31) == 0) {
    asm volatile("cp.async.bulk.global.shared::cta.bulk_group [%0], [%1], %2;" ::"l"(gdst), "r"(ssrc), "r"(bytes) : "memory");
    asm volatile("cp.async.bulk.commit_group;" ::: "memory");
  }
}
template <int N> __device__ __forceinline__ void warp_bulk_wait_read() {
  if ((threadIdx.x & 31) == 0) asm volatile("cp.async.bulk.wait_group.read %0;" ::"n"(N) : "memory");
  __syncwarp();
}
__device__ __forceinline__ void sts128(uint32_t a, uint32_t x, uint32_t y, uint32_t z, uint32_t w) {
  asm volatile("st.shared.v4.b32 [%0], {%1,%2,%3,%4};" ::"r"(a), "r"(x), "r"(y), "r"(z), "r"(w) : "memory");
}
__device__ __forceinline__ void lds128(uint32_t a, uint32_t (&r)[4]) {
  asm volatile("ld.shared.v4.b32 {%0,%1,%2,%3}, [%4];" : "=r"(r[0]), "=r"(r[1]), "=r"(r[2]), "=r"(r[3]) : "r"(a) : "memory");
}

constexpr int SK = 2048, WIN = 512;
constexpr int FF = 1792, FSL = 224;
constexpr int NTILES = 80;
constexpr int NSLOT = 4;
constexpr uint32_t SLOT = 32768;
constexpr uint32_t SM_PARK = 0;
constexpr uint32_t SM_RING = 3 * SLOT;
constexpr uint32_t SM_TAB = 7 * SLOT;
constexpr uint32_t SM_RED = SM_TAB + 2048;
constexpr uint32_t SM_BAR = SM_RED + 256;
constexpr uint32_t SM_TOTAL = SM_BAR + 128;

__device__ uint4 g_P[16 * 8 * 8 * 32 * 32];
__device__ uint4 g_G[16 * 8 * 32 * 32];
__device__ uint4 g_mod1[8 * 256];
__device__ uint4 g_mod2[512];
__device__ uint4 g_uv[2 * 448];
__device__ uint4 g_stat[16 * 8 * 8 * 2];
__device__ uint32_t g_epoch;

#define TS(i) do { } while (0)

struct Params {
  const __nv_bfloat16* x;
  const __nv_bfloat16* c;
  const __nv_bfloat16* wmod;
  const __nv_bfloat16* wo;
  const __nv_bfloat16* w1;
  const __nv_bfloat16* w2;
  __nv_bfloat16* out;
};

constexpr uint32_t HI128 = (1024 >> 4) | (1u << 30);
constexpr uint32_t HI64 = (512 >> 4) | (2u << 30);
constexpr int LB_MN128 = (16384 >> 4) << 16;
constexpr int LB_K128 = 1 << 16;
constexpr int LB_W1 = (4096 >> 4) << 16;
constexpr int LB_W2 = (14336 >> 4) << 16;

template <int I> struct IC {
  __host__ __device__ constexpr operator int() const { return I; }
};
template <int I, int N, typename F> __device__ __forceinline__ void static_for(F&& f) {
  if constexpr (I < N) {
    f(IC<I>{});
    static_for<I + 1, N>(f);
  }
}

struct Ring {
  uint32_t base16, bars;
  __device__ __forceinline__ uint32_t wait_full(uint32_t slot, uint32_t parity) const {
    mbar_wait(bars + slot * 8, parity);
    return base16 + slot * (SLOT >> 4);
  }
  __device__ __forceinline__ void release(uint32_t slot) const {
    if ((threadIdx.x & 31) == 0) mbar_arrive(bars + 32 + slot * 8);
  }
};

__device__ __forceinline__ float silu_c(uint32_t bits) {
  float x = bf_lo(bits);
  return round_bf16(x * rcp_hw(1.f + ex2(-1.4426950408889634f * x)));
}
__device__ __forceinline__ void pack8(uint32_t (&o)[4], const float* v) {
  o[0] = pack_bf16(v[0], v[1]); o[1] = pack_bf16(v[2], v[3]); o[2] = pack_bf16(v[4], v[5]); o[3] = pack_bf16(v[6], v[7]);
}

template <int TAG, int N>
__device__ __forceinline__ void issue_pkts(const uint4* p, int stride, uint32_t (*r)[4]) {
#pragma unroll
  for (int i = 0; i < N; i++) ld_pkt(p + i * stride, r[i]);
}
__device__ __forceinline__ void ld_mod(const uint4* p, uint32_t tag, uint32_t (&r)[4]) {
  int spins = 0;
  ld_pkt(p, r);
  while (r[2] != tag && ++spins < SPIN_LIMIT) ld_pkt(p, r);
}

#define EARLY_TILES 2
#define PF_WMOD 1
#define MOD1_DELAY 300
#define RED3_UNIT 3
#define G_DELAY 300

__global__ void __launch_bounds__(384, 1)
adaln_block_kernel(const __grid_constant__ CUtensorMap tmWq, const __grid_constant__ CUtensorMap tmK,
                   const __grid_constant__ CUtensorMap tmV, const __grid_constant__ CUtensorMap tmWo,
                   const __grid_constant__ CUtensorMap tmW1, const __grid_constant__ CUtensorMap tmW2,
                   const Params p) {
  extern __shared__ __align__(1024) uint8_t smem_raw[];
  const uint32_t sb = smem_u32(smem_raw);
  const int tid = threadIdx.x, lane = tid & 31;
  const int warp = __shfl_sync(0xffffffffu, tid >> 5, 0);
  const int bid = blockIdx.x, j = bid >> 4, rt = bid & 15;
  const uint32_t bars = sb + SM_BAR;

  if (warp >= 8) {
    asm volatile("setmaxnreg.dec.sync.aligned.u32 40;");
    const int t = tid - 256;
    uint32_t tag;
    {
      uint4 w[4];
      uint32_t cb[4];
      if (t >= 32 && t < 36) l2_prefetch(p.wmod + (size_t)(bid * 4 + t - 32) * 3072, 2048);
      if (t == 0) {
        asm volatile("prefetch.tensormap [%0];" ::"l"(&tmWq) : "memory");
        for (int i = 0; i < NSLOT; i++) { mbar_init(bars + i * 8, 1); mbar_init(bars + 32 + i * 8, 8); }
        mbar_init(bars + 72, 2);
        asm volatile("fence.mbarrier_init.release.cluster;" ::: "memory");
        asm volatile("fence.proxy.async.shared::cta;" ::: "memory");
      }
      __syncwarp();
#pragma unroll
      for (int i = 0; i < 4; i++) w[i] = ldg128(p.wmod + (size_t)(t + 128 * i) * 3072 + bid * 8);
#pragma unroll
      for (int i = 0; i < 4; i++) cb[i] = ldg16(p.c + t + 128 * i);
      asm volatile("ld.relaxed.gpu.global.u32 %0, [%1];" : "=r"(tag) : "l"(&g_epoch) : "memory");
      TS(0);
      tag += 1;
      float a[8];
#pragma unroll
      for (int k = 0; k < 8; k++) a[k] = 0.f;
#pragma unroll
      for (int i = 0; i < 4; i++) {
        const float s = silu_c(cb[i]);
        a[0] = fmaf(s, bf_lo(w[i].x), a[0]); a[1] = fmaf(s, bf_hi(w[i].x), a[1]);
        a[2] = fmaf(s, bf_lo(w[i].y), a[2]); a[3] = fmaf(s, bf_hi(w[i].y), a[3]);
        a[4] = fmaf(s, bf_lo(w[i].z), a[4]); a[5] = fmaf(s, bf_hi(w[i].z), a[5]);
        a[6] = fmaf(s, bf_lo(w[i].w), a[6]); a[7] = fmaf(s, bf_hi(w[i].w), a[7]);
      }
      const bool h16 = lane & 16, h8 = lane & 8, h4 = lane & 4;
#pragma unroll
      for (int k = 0; k < 4; k++) {
        float send = h16 ? a[k] : a[k + 4], keep = h16 ? a[k + 4] : a[k];
        a[k] = keep + __shfl_xor_sync(0xffffffffu, send, 16);
      }
#pragma unroll
      for (int k = 0; k < 2; k++) {
        float send = h8 ? a[k] : a[k + 2], keep = h8 ? a[k + 2] : a[k];
        a[k] = keep + __shfl_xor_sync(0xffffffffu, send, 8);
      }
      {
        float send = h4 ? a[0] : a[1], keep = h4 ? a[1] : a[0];
        a[0] = keep + __shfl_xor_sync(0xffffffffu, send, 4);
      }
      a[0] += __shfl_xor_sync(0xffffffffu, a[0], 2);
      a[0] += __shfl_xor_sync(0xffffffffu, a[0], 1);
      float* red = (float*)(smem_raw + SM_RED);
      if ((lane & 3) == 0) red[(warp - 8) * 8 + (lane >> 2)] = a[0];
      if (t == 0) *(uint32_t*)(smem_raw + SM_BAR + 64) = tag;
      bar_sync(5, 128);
      TS(1);
      if (t == 0) {
#pragma unroll
        for (int i = 0; i < EARLY_TILES; i++) {
          mbar_expect(bars + i * 8, SLOT);
          tma3d(sb + SM_RING + i * SLOT, &tmWq, bars + i * 8, 0, i * 128, (j * 4 + 1) * 2);
        }
      }
      if (warp == 9) {
        const int cl = lane & 7;
        float v = round_bf16(red[cl] + red[8 + cl] + red[16 + cl] + red[24 + cl]);
        if (bid >= 64) v = 1.f + v;
        float vn = __shfl_down_sync(0xffffffffu, v, 1);
        uint32_t wd = pack_bf16(v, vn);
        uint32_t w0 = __shfl_sync(0xffffffffu, wd, (lane & 1) * 4);
        uint32_t w1 = __shfl_sync(0xffffffffu, wd, (lane & 1) * 4 + 2);
        if (lane < 16) st_pkt(&g_mod1[(lane >> 1) * 256 + bid * 2 + (lane & 1)], w0, w1, tag, 0);
      }
      uint32_t r0[4], r1[4];
      const uint4* src = &g_mod1[j * 256 + t];
      __nanosleep(MOD1_DELAY);
      int spins = 0;
      do {
        ld_pkt(src, r0);
        ld_pkt(src + 128, r1);
      } while ((r0[2] != tag || r1[2] != tag) && ++spins < SPIN_LIMIT);
      const int g = t >> 2, pp = (t & 3) * 2;
      const uint32_t ad = sb + SM_TAB + (uint32_t)(g * 4 + (pp & 3)) * 16 + (pp >> 2) * 4;
      asm volatile("st.shared.b32 [%0], %1;" ::"r"(ad + 8), "r"(r0[0]) : "memory");
      asm volatile("st.shared.b32 [%0], %1;" ::"r"(ad + 24), "r"(r0[1]) : "memory");
      asm volatile("st.shared.b32 [%0], %1;" ::"r"(ad), "r"(r1[0]) : "memory");
      asm volatile("st.shared.b32 [%0], %1;" ::"r"(ad + 16), "r"(r1[1]) : "memory");
      bar_arrive(1, 384);
      TS(2);
    }
    if (warp == 8) {
      if (lane == 0) {
        uint32_t s = EARLY_TILES & 3, ph = 1 ^ (EARLY_TILES >> 2);
#pragma unroll 1
        for (int tt = EARLY_TILES; tt < NTILES; tt++) {
          const CUtensorMap* tm;
          int c1, c2;
          uint32_t bytes = SLOT;
          if (tt < 16) {
            tm = &tmWq; c1 = (tt & 3) * 128; c2 = (j * 4 + (((tt >> 2) + 1) & 3)) * 2;
          } else if (tt < 48) {
            const int u = tt - 16;
            const bool isK = (u == 0) || ((u & 1) && u != 31);
            const int n = isK ? ((u + 1) >> 1) : (u == 31 ? 15 : (u >> 1) - 1);
            tm = isK ? &tmK : &tmV; c1 = j * SK + (SK - WIN) + (n & 3) * 128; c2 = 0;
          } else if (tt < 64) {
            const int u = tt - 48;
            tm = &tmWo; c1 = j * 512 + (u & 3) * 128; c2 = (u >> 2) * 2;
          } else if (tt < 72) {
            tm = &tmW1; c1 = (tt - 64) * 64; c2 = j * 7; bytes = 28672;
          } else {
            const int u = tt - 72;
            tm = &tmW2; c1 = j * FSL + (u & 1) * 112; c2 = (u >> 1) * 2; bytes = 28672;
          }
          mbar_wait(bars + 32 + s * 8, ph);
          mbar_expect(bars + s * 8, bytes);
          tma3d(sb + SM_RING + s * SLOT, tm, bars + s * 8, 0, c1, c2);
          if (++s == (tt < 48 ? 4u : 3u)) { s = 0; ph ^= 1; }
        }
      }
    } else if (warp >= 10) {
      const int t2 = tid - 320, hf = t2 & 1, r0 = t2 >> 1;
      float a[8];
#pragma unroll
      for (int k = 0; k < 8; k++) a[k] = 0.f;
#pragma unroll 1
      for (int b = 0; b < 8; b++) {
        uint4 w[2];
        uint32_t cb[2];
#pragma unroll
        for (int i = 0; i < 2; i++) {
          w[i] = ldg128(p.wmod + (size_t)(r0 + 32 * (2 * b + i)) * 3072 + 1024 + bid * 16 + hf * 8);
          cb[i] = ldg16(p.c + r0 + 32 * (2 * b + i));
        }
#pragma unroll
        for (int i = 0; i < 2; i++) {
          const float s = silu_c(cb[i]);
          a[0] = fmaf(s, bf_lo(w[i].x), a[0]); a[1] = fmaf(s, bf_hi(w[i].x), a[1]);
          a[2] = fmaf(s, bf_lo(w[i].y), a[2]); a[3] = fmaf(s, bf_hi(w[i].y), a[3]);
          a[4] = fmaf(s, bf_lo(w[i].z), a[4]); a[5] = fmaf(s, bf_hi(w[i].z), a[5]);
          a[6] = fmaf(s, bf_lo(w[i].w), a[6]); a[7] = fmaf(s, bf_hi(w[i].w), a[7]);
        }
      }
      const bool h16 = lane & 16, h8 = lane & 8, h4 = lane & 4;
#pragma unroll
      for (int k = 0; k < 4; k++) {
        float send = h16 ? a[k] : a[k + 4], keep = h16 ? a[k + 4] : a[k];
        a[k] = keep + __shfl_xor_sync(0xffffffffu, send, 16);
      }
#pragma unroll
      for (int k = 0; k < 2; k++) {
        float send = h8 ? a[k] : a[k + 2], keep = h8 ? a[k + 2] : a[k];
        a[k] = keep + __shfl_xor_sync(0xffffffffu, send, 8);
      }
      {
        float send = h4 ? a[0] : a[1], keep = h4 ? a[1] : a[0];
        a[0] = keep + __shfl_xor_sync(0xffffffffu, send, 4);
      }
      a[0] += __shfl_xor_sync(0xffffffffu, a[0], 2);
      float* red = (float*)(smem_raw + SM_RED) + 32;
      if ((lane & 2) == 0) red[(warp - 10) * 16 + hf * 8 + (lane >> 2)] = a[0];
      bar_sync(4, 64);
      if (warp == 10) {
        const int cl = lane & 15;
        float v = round_bf16(red[cl] + red[16 + cl]);
        if ((bid >> 5) == 2) v = 1.f + v;
        float vn = __shfl_down_sync(0xffffffffu, v, 1);
        uint32_t wd = pack_bf16(v, vn);
        uint32_t w0 = __shfl_sync(0xffffffffu, wd, (lane & 3) * 2);
        uint32_t w1 = __shfl_sync(0xffffffffu, wd, (lane & 3) * 2 + 8);
        if (lane < 4) st_pkt(&g_mod2[bid * 4 + lane], w0, w1, tag, 0);
      }
      const int isv = warp - 10;
      if (bid < 112) {
        const int kk = lane >> 1;
        const uint4* mp = &g_mod2[(isv ? 1 : 2) * 128 + ((kk & 7) >> 1)];
#pragma unroll
        for (int k = 0; k < 8; k++) a[k] = 0.f;
#pragma unroll 2
        for (int g = 0; g < 32; g++) {
          const uint4 w = ldg128(p.w1 + (size_t)(g * 16 + kk) * FF + bid * 16 + (lane & 1) * 8);
          uint32_t m[4];
          ld_mod(mp + g * 4, tag, m);
          const uint32_t mw = (kk & 8) ? m[1] : m[0];
          const float s = (kk & 1) ? bf_hi(mw) : bf_lo(mw);
          a[0] = fmaf(s, bf_lo(w.x), a[0]); a[1] = fmaf(s, bf_hi(w.x), a[1]);
          a[2] = fmaf(s, bf_lo(w.y), a[2]); a[3] = fmaf(s, bf_hi(w.y), a[3]);
          a[4] = fmaf(s, bf_lo(w.z), a[4]); a[5] = fmaf(s, bf_hi(w.z), a[5]);
          a[6] = fmaf(s, bf_lo(w.w), a[6]); a[7] = fmaf(s, bf_hi(w.w), a[7]);
        }
#pragma unroll
        for (int k = 0; k < 4; k++) {
          float send = h16 ? a[k] : a[k + 4], keep = h16 ? a[k + 4] : a[k];
          a[k] = keep + __shfl_xor_sync(0xffffffffu, send, 16);
        }
#pragma unroll
        for (int o = 8; o > 1; o >>= 1) {
#pragma unroll
          for (int k = 0; k < 4; k++) a[k] += __shfl_xor_sync(0xffffffffu, a[k], o);
        }
        const float sc = isv ? 0.5f : 1.f;
        if ((lane & 14) == 0)
          st_pkt(&g_uv[isv * 448 + bid * 4 + (lane & 1) * 2 + (lane >> 4)],
                 (__float_as_uint(a[0] * sc) & ~1u) | (tag & 1u), __float_as_uint(a[1] * sc), __float_as_uint(a[2] * sc),
                 __float_as_uint(a[3] * sc));
      }
      bar_sync(6, 320);
#pragma unroll 1
      for (int i = lane; i < 56; i += 32) {
        uint32_t m[4];
        int spins = 0;
        do { ld_pkt(&g_uv[isv * 448 + j * 56 + i], m); } while (((m[0] ^ tag) & 1u) && ++spins < SPIN_LIMIT);
        const uint32_t ad = sb + SM_TAB + i * 32 + isv * 8;
        asm volatile("st.shared.v2.b32 [%0], {%1,%2};" ::"r"(ad), "r"(m[0]), "r"(m[1]) : "memory");
        asm volatile("st.shared.v2.b32 [%0], {%1,%2};" ::"r"(ad + 16), "r"(m[2]), "r"(m[3]) : "memory");
      }
      __syncwarp();
      if (lane == 0) mbar_arrive(bars + 72);
    } else {
      if (lane < 8) l2_prefetch((const char*)p.wo + (size_t)bid * 32768 + lane * 4096, 4096);
      else if (lane < 12) l2_prefetch((const char*)p.w1 + (size_t)bid * 14336 + (lane - 8) * 3584, 3584);
      else if (lane < 16) l2_prefetch((const char*)p.w2 + (size_t)bid * 14336 + (lane - 12) * 3584, 3584);
    }
  } else {
    const int wg = warp >> 2;
    const int q = lane & 3, gq = lane >> 2;
    const Ring ring{(sb + SM_RING) >> 4, bars};
    const uint32_t xoff = (uint32_t)(rt * 128 + 16 * j + warp) * 256 + gq * 8 + q;
    const uint32_t ooff = ((uint32_t)(rt * 8 + j) * 32 + gq) * 32 + warp * 4 + q;
    const uint32_t goff = (uint32_t)(rt * 8 + warp) * 1024 + lane;

    {
      const uint32_t* xo = (const uint32_t*)p.x + xoff;
      uint32_t xr[4][4];
#pragma unroll
      for (int c = 0; c < 4; c++) {
        xr[c][0] = ldg32(xo + c * 64);
        xr[c][1] = ldg32(xo + c * 64 + 8 * 256);
        xr[c][2] = ldg32(xo + c * 64 + 4);
        xr[c][3] = ldg32(xo + c * 64 + 4 + 8 * 256);
      }
      float s0 = 0.f, s1 = 0.f, v0 = 0.f, v1 = 0.f;
#pragma unroll
      for (int c = 0; c < 4; c++) {
#pragma unroll
        for (int e = 0; e < 4; e++) {
          const float a = bf_lo(xr[c][e]), b = bf_hi(xr[c][e]);
          if (e & 1) { s1 += a + b; v1 = fmaf(a, a, fmaf(b, b, v1)); }
          else { s0 += a + b; v0 = fmaf(a, a, fmaf(b, b, v0)); }
        }
      }
#pragma unroll
      for (int o = 16; o > 0; o >>= 1) {
        s0 += __shfl_xor_sync(0xffffffffu, s0, o);
        s1 += __shfl_xor_sync(0xffffffffu, s1, o);
        v0 += __shfl_xor_sync(0xffffffffu, v0, o);
        v1 += __shfl_xor_sync(0xffffffffu, v1, o);
      }
      const float m0 = s0 * (1.f / 512.f), m1 = s1 * (1.f / 512.f);
      const float r0 = rsqrtf(fmaxf(fmaf(-m0, m0, v0 * (1.f / 512.f)), 0.f) + 1e-5f);
      const float r1 = rsqrtf(fmaxf(fmaf(-m1, m1, v1 * (1.f / 512.f)), 0.f) + 1e-5f);
#pragma unroll
      for (int c = 0; c < 4; c++) {
        st_pkt(g_G + ooff + c * 256,
               pack_tag<1>((bf_lo(xr[c][0]) - m0) * r0, (bf_hi(xr[c][0]) - m0) * r0),
               pack_bf16((bf_lo(xr[c][1]) - m1) * r1, (bf_hi(xr[c][1]) - m1) * r1),
               pack_bf16((bf_lo(xr[c][2]) - m0) * r0, (bf_hi(xr[c][2]) - m0) * r0),
               pack_bf16((bf_lo(xr[c][3]) - m1) * r1, (bf_hi(xr[c][3]) - m1) * r1));
      }
    }
    TS(0);
    asm volatile("setmaxnreg.inc.sync.aligned.u32 232;");
    uint32_t qf[8][4];
    {
      uint32_t h[32][4];
      float acc[64];
      const uint4* Gin = g_G + goff;
      __nanosleep(G_DELAY);
      issue_pkts<1, 8>(Gin, 32, h);
      verify8_tag1<512>(Gin, h);
      issue_pkts<1, 8>(Gin + 256, 32, h + 8);
      TS(1);
      bar_sync(1, 384);
#pragma unroll
      for (int c = 0; c < 4; c++) {
        if (c > 0) verify8_tag1<512>(Gin + c * 256, h + c * 8);
        if (c > 0 && c < 3) issue_pkts<1, 8>(Gin + (c + 1) * 256, 32, h + (c + 1) * 8);
#pragma unroll
        for (int i = 0; i < 8; i++) {
          uint32_t m[4];
          lds128(sb + SM_TAB + (uint32_t)((c * 8 + i) * 4 + q) * 16, m);
          uint32_t* hh = h[c * 8 + i];
          hh[0] = hfma2_bf16(hh[0], m[0], m[2]);
          hh[1] = hfma2_bf16(hh[1], m[0], m[2]);
          hh[2] = hfma2_bf16(hh[2], m[1], m[3]);
          hh[3] = hfma2_bf16(hh[3], m[1], m[3]);
        }
        fence_frags<8>(h + c * 8);
        const uint32_t b = ring.wait_full(c, 0);
        if (c > 0) { wg_wait<0>(); ring.release(c - 1); }
        if (c == 0) TS(2);
        wg_fence();
        static_for<0, 8>([&](auto K) { wgmma_rs_n128_tb1<LB_MN128 + K * 128, HI128>(acc, h[c * 8 + K], b, (c | K) != 0); });
        wg_commit();
      }
      bar_arrive(6, 320);
#pragma unroll 1
      for (int ps = 1; ps < 4; ps++) {
        wg_wait<0>();
        ring.release(3);
        fence_regs(acc);
#pragma unroll
        for (int i = 0; i < 8; i++) {
          uint32_t o[4];
          pack8(o, acc + 8 * i);
          sts128(sb + SM_PARK + (ps - 1) * SLOT + i * 4096 + tid * 16, o[0], o[1], o[2], o[3]);
        }
#pragma unroll
        for (int c = 0; c < 4; c++) {
          const uint32_t b = ring.wait_full(c, ps & 1);
          if (c > 0) { wg_wait<0>(); ring.release(c - 1); }
          wg_fence();
          static_for<0, 8>([&](auto K) { wgmma_rs_n128_tb1<LB_MN128 + K * 128, HI128>(acc, h[c * 8 + K], b, (c | K) != 0); });
          wg_commit();
        }
      }
      wg_wait<0>();
      ring.release(3);
      fence_regs(acc);
#pragma unroll
      for (int i = 0; i < 8; i++) pack8(qf[i], acc + 8 * i);
    }
    fence_regs(qf);
    TS(3);

    float S[64];
    {
      float O[64];
      uint32_t P[8][4];
      const float cs = 0.08838834764831845f * 1.4426950408889634f;
      const int TAU = 0x41800000;
      float m0, m1, l0, l1;

      auto first_block_max = [&]() {
        int a0 = __vimax3_s32(__float_as_int(S[0]), __float_as_int(S[1]), __float_as_int(S[1]));
        int a1 = __vimax3_s32(__float_as_int(S[2]), __float_as_int(S[3]), __float_as_int(S[3]));
#pragma unroll
        for (int i = 1; i < 16; i++) {
          a0 = __vimax3_s32(a0, __float_as_int(S[4 * i]), __float_as_int(S[4 * i + 1]));
          a1 = __vimax3_s32(a1, __float_as_int(S[4 * i + 2]), __float_as_int(S[4 * i + 3]));
        }
        a0 = max(a0, __shfl_xor_sync(0xffffffffu, a0, 1)); a1 = max(a1, __shfl_xor_sync(0xffffffffu, a1, 1));
        a0 = max(a0, __shfl_xor_sync(0xffffffffu, a0, 2)); a1 = max(a1, __shfl_xor_sync(0xffffffffu, a1, 2));
        float b0 = __int_as_float(a0), b1 = __int_as_float(a1);
        if (__any_sync(0xffffffffu, (a0 | a1) < 0)) {
          b0 = fmaxf(S[0], S[1]); b1 = fmaxf(S[2], S[3]);
#pragma unroll
          for (int i = 1; i < 16; i++) {
            b0 = fmaxf(b0, fmaxf(S[4 * i], S[4 * i + 1]));
            b1 = fmaxf(b1, fmaxf(S[4 * i + 2], S[4 * i + 3]));
          }
          b0 = fmaxf(b0, __shfl_xor_sync(0xffffffffu, b0, 1)); b1 = fmaxf(b1, __shfl_xor_sync(0xffffffffu, b1, 1));
          b0 = fmaxf(b0, __shfl_xor_sync(0xffffffffu, b0, 2)); b1 = fmaxf(b1, __shfl_xor_sync(0xffffffffu, b1, 2));
        }
        m0 = b0 * cs; m1 = b1 * cs;
      };
      auto scale_sub = [&]() {
#pragma unroll
        for (int i = 0; i < 16; i++) {
          S[4 * i] = fmaf(S[4 * i], cs, -m0); S[4 * i + 1] = fmaf(S[4 * i + 1], cs, -m0);
          S[4 * i + 2] = fmaf(S[4 * i + 2], cs, -m1); S[4 * i + 3] = fmaf(S[4 * i + 3], cs, -m1);
        }
      };
      auto exps = [&](int i0, int i1) {
#pragma unroll
        for (int i = i0; i < i1; i++) {
          S[4 * i] = ex2(S[4 * i]); S[4 * i + 1] = ex2(S[4 * i + 1]);
          S[4 * i + 2] = ex2(S[4 * i + 2]); S[4 * i + 3] = ex2(S[4 * i + 3]);
          l0 += S[4 * i]; l1 += S[4 * i + 2]; l0 += S[4 * i + 1]; l1 += S[4 * i + 3];
        }
      };
      {
        const uint32_t b = ring.wait_full(0, 0);
        wg_fence();
        static_for<0, 8>([&](auto K) { wgmma_rs_n128_tb0<LB_K128 + (K >> 2) * 1024 + (K & 3) * 2, HI128>(S, qf[K], b, K != 0); });
        wg_commit();
        wg_wait<0>();
        fence_regs(S);
        ring.release(0);
        first_block_max();
        scale_sub();
        l0 = 0.f; l1 = 0.f;
        exps(0, 16);
#pragma unroll
        for (int i = 0; i < 8; i++) pack8(P[i], S + 8 * i);
      }
      fence_regs(P);
      if (wg == 1) bar_arrive(2, 256);
#pragma unroll 1
      for (int n = 1; n < 16; n++) {
        const uint32_t tk = 2 * n - 1, tv = 2 * n;
        const bool newhead = (n & 3) == 0;
        const uint32_t bk = ring.wait_full(tk & 3, (tk >> 2) & 1);
        const uint32_t bv = ring.wait_full(tv & 3, (tv >> 2) & 1);
        bar_sync(2 + wg, 256);
        wg_fence();
        static_for<0, 8>([&](auto K) { wgmma_rs_n128_tb0<LB_K128 + (K >> 2) * 1024 + (K & 3) * 2, HI128>(S, qf[K], bk, K != 0); });
        wg_commit();
        static_for<0, 8>([&](auto K) { wgmma_rs_n128_tb1<LB_MN128 + K * 128, HI128>(O, P[K], bv, K != 0 || (n & 3) != 1); });
        wg_commit();
        bar_arrive(2 + (wg ^ 1), 256);
        wg_wait<1>();
        fence_regs(S);
        ring.release(tk & 3);
        if ((n & 3) == 3 && n != 15) {
          fence_regs(qf);
#pragma unroll
          for (int i = 0; i < 8; i++) lds128(sb + SM_PARK + (n >> 2) * SLOT + i * 4096 + tid * 16, qf[i]);
        }
        float f0 = 1.f, f1 = 1.f;
        bool resc = newhead;
        if (newhead) {
          l0 += __shfl_xor_sync(0xffffffffu, l0, 1); l1 += __shfl_xor_sync(0xffffffffu, l1, 1);
          l0 += __shfl_xor_sync(0xffffffffu, l0, 2); l1 += __shfl_xor_sync(0xffffffffu, l1, 2);
          f0 = rcp_hw(l0); f1 = rcp_hw(l1);
          l0 = 0.f; l1 = 0.f;
          first_block_max();
          scale_sub();
        } else {
          scale_sub();
          int a0 = __vimax3_s32(__float_as_int(S[0]), __float_as_int(S[1]), __float_as_int(S[1]));
          int a1 = __vimax3_s32(__float_as_int(S[2]), __float_as_int(S[3]), __float_as_int(S[3]));
#pragma unroll
          for (int i = 1; i < 16; i++) {
            a0 = __vimax3_s32(a0, __float_as_int(S[4 * i]), __float_as_int(S[4 * i + 1]));
            a1 = __vimax3_s32(a1, __float_as_int(S[4 * i + 2]), __float_as_int(S[4 * i + 3]));
          }
          if (__any_sync(0xffffffffu, max(a0, a1) > TAU)) {
            a0 = max(a0, 0); a1 = max(a1, 0);
            a0 = max(a0, __shfl_xor_sync(0xffffffffu, a0, 1)); a1 = max(a1, __shfl_xor_sync(0xffffffffu, a1, 1));
            a0 = max(a0, __shfl_xor_sync(0xffffffffu, a0, 2)); a1 = max(a1, __shfl_xor_sync(0xffffffffu, a1, 2));
            const float d0 = __int_as_float(a0), d1 = __int_as_float(a1);
#pragma unroll
            for (int i = 0; i < 16; i++) { S[4 * i] -= d0; S[4 * i + 1] -= d0; S[4 * i + 2] -= d1; S[4 * i + 3] -= d1; }
            m0 += d0; m1 += d1;
            f0 = ex2(-d0); f1 = ex2(-d1);
            l0 *= f0; l1 *= f1;
            resc = true;
          }
        }
        exps(0, 4);
        wg_wait<0>();
        fence_regs(O);
        fence_regs(P);
        ring.release(tv & 3);
        if (resc) {
#pragma unroll
          for (int i = 0; i < 16; i++) {
            O[4 * i] *= f0; O[4 * i + 1] *= f0; O[4 * i + 2] *= f1; O[4 * i + 3] *= f1;
          }
          if (newhead) {
#pragma unroll
            for (int i = 0; i < 8; i++) {
              uint32_t o[4];
              pack8(o, O + 8 * i);
              sts128(sb + SM_PARK + ((n >> 2) - 1) * SLOT + i * 4096 + tid * 16, o[0], o[1], o[2], o[3]);
            }
          }
        }
        exps(4, 16);
#pragma unroll
        for (int i = 0; i < 8; i++) pack8(P[i], S + 8 * i);
        fence_regs(P);
        fence_regs(O);
      }
      {
        const uint32_t bv = ring.wait_full(3, 1);
        if (wg == 0) bar_sync(2, 256);
        wg_fence();
        static_for<0, 8>([&](auto K) { wgmma_rs_n128_tb1<LB_MN128 + K * 128, HI128>(O, P[K], bv, 1); });
        wg_commit();
        l0 += __shfl_xor_sync(0xffffffffu, l0, 1); l1 += __shfl_xor_sync(0xffffffffu, l1, 1);
        l0 += __shfl_xor_sync(0xffffffffu, l0, 2); l1 += __shfl_xor_sync(0xffffffffu, l1, 2);
        const float f0 = rcp_hw(l0), f1 = rcp_hw(l1);
        wg_wait<0>();
        fence_regs(O);
#pragma unroll
        for (int i = 0; i < 8; i++) {
          qf[i][0] = pack_bf16(O[8 * i] * f0, O[8 * i + 1] * f0); qf[i][1] = pack_bf16(O[8 * i + 2] * f1, O[8 * i + 3] * f1);
          qf[i][2] = pack_bf16(O[8 * i + 4] * f0, O[8 * i + 5] * f0); qf[i][3] = pack_bf16(O[8 * i + 6] * f1, O[8 * i + 7] * f1);
        }
      }
    }
    fence_regs(qf);
    TS(4);

    uint4* const Pout = g_P + ((size_t)(rt * 8 + warp) * 8 + j) * 1024;
    const uint32_t stage = sb + SM_RING + 3 * SLOT + warp * 4096;
    const uint32_t stoff = gq * 512 + (gq & 1) * 64 + q * 16;
    const uint32_t tag = *(volatile uint32_t*)(smem_raw + SM_BAR + 64);
    const uint4* const Pown = g_P + (size_t)(rt * 8 + j) * 8192 + warp * 32 + lane;
    const int go = gq ^ (warp & 1);
    const uint32_t xoff2 = (uint32_t)(rt * 128 + 16 * j + warp) * 256 + go * 8 + q;
    const uint32_t ooff2 = ((uint32_t)(rt * 8 + j) * 32 + go) * 32 + warp * 4 + q;
    const uint4* const mod2p = g_mod2 + go * 4 + q;

    auto store_partial = [&](auto TAGC, uint32_t stg, int c) {
#pragma unroll
      for (int i = 0; i < 8; i++)
        sts128(stg + (stoff ^ (i * 64)), pack_tag<TAGC>(S[8 * i], S[8 * i + 1]), pack_bf16(S[8 * i + 2], S[8 * i + 3]),
               pack_bf16(S[8 * i + 4], S[8 * i + 5]), pack_bf16(S[8 * i + 6], S[8 * i + 7]));
      warp_bulk_store(Pout + c * 256, stg, 4096);
    };
    uint32_t r[8][4], xr[4], ga[4], g2[4];
    float s0 = 0.f, s1 = 0.f, v0 = 0.f, v1 = 0.f;
    auto red1_issue = [&](int c) {
      issue_pkts<1, 8>(Pown + c * 256, 1024, r);
      const uint32_t* xo = (const uint32_t*)p.x + xoff2 + c * 64;
      xr[0] = ldg32(xo); xr[1] = ldg32(xo + 8 * 256); xr[2] = ldg32(xo + 4); xr[3] = ldg32(xo + 4 + 8 * 256);
      ld_pkt(mod2p + c * 32, ga);
      ld_pkt(mod2p + 256 + c * 32, g2);
    };
    auto red1_process = [&](int c, float (&x2)[8]) {
      if (ga[2] != tag) ld_mod(mod2p + c * 32, tag, ga);
      if (g2[2] != tag) ld_mod(mod2p + 256 + c * 32, tag, g2);
      verify8_tag1<16384>(Pown + c * 256, r);
      float hv[8];
#pragma unroll
      for (int e = 0; e < 4; e++) {
        float y0 = bf_lo(r[0][e]), y1 = bf_hi(r[0][e]);
#pragma unroll
        for (int s = 1; s < 8; s++) { y0 += bf_lo(r[s][e]); y1 += bf_hi(r[s][e]); }
        const float a = fmaf(bf_lo(ga[e >> 1]), y0, bf_lo(xr[e])), b = fmaf(bf_hi(ga[e >> 1]), y1, bf_hi(xr[e]));
        x2[2 * e] = a; x2[2 * e + 1] = b;
        hv[2 * e] = a * bf_lo(g2[e >> 1]); hv[2 * e + 1] = b * bf_hi(g2[e >> 1]);
        if (e & 1) { s1 += a + b; v1 = fmaf(a, a, fmaf(b, b, v1)); }
        else { s0 += a + b; v0 = fmaf(a, a, fmaf(b, b, v0)); }
      }
      st_pkt(g_G + ooff2 + c * 256, pack_tag<0>(hv[0], hv[1]), pack_bf16(hv[2], hv[3]), pack_bf16(hv[4], hv[5]),
             pack_bf16(hv[6], hv[7]));
    };
    auto park_x2 = [&](int c, const float (&x2)[8]) {
      sts128(sb + SM_PARK + (2 * c) * 4096 + tid * 16, __float_as_uint(x2[0]), __float_as_uint(x2[1]),
             __float_as_uint(x2[2]), __float_as_uint(x2[3]));
      sts128(sb + SM_PARK + (2 * c + 1) * 4096 + tid * 16, __float_as_uint(x2[4]), __float_as_uint(x2[5]),
             __float_as_uint(x2[6]), __float_as_uint(x2[7]));
    };

    const uint4* const Gin = g_G + goff;
    uint32_t fa[2][4][4];
    {
      float x2a[8];
      uint32_t a[8][4];
#pragma unroll
      for (int i = 0; i < 8; i++) lds128(sb + SM_PARK + i * 4096 + tid * 16, a[i]);
      uint32_t b = ring.wait_full(0, 0);
      static_for<0, 16>([&](auto U) {
        constexpr int u = U, hh = u & 3, c = u >> 2;
        wg_fence();
        static_for<0, 8>([&](auto K) { wgmma_rs_n128_tb1<LB_MN128 + K * 128, HI128>(S, hh < 3 ? a[K] : qf[K], b, (hh | K) != 0); });
        wg_commit();
        if constexpr (u == 7 || u == 11 || u == 15) red1_issue(c - 1);
        if constexpr (u == 8) red1_process(0, x2a);
        if constexpr (u == 12) {
          float x2b[8];
          red1_process(1, x2b);
          park_x2(0, x2a);
          park_x2(1, x2b);
        }
        if constexpr (u == 15) issue_pkts<0, 4>(Gin, 32, fa[0]);
        if constexpr (hh == 3) warp_bulk_wait_read<0>();
        b = ring.wait_full((u + 1) % 3, ((u + 1) / 3) & 1);
        wg_wait<0>();
        ring.release(u % 3);
        if constexpr (hh != 2 && u != 15) {
          fence_regs(a);
#pragma unroll
          for (int i = 0; i < 8; i++) lds128(sb + SM_PARK + ((hh + 1) & 3) * SLOT + i * 4096 + tid * 16, a[i]);
        }
        if constexpr (hh == 3) {
          fence_regs(S);
          store_partial(IC<1>{}, stage, c);
        }
      });
    }
    TS(5);

    uint32_t H[14][4];
    {
      float acc[112];
      uint32_t st[4];
      uint32_t b = ring.base16 + (16 % 3) * (SLOT >> 4);
      static_for<0, 8>([&](auto U) {
        constexpr int u = U;
        verify4_tag0<512>(Gin + u * 128, fa[u & 1]);
        if constexpr (u == 0) TS(6);
        if constexpr (u == 6) TS(7);
        wg_fence();
        static_for<0, 4>([&](auto K) { wgmma_rs_n224_tb1<LB_W1 + K * 64, HI64>(acc, fa[u & 1][K], b, (u | K) != 0); });
        wg_commit();
        if constexpr (u != 5 && u < 7) issue_pkts<0, 4>(Gin + (u + 1) * 128, 32, fa[(u + 1) & 1]);
        if constexpr (u == 0) { float x2[8]; red1_process(2, x2); park_x2(2, x2); }
        if constexpr (u == RED3_UNIT) {
          float x2[8];
          red1_issue(3);
          red1_process(3, x2);
          park_x2(3, x2);
#pragma unroll
          for (int o = 16; o > 0; o >>= 1) {
            s0 += __shfl_xor_sync(0xffffffffu, s0, o);
            s1 += __shfl_xor_sync(0xffffffffu, s1, o);
            v0 += __shfl_xor_sync(0xffffffffu, v0, o);
            v1 += __shfl_xor_sync(0xffffffffu, v1, o);
          }
          const float m0 = s0 * (1.f / 512.f), m1 = s1 * (1.f / 512.f);
          const float r0 = 0.5f * rsqrtf(fmaxf(fmaf(-m0, m0, v0 * (1.f / 512.f)), 0.f) + 1e-5f);
          const float r1 = 0.5f * rsqrtf(fmaxf(fmaf(-m1, m1, v1 * (1.f / 512.f)), 0.f) + 1e-5f);
          if (lane < 2)
            st_pkt(&g_stat[((rt * 8 + j) * 8 + warp) * 2 + lane], (__float_as_uint(r0) & ~1u) | (tag & 1u),
                   __float_as_uint(-m0 * r0), __float_as_uint(r1), __float_as_uint(-m1 * r1));
        }
        if constexpr (u == 7) {
          ld_pkt(&g_stat[((rt * 8 + warp) * 8 + gq) * 2], st);
          mbar_wait(bars + 72, 0);
        }
        b = ring.wait_full((16 + u + 1) % 3, ((16 + u + 1) / 3) & 1);
        if constexpr (u == 5) issue_pkts<0, 4>(Gin + (u + 1) * 128, 32, fa[(u + 1) & 1]);
        wg_wait<0>();
        ring.release((16 + u) % 3);
      });
      fence_regs(acc);
      TS(9);
      {
        int spins = 0;
        while (((st[0] ^ tag) & 1u) && ++spins < SPIN_LIMIT) ld_pkt(&g_stat[((rt * 8 + warp) * 8 + gq) * 2], st);
      }
      const float ra0 = __uint_as_float(st[0]), rb0 = __uint_as_float(st[1]), ra1 = __uint_as_float(st[2]),
                  rb1 = __uint_as_float(st[3]);
#pragma unroll
      for (int i = 0; i < 28; i++) {
        uint32_t m[4];
        lds128(sb + SM_TAB + (i * 4 + q) * 16, m);
        const float u0 = __uint_as_float(m[0]), u1 = __uint_as_float(m[1]), w0 = __uint_as_float(m[2]), w1 = __uint_as_float(m[3]);
        const float z0 = fmaf(acc[4 * i], ra0, fmaf(u0, rb0, w0)), z1 = fmaf(acc[4 * i + 1], ra0, fmaf(u1, rb0, w1));
        const float z2 = fmaf(acc[4 * i + 2], ra1, fmaf(u0, rb1, w0)), z3 = fmaf(acc[4 * i + 3], ra1, fmaf(u1, rb1, w1));
        H[i >> 1][(i & 1) * 2] = pack_bf16(fmaf(z0, tanh_hw(z0), z0), fmaf(z1, tanh_hw(z1), z1));
        H[i >> 1][(i & 1) * 2 + 1] = pack_bf16(fmaf(z2, tanh_hw(z2), z2), fmaf(z3, tanh_hw(z3), z3));
      }
    }
    fence_regs(H);
    TS(10);
    {
      uint32_t gb[4][4];
      uint32_t r2[8][4];
      uint32_t* const oo = (uint32_t*)p.out + xoff2;
      auto red2_process = [&](int c, uint32_t (*rr)[4]) {
        uint32_t xa[2][4];
        lds128(sb + SM_PARK + (2 * c) * 4096 + tid * 16, xa[0]);
        lds128(sb + SM_PARK + (2 * c + 1) * 4096 + tid * 16, xa[1]);
        if (gb[c][2] != tag) ld_mod(mod2p + 384 + c * 32, tag, gb[c]);
        verify8_tag0<16384>(Pown + c * 256, rr);
#pragma unroll
        for (int e = 0; e < 4; e++) {
          float y0 = bf_lo(rr[0][e]), y1 = bf_hi(rr[0][e]);
#pragma unroll
          for (int s = 1; s < 8; s++) { y0 += bf_lo(rr[s][e]); y1 += bf_hi(rr[s][e]); }
          oo[c * 64 + (e >> 1) * 4 + (e & 1) * 8 * 256] =
              pack_bf16(fmaf(bf_lo(gb[c][e >> 1]), y0, __uint_as_float(xa[e >> 1][(e & 1) * 2])),
                        fmaf(bf_hi(gb[c][e >> 1]), y1, __uint_as_float(xa[e >> 1][(e & 1) * 2 + 1])));
        }
      };
      uint32_t b = ring.base16 + (24 % 3) * (SLOT >> 4);
      static_for<0, 8>([&](auto U) {
        constexpr int u = U, hf = u & 1, c = u >> 1;
        wg_fence();
        static_for<0, 7>([&](auto K) { wgmma_rs_n128_tb1<LB_W2 + K * 128, HI128>(S, H[hf * 7 + K], b, (hf | K) != 0); });
        wg_commit();
        if constexpr (u == 0) {
#pragma unroll
          for (int cc = 0; cc < 4; cc++) ld_pkt(mod2p + 384 + cc * 32, gb[cc]);
        }
        if constexpr (u == 6) issue_pkts<0, 8>(Pown, 1024, r);
        if constexpr (hf == 1) warp_bulk_wait_read<2>();
        if constexpr (u < 7) b = ring.wait_full((24 + u + 1) % 3, ((24 + u + 1) / 3) & 1);
        wg_wait<0>();
        if constexpr (u < 5) ring.release((24 + u) % 3);
        if constexpr (hf == 1) {
          fence_regs(S);
          store_partial(IC<0>{}, c == 2 ? stage : sb + SM_PARK + (c == 1 ? 2 : 1) * SLOT + warp * 4096, c);
        }
      });
      TS(11);
      issue_pkts<0, 8>(Pown + 256, 1024, r2);
      red2_process(0, r);
      red2_process(1, r2);
      TS(13);
      issue_pkts<0, 8>(Pown + 512, 1024, r);
      red2_process(2, r);
      TS(14);
      issue_pkts<0, 8>(Pown + 768, 1024, r2);
      red2_process(3, r2);
    }
    warp_bulk_wait_read<0>();
    TS(12);
    if (bid == 0 && tid == 0) asm volatile("st.relaxed.gpu.global.u32 [%0], %1;" ::"l"(&g_epoch), "r"(tag) : "memory");
  }
}

typedef CUresult (*EncodeFn)(CUtensorMap*, CUtensorMapDataType, cuuint32_t, void*, const cuuint64_t*, const cuuint64_t*,
                             const cuuint32_t*, const cuuint32_t*, CUtensorMapInterleave, CUtensorMapSwizzle,
                             CUtensorMapL2promotion, CUtensorMapFloatOOBfill);

static void make_map(EncodeFn fn, CUtensorMap* tm, const void* ptr, int inner, int rows, int cols, int box_rows, int box_outer,
                     CUtensorMapSwizzle swz) {
  cuuint64_t gd[3] = {(cuuint64_t)inner, (cuuint64_t)rows, (cuuint64_t)(cols / inner)};
  cuuint64_t gs[2] = {(cuuint64_t)cols * 2, (cuuint64_t)inner * 2};
  cuuint32_t bx[3] = {(cuuint32_t)inner, (cuuint32_t)box_rows, (cuuint32_t)box_outer};
  cuuint32_t es[3] = {1, 1, 1};
  fn(tm, CU_TENSOR_MAP_DATA_TYPE_BFLOAT16, 3, const_cast<void*>(ptr), gd, gs, bx, es, CU_TENSOR_MAP_INTERLEAVE_NONE, swz,
     CU_TENSOR_MAP_L2_PROMOTION_L2_128B, CU_TENSOR_MAP_FLOAT_OOB_FILL_NONE);
}

extern "C" void kernel_launch(void* const* d_in, const int* in_sizes, int n_in, void* d_out, int out_size) {
  (void)in_sizes; (void)n_in; (void)out_size;
  void* fnp = nullptr;
  cudaDriverEntryPointQueryResult qr;
  cudaGetDriverEntryPoint("cuTensorMapEncodeTiled", &fnp, cudaEnableDefault, &qr);
  EncodeFn fn = (EncodeFn)fnp;
  CUtensorMap tmWq, tmK, tmV, tmWo, tmW1, tmW2;
  make_map(fn, &tmWq, d_in[3], 64, 512, 4096, 128, 2, CU_TENSOR_MAP_SWIZZLE_128B);
  make_map(fn, &tmK, d_in[1], 64, 8 * SK, 128, 128, 2, CU_TENSOR_MAP_SWIZZLE_128B);
  make_map(fn, &tmV, d_in[2], 64, 8 * SK, 128, 128, 2, CU_TENSOR_MAP_SWIZZLE_128B);
  make_map(fn, &tmWo, d_in[4], 64, 4096, 512, 128, 2, CU_TENSOR_MAP_SWIZZLE_128B);
  make_map(fn, &tmW1, d_in[6], 32, 512, FF, 64, 7, CU_TENSOR_MAP_SWIZZLE_64B);
  make_map(fn, &tmW2, d_in[7], 64, FF, 512, 112, 2, CU_TENSOR_MAP_SWIZZLE_128B);
  Params p;
  p.x = (const __nv_bfloat16*)d_in[0];
  p.c = (const __nv_bfloat16*)d_in[8];
  p.wmod = (const __nv_bfloat16*)d_in[9];
  p.wo = (const __nv_bfloat16*)d_in[4];
  p.w1 = (const __nv_bfloat16*)d_in[6];
  p.w2 = (const __nv_bfloat16*)d_in[7];
  p.out = (__nv_bfloat16*)d_out;
  cudaFuncSetAttribute(adaln_block_kernel, cudaFuncAttributeMaxDynamicSharedMemorySize, SM_TOTAL);
  adaln_block_kernel<<<128, 384, SM_TOTAL>>>(tmWq, tmK, tmV, tmWo, tmW1, tmW2, p);
}
```

```cpp
#include <cuda_runtime.h>
#include <cuda_bf16.h>
#include <cuda.h>
#include <stdint.h>

template <int OFF, uint32_t HI>
__device__ __forceinline__ void wgmma_rs_n128_tb0(float (&d)[64], const uint32_t (&a)[4], uint32_t lo, int sd) {
  asm volatile("{\n.reg .pred p;\n.reg .b32 l;\n.reg .b64 db;\nsetp.ne.b32 p, %69, 0;\n"
    "add.u32 l, %68, %70;\nmov.b64 db, {l, %71};\n"
    "wgmma.mma_async.sync.aligned.m64n128k16.f32.bf16.bf16 "
    "{%0,%1,%2,%3,%4,%5,%6,%7,%8,%9,%10,%11,%12,%13,%14,%15,"
    "%16,%17,%18,%19,%20,%21,%22,%23,%24,%25,%26,%27,%28,%29,%30,%31,"
    "%32,%33,%34,%35,%36,%37,%38,%39,%40,%41,%42,%43,%44,%45,%46,%47,"
    "%48,%49,%50,%51,%52,%53,%54,%55,%56,%57,%58,%59,%60,%61,%62,%63}, "
    "{%64,%65,%66,%67}, db, p, 1, 1, 0;\n}\n"
    : "+f"(d[0]), "+f"(d[1]), "+f"(d[2]), "+f"(d[3]), "+f"(d[4]), "+f"(d[5]), "+f"(d[6]), "+f"(d[7]),
      "+f"(d[8]), "+f"(d[9]), "+f"(d[10]), "+f"(d[11]), "+f"(d[12]), "+f"(d[13]), "+f"(d[14]), "+f"(d[15]),
      "+f"(d[16]), "+f"(d[17]), "+f"(d[18]), "+f"(d[19]), "+f"(d[20]), "+f"(d[21]), "+f"(d[22]), "+f"(d[23]),
      "+f"(d[24]), "+f"(d[25]), "+f"(d[26]), "+f"(d[27]), "+f"(d[28]), "+f"(d[29]), "+f"(d[30]), "+f"(d[31]),
      "+f"(d[32]), "+f"(d[33]), "+f"(d[34]), "+f"(d[35]), "+f"(d[36]), "+f"(d[37]), "+f"(d[38]), "+f"(d[39]),
      "+f"(d[40]), "+f"(d[41]), "+f"(d[42]), "+f"(d[43]), "+f"(d[44]), "+f"(d[45]), "+f"(d[46]), "+f"(d[47]),
      "+f"(d[48]), "+f"(d[49]), "+f"(d[50]), "+f"(d[51]), "+f"(d[52]), "+f"(d[53]), "+f"(d[54]), "+f"(d[55]),
      "+f"(d[56]), "+f"(d[57]), "+f"(d[58]), "+f"(d[59]), "+f"(d[60]), "+f"(d[61]), "+f"(d[62]), "+f"(d[63])
    : "r"(a[0]), "r"(a[1]), "r"(a[2]), "r"(a[3]), "r"(lo), "r"(sd), "n"(OFF), "n"(HI));
}

template <int OFF, uint32_t HI>
__device__ __forceinline__ void wgmma_rs_n128_tb1(float (&d)[64], const uint32_t (&a)[4], uint32_t lo, int sd) {
  asm volatile("{\n.reg .pred p;\n.reg .b32 l;\n.reg .b64 db;\nsetp.ne.b32 p, %69, 0;\n"
    "add.u32 l, %68, %70;\nmov.b64 db, {l, %71};\n"
    "wgmma.mma_async.sync.aligned.m64n128k16.f32.bf16.bf16 "
    "{%0,%1,%2,%3,%4,%5,%6,%7,%8,%9,%10,%11,%12,%13,%14,%15,"
    "%16,%17,%18,%19,%20,%21,%22,%23,%24,%25,%26,%27,%28,%29,%30,%31,"
    "%32,%33,%34,%35,%36,%37,%38,%39,%40,%41,%42,%43,%44,%45,%46,%47,"
    "%48,%49,%50,%51,%52,%53,%54,%55,%56,%57,%58,%59,%60,%61,%62,%63}, "
    "{%64,%65,%66,%67}, db, p, 1, 1, 1;\n}\n"
    : "+f"(d[0]), "+f"(d[1]), "+f"(d[2]), "+f"(d[3]), "+f"(d[4]), "+f"(d[5]), "+f"(d[6]), "+f"(d[7]),
      "+f"(d[8]), "+f"(d[9]), "+f"(d[10]), "+f"(d[11]), "+f"(d[12]), "+f"(d[13]), "+f"(d[14]), "+f"(d[15]),
      "+f"(d[16]), "+f"(d[17]), "+f"(d[18]), "+f"(d[19]), "+f"(d[20]), "+f"(d[21]), "+f"(d[22]), "+f"(d[23]),
      "+f"(d[24]), "+f"(d[25]), "+f"(d[26]), "+f"(d[27]), "+f"(d[28]), "+f"(d[29]), "+f"(d[30]), "+f"(d[31]),
      "+f"(d[32]), "+f"(d[33]), "+f"(d[34]), "+f"(d[35]), "+f"(d[36]), "+f"(d[37]), "+f"(d[38]), "+f"(d[39]),
      "+f"(d[40]), "+f"(d[41]), "+f"(d[42]), "+f"(d[43]), "+f"(d[44]), "+f"(d[45]), "+f"(d[46]), "+f"(d[47]),
      "+f"(d[48]), "+f"(d[49]), "+f"(d[50]), "+f"(d[51]), "+f"(d[52]), "+f"(d[53]), "+f"(d[54]), "+f"(d[55]),
      "+f"(d[56]), "+f"(d[57]), "+f"(d[58]), "+f"(d[59]), "+f"(d[60]), "+f"(d[61]), "+f"(d[62]), "+f"(d[63])
    : "r"(a[0]), "r"(a[1]), "r"(a[2]), "r"(a[3]), "r"(lo), "r"(sd), "n"(OFF), "n"(HI));
}

template <int OFF, uint32_t HI>
__device__ __forceinline__ void wgmma_rs_n224_tb1(float (&d)[112], const uint32_t (&a)[4], uint32_t lo, int sd) {
  asm volatile("{\n.reg .pred p;\n.reg .b32 l;\n.reg .b64 db;\nsetp.ne.b32 p, %117, 0;\n"
    "add.u32 l, %116, %118;\nmov.b64 db, {l, %119};\n"
    "wgmma.mma_async.sync.aligned.m64n224k16.f32.bf16.bf16 "
    "{%0,%1,%2,%3,%4,%5,%6,%7,%8,%9,%10,%11,%12,%13,%14,%15,"
    "%16,%17,%18,%19,%20,%21,%22,%23,%24,%25,%26,%27,%28,%29,%30,%31,"
    "%32,%33,%34,%35,%36,%37,%38,%39,%40,%41,%42,%43,%44,%45,%46,%47,"
    "%48,%49,%50,%51,%52,%53,%54,%55,%56,%57,%58,%59,%60,%61,%62,%63,"
    "%64,%65,%66,%67,%68,%69,%70,%71,%72,%73,%74,%75,%76,%77,%78,%79,"
    "%80,%81,%82,%83,%84,%85,%86,%87,%88,%89,%90,%91,%92,%93,%94,%95,"
    "%96,%97,%98,%99,%100,%101,%102,%103,%104,%105,%106,%107,%108,%109,%110,%111}, "
    "{%112,%113,%114,%115}, db, p, 1, 1, 1;\n}\n"
    : "+f"(d[0]), "+f"(d[1]), "+f"(d[2]), "+f"(d[3]), "+f"(d[4]), "+f"(d[5]), "+f"(d[6]), "+f"(d[7]),
      "+f"(d[8]), "+f"(d[9]), "+f"(d[10]), "+f"(d[11]), "+f"(d[12]), "+f"(d[13]), "+f"(d[14]), "+f"(d[15]),
      "+f"(d[16]), "+f"(d[17]), "+f"(d[18]), "+f"(d[19]), "+f"(d[20]), "+f"(d[21]), "+f"(d[22]), "+f"(d[23]),
      "+f"(d[24]), "+f"(d[25]), "+f"(d[26]), "+f"(d[27]), "+f"(d[28]), "+f"(d[29]), "+f"(d[30]), "+f"(d[31]),
      "+f"(d[32]), "+f"(d[33]), "+f"(d[34]), "+f"(d[35]), "+f"(d[36]), "+f"(d[37]), "+f"(d[38]), "+f"(d[39]),
      "+f"(d[40]), "+f"(d[41]), "+f"(d[42]), "+f"(d[43]), "+f"(d[44]), "+f"(d[45]), "+f"(d[46]), "+f"(d[47]),
      "+f"(d[48]), "+f"(d[49]), "+f"(d[50]), "+f"(d[51]), "+f"(d[52]), "+f"(d[53]), "+f"(d[54]), "+f"(d[55]),
      "+f"(d[56]), "+f"(d[57]), "+f"(d[58]), "+f"(d[59]), "+f"(d[60]), "+f"(d[61]), "+f"(d[62]), "+f"(d[63]),
      "+f"(d[64]), "+f"(d[65]), "+f"(d[66]), "+f"(d[67]), "+f"(d[68]), "+f"(d[69]), "+f"(d[70]), "+f"(d[71]),
      "+f"(d[72]), "+f"(d[73]), "+f"(d[74]), "+f"(d[75]), "+f"(d[76]), "+f"(d[77]), "+f"(d[78]), "+f"(d[79]),
      "+f"(d[80]), "+f"(d[81]), "+f"(d[82]), "+f"(d[83]), "+f"(d[84]), "+f"(d[85]), "+f"(d[86]), "+f"(d[87]),
      "+f"(d[88]), "+f"(d[89]), "+f"(d[90]), "+f"(d[91]), "+f"(d[92]), "+f"(d[93]), "+f"(d[94]), "+f"(d[95]),
      "+f"(d[96]), "+f"(d[97]), "+f"(d[98]), "+f"(d[99]), "+f"(d[100]), "+f"(d[101]), "+f"(d[102]), "+f"(d[103]),
      "+f"(d[104]), "+f"(d[105]), "+f"(d[106]), "+f"(d[107]), "+f"(d[108]), "+f"(d[109]), "+f"(d[110]), "+f"(d[111])
    : "r"(a[0]), "r"(a[1]), "r"(a[2]), "r"(a[3]), "r"(lo), "r"(sd), "n"(OFF), "n"(HI));
}

template <int STR>
__device__ __forceinline__ void verify8_tag1(const uint4* p, uint32_t (*r)[4]) {
  asm volatile("{\n.reg .pred p, q;\n.reg .b32 a, n;\nmov.u32 n, 0;\n"
    "LAB_CHK:\n"
    "and.b32 a, %0, %4;\n"
    "and.b32 a, a, %8;\n"
    "and.b32 a, a, %12;\n"
    "and.b32 a, a, %16;\n"
    "and.b32 a, a, %20;\n"
    "and.b32 a, a, %24;\n"
    "and.b32 a, a, %28;\n"
    "and.b32 a, a, 1;\nsetp.eq.u32 p, a, 1;\nvote.sync.all.pred p, p, 0xffffffff;\n"
    "@p bra.uni LAB_OK;\n"
    "ld.relaxed.gpu.global.v4.b32 {%0,%1,%2,%3}, [%32+%33];\n"
    "ld.relaxed.gpu.global.v4.b32 {%4,%5,%6,%7}, [%32+%34];\n"
    "ld.relaxed.gpu.global.v4.b32 {%8,%9,%10,%11}, [%32+%35];\n"
    "ld.relaxed.gpu.global.v4.b32 {%12,%13,%14,%15}, [%32+%36];\n"
    "ld.relaxed.gpu.global.v4.b32 {%16,%17,%18,%19}, [%32+%37];\n"
    "ld.relaxed.gpu.global.v4.b32 {%20,%21,%22,%23}, [%32+%38];\n"
    "ld.relaxed.gpu.global.v4.b32 {%24,%25,%26,%27}, [%32+%39];\n"
    "ld.relaxed.gpu.global.v4.b32 {%28,%29,%30,%31}, [%32+%40];\n"
    "add.u32 n, n, 1;\nsetp.lt.u32 q, n, 262144;\n@q bra.uni LAB_CHK;\n"
    "LAB_OK:\n"
    "}\n"
    : "+r"(r[0][0]), "+r"(r[0][1]), "+r"(r[0][2]), "+r"(r[0][3]), "+r"(r[1][0]), "+r"(r[1][1]), "+r"(r[1][2]), "+r"(r[1][3]),
      "+r"(r[2][0]), "+r"(r[2][1]), "+r"(r[2][2]), "+r"(r[2][3]), "+r"(r[3][0]), "+r"(r[3][1]), "+r"(r[3][2]), "+r"(r[3][3]),
      "+r"(r[4][0]), "+r"(r[4][1]), "+r"(r[4][2]), "+r"(r[4][3]), "+r"(r[5][0]), "+r"(r[5][1]), "+r"(r[5][2]), "+r"(r[5][3]),
      "+r"(r[6][0]), "+r"(r[6][1]), "+r"(r[6][2]), "+r"(r[6][3]), "+r"(r[7][0]), "+r"(r[7][1]), "+r"(r[7][2]), "+r"(r[7][3])
    : "l"(p), "n"(0 * STR), "n"(1 * STR), "n"(2 * STR), "n"(3 * STR), "n"(4 * STR), "n"(5 * STR), "n"(6 * STR), "n"(7 * STR)
    : "memory");
}

template <int STR>
__device__ __forceinline__ void verify8_tag0(const uint4* p, uint32_t (*r)[4]) {
  asm volatile("{\n.reg .pred p, q;\n.reg .b32 a, n;\nmov.u32 n, 0;\n"
    "LAB_CHK:\n"
    "or.b32 a, %0, %4;\n"
    "or.b32 a, a, %8;\n"
    "or.b32 a, a, %12;\n"
    "or.b32 a, a, %16;\n"
    "or.b32 a, a, %20;\n"
    "or.b32 a, a, %24;\n"
    "or.b32 a, a, %28;\n"
    "and.b32 a, a, 1;\nsetp.eq.u32 p, a, 0;\nvote.sync.all.pred p, p, 0xffffffff;\n"
    "@p bra.uni LAB_OK;\n"
    "ld.relaxed.gpu.global.v4.b32 {%0,%1,%2,%3}, [%32+%33];\n"
    "ld.relaxed.gpu.global.v4.b32 {%4,%5,%6,%7}, [%32+%34];\n"
    "ld.relaxed.gpu.global.v4.b32 {%8,%9,%10,%11}, [%32+%35];\n"
    "ld.relaxed.gpu.global.v4.b32 {%12,%13,%14,%15}, [%32+%36];\n"
    "ld.relaxed.gpu.global.v4.b32 {%16,%17,%18,%19}, [%32+%37];\n"
    "ld.relaxed.gpu.global.v4.b32 {%20,%21,%22,%23}, [%32+%38];\n"
    "ld.relaxed.gpu.global.v4.b32 {%24,%25,%26,%27}, [%32+%39];\n"
    "ld.relaxed.gpu.global.v4.b32 {%28,%29,%30,%31}, [%32+%40];\n"
    "add.u32 n, n, 1;\nsetp.lt.u32 q, n, 262144;\n@q bra.uni LAB_CHK;\n"
    "LAB_OK:\n"
    "or.b32 %0, %0, 1;\n"
    "or.b32 %4, %4, 1;\n"
    "or.b32 %8, %8, 1;\n"
    "or.b32 %12, %12, 1;\n"
    "or.b32 %16, %16, 1;\n"
    "or.b32 %20, %20, 1;\n"
    "or.b32 %24, %24, 1;\n"
    "or.b32 %28, %28, 1;\n"
    "}\n"
    : "+r"(r[0][0]), "+r"(r[0][1]), "+r"(r[0][2]), "+r"(r[0][3]), "+r"(r[1][0]), "+r"(r[1][1]), "+r"(r[1][2]), "+r"(r[1][3]),
      "+r"(r[2][0]), "+r"(r[2][1]), "+r"(r[2][2]), "+r"(r[2][3]), "+r"(r[3][0]), "+r"(r[3][1]), "+r"(r[3][2]), "+r"(r[3][3]),
      "+r"(r[4][0]), "+r"(r[4][1]), "+r"(r[4][2]), "+r"(r[4][3]), "+r"(r[5][0]), "+r"(r[5][1]), "+r"(r[5][2]), "+r"(r[5][3]),
      "+r"(r[6][0]), "+r"(r[6][1]), "+r"(r[6][2]), "+r"(r[6][3]), "+r"(r[7][0]), "+r"(r[7][1]), "+r"(r[7][2]), "+r"(r[7][3])
    : "l"(p), "n"(0 * STR), "n"(1 * STR), "n"(2 * STR), "n"(3 * STR), "n"(4 * STR), "n"(5 * STR), "n"(6 * STR), "n"(7 * STR)
    : "memory");
}

template <int STR>
__device__ __forceinline__ void verify4_tag0(const uint4* p, uint32_t (*r)[4]) {
  asm volatile("{\n.reg .pred p, q;\n.reg .b32 a, n;\nmov.u32 n, 0;\n"
    "LAB_CHK:\n"
    "or.b32 a, %0, %4;\n"
    "or.b32 a, a, %8;\n"
    "or.b32 a, a, %12;\n"
    "and.b32 a, a, 1;\nsetp.eq.u32 p, a, 0;\nvote.sync.all.pred p, p, 0xffffffff;\n"
    "@p bra.uni LAB_OK;\n"
    "ld.relaxed.gpu.global.v4.b32 {%0,%1,%2,%3}, [%16+%17];\n"
    "ld.relaxed.gpu.global.v4.b32 {%4,%5,%6,%7}, [%16+%18];\n"
    "ld.relaxed.gpu.global.v4.b32 {%8,%9,%10,%11}, [%16+%19];\n"
    "ld.relaxed.gpu.global.v4.b32 {%12,%13,%14,%15}, [%16+%20];\n"
    "add.u32 n, n, 1;\nsetp.lt.u32 q, n, 262144;\n@q bra.uni LAB_CHK;\n"
    "LAB_OK:\n"
    "or.b32 %0, %0, 1;\n"
    "or.b32 %4, %4, 1;\n"
    "or.b32 %8, %8, 1;\n"
    "or.b32 %12, %12, 1;\n"
    "}\n"
    : "+r"(r[0][0]), "+r"(r[0][1]), "+r"(r[0][2]), "+r"(r[0][3]), "+r"(r[1][0]), "+r"(r[1][1]), "+r"(r[1][2]), "+r"(r[1][3]),
      "+r"(r[2][0]), "+r"(r[2][1]), "+r"(r[2][2]), "+r"(r[2][3]), "+r"(r[3][0]), "+r"(r[3][1]), "+r"(r[3][2]), "+r"(r[3][3])
    : "l"(p), "n"(0 * STR), "n"(1 * STR), "n"(2 * STR), "n"(3 * STR)
    : "memory");
}

#define SPIN_LIMIT (1 << 18)

__device__ __forceinline__ uint32_t smem_u32(const void* p) { return (uint32_t)__cvta_generic_to_shared(p); }
__device__ __forceinline__ void mbar_init(uint32_t a, uint32_t c) {
  asm volatile("mbarrier.init.shared::cta.b64 [%0], %1;" ::"r"(a), "r"(c) : "memory");
}
__device__ __forceinline__ void mbar_expect(uint32_t a, uint32_t b) {
  asm volatile("mbarrier.arrive.expect_tx.shared::cta.b64 _, [%0], %1;" ::"r"(a), "r"(b) : "memory");
}
__device__ __forceinline__ void mbar_arrive(uint32_t a) {
  asm volatile("mbarrier.arrive.shared::cta.b64 _, [%0];" ::"r"(a) : "memory");
}
__device__ __forceinline__ void mbar_wait(uint32_t a, uint32_t parity) {
  asm volatile(
      "{\n.reg .pred p;\n.reg .u32 n;\nmov.u32 n, 0;\n"
      "LAB_WAIT:\n"
      "mbarrier.try_wait.parity.shared::cta.b64 p, [%0], %1;\n"
      "@p bra LAB_DONE;\n"
      "add.u32 n, n, 1;\n"
      "setp.lt.u32 p, n, 262144;\n"
      "@p bra LAB_WAIT;\n"
      "LAB_DONE:\n}\n" ::"r"(a), "r"(parity) : "memory");
}
__device__ __forceinline__ void tma3d(uint32_t dst, const CUtensorMap* tm, uint32_t bar, int c0, int c1, int c2) {
  asm volatile(
      "cp.async.bulk.tensor.3d.shared::cluster.global.mbarrier::complete_tx::bytes [%0], [%1, {%3,%4,%5}], [%2];"
      ::"r"(dst), "l"(tm), "r"(bar), "r"(c0), "r"(c1), "r"(c2) : "memory");
}
__device__ __forceinline__ void wg_fence() { asm volatile("wgmma.fence.sync.aligned;" ::: "memory"); }
__device__ __forceinline__ void wg_commit() { asm volatile("wgmma.commit_group.sync.aligned;" ::: "memory"); }
template <int N> __device__ __forceinline__ void wg_wait() {
  asm volatile("wgmma.wait_group.sync.aligned %0;" ::"n"(N) : "memory");
}
template <int N> __device__ __forceinline__ void fence_regs(float (&d)[N]) {
#pragma unroll
  for (int i = 0; i < N; i++) asm volatile("" : "+f"(d[i])::"memory");
}
template <int N> __device__ __forceinline__ void fence_regs(uint32_t (&d)[N][4]) {
#pragma unroll
  for (int i = 0; i < N; i++) asm volatile("" : "+r"(d[i][0]), "+r"(d[i][1]), "+r"(d[i][2]), "+r"(d[i][3])::"memory");
}
template <int N> __device__ __forceinline__ void fence_frags(uint32_t (*d)[4]) {
#pragma unroll
  for (int i = 0; i < N; i++) asm volatile("" : "+r"(d[i][0]), "+r"(d[i][1]), "+r"(d[i][2]), "+r"(d[i][3])::"memory");
}
__device__ __forceinline__ void bar_sync(int id, int n) { asm volatile("bar.sync %0, %1;" ::"r"(id), "r"(n) : "memory"); }
__device__ __forceinline__ void bar_arrive(int id, int n) { asm volatile("bar.arrive %0, %1;" ::"r"(id), "r"(n) : "memory"); }

__device__ __forceinline__ uint32_t pack_bf16(float lo, float hi) {
  uint32_t r;
  asm("cvt.rn.bf16x2.f32 %0, %1, %2;" : "=r"(r) : "f"(hi), "f"(lo));
  return r;
}
__device__ __forceinline__ float bf_lo(uint32_t w) { return __uint_as_float(w << 16); }
__device__ __forceinline__ float bf_hi(uint32_t w) { return __uint_as_float(w & 0xFFFF0000u); }
__device__ __forceinline__ float round_bf16(float x) { return bf_lo(pack_bf16(x, 0.f)); }
__device__ __forceinline__ uint32_t hfma2_bf16(uint32_t a, uint32_t b, uint32_t c) {
  uint32_t r;
  asm("fma.rn.bf16x2 %0, %1, %2, %3;" : "=r"(r) : "r"(a), "r"(b), "r"(c));
  return r;
}
__device__ __forceinline__ float ex2(float x) {
  float r;
  asm("ex2.approx.ftz.f32 %0, %1;" : "=f"(r) : "f"(x));
  return r;
}
__device__ __forceinline__ float tanh_hw(float x) {
  float r;
  asm("tanh.approx.f32 %0, %1;" : "=f"(r) : "f"(x));
  return r;
}
template <int TAG> __device__ __forceinline__ uint32_t pack_tag(float lo, float hi) {
  uint32_t w = __byte_perm(__float_as_uint(lo), pack_bf16(lo, hi), 0x7632);
  return TAG ? (w | 1u) : (w & ~1u);
}
__device__ __forceinline__ void st_pkt(uint4* p, uint32_t a, uint32_t b, uint32_t c, uint32_t d) {
  asm volatile(
      "st.relaxed.gpu.global.v4.b32 [%0], {%1,%2,%3,%4};" ::"l"(p), "r"(a), "r"(b), "r"(c), "r"(d) : "memory");
}
__device__ __forceinline__ void ld_pkt(const uint4* p, uint32_t (&r)[4]) {
  asm volatile(
      "ld.relaxed.gpu.global.v4.b32 {%0,%1,%2,%3}, [%4];"
      : "=r"(r[0]), "=r"(r[1]), "=r"(r[2]), "=r"(r[3]) : "l"(p) : "memory");
}
__device__ __forceinline__ uint32_t ldg32(const void* p) {
  uint32_t r;
  asm volatile("ld.global.nc.b32 %0, [%1];" : "=r"(r) : "l"(p));
  return r;
}
__device__ __forceinline__ uint32_t ldg16(const void* p) {
  uint16_t r;
  asm volatile("ld.global.nc.b16 %0, [%1];" : "=h"(r) : "l"(p));
  return r;
}
__device__ __forceinline__ uint4 ldg128(const void* p) {
  uint4 r;
  asm volatile("ld.global.nc.v4.b32 {%0,%1,%2,%3}, [%4];" : "=r"(r.x), "=r"(r.y), "=r"(r.z), "=r"(r.w) : "l"(p));
  return r;
}
__device__ __forceinline__ void l2_prefetch(const void* p, uint32_t bytes) {
  asm volatile("cp.async.bulk.prefetch.L2.global [%0], %1;" ::"l"(p), "r"(bytes) : "memory");
}
__device__ __forceinline__ float rcp_hw(float x) {
  float r;
  asm("rcp.approx.ftz.f32 %0, %1;" : "=f"(r) : "f"(x));
  return r;
}
__device__ __forceinline__ void warp_bulk_store(void* gdst, uint32_t ssrc, uint32_t bytes) {
  asm volatile("fence.proxy.async.shared::cta;" ::: "memory");
  __syncwarp();
  if ((threadIdx.x & 31) == 0) {
    asm volatile("cp.async.bulk.global.shared::cta.bulk_group [%0], [%1], %2;" ::"l"(gdst), "r"(ssrc), "r"(bytes) : "memory");
    asm volatile("cp.async.bulk.commit_group;" ::: "memory");
  }
}
template <int N> __device__ __forceinline__ void warp_bulk_wait_read() {
  if ((threadIdx.x & 31) == 0) asm volatile("cp.async.bulk.wait_group.read %0;" ::"n"(N) : "memory");
  __syncwarp();
}
__device__ __forceinline__ void sts128(uint32_t a, uint32_t x, uint32_t y, uint32_t z, uint32_t w) {
  asm volatile("st.shared.v4.b32 [%0], {%1,%2,%3,%4};" ::"r"(a), "r"(x), "r"(y), "r"(z), "r"(w) : "memory");
}
__device__ __forceinline__ void lds128(uint32_t a, uint32_t (&r)[4]) {
  asm volatile("ld.shared.v4.b32 {%0,%1,%2,%3}, [%4];" : "=r"(r[0]), "=r"(r[1]), "=r"(r[2]), "=r"(r[3]) : "r"(a) : "memory");
}

constexpr int SK = 2048, WIN = 512;
constexpr int FF = 1792, FSL = 224;
constexpr int NTILES = 80;
constexpr int NSLOT = 4;
constexpr uint32_t SLOT = 32768;
constexpr uint32_t SM_PARK = 0;
constexpr uint32_t SM_RING = 3 * SLOT;
constexpr uint32_t SM_TAB = 7 * SLOT;
constexpr uint32_t SM_RED = SM_TAB + 2048;
constexpr uint32_t SM_BAR = SM_RED + 256;
constexpr uint32_t SM_TOTAL = SM_BAR + 128;

struct Scratch {
  uint4 P[16 * 8 * 8 * 1024];
  uint4 G[16 * 8 * 32 * 32];
  uint4 mod1[8 * 256];
  uint4 mod2[512];
  uint4 uv[2 * 448];
  uint4 stat[16 * 8 * 8 * 2];
  uint32_t epoch;
};
__device__ Scratch g_scratch;

#define TS(i) do { } while (0)
#define CK_(v)
#define CKS(i, v)

struct Params {
  const __nv_bfloat16* x;
  const __nv_bfloat16* c;
  const __nv_bfloat16* wmod;
  const __nv_bfloat16* wo;
  const __nv_bfloat16* w1;
  const __nv_bfloat16* w2;
  __nv_bfloat16* out;
  Scratch* s;
};

constexpr uint32_t HI128 = (1024 >> 4) | (1u << 30);
constexpr uint32_t HI64 = (512 >> 4) | (2u << 30);
constexpr int LB_MN128 = (16384 >> 4) << 16;
constexpr int LB_K128 = 1 << 16;
constexpr int LB_W1 = (4096 >> 4) << 16;
constexpr int LB_W2 = (14336 >> 4) << 16;

template <int I> struct IC {
  __host__ __device__ constexpr operator int() const { return I; }
};
template <int I, int N, typename F> __device__ __forceinline__ void static_for(F&& f) {
  if constexpr (I < N) {
    f(IC<I>{});
    static_for<I + 1, N>(f);
  }
}

struct Ring {
  uint32_t base16, bars;
  __device__ __forceinline__ uint32_t wait_full(uint32_t slot, uint32_t parity) const {
    mbar_wait(bars + slot * 8, parity);
    return base16 + slot * (SLOT >> 4);
  }
  __device__ __forceinline__ void release(uint32_t slot) const {
    if ((threadIdx.x & 31) == 0) mbar_arrive(bars + 32 + slot * 8);
  }
};

__device__ __forceinline__ float silu_c(uint32_t bits) {
  float x = bf_lo(bits);
  return round_bf16(x * rcp_hw(1.f + ex2(-1.4426950408889634f * x)));
}
__device__ __forceinline__ void pack8(uint32_t (&o)[4], const float* v) {
  o[0] = pack_bf16(v[0], v[1]); o[1] = pack_bf16(v[2], v[3]); o[2] = pack_bf16(v[4], v[5]); o[3] = pack_bf16(v[6], v[7]);
}

template <int TAG, int N>
__device__ __forceinline__ void issue_pkts(const uint4* p, int stride, uint32_t (*r)[4]) {
#pragma unroll
  for (int i = 0; i < N; i++) ld_pkt(p + i * stride, r[i]);
}
__device__ __forceinline__ void ld_mod(const uint4* p, uint32_t tag, uint32_t (&r)[4]) {
  int spins = 0;
  ld_pkt(p, r);
  while (r[2] != tag && ++spins < SPIN_LIMIT) ld_pkt(p, r);
}

#define EARLY_TILES 2
#define PF_WMOD 1
#define MOD1_DELAY 300
#define RED3_UNIT 3
#define G_DELAY 300

__global__ void __launch_bounds__(384, 1)
adaln_block_kernel(const __grid_constant__ CUtensorMap tmWq, const __grid_constant__ CUtensorMap tmK,
                   const __grid_constant__ CUtensorMap tmV, const __grid_constant__ CUtensorMap tmWo,
                   const __grid_constant__ CUtensorMap tmW1, const __grid_constant__ CUtensorMap tmW2,
                   const Params p) {
  extern __shared__ __align__(1024) uint8_t smem_raw[];
  const uint32_t sb = smem_u32(smem_raw);
  const int tid = threadIdx.x, lane = tid & 31;
  const int warp = __shfl_sync(0xffffffffu, tid >> 5, 0);
  const int bid = blockIdx.x, j = bid >> 4, rt = bid & 15;
  const uint32_t bars = sb + SM_BAR;

  if (warp >= 8) {
    CK_(c0);
    asm volatile("setmaxnreg.dec.sync.aligned.u32 40;");
    CK_(c1);
    const int t = tid - 256;
    uint32_t tag;
    {
      uint4 w[4];
      uint32_t cb[4];
      if (t >= 32 && t < 36) l2_prefetch(p.wmod + (size_t)(bid * 4 + t - 32) * 3072, 2048);
      if (t == 0) {
        asm volatile("prefetch.tensormap [%0];" ::"l"(&tmWq) : "memory");
        for (int i = 0; i < NSLOT; i++) { mbar_init(bars + i * 8, 1); mbar_init(bars + 32 + i * 8, 8); }
        mbar_init(bars + 72, 2);
        asm volatile("fence.mbarrier_init.release.cluster;" ::: "memory");
        asm volatile("fence.proxy.async.shared::cta;" ::: "memory");
      }
      __syncwarp();
      CK_(c2);
#pragma unroll
      for (int i = 0; i < 4; i++) w[i] = ldg128(p.wmod + (size_t)(t + 128 * i) * 3072 + bid * 8);
#pragma unroll
      for (int i = 0; i < 4; i++) cb[i] = ldg16(p.c + t + 128 * i);
      asm volatile("ld.relaxed.gpu.global.u32 %0, [%1];" : "=r"(tag) : "l"(&p.s->epoch) : "memory");
      CK_(c3);
      tag += 1;
      float a[8];
#pragma unroll
      for (int k = 0; k < 8; k++) a[k] = 0.f;
#pragma unroll
      for (int i = 0; i < 4; i++) {
        const float s = silu_c(cb[i]);
        a[0] = fmaf(s, bf_lo(w[i].x), a[0]); a[1] = fmaf(s, bf_hi(w[i].x), a[1]);
        a[2] = fmaf(s, bf_lo(w[i].y), a[2]); a[3] = fmaf(s, bf_hi(w[i].y), a[3]);
        a[4] = fmaf(s, bf_lo(w[i].z), a[4]); a[5] = fmaf(s, bf_hi(w[i].z), a[5]);
        a[6] = fmaf(s, bf_lo(w[i].w), a[6]); a[7] = fmaf(s, bf_hi(w[i].w), a[7]);
      }
      const bool h16 = lane & 16, h8 = lane & 8, h4 = lane & 4;
#pragma unroll
      for (int k = 0; k < 4; k++) {
        float send = h16 ? a[k] : a[k + 4], keep = h16 ? a[k + 4] : a[k];
        a[k] = keep + __shfl_xor_sync(0xffffffffu, send, 16);
      }
#pragma unroll
      for (int k = 0; k < 2; k++) {
        float send = h8 ? a[k] : a[k + 2], keep = h8 ? a[k + 2] : a[k];
        a[k] = keep + __shfl_xor_sync(0xffffffffu, send, 8);
      }
      {
        float send = h4 ? a[0] : a[1], keep = h4 ? a[1] : a[0];
        a[0] = keep + __shfl_xor_sync(0xffffffffu, send, 4);
      }
      a[0] += __shfl_xor_sync(0xffffffffu, a[0], 2);
      a[0] += __shfl_xor_sync(0xffffffffu, a[0], 1);
      float* red = (float*)(smem_raw + SM_RED);
      if ((lane & 3) == 0) red[(warp - 8) * 8 + (lane >> 2)] = a[0];
      if (t == 0) *(uint32_t*)(smem_raw + SM_BAR + 64) = tag;
      CK_(c4);
      bar_sync(5, 128);
      CK_(c5);
      if (t == 0) {
#pragma unroll
        for (int i = 0; i < EARLY_TILES; i++) {
          mbar_expect(bars + i * 8, SLOT);
          tma3d(sb + SM_RING + i * SLOT, &tmWq, bars + i * 8, 0, i * 128, (j * 4 + 1) * 2);
        }
      }
      if (warp == 9) {
        const int cl = lane & 7;
        float v = round_bf16(red[cl] + red[8 + cl] + red[16 + cl] + red[24 + cl]);
        if (bid >= 64) v = 1.f + v;
        float vn = __shfl_down_sync(0xffffffffu, v, 1);
        uint32_t wd = pack_bf16(v, vn);
        uint32_t w0 = __shfl_sync(0xffffffffu, wd, (lane & 1) * 4);
        uint32_t w1 = __shfl_sync(0xffffffffu, wd, (lane & 1) * 4 + 2);
        if (lane < 16) st_pkt(&p.s->mod1[(lane >> 1) * 256 + bid * 2 + (lane & 1)], w0, w1, tag, 0);
      }
      uint32_t r0[4], r1[4];
      const uint4* src = &p.s->mod1[j * 256 + t];
      CK_(c6);
      __nanosleep(MOD1_DELAY);
      CK_(c7);
      int spins = 0;
      do {
        ld_pkt(src, r0);
        ld_pkt(src + 128, r1);
      } while ((r0[2] != tag || r1[2] != tag) && ++spins < SPIN_LIMIT);
      const int g = t >> 2, pp = (t & 3) * 2;
      const uint32_t ad = sb + SM_TAB + (uint32_t)(g * 4 + (pp & 3)) * 16 + (pp >> 2) * 4;
      asm volatile("st.shared.b32 [%0], %1;" ::"r"(ad + 8), "r"(r0[0]) : "memory");
      asm volatile("st.shared.b32 [%0], %1;" ::"r"(ad + 24), "r"(r0[1]) : "memory");
      asm volatile("st.shared.b32 [%0], %1;" ::"r"(ad), "r"(r1[0]) : "memory");
      asm volatile("st.shared.b32 [%0], %1;" ::"r"(ad + 16), "r"(r1[1]) : "memory");
      bar_arrive(1, 384);
      CK_(c8);
      CKS(0, c0); CKS(1, c1); CKS(2, c2); CKS(3, c3); CKS(4, c4); CKS(5, c5); CKS(6, c6); CKS(7, c7); CKS(8, c8);
    }
    if (warp == 8) {
      if (lane == 0) {
        uint32_t s = EARLY_TILES & 3, ph = 1 ^ (EARLY_TILES >> 2);
#pragma unroll 1
        for (int tt = EARLY_TILES; tt < NTILES; tt++) {
          const CUtensorMap* tm;
          int c1, c2;
          uint32_t bytes = SLOT;
          if (tt < 16) {
            tm = &tmWq; c1 = (tt & 3) * 128; c2 = (j * 4 + (((tt >> 2) + 1) & 3)) * 2;
          } else if (tt < 48) {
            const int u = tt - 16;
            const bool isK = (u == 0) || ((u & 1) && u != 31);
            const int n = isK ? ((u + 1) >> 1) : (u == 31 ? 15 : (u >> 1) - 1);
            tm = isK ? &tmK : &tmV; c1 = j * SK + (SK - WIN) + (n & 3) * 128; c2 = 0;
          } else if (tt < 64) {
            const int u = tt - 48;
            tm = &tmWo; c1 = j * 512 + (u & 3) * 128; c2 = (u >> 2) * 2;
          } else if (tt < 72) {
            tm = &tmW1; c1 = (tt - 64) * 64; c2 = j * 7; bytes = 28672;
          } else {
            const int u = tt - 72;
            tm = &tmW2; c1 = j * FSL + (u & 1) * 112; c2 = (u >> 1) * 2; bytes = 28672;
          }
          mbar_wait(bars + 32 + s * 8, ph);
          mbar_expect(bars + s * 8, bytes);
          tma3d(sb + SM_RING + s * SLOT, tm, bars + s * 8, 0, c1, c2);
          if (++s == (tt < 48 ? 4u : 3u)) { s = 0; ph ^= 1; }
        }
      }
    } else if (warp >= 10) {
      const int t2 = tid - 320, hf = t2 & 1, r0 = t2 >> 1;
      float a[8];
#pragma unroll
      for (int k = 0; k < 8; k++) a[k] = 0.f;
#pragma unroll 1
      for (int b = 0; b < 8; b++) {
        uint4 w[2];
        uint32_t cb[2];
#pragma unroll
        for (int i = 0; i < 2; i++) {
          w[i] = ldg128(p.wmod + (size_t)(r0 + 32 * (2 * b + i)) * 3072 + 1024 + bid * 16 + hf * 8);
          cb[i] = ldg16(p.c + r0 + 32 * (2 * b + i));
        }
#pragma unroll
        for (int i = 0; i < 2; i++) {
          const float s = silu_c(cb[i]);
          a[0] = fmaf(s, bf_lo(w[i].x), a[0]); a[1] = fmaf(s, bf_hi(w[i].x), a[1]);
          a[2] = fmaf(s, bf_lo(w[i].y), a[2]); a[3] = fmaf(s, bf_hi(w[i].y), a[3]);
          a[4] = fmaf(s, bf_lo(w[i].z), a[4]); a[5] = fmaf(s, bf_hi(w[i].z), a[5]);
          a[6] = fmaf(s, bf_lo(w[i].w), a[6]); a[7] = fmaf(s, bf_hi(w[i].w), a[7]);
        }
      }
      const bool h16 = lane & 16, h8 = lane & 8, h4 = lane & 4;
#pragma unroll
      for (int k = 0; k < 4; k++) {
        float send = h16 ? a[k] : a[k + 4], keep = h16 ? a[k + 4] : a[k];
        a[k] = keep + __shfl_xor_sync(0xffffffffu, send, 16);
      }
#pragma unroll
      for (int k = 0; k < 2; k++) {
        float send = h8 ? a[k] : a[k + 2], keep = h8 ? a[k + 2] : a[k];
        a[k] = keep + __shfl_xor_sync(0xffffffffu, send, 8);
      }
      {
        float send = h4 ? a[0] : a[1], keep = h4 ? a[1] : a[0];
        a[0] = keep + __shfl_xor_sync(0xffffffffu, send, 4);
      }
      a[0] += __shfl_xor_sync(0xffffffffu, a[0], 2);
      float* red = (float*)(smem_raw + SM_RED) + 32;
      if ((lane & 2) == 0) red[(warp - 10) * 16 + hf * 8 + (lane >> 2)] = a[0];
      bar_sync(4, 64);
      if (warp == 10) {
        const int cl = lane & 15;
        float v = round_bf16(red[cl] + red[16 + cl]);
        if ((bid >> 5) == 2) v = 1.f + v;
        float vn = __shfl_down_sync(0xffffffffu, v, 1);
        uint32_t wd = pack_bf16(v, vn);
        uint32_t w0 = __shfl_sync(0xffffffffu, wd, (lane & 3) * 2);
        uint32_t w1 = __shfl_sync(0xffffffffu, wd, (lane & 3) * 2 + 8);
        if (lane < 4) st_pkt(&p.s->mod2[bid * 4 + lane], w0, w1, tag, 0);
      }
      const int isv = warp - 10;
      if (bid < 112) {
        const int kk = lane >> 1;
        const uint4* mp = &p.s->mod2[(isv ? 1 : 2) * 128 + ((kk & 7) >> 1)];
#pragma unroll
        for (int k = 0; k < 8; k++) a[k] = 0.f;
#pragma unroll 1
        for (int g = 0; g < 32; g++) {
          const uint4 w = ldg128(p.w1 + (size_t)(g * 16 + kk) * FF + bid * 16 + (lane & 1) * 8);
          uint32_t m[4];
          ld_mod(mp + g * 4, tag, m);
          const uint32_t mw = (kk & 8) ? m[1] : m[0];
          const float s = (kk & 1) ? bf_hi(mw) : bf_lo(mw);
          a[0] = fmaf(s, bf_lo(w.x), a[0]); a[1] = fmaf(s, bf_hi(w.x), a[1]);
          a[2] = fmaf(s, bf_lo(w.y), a[2]); a[3] = fmaf(s, bf_hi(w.y), a[3]);
          a[4] = fmaf(s, bf_lo(w.z), a[4]); a[5] = fmaf(s, bf_hi(w.z), a[5]);
          a[6] = fmaf(s, bf_lo(w.w), a[6]); a[7] = fmaf(s, bf_hi(w.w), a[7]);
        }
#pragma unroll
        for (int k = 0; k < 4; k++) {
          float send = h16 ? a[k] : a[k + 4], keep = h16 ? a[k + 4] : a[k];
          a[k] = keep + __shfl_xor_sync(0xffffffffu, send, 16);
        }
#pragma unroll
        for (int o = 8; o > 1; o >>= 1) {
#pragma unroll
          for (int k = 0; k < 4; k++) a[k] += __shfl_xor_sync(0xffffffffu, a[k], o);
        }
        const float sc = isv ? 0.5f : 1.f;
        if ((lane & 14) == 0)
          st_pkt(&p.s->uv[isv * 448 + bid * 4 + (lane & 1) * 2 + (lane >> 4)],
                 (__float_as_uint(a[0] * sc) & ~1u) | (tag & 1u), __float_as_uint(a[1] * sc), __float_as_uint(a[2] * sc),
                 __float_as_uint(a[3] * sc));
      }
      bar_sync(6, 320);
#pragma unroll 1
      for (int i = lane; i < 56; i += 32) {
        uint32_t m[4];
        int spins = 0;
        do { ld_pkt(&p.s->uv[isv * 448 + j * 56 + i], m); } while (((m[0] ^ tag) & 1u) && ++spins < SPIN_LIMIT);
        const uint32_t ad = sb + SM_TAB + i * 32 + isv * 8;
        asm volatile("st.shared.v2.b32 [%0], {%1,%2};" ::"r"(ad), "r"(m[0]), "r"(m[1]) : "memory");
        asm volatile("st.shared.v2.b32 [%0], {%1,%2};" ::"r"(ad + 16), "r"(m[2]), "r"(m[3]) : "memory");
      }
      __syncwarp();
      if (lane == 0) mbar_arrive(bars + 72);
    } else {
      if (lane < 8) l2_prefetch((const char*)p.wo + (size_t)bid * 32768 + lane * 4096, 4096);
      else if (lane < 12) l2_prefetch((const char*)p.w1 + (size_t)bid * 14336 + (lane - 8) * 3584, 3584);
      else if (lane < 16) l2_prefetch((const char*)p.w2 + (size_t)bid * 14336 + (lane - 12) * 3584, 3584);
    }
  } else {
    const int wg = warp >> 2;
    const int q = lane & 3, gq = lane >> 2;
    const Ring ring{(sb + SM_RING) >> 4, bars};
    const uint32_t xoff = (uint32_t)(rt * 128 + 16 * j + warp) * 256 + gq * 8 + q;
    const uint32_t ooff = ((uint32_t)(rt * 8 + j) * 32 + gq) * 32 + warp * 4 + q;
    const uint32_t goff = (uint32_t)(rt * 8 + warp) * 1024 + lane;

    {
      const uint32_t* xo = (const uint32_t*)p.x + xoff;
      uint32_t xr[4][4];
      CK_(d0);
#pragma unroll
      for (int c = 0; c < 4; c++) {
        xr[c][0] = ldg32(xo + c * 64);
        xr[c][1] = ldg32(xo + c * 64 + 8 * 256);
        xr[c][2] = ldg32(xo + c * 64 + 4);
        xr[c][3] = ldg32(xo + c * 64 + 4 + 8 * 256);
      }
      CK_(d1);
      fence_regs(xr);
      CK_(d2);
      float s0 = 0.f, s1 = 0.f, v0 = 0.f, v1 = 0.f;
#pragma unroll
      for (int c = 0; c < 4; c++) {
#pragma unroll
        for (int e = 0; e < 4; e++) {
          const float a = bf_lo(xr[c][e]), b = bf_hi(xr[c][e]);
          if (e & 1) { s1 += a + b; v1 = fmaf(a, a, fmaf(b, b, v1)); }
          else { s0 += a + b; v0 = fmaf(a, a, fmaf(b, b, v0)); }
        }
      }
#pragma unroll
      for (int o = 16; o > 0; o >>= 1) {
        s0 += __shfl_xor_sync(0xffffffffu, s0, o);
        s1 += __shfl_xor_sync(0xffffffffu, s1, o);
        v0 += __shfl_xor_sync(0xffffffffu, v0, o);
        v1 += __shfl_xor_sync(0xffffffffu, v1, o);
      }
      const float m0 = s0 * (1.f / 512.f), m1 = s1 * (1.f / 512.f);
      const float r0 = rsqrtf(fmaxf(fmaf(-m0, m0, v0 * (1.f / 512.f)), 0.f) + 1e-5f);
      const float r1 = rsqrtf(fmaxf(fmaf(-m1, m1, v1 * (1.f / 512.f)), 0.f) + 1e-5f);
#pragma unroll
      for (int c = 0; c < 4; c++) {
        st_pkt(p.s->G + ooff + c * 256,
               pack_tag<1>((bf_lo(xr[c][0]) - m0) * r0, (bf_hi(xr[c][0]) - m0) * r0),
               pack_bf16((bf_lo(xr[c][1]) - m1) * r1, (bf_hi(xr[c][1]) - m1) * r1),
               pack_bf16((bf_lo(xr[c][2]) - m0) * r0, (bf_hi(xr[c][2]) - m0) * r0),
               pack_bf16((bf_lo(xr[c][3]) - m1) * r1, (bf_hi(xr[c][3]) - m1) * r1));
      }
      CK_(d3);
      CKS(16, d0); CKS(17, d1); CKS(18, d2); CKS(19, d3);

    }
    asm volatile("setmaxnreg.inc.sync.aligned.u32 232;");
    uint32_t qf[8][4];
    {
      uint32_t h[32][4];
      float acc[64];
      const uint4* Gin = p.s->G + goff;
      __nanosleep(G_DELAY);
      issue_pkts<1, 8>(Gin, 32, h);
      verify8_tag1<512>(Gin, h);
      issue_pkts<1, 8>(Gin + 256, 32, h + 8);
      TS(1);
      bar_sync(1, 384);
#pragma unroll
      for (int c = 0; c < 4; c++) {
        if (c > 0) verify8_tag1<512>(Gin + c * 256, h + c * 8);
        if (c > 0 && c < 3) issue_pkts<1, 8>(Gin + (c + 1) * 256, 32, h + (c + 1) * 8);
#pragma unroll
        for (int i = 0; i < 8; i++) {
          uint32_t m[4];
          lds128(sb + SM_TAB + (uint32_t)((c * 8 + i) * 4 + q) * 16, m);
          uint32_t* hh = h[c * 8 + i];
          hh[0] = hfma2_bf16(hh[0], m[0], m[2]);
          hh[1] = hfma2_bf16(hh[1], m[0], m[2]);
          hh[2] = hfma2_bf16(hh[2], m[1], m[3]);
          hh[3] = hfma2_bf16(hh[3], m[1], m[3]);
        }
        fence_frags<8>(h + c * 8);
        const uint32_t b = ring.wait_full(c, 0);
        if (c > 0) { wg_wait<0>(); ring.release(c - 1); }
        if (c == 0) TS(2);
        wg_fence();
        static_for<0, 8>([&](auto K) { wgmma_rs_n128_tb1<LB_MN128 + K * 128, HI128>(acc, h[c * 8 + K], b, (c | K) != 0); });
        wg_commit();
      }
      bar_arrive(6, 320);
#pragma unroll 1
      for (int ps = 1; ps < 4; ps++) {
        wg_wait<0>();
        ring.release(3);
        fence_regs(acc);
#pragma unroll
        for (int i = 0; i < 8; i++) {
          uint32_t o[4];
          pack8(o, acc + 8 * i);
          sts128(sb + SM_PARK + (ps - 1) * SLOT + i * 4096 + tid * 16, o[0], o[1], o[2], o[3]);
        }
#pragma unroll
        for (int c = 0; c < 4; c++) {
          const uint32_t b = ring.wait_full(c, ps & 1);
          if (c > 0) { wg_wait<0>(); ring.release(c - 1); }
          wg_fence();
          static_for<0, 8>([&](auto K) { wgmma_rs_n128_tb1<LB_MN128 + K * 128, HI128>(acc, h[c * 8 + K], b, (c | K) != 0); });
          wg_commit();
        }
      }
      wg_wait<0>();
      ring.release(3);
      fence_regs(acc);
#pragma unroll
      for (int i = 0; i < 8; i++) pack8(qf[i], acc + 8 * i);
    }
    fence_regs(qf);
    TS(3);

    float S[64];
    {
      float O[64];
      uint32_t P[8][4];
      const float cs = 0.08838834764831845f * 1.4426950408889634f;
      const int TAU = 0x41800000;
      float m0, m1, l0, l1;

      auto first_block_max = [&]() {
        int a0 = __vimax3_s32(__float_as_int(S[0]), __float_as_int(S[1]), __float_as_int(S[1]));
        int a1 = __vimax3_s32(__float_as_int(S[2]), __float_as_int(S[3]), __float_as_int(S[3]));
#pragma unroll
        for (int i = 1; i < 16; i++) {
          a0 = __vimax3_s32(a0, __float_as_int(S[4 * i]), __float_as_int(S[4 * i + 1]));
          a1 = __vimax3_s32(a1, __float_as_int(S[4 * i + 2]), __float_as_int(S[4 * i + 3]));
        }
        a0 = max(a0, __shfl_xor_sync(0xffffffffu, a0, 1)); a1 = max(a1, __shfl_xor_sync(0xffffffffu, a1, 1));
        a0 = max(a0, __shfl_xor_sync(0xffffffffu, a0, 2)); a1 = max(a1, __shfl_xor_sync(0xffffffffu, a1, 2));
        float b0 = __int_as_float(a0), b1 = __int_as_float(a1);
        if (__any_sync(0xffffffffu, (a0 | a1) < 0)) {
          b0 = fmaxf(S[0], S[1]); b1 = fmaxf(S[2], S[3]);
#pragma unroll
          for (int i = 1; i < 16; i++) {
            b0 = fmaxf(b0, fmaxf(S[4 * i], S[4 * i + 1]));
            b1 = fmaxf(b1, fmaxf(S[4 * i + 2], S[4 * i + 3]));
          }
          b0 = fmaxf(b0, __shfl_xor_sync(0xffffffffu, b0, 1)); b1 = fmaxf(b1, __shfl_xor_sync(0xffffffffu, b1, 1));
          b0 = fmaxf(b0, __shfl_xor_sync(0xffffffffu, b0, 2)); b1 = fmaxf(b1, __shfl_xor_sync(0xffffffffu, b1, 2));
        }
        m0 = b0 * cs; m1 = b1 * cs;
      };
      auto scale_sub = [&]() {
#pragma unroll
        for (int i = 0; i < 16; i++) {
          S[4 * i] = fmaf(S[4 * i], cs, -m0); S[4 * i + 1] = fmaf(S[4 * i + 1], cs, -m0);
          S[4 * i + 2] = fmaf(S[4 * i + 2], cs, -m1); S[4 * i + 3] = fmaf(S[4 * i + 3], cs, -m1);
        }
      };
      auto exps = [&](int i0, int i1) {
#pragma unroll
        for (int i = i0; i < i1; i++) {
          S[4 * i] = ex2(S[4 * i]); S[4 * i + 1] = ex2(S[4 * i + 1]);
          S[4 * i + 2] = ex2(S[4 * i + 2]); S[4 * i + 3] = ex2(S[4 * i + 3]);
          l0 += S[4 * i]; l1 += S[4 * i + 2]; l0 += S[4 * i + 1]; l1 += S[4 * i + 3];
        }
      };
      m0 = m1 = 0.f; l0 = l1 = 1.f;
      if (wg == 1) bar_arrive(2, 256);
#pragma unroll 1
      for (int n = 0; n < 16; n++) {
        const uint32_t tk = n ? 2 * n - 1 : 0, tv = 2 * n;
        const bool newhead = (n & 3) == 0;
        const uint32_t bk = ring.wait_full(tk & 3, (tk >> 2) & 1);
        const uint32_t bv = ring.wait_full(tv & 3, (tv >> 2) & 1);
        bar_sync(2 + wg, 256);
        wg_fence();
        static_for<0, 8>([&](auto K) { wgmma_rs_n128_tb0<LB_K128 + (K >> 2) * 1024 + (K & 3) * 2, HI128>(S, qf[K], bk, K != 0); });
        wg_commit();
        if (n != 0)
          static_for<0, 8>([&](auto K) { wgmma_rs_n128_tb1<LB_MN128 + K * 128, HI128>(O, P[K], bv, K != 0 || (n & 3) != 1); });
        wg_commit();
        bar_arrive(2 + (wg ^ 1), 256);
        wg_wait<1>();
        fence_regs(S);
        ring.release(tk & 3);
        if ((n & 3) == 3 && n != 15) {
          fence_regs(qf);
#pragma unroll
          for (int i = 0; i < 8; i++) lds128(sb + SM_PARK + (n >> 2) * SLOT + i * 4096 + tid * 16, qf[i]);
        }
        float f0 = 1.f, f1 = 1.f;
        bool resc = newhead && n != 0;
        if (newhead) {
          l0 += __shfl_xor_sync(0xffffffffu, l0, 1); l1 += __shfl_xor_sync(0xffffffffu, l1, 1);
          l0 += __shfl_xor_sync(0xffffffffu, l0, 2); l1 += __shfl_xor_sync(0xffffffffu, l1, 2);
          f0 = rcp_hw(l0); f1 = rcp_hw(l1);
          l0 = 0.f; l1 = 0.f;
          first_block_max();
          scale_sub();
        } else {
          scale_sub();
          int a0 = __vimax3_s32(__float_as_int(S[0]), __float_as_int(S[1]), __float_as_int(S[1]));
          int a1 = __vimax3_s32(__float_as_int(S[2]), __float_as_int(S[3]), __float_as_int(S[3]));
#pragma unroll
          for (int i = 1; i < 16; i++) {
            a0 = __vimax3_s32(a0, __float_as_int(S[4 * i]), __float_as_int(S[4 * i + 1]));
            a1 = __vimax3_s32(a1, __float_as_int(S[4 * i + 2]), __float_as_int(S[4 * i + 3]));
          }
          if (__any_sync(0xffffffffu, max(a0, a1) > TAU)) {
            a0 = max(a0, 0); a1 = max(a1, 0);
            a0 = max(a0, __shfl_xor_sync(0xffffffffu, a0, 1)); a1 = max(a1, __shfl_xor_sync(0xffffffffu, a1, 1));
            a0 = max(a0, __shfl_xor_sync(0xffffffffu, a0, 2)); a1 = max(a1, __shfl_xor_sync(0xffffffffu, a1, 2));
            const float d0 = __int_as_float(a0), d1 = __int_as_float(a1);
#pragma unroll
            for (int i = 0; i < 16; i++) { S[4 * i] -= d0; S[4 * i + 1] -= d0; S[4 * i + 2] -= d1; S[4 * i + 3] -= d1; }
            m0 += d0; m1 += d1;
            f0 = ex2(-d0); f1 = ex2(-d1);
            l0 *= f0; l1 *= f1;
            resc = true;
          }
        }
        exps(0, 4);
        wg_wait<0>();
        fence_regs(O);
        fence_regs(P);
        if (n != 0) ring.release(tv & 3);
        if (resc) {
#pragma unroll
          for (int i = 0; i < 16; i++) {
            O[4 * i] *= f0; O[4 * i + 1] *= f0; O[4 * i + 2] *= f1; O[4 * i + 3] *= f1;
          }
          if (newhead) {
#pragma unroll
            for (int i = 0; i < 8; i++) {
              uint32_t o[4];
              pack8(o, O + 8 * i);
              sts128(sb + SM_PARK + ((n >> 2) - 1) * SLOT + i * 4096 + tid * 16, o[0], o[1], o[2], o[3]);
            }
          }
        }
        exps(4, 16);
#pragma unroll
        for (int i = 0; i < 8; i++) pack8(P[i], S + 8 * i);
        fence_regs(P);
        fence_regs(O);
      }
      {
        const uint32_t bv = ring.wait_full(3, 1);
        if (wg == 0) bar_sync(2, 256);
        wg_fence();
        static_for<0, 8>([&](auto K) { wgmma_rs_n128_tb1<LB_MN128 + K * 128, HI128>(O, P[K], bv, 1); });
        wg_commit();
        l0 += __shfl_xor_sync(0xffffffffu, l0, 1); l1 += __shfl_xor_sync(0xffffffffu, l1, 1);
        l0 += __shfl_xor_sync(0xffffffffu, l0, 2); l1 += __shfl_xor_sync(0xffffffffu, l1, 2);
        const float f0 = rcp_hw(l0), f1 = rcp_hw(l1);
        wg_wait<0>();
        fence_regs(O);
#pragma unroll
        for (int i = 0; i < 8; i++) {
          qf[i][0] = pack_bf16(O[8 * i] * f0, O[8 * i + 1] * f0); qf[i][1] = pack_bf16(O[8 * i + 2] * f1, O[8 * i + 3] * f1);
          qf[i][2] = pack_bf16(O[8 * i + 4] * f0, O[8 * i + 5] * f0); qf[i][3] = pack_bf16(O[8 * i + 6] * f1, O[8 * i + 7] * f1);
        }
      }
    }
    fence_regs(qf);
    TS(4);

    uint4* const Pout = p.s->P + ((size_t)(rt * 8 + warp) * 8 + j) * 1024;
    const uint32_t stage = sb + SM_RING + 3 * SLOT + warp * 4096;
    const uint32_t stoff = gq * 512 + (gq & 1) * 64 + q * 16;
    const uint32_t tag = *(volatile uint32_t*)(smem_raw + SM_BAR + 64);
    const uint4* const Pown = p.s->P + (size_t)(rt * 8 + j) * 8192 + warp * 32 + lane;
    const int go = gq ^ (warp & 1);
    const uint32_t xoff2 = (uint32_t)(rt * 128 + 16 * j + warp) * 256 + go * 8 + q;
    const uint32_t ooff2 = ((uint32_t)(rt * 8 + j) * 32 + go) * 32 + warp * 4 + q;
    const uint4* const mod2p = p.s->mod2 + go * 4 + q;

    auto store_partial = [&](auto TAGC, uint32_t stg, int c) {
#pragma unroll
      for (int i = 0; i < 8; i++)
        sts128(stg + (stoff ^ (i * 64)), pack_tag<TAGC>(S[8 * i], S[8 * i + 1]), pack_bf16(S[8 * i + 2], S[8 * i + 3]),
               pack_bf16(S[8 * i + 4], S[8 * i + 5]), pack_bf16(S[8 * i + 6], S[8 * i + 7]));
      warp_bulk_store(Pout + c * 256, stg, 4096);
    };
    uint32_t r[8][4], xr[4], ga[4], g2[4];
    float s0 = 0.f, s1 = 0.f, v0 = 0.f, v1 = 0.f;
    auto red1_issue = [&](int c) {
      issue_pkts<1, 8>(Pown + c * 256, 1024, r);
      const uint32_t* xo = (const uint32_t*)p.x + xoff2 + c * 64;
      xr[0] = ldg32(xo); xr[1] = ldg32(xo + 8 * 256); xr[2] = ldg32(xo + 4); xr[3] = ldg32(xo + 4 + 8 * 256);
      ld_pkt(mod2p + c * 32, ga);
      ld_pkt(mod2p + 256 + c * 32, g2);
    };
    auto red1_process = [&](int c) {
      float x2[8];
      if (ga[2] != tag) ld_mod(mod2p + c * 32, tag, ga);
      if (g2[2] != tag) ld_mod(mod2p + 256 + c * 32, tag, g2);
      verify8_tag1<16384>(Pown + c * 256, r);
      float hv[8];
#pragma unroll
      for (int e = 0; e < 4; e++) {
        float y0 = bf_lo(r[0][e]), y1 = bf_hi(r[0][e]);
#pragma unroll
        for (int s = 1; s < 8; s++) { y0 += bf_lo(r[s][e]); y1 += bf_hi(r[s][e]); }
        const float a = fmaf(bf_lo(ga[e >> 1]), y0, bf_lo(xr[e])), b = fmaf(bf_hi(ga[e >> 1]), y1, bf_hi(xr[e]));
        x2[2 * e] = a; x2[2 * e + 1] = b;
        hv[2 * e] = a * bf_lo(g2[e >> 1]); hv[2 * e + 1] = b * bf_hi(g2[e >> 1]);
        if (e & 1) { s1 += a + b; v1 = fmaf(a, a, fmaf(b, b, v1)); }
        else { s0 += a + b; v0 = fmaf(a, a, fmaf(b, b, v0)); }
      }
      st_pkt(p.s->G + ooff2 + c * 256, pack_tag<0>(hv[0], hv[1]), pack_bf16(hv[2], hv[3]), pack_bf16(hv[4], hv[5]),
             pack_bf16(hv[6], hv[7]));
      sts128(sb + SM_PARK + (2 * c) * 4096 + tid * 16, __float_as_uint(x2[0]), __float_as_uint(x2[1]),
             __float_as_uint(x2[2]), __float_as_uint(x2[3]));
      sts128(sb + SM_PARK + (2 * c + 1) * 4096 + tid * 16, __float_as_uint(x2[4]), __float_as_uint(x2[5]),
             __float_as_uint(x2[6]), __float_as_uint(x2[7]));
    };

    const uint4* const Gin = p.s->G + goff;
    uint32_t fa[2][4][4];
    uint32_t rs = 0, rp = 0, b = ring.wait_full(0, 0);
    auto next_tile = [&]() {
      const uint32_t cur = rs;
      if (++rs == 3) { rs = 0; rp ^= 1; }
      b = ring.wait_full(rs, rp);
      wg_wait<0>();
      ring.release(cur);
    };
    {
      uint32_t o0[8][4], a[8][4];
#pragma unroll
      for (int i = 0; i < 8; i++) lds128(sb + SM_PARK + i * 4096 + tid * 16, o0[i]);
#pragma unroll 1
      for (int c = 0; c < 4; c++) {
        static_for<0, 4>([&](auto HH) {
          constexpr int hh = HH;
          wg_fence();
          static_for<0, 8>([&](auto K) {
            wgmma_rs_n128_tb1<LB_MN128 + K * 128, HI128>(S, hh == 0 ? o0[K] : hh == 3 ? qf[K] : a[K], b, (hh | K) != 0);
          });
          wg_commit();
          if constexpr (hh == 0) {
#pragma unroll
            for (int i = 0; i < 8; i++) lds128(sb + SM_PARK + SLOT + i * 4096 + tid * 16, a[i]);
            if (c > 1) red1_process(c - 2);
          }
          if constexpr (hh == 3) {
            if (c > 0) red1_issue(c - 1);
            if (c == 3) issue_pkts<0, 4>(Gin, 32, fa[0]);
            warp_bulk_wait_read<0>();
          }
          next_tile();
          if constexpr (hh == 1) {
            fence_regs(a);
#pragma unroll
            for (int i = 0; i < 8; i++) lds128(sb + SM_PARK + 2 * SLOT + i * 4096 + tid * 16, a[i]);
          }
        });
        fence_regs(S);
        store_partial(IC<1>{}, stage, c);
      }
    }
    TS(5);

    uint32_t H[14][4];
    {
      float acc[112];
      uint32_t st[4];
      const uint4* const statp = &p.s->stat[((rt * 8 + warp) * 8 + gq) * 2];
#pragma unroll 1
      for (int it = 0; it < 4; it++) {
        verify4_tag0<512>(Gin + it * 256, fa[0]);
        if (it == 0) TS(6);
        if (it == 3) TS(7);
        wg_fence();
        static_for<0, 4>([&](auto K) { wgmma_rs_n224_tb1<LB_W1 + K * 64, HI64>(acc, fa[0][K], b, (it | K) != 0); });
        wg_commit();
        issue_pkts<0, 4>(Gin + it * 256 + 128, 32, fa[1]);
        next_tile();
        verify4_tag0<512>(Gin + it * 256 + 128, fa[1]);
        wg_fence();
        static_for<0, 4>([&](auto K) { wgmma_rs_n224_tb1<LB_W1 + K * 64, HI64>(acc, fa[1][K], b, 1); });
        wg_commit();
        if (it < 3) issue_pkts<0, 4>(Gin + it * 256 + 256, 32, fa[0]);
        else ld_pkt(statp, st);
        if (it < 2) {
          if (it == 1) red1_issue(3);
          red1_process(2 + it);
          if (it == 1) {
#pragma unroll
            for (int o = 16; o > 0; o >>= 1) {
              s0 += __shfl_xor_sync(0xffffffffu, s0, o);
              s1 += __shfl_xor_sync(0xffffffffu, s1, o);
              v0 += __shfl_xor_sync(0xffffffffu, v0, o);
              v1 += __shfl_xor_sync(0xffffffffu, v1, o);
            }
            const float m0 = s0 * (1.f / 512.f), m1 = s1 * (1.f / 512.f);
            const float r0 = 0.5f * rsqrtf(fmaxf(fmaf(-m0, m0, v0 * (1.f / 512.f)), 0.f) + 1e-5f);
            const float r1 = 0.5f * rsqrtf(fmaxf(fmaf(-m1, m1, v1 * (1.f / 512.f)), 0.f) + 1e-5f);
            if (lane < 2)
              st_pkt(&p.s->stat[((rt * 8 + j) * 8 + warp) * 2 + lane], (__float_as_uint(r0) & ~1u) | (tag & 1u),
                     __float_as_uint(-m0 * r0), __float_as_uint(r1), __float_as_uint(-m1 * r1));
          }
        }
        next_tile();
      }
      fence_regs(acc);
      TS(9);
      mbar_wait(bars + 72, 0);
      {
        int spins = 0;
        while (((st[0] ^ tag) & 1u) && ++spins < SPIN_LIMIT) ld_pkt(statp, st);
      }
      const float ra0 = __uint_as_float(st[0]), rb0 = __uint_as_float(st[1]), ra1 = __uint_as_float(st[2]),
                  rb1 = __uint_as_float(st[3]);
#pragma unroll
      for (int i = 0; i < 28; i++) {
        uint32_t m[4];
        lds128(sb + SM_TAB + (i * 4 + q) * 16, m);
        const float u0 = __uint_as_float(m[0]), u1 = __uint_as_float(m[1]), w0 = __uint_as_float(m[2]), w1 = __uint_as_float(m[3]);
        const float z0 = fmaf(acc[4 * i], ra0, fmaf(u0, rb0, w0)), z1 = fmaf(acc[4 * i + 1], ra0, fmaf(u1, rb0, w1));
        const float z2 = fmaf(acc[4 * i + 2], ra1, fmaf(u0, rb1, w0)), z3 = fmaf(acc[4 * i + 3], ra1, fmaf(u1, rb1, w1));
        H[i >> 1][(i & 1) * 2] = pack_bf16(fmaf(z0, tanh_hw(z0), z0), fmaf(z1, tanh_hw(z1), z1));
        H[i >> 1][(i & 1) * 2 + 1] = pack_bf16(fmaf(z2, tanh_hw(z2), z2), fmaf(z3, tanh_hw(z3), z3));
      }
    }
    fence_regs(H);
    TS(10);
#pragma unroll 1
    for (int c = 0; c < 4; c++) {
      wg_fence();
      static_for<0, 7>([&](auto K) { wgmma_rs_n128_tb1<LB_W2 + K * 128, HI128>(S, H[K], b, K != 0); });
      wg_commit();
      if (c == 3) {
        issue_pkts<0, 8>(Pown, 1024, r);
        ld_pkt(mod2p + 384, ga);
      }
      next_tile();
      wg_fence();
      static_for<0, 7>([&](auto K) { wgmma_rs_n128_tb1<LB_W2 + K * 128, HI128>(S, H[7 + K], b, 1); });
      wg_commit();
      warp_bulk_wait_read<2>();
      if (c < 3) next_tile();
      wg_wait<0>();
      fence_regs(S);
      store_partial(IC<0>{}, c == 2 ? stage : sb + SM_PARK + (c == 1 ? 2 : 1) * SLOT + warp * 4096, c);
    }
    TS(11);
#pragma unroll 1
    for (int c = 0; c < 4; c++) {
      uint32_t* const oo = (uint32_t*)p.out + xoff2 + c * 64;
      uint32_t xa[2][4];
      if (c > 0) {
        issue_pkts<0, 8>(Pown + c * 256, 1024, r);
        ld_pkt(mod2p + 384 + c * 32, ga);
      }
      lds128(sb + SM_PARK + (2 * c) * 4096 + tid * 16, xa[0]);
      lds128(sb + SM_PARK + (2 * c + 1) * 4096 + tid * 16, xa[1]);
      if (ga[2] != tag) ld_mod(mod2p + 384 + c * 32, tag, ga);
      verify8_tag0<16384>(Pown + c * 256, r);
#pragma unroll
      for (int e = 0; e < 4; e++) {
        float y0 = bf_lo(r[0][e]), y1 = bf_hi(r[0][e]);
#pragma unroll
        for (int s = 1; s < 8; s++) { y0 += bf_lo(r[s][e]); y1 += bf_hi(r[s][e]); }
        oo[(e >> 1) * 4 + (e & 1) * 8 * 256] =
            pack_bf16(fmaf(bf_lo(ga[e >> 1]), y0, __uint_as_float(xa[e >> 1][(e & 1) * 2])),
                      fmaf(bf_hi(ga[e >> 1]), y1, __uint_as_float(xa[e >> 1][(e & 1) * 2 + 1])));
      }
      if (c == 1) TS(13);
      if (c == 2) TS(14);
    }
    warp_bulk_wait_read<0>();
    TS(12);
    if (bid == 0 && tid == 0) asm volatile("st.relaxed.gpu.global.u32 [%0], %1;" ::"l"(&p.s->epoch), "r"(tag) : "memory");
  }
}

typedef CUresult (*EncodeFn)(CUtensorMap*, CUtensorMapDataType, cuuint32_t, void*, const cuuint64_t*, const cuuint64_t*,
                             const cuuint32_t*, const cuuint32_t*, CUtensorMapInterleave, CUtensorMapSwizzle,
                             CUtensorMapL2promotion, CUtensorMapFloatOOBfill);

static void make_map(EncodeFn fn, CUtensorMap* tm, const void* ptr, int inner, int rows, int cols, int box_rows, int box_outer,
                     CUtensorMapSwizzle swz) {
  cuuint64_t gd[3] = {(cuuint64_t)inner, (cuuint64_t)rows, (cuuint64_t)(cols / inner)};
  cuuint64_t gs[2] = {(cuuint64_t)cols * 2, (cuuint64_t)inner * 2};
  cuuint32_t bx[3] = {(cuuint32_t)inner, (cuuint32_t)box_rows, (cuuint32_t)box_outer};
  cuuint32_t es[3] = {1, 1, 1};
  fn(tm, CU_TENSOR_MAP_DATA_TYPE_BFLOAT16, 3, const_cast<void*>(ptr), gd, gs, bx, es, CU_TENSOR_MAP_INTERLEAVE_NONE, swz,
     CU_TENSOR_MAP_L2_PROMOTION_L2_128B, CU_TENSOR_MAP_FLOAT_OOB_FILL_NONE);
}

extern "C" void kernel_launch(void* const* d_in, const int* in_sizes, int n_in, void* d_out, int out_size) {
  (void)in_sizes; (void)n_in; (void)out_size;
  void* fnp = nullptr;
  cudaDriverEntryPointQueryResult qr;
  cudaGetDriverEntryPoint("cuTensorMapEncodeTiled", &fnp, cudaEnableDefault, &qr);
  EncodeFn fn = (EncodeFn)fnp;
  CUtensorMap tmWq, tmK, tmV, tmWo, tmW1, tmW2;
  make_map(fn, &tmWq, d_in[3], 64, 512, 4096, 128, 2, CU_TENSOR_MAP_SWIZZLE_128B);
  make_map(fn, &tmK, d_in[1], 64, 8 * SK, 128, 128, 2, CU_TENSOR_MAP_SWIZZLE_128B);
  make_map(fn, &tmV, d_in[2], 64, 8 * SK, 128, 128, 2, CU_TENSOR_MAP_SWIZZLE_128B);
  make_map(fn, &tmWo, d_in[4], 64, 4096, 512, 128, 2, CU_TENSOR_MAP_SWIZZLE_128B);
  make_map(fn, &tmW1, d_in[6], 32, 512, FF, 64, 7, CU_TENSOR_MAP_SWIZZLE_64B);
  make_map(fn, &tmW2, d_in[7], 64, FF, 512, 112, 2, CU_TENSOR_MAP_SWIZZLE_128B);
  Params p;
  p.x = (const __nv_bfloat16*)d_in[0];
  p.c = (const __nv_bfloat16*)d_in[8];
  p.wmod = (const __nv_bfloat16*)d_in[9];
  p.wo = (const __nv_bfloat16*)d_in[4];
  p.w1 = (const __nv_bfloat16*)d_in[6];
  p.w2 = (const __nv_bfloat16*)d_in[7];
  p.out = (__nv_bfloat16*)d_out;
  cudaGetSymbolAddress((void**)&p.s, g_scratch);
  cudaFuncSetAttribute(adaln_block_kernel, cudaFuncAttributeMaxDynamicSharedMemorySize, SM_TOTAL);
  adaln_block_kernel<<<128, 384, SM_TOTAL>>>(tmWq, tmK, tmV, tmWo, tmW1, tmW2, p);
}
```

```cpp
#include <cuda_runtime.h>
#include <cuda_bf16.h>
#include <cuda.h>
#include <stdint.h>

template <int OFF, uint32_t HI>
__device__ __forceinline__ void wgmma_rs_n128_tb0(float (&d)[64], const uint32_t (&a)[4], uint32_t lo, int sd) {
  asm volatile("{\n.reg .pred p;\n.reg .b32 l;\n.reg .b64 db;\nsetp.ne.b32 p, %69, 0;\n"
    "add.u32 l, %68, %70;\nmov.b64 db, {l, %71};\n"
    "wgmma.mma_async.sync.aligned.m64n128k16.f32.bf16.bf16 "
    "{%0,%1,%2,%3,%4,%5,%6,%7,%8,%9,%10,%11,%12,%13,%14,%15,"
    "%16,%17,%18,%19,%20,%21,%22,%23,%24,%25,%26,%27,%28,%29,%30,%31,"
    "%32,%33,%34,%35,%36,%37,%38,%39,%40,%41,%42,%43,%44,%45,%46,%47,"
    "%48,%49,%50,%51,%52,%53,%54,%55,%56,%57,%58,%59,%60,%61,%62,%63}, "
    "{%64,%65,%66,%67}, db, p, 1, 1, 0;\n}\n"
    : "+f"(d[0]), "+f"(d[1]), "+f"(d[2]), "+f"(d[3]), "+f"(d[4]), "+f"(d[5]), "+f"(d[6]), "+f"(d[7]),
      "+f"(d[8]), "+f"(d[9]), "+f"(d[10]), "+f"(d[11]), "+f"(d[12]), "+f"(d[13]), "+f"(d[14]), "+f"(d[15]),
      "+f"(d[16]), "+f"(d[17]), "+f"(d[18]), "+f"(d[19]), "+f"(d[20]), "+f"(d[21]), "+f"(d[22]), "+f"(d[23]),
      "+f"(d[24]), "+f"(d[25]), "+f"(d[26]), "+f"(d[27]), "+f"(d[28]), "+f"(d[29]), "+f"(d[30]), "+f"(d[31]),
      "+f"(d[32]), "+f"(d[33]), "+f"(d[34]), "+f"(d[35]), "+f"(d[36]), "+f"(d[37]), "+f"(d[38]), "+f"(d[39]),
      "+f"(d[40]), "+f"(d[41]), "+f"(d[42]), "+f"(d[43]), "+f"(d[44]), "+f"(d[45]), "+f"(d[46]), "+f"(d[47]),
      "+f"(d[48]), "+f"(d[49]), "+f"(d[50]), "+f"(d[51]), "+f"(d[52]), "+f"(d[53]), "+f"(d[54]), "+f"(d[55]),
      "+f"(d[56]), "+f"(d[57]), "+f"(d[58]), "+f"(d[59]), "+f"(d[60]), "+f"(d[61]), "+f"(d[62]), "+f"(d[63])
    : "r"(a[0]), "r"(a[1]), "r"(a[2]), "r"(a[3]), "r"(lo), "r"(sd), "n"(OFF), "n"(HI));
}

template <int OFF, uint32_t HI>
__device__ __forceinline__ void wgmma_rs_n128_tb1(float (&d)[64], const uint32_t (&a)[4], uint32_t lo, int sd) {
  asm volatile("{\n.reg .pred p;\n.reg .b32 l;\n.reg .b64 db;\nsetp.ne.b32 p, %69, 0;\n"
    "add.u32 l, %68, %70;\nmov.b64 db, {l, %71};\n"
    "wgmma.mma_async.sync.aligned.m64n128k16.f32.bf16.bf16 "
    "{%0,%1,%2,%3,%4,%5,%6,%7,%8,%9,%10,%11,%12,%13,%14,%15,"
    "%16,%17,%18,%19,%20,%21,%22,%23,%24,%25,%26,%27,%28,%29,%30,%31,"
    "%32,%33,%34,%35,%36,%37,%38,%39,%40,%41,%42,%43,%44,%45,%46,%47,"
    "%48,%49,%50,%51,%52,%53,%54,%55,%56,%57,%58,%59,%60,%61,%62,%63}, "
    "{%64,%65,%66,%67}, db, p, 1, 1, 1;\n}\n"
    : "+f"(d[0]), "+f"(d[1]), "+f"(d[2]), "+f"(d[3]), "+f"(d[4]), "+f"(d[5]), "+f"(d[6]), "+f"(d[7]),
      "+f"(d[8]), "+f"(d[9]), "+f"(d[10]), "+f"(d[11]), "+f"(d[12]), "+f"(d[13]), "+f"(d[14]), "+f"(d[15]),
      "+f"(d[16]), "+f"(d[17]), "+f"(d[18]), "+f"(d[19]), "+f"(d[20]), "+f"(d[21]), "+f"(d[22]), "+f"(d[23]),
      "+f"(d[24]), "+f"(d[25]), "+f"(d[26]), "+f"(d[27]), "+f"(d[28]), "+f"(d[29]), "+f"(d[30]), "+f"(d[31]),
      "+f"(d[32]), "+f"(d[33]), "+f"(d[34]), "+f"(d[35]), "+f"(d[36]), "+f"(d[37]), "+f"(d[38]), "+f"(d[39]),
      "+f"(d[40]), "+f"(d[41]), "+f"(d[42]), "+f"(d[43]), "+f"(d[44]), "+f"(d[45]), "+f"(d[46]), "+f"(d[47]),
      "+f"(d[48]), "+f"(d[49]), "+f"(d[50]), "+f"(d[51]), "+f"(d[52]), "+f"(d[53]), "+f"(d[54]), "+f"(d[55]),
      "+f"(d[56]), "+f"(d[57]), "+f"(d[58]), "+f"(d[59]), "+f"(d[60]), "+f"(d[61]), "+f"(d[62]), "+f"(d[63])
    : "r"(a[0]), "r"(a[1]), "r"(a[2]), "r"(a[3]), "r"(lo), "r"(sd), "n"(OFF), "n"(HI));
}

template <int OFF, uint32_t HI>
__device__ __forceinline__ void wgmma_rs_n224_tb1(float (&d)[112], const uint32_t (&a)[4], uint32_t lo, int sd) {
  asm volatile("{\n.reg .pred p;\n.reg .b32 l;\n.reg .b64 db;\nsetp.ne.b32 p, %117, 0;\n"
    "add.u32 l, %116, %118;\nmov.b64 db, {l, %119};\n"
    "wgmma.mma_async.sync.aligned.m64n224k16.f32.bf16.bf16 "
    "{%0,%1,%2,%3,%4,%5,%6,%7,%8,%9,%10,%11,%12,%13,%14,%15,"
    "%16,%17,%18,%19,%20,%21,%22,%23,%24,%25,%26,%27,%28,%29,%30,%31,"
    "%32,%33,%34,%35,%36,%37,%38,%39,%40,%41,%42,%43,%44,%45,%46,%47,"
    "%48,%49,%50,%51,%52,%53,%54,%55,%56,%57,%58,%59,%60,%61,%62,%63,"
    "%64,%65,%66,%67,%68,%69,%70,%71,%72,%73,%74,%75,%76,%77,%78,%79,"
    "%80,%81,%82,%83,%84,%85,%86,%87,%88,%89,%90,%91,%92,%93,%94,%95,"
    "%96,%97,%98,%99,%100,%101,%102,%103,%104,%105,%106,%107,%108,%109,%110,%111}, "
    "{%112,%113,%114,%115}, db, p, 1, 1, 1;\n}\n"
    : "+f"(d[0]), "+f"(d[1]), "+f"(d[2]), "+f"(d[3]), "+f"(d[4]), "+f"(d[5]), "+f"(d[6]), "+f"(d[7]),
      "+f"(d[8]), "+f"(d[9]), "+f"(d[10]), "+f"(d[11]), "+f"(d[12]), "+f"(d[13]), "+f"(d[14]), "+f"(d[15]),
      "+f"(d[16]), "+f"(d[17]), "+f"(d[18]), "+f"(d[19]), "+f"(d[20]), "+f"(d[21]), "+f"(d[22]), "+f"(d[23]),
      "+f"(d[24]), "+f"(d[25]), "+f"(d[26]), "+f"(d[27]), "+f"(d[28]), "+f"(d[29]), "+f"(d[30]), "+f"(d[31]),
      "+f"(d[32]), "+f"(d[33]), "+f"(d[34]), "+f"(d[35]), "+f"(d[36]), "+f"(d[37]), "+f"(d[38]), "+f"(d[39]),
      "+f"(d[40]), "+f"(d[41]), "+f"(d[42]), "+f"(d[43]), "+f"(d[44]), "+f"(d[45]), "+f"(d[46]), "+f"(d[47]),
      "+f"(d[48]), "+f"(d[49]), "+f"(d[50]), "+f"(d[51]), "+f"(d[52]), "+f"(d[53]), "+f"(d[54]), "+f"(d[55]),
      "+f"(d[56]), "+f"(d[57]), "+f"(d[58]), "+f"(d[59]), "+f"(d[60]), "+f"(d[61]), "+f"(d[62]), "+f"(d[63]),
      "+f"(d[64]), "+f"(d[65]), "+f"(d[66]), "+f"(d[67]), "+f"(d[68]), "+f"(d[69]), "+f"(d[70]), "+f"(d[71]),
      "+f"(d[72]), "+f"(d[73]), "+f"(d[74]), "+f"(d[75]), "+f"(d[76]), "+f"(d[77]), "+f"(d[78]), "+f"(d[79]),
      "+f"(d[80]), "+f"(d[81]), "+f"(d[82]), "+f"(d[83]), "+f"(d[84]), "+f"(d[85]), "+f"(d[86]), "+f"(d[87]),
      "+f"(d[88]), "+f"(d[89]), "+f"(d[90]), "+f"(d[91]), "+f"(d[92]), "+f"(d[93]), "+f"(d[94]), "+f"(d[95]),
      "+f"(d[96]), "+f"(d[97]), "+f"(d[98]), "+f"(d[99]), "+f"(d[100]), "+f"(d[101]), "+f"(d[102]), "+f"(d[103]),
      "+f"(d[104]), "+f"(d[105]), "+f"(d[106]), "+f"(d[107]), "+f"(d[108]), "+f"(d[109]), "+f"(d[110]), "+f"(d[111])
    : "r"(a[0]), "r"(a[1]), "r"(a[2]), "r"(a[3]), "r"(lo), "r"(sd), "n"(OFF), "n"(HI));
}

template <int STR>
__device__ __forceinline__ void verify8_tag1(const uint4* p, uint32_t (*r)[4]) {
  asm volatile("{\n.reg .pred p, q;\n.reg .b32 a, n;\nmov.u32 n, 0;\n"
    "LAB_CHK:\n"
    "and.b32 a, %0, %4;\n"
    "and.b32 a, a, %8;\n"
    "and.b32 a, a, %12;\n"
    "and.b32 a, a, %16;\n"
    "and.b32 a, a, %20;\n"
    "and.b32 a, a, %24;\n"
    "and.b32 a, a, %28;\n"
    "and.b32 a, a, 1;\nsetp.eq.u32 p, a, 1;\nvote.sync.all.pred p, p, 0xffffffff;\n"
    "@p bra.uni LAB_OK;\n"
    "ld.relaxed.gpu.global.v4.b32 {%0,%1,%2,%3}, [%32+%33];\n"
    "ld.relaxed.gpu.global.v4.b32 {%4,%5,%6,%7}, [%32+%34];\n"
    "ld.relaxed.gpu.global.v4.b32 {%8,%9,%10,%11}, [%32+%35];\n"
    "ld.relaxed.gpu.global.v4.b32 {%12,%13,%14,%15}, [%32+%36];\n"
    "ld.relaxed.gpu.global.v4.b32 {%16,%17,%18,%19}, [%32+%37];\n"
    "ld.relaxed.gpu.global.v4.b32 {%20,%21,%22,%23}, [%32+%38];\n"
    "ld.relaxed.gpu.global.v4.b32 {%24,%25,%26,%27}, [%32+%39];\n"
    "ld.relaxed.gpu.global.v4.b32 {%28,%29,%30,%31}, [%32+%40];\n"
    "add.u32 n, n, 1;\nsetp.lt.u32 q, n, 262144;\n@q bra.uni LAB_CHK;\n"
    "LAB_OK:\n"
    "}\n"
    : "+r"(r[0][0]), "+r"(r[0][1]), "+r"(r[0][2]), "+r"(r[0][3]), "+r"(r[1][0]), "+r"(r[1][1]), "+r"(r[1][2]), "+r"(r[1][3]),
      "+r"(r[2][0]), "+r"(r[2][1]), "+r"(r[2][2]), "+r"(r[2][3]), "+r"(r[3][0]), "+r"(r[3][1]), "+r"(r[3][2]), "+r"(r[3][3]),
      "+r"(r[4][0]), "+r"(r[4][1]), "+r"(r[4][2]), "+r"(r[4][3]), "+r"(r[5][0]), "+r"(r[5][1]), "+r"(r[5][2]), "+r"(r[5][3]),
      "+r"(r[6][0]), "+r"(r[6][1]), "+r"(r[6][2]), "+r"(r[6][3]), "+r"(r[7][0]), "+r"(r[7][1]), "+r"(r[7][2]), "+r"(r[7][3])
    : "l"(p), "n"(0 * STR), "n"(1 * STR), "n"(2 * STR), "n"(3 * STR), "n"(4 * STR), "n"(5 * STR), "n"(6 * STR), "n"(7 * STR)
    : "memory");
}

template <int STR>
__device__ __forceinline__ void verify8_tag0(const uint4* p, uint32_t (*r)[4]) {
  asm volatile("{\n.reg .pred p, q;\n.reg .b32 a, n;\nmov.u32 n, 0;\n"
    "LAB_CHK:\n"
    "or.b32 a, %0, %4;\n"
    "or.b32 a, a, %8;\n"
    "or.b32 a, a, %12;\n"
    "or.b32 a, a, %16;\n"
    "or.b32 a, a, %20;\n"
    "or.b32 a, a, %24;\n"
    "or.b32 a, a, %28;\n"
    "and.b32 a, a, 1;\nsetp.eq.u32 p, a, 0;\nvote.sync.all.pred p, p, 0xffffffff;\n"
    "@p bra.uni LAB_OK;\n"
    "ld.relaxed.gpu.global.v4.b32 {%0,%1,%2,%3}, [%32+%33];\n"
    "ld.relaxed.gpu.global.v4.b32 {%4,%5,%6,%7}, [%32+%34];\n"
    "ld.relaxed.gpu.global.v4.b32 {%8,%9,%10,%11}, [%32+%35];\n"
    "ld.relaxed.gpu.global.v4.b32 {%12,%13,%14,%15}, [%32+%36];\n"
    "ld.relaxed.gpu.global.v4.b32 {%16,%17,%18,%19}, [%32+%37];\n"
    "ld.relaxed.gpu.global.v4.b32 {%20,%21,%22,%23}, [%32+%38];\n"
    "ld.relaxed.gpu.global.v4.b32 {%24,%25,%26,%27}, [%32+%39];\n"
    "ld.relaxed.gpu.global.v4.b32 {%28,%29,%30,%31}, [%32+%40];\n"
    "add.u32 n, n, 1;\nsetp.lt.u32 q, n, 262144;\n@q bra.uni LAB_CHK;\n"
    "LAB_OK:\n"
    "or.b32 %0, %0, 1;\n"
    "or.b32 %4, %4, 1;\n"
    "or.b32 %8, %8, 1;\n"
    "or.b32 %12, %12, 1;\n"
    "or.b32 %16, %16, 1;\n"
    "or.b32 %20, %20, 1;\n"
    "or.b32 %24, %24, 1;\n"
    "or.b32 %28, %28, 1;\n"
    "}\n"
    : "+r"(r[0][0]), "+r"(r[0][1]), "+r"(r[0][2]), "+r"(r[0][3]), "+r"(r[1][0]), "+r"(r[1][1]), "+r"(r[1][2]), "+r"(r[1][3]),
      "+r"(r[2][0]), "+r"(r[2][1]), "+r"(r[2][2]), "+r"(r[2][3]), "+r"(r[3][0]), "+r"(r[3][1]), "+r"(r[3][2]), "+r"(r[3][3]),
      "+r"(r[4][0]), "+r"(r[4][1]), "+r"(r[4][2]), "+r"(r[4][3]), "+r"(r[5][0]), "+r"(r[5][1]), "+r"(r[5][2]), "+r"(r[5][3]),
      "+r"(r[6][0]), "+r"(r[6][1]), "+r"(r[6][2]), "+r"(r[6][3]), "+r"(r[7][0]), "+r"(r[7][1]), "+r"(r[7][2]), "+r"(r[7][3])
    : "l"(p), "n"(0 * STR), "n"(1 * STR), "n"(2 * STR), "n"(3 * STR), "n"(4 * STR), "n"(5 * STR), "n"(6 * STR), "n"(7 * STR)
    : "memory");
}

template <int STR>
__device__ __forceinline__ void verify4_tag0(const uint4* p, uint32_t (*r)[4]) {
  asm volatile("{\n.reg .pred p, q;\n.reg .b32 a, n;\nmov.u32 n, 0;\n"
    "LAB_CHK:\n"
    "or.b32 a, %0, %4;\n"
    "or.b32 a, a, %8;\n"
    "or.b32 a, a, %12;\n"
    "and.b32 a, a, 1;\nsetp.eq.u32 p, a, 0;\nvote.sync.all.pred p, p, 0xffffffff;\n"
    "@p bra.uni LAB_OK;\n"
    "ld.relaxed.gpu.global.v4.b32 {%0,%1,%2,%3}, [%16+%17];\n"
    "ld.relaxed.gpu.global.v4.b32 {%4,%5,%6,%7}, [%16+%18];\n"
    "ld.relaxed.gpu.global.v4.b32 {%8,%9,%10,%11}, [%16+%19];\n"
    "ld.relaxed.gpu.global.v4.b32 {%12,%13,%14,%15}, [%16+%20];\n"
    "add.u32 n, n, 1;\nsetp.lt.u32 q, n, 262144;\n@q bra.uni LAB_CHK;\n"
    "LAB_OK:\n"
    "or.b32 %0, %0, 1;\n"
    "or.b32 %4, %4, 1;\n"
    "or.b32 %8, %8, 1;\n"
    "or.b32 %12, %12, 1;\n"
    "}\n"
    : "+r"(r[0][0]), "+r"(r[0][1]), "+r"(r[0][2]), "+r"(r[0][3]), "+r"(r[1][0]), "+r"(r[1][1]), "+r"(r[1][2]), "+r"(r[1][3]),
      "+r"(r[2][0]), "+r"(r[2][1]), "+r"(r[2][2]), "+r"(r[2][3]), "+r"(r[3][0]), "+r"(r[3][1]), "+r"(r[3][2]), "+r"(r[3][3])
    : "l"(p), "n"(0 * STR), "n"(1 * STR), "n"(2 * STR), "n"(3 * STR)
    : "memory");
}

#define SPIN_LIMIT (1 << 18)

__device__ __forceinline__ uint32_t smem_u32(const void* p) { return (uint32_t)__cvta_generic_to_shared(p); }
__device__ __forceinline__ void mbar_init(uint32_t a, uint32_t c) {
  asm volatile("mbarrier.init.shared::cta.b64 [%0], %1;" ::"r"(a), "r"(c) : "memory");
}
__device__ __forceinline__ void mbar_expect(uint32_t a, uint32_t b) {
  asm volatile("mbarrier.arrive.expect_tx.shared::cta.b64 _, [%0], %1;" ::"r"(a), "r"(b) : "memory");
}
__device__ __forceinline__ void mbar_arrive(uint32_t a) {
  asm volatile("mbarrier.arrive.shared::cta.b64 _, [%0];" ::"r"(a) : "memory");
}
__device__ __forceinline__ void mbar_wait(uint32_t a, uint32_t parity) {
  asm volatile(
      "{\n.reg .pred p;\n.reg .u32 n;\nmov.u32 n, 0;\n"
      "LAB_WAIT:\n"
      "mbarrier.try_wait.parity.shared::cta.b64 p, [%0], %1;\n"
      "@p bra LAB_DONE;\n"
      "add.u32 n, n, 1;\n"
      "setp.lt.u32 p, n, 262144;\n"
      "@p bra LAB_WAIT;\n"
      "LAB_DONE:\n}\n" ::"r"(a), "r"(parity) : "memory");
}
__device__ __forceinline__ void tma3d(uint32_t dst, const CUtensorMap* tm, uint32_t bar, int c0, int c1, int c2) {
  asm volatile(
      "cp.async.bulk.tensor.3d.shared::cluster.global.mbarrier::complete_tx::bytes [%0], [%1, {%3,%4,%5}], [%2];"
      ::"r"(dst), "l"(tm), "r"(bar), "r"(c0), "r"(c1), "r"(c2) : "memory");
}
__device__ __forceinline__ void wg_fence() { asm volatile("wgmma.fence.sync.aligned;" ::: "memory"); }
__device__ __forceinline__ void wg_commit() { asm volatile("wgmma.commit_group.sync.aligned;" ::: "memory"); }
template <int N> __device__ __forceinline__ void wg_wait() {
  asm volatile("wgmma.wait_group.sync.aligned %0;" ::"n"(N) : "memory");
}
template <int N> __device__ __forceinline__ void fence_regs(float (&d)[N]) {
#pragma unroll
  for (int i = 0; i < N; i++) asm volatile("" : "+f"(d[i])::"memory");
}
template <int N> __device__ __forceinline__ void fence_regs(uint32_t (&d)[N][4]) {
#pragma unroll
  for (int i = 0; i < N; i++) asm volatile("" : "+r"(d[i][0]), "+r"(d[i][1]), "+r"(d[i][2]), "+r"(d[i][3])::"memory");
}
template <int N> __device__ __forceinline__ void fence_frags(uint32_t (*d)[4]) {
#pragma unroll
  for (int i = 0; i < N; i++) asm volatile("" : "+r"(d[i][0]), "+r"(d[i][1]), "+r"(d[i][2]), "+r"(d[i][3])::"memory");
}
__device__ __forceinline__ void bar_sync(int id, int n) { asm volatile("bar.sync %0, %1;" ::"r"(id), "r"(n) : "memory"); }
__device__ __forceinline__ void bar_arrive(int id, int n) { asm volatile("bar.arrive %0, %1;" ::"r"(id), "r"(n) : "memory"); }

__device__ __forceinline__ uint32_t pack_bf16(float lo, float hi) {
  uint32_t r;
  asm("cvt.rn.bf16x2.f32 %0, %1, %2;" : "=r"(r) : "f"(hi), "f"(lo));
  return r;
}
__device__ __forceinline__ float bf_lo(uint32_t w) { return __uint_as_float(w << 16); }
__device__ __forceinline__ float bf_hi(uint32_t w) { return __uint_as_float(w & 0xFFFF0000u); }
__device__ __forceinline__ float round_bf16(float x) { return bf_lo(pack_bf16(x, 0.f)); }
__device__ __forceinline__ uint32_t hfma2_bf16(uint32_t a, uint32_t b, uint32_t c) {
  uint32_t r;
  asm("fma.rn.bf16x2 %0, %1, %2, %3;" : "=r"(r) : "r"(a), "r"(b), "r"(c));
  return r;
}
__device__ __forceinline__ float ex2(float x) {
  float r;
  asm("ex2.approx.ftz.f32 %0, %1;" : "=f"(r) : "f"(x));
  return r;
}
__device__ __forceinline__ float tanh_hw(float x) {
  float r;
  asm("tanh.approx.f32 %0, %1;" : "=f"(r) : "f"(x));
  return r;
}
template <int TAG> __device__ __forceinline__ uint32_t pack_tag(float lo, float hi) {
  uint32_t w = __byte_perm(__float_as_uint(lo), pack_bf16(lo, hi), 0x7632);
  return TAG ? (w | 1u) : (w & ~1u);
}
__device__ __forceinline__ void st_pkt(uint4* p, uint32_t a, uint32_t b, uint32_t c, uint32_t d) {
  asm volatile(
      "st.relaxed.gpu.global.v4.b32 [%0], {%1,%2,%3,%4};" ::"l"(p), "r"(a), "r"(b), "r"(c), "r"(d) : "memory");
}
__device__ __forceinline__ void ld_pkt(const uint4* p, uint32_t (&r)[4]) {
  asm volatile(
      "ld.relaxed.gpu.global.v4.b32 {%0,%1,%2,%3}, [%4];"
      : "=r"(r[0]), "=r"(r[1]), "=r"(r[2]), "=r"(r[3]) : "l"(p) : "memory");
}
__device__ __forceinline__ uint32_t ldg32(const void* p) {
  uint32_t r;
  asm volatile("ld.global.nc.b32 %0, [%1];" : "=r"(r) : "l"(p));
  return r;
}
__device__ __forceinline__ uint32_t ldg16(const void* p) {
  uint16_t r;
  asm volatile("ld.global.nc.b16 %0, [%1];" : "=h"(r) : "l"(p));
  return r;
}
__device__ __forceinline__ uint4 ldg128(const void* p) {
  uint4 r;
  asm volatile("ld.global.nc.v4.b32 {%0,%1,%2,%3}, [%4];" : "=r"(r.x), "=r"(r.y), "=r"(r.z), "=r"(r.w) : "l"(p));
  return r;
}
__device__ __forceinline__ void l2_prefetch(const void* p, uint32_t bytes) {
  asm volatile("cp.async.bulk.prefetch.L2.global [%0], %1;" ::"l"(p), "r"(bytes) : "memory");
}
__device__ __forceinline__ float rcp_hw(float x) {
  float r;
  asm("rcp.approx.ftz.f32 %0, %1;" : "=f"(r) : "f"(x));
  return r;
}
__device__ __forceinline__ void warp_bulk_store(void* gdst, uint32_t ssrc, uint32_t bytes) {
  asm volatile("fence.proxy.async.shared::cta;" ::: "memory");
  __syncwarp();
  if ((threadIdx.x & 31) == 0) {
    asm volatile("cp.async.bulk.global.shared::cta.bulk_group [%0], [%1], %2;" ::"l"(gdst), "r"(ssrc), "r"(bytes) : "memory");
    asm volatile("cp.async.bulk.commit_group;" ::: "memory");
  }
}
template <int N> __device__ __forceinline__ void warp_bulk_wait_read() {
  if ((threadIdx.x & 31) == 0) asm volatile("cp.async.bulk.wait_group.read %0;" ::"n"(N) : "memory");
  __syncwarp();
}
__device__ __forceinline__ void sts128(uint32_t a, uint32_t x, uint32_t y, uint32_t z, uint32_t w) {
  asm volatile("st.shared.v4.b32 [%0], {%1,%2,%3,%4};" ::"r"(a), "r"(x), "r"(y), "r"(z), "r"(w) : "memory");
}
__device__ __forceinline__ void lds128(uint32_t a, uint32_t (&r)[4]) {
  asm volatile("ld.shared.v4.b32 {%0,%1,%2,%3}, [%4];" : "=r"(r[0]), "=r"(r[1]), "=r"(r[2]), "=r"(r[3]) : "r"(a) : "memory");
}

constexpr int SK = 2048, WIN = 512;
constexpr int FF = 1792, FSL = 224;
constexpr int NTILES = 80;
constexpr int NSLOT = 4;
constexpr uint32_t SLOT = 32768;
constexpr uint32_t SM_PARK = 0;
constexpr uint32_t SM_RING = 3 * SLOT;
constexpr uint32_t SM_TAB = 7 * SLOT;
constexpr uint32_t SM_RED = SM_TAB + 2048;
constexpr uint32_t SM_BAR = SM_RED + 256;
constexpr uint32_t SM_TOTAL = SM_BAR + 128;

struct Scratch {
  uint4 P[16 * 8 * 8 * 1024];
  uint4 G[16 * 8 * 32 * 32];
  uint4 mod1[8 * 256];
  uint4 mod2[512];
  uint4 uv[2 * 448];
  uint4 stat[16 * 8 * 8 * 2];
  uint32_t epoch;
};
__device__ Scratch g_scratch;

#define TS(i) do { } while (0)
#define CK_(v)
#define CKS(i, v)

struct Params {
  const __nv_bfloat16* x;
  const __nv_bfloat16* c;
  const __nv_bfloat16* wmod;
  const __nv_bfloat16* wo;
  const __nv_bfloat16* w1;
  const __nv_bfloat16* w2;
  __nv_bfloat16* out;
  Scratch* s;
};

constexpr uint32_t HI128 = (1024 >> 4) | (1u << 30);
constexpr uint32_t HI64 = (512 >> 4) | (2u << 30);
constexpr int LB_MN128 = (16384 >> 4) << 16;
constexpr int LB_K128 = 1 << 16;
constexpr int LB_W1 = (4096 >> 4) << 16;
constexpr int LB_W2 = (14336 >> 4) << 16;

template <int I> struct IC {
  __host__ __device__ constexpr operator int() const { return I; }
};
template <int I, int N, typename F> __device__ __forceinline__ void static_for(F&& f) {
  if constexpr (I < N) {
    f(IC<I>{});
    static_for<I + 1, N>(f);
  }
}

struct Ring {
  uint32_t base16, bars;
  __device__ __forceinline__ uint32_t wait_full(uint32_t slot, uint32_t parity) const {
    mbar_wait(bars + slot * 8, parity);
    return base16 + slot * (SLOT >> 4);
  }
  __device__ __forceinline__ void release(uint32_t slot) const {
    if ((threadIdx.x & 31) == 0) mbar_arrive(bars + 32 + slot * 8);
  }
};

__device__ __forceinline__ float silu_c(uint32_t bits) {
  float x = bf_lo(bits);
  return round_bf16(x * rcp_hw(1.f + ex2(-1.4426950408889634f * x)));
}
__device__ __forceinline__ void pack8(uint32_t (&o)[4], const float* v) {
  o[0] = pack_bf16(v[0], v[1]); o[1] = pack_bf16(v[2], v[3]); o[2] = pack_bf16(v[4], v[5]); o[3] = pack_bf16(v[6], v[7]);
}

template <int TAG, int N>
__device__ __forceinline__ void issue_pkts(const uint4* p, int stride, uint32_t (*r)[4]) {
#pragma unroll
  for (int i = 0; i < N; i++) ld_pkt(p + i * stride, r[i]);
}
__device__ __forceinline__ void ld_mod(const uint4* p, uint32_t tag, uint32_t (&r)[4]) {
  int spins = 0;
  ld_pkt(p, r);
  while (r[2] != tag && ++spins < SPIN_LIMIT) ld_pkt(p, r);
}

#define EARLY_TILES 2
#define PF_WMOD 1
#define MOD1_DELAY 300
#define RED3_UNIT 3
#define G_DELAY 300

__global__ void __launch_bounds__(384, 1)
adaln_block_kernel(const __grid_constant__ CUtensorMap tmWq, const __grid_constant__ CUtensorMap tmK,
                   const __grid_constant__ CUtensorMap tmV, const __grid_constant__ CUtensorMap tmWo,
                   const __grid_constant__ CUtensorMap tmW1, const __grid_constant__ CUtensorMap tmW2,
                   const __grid_constant__ CUtensorMap tmWm, const Params p) {
  extern __shared__ __align__(1024) uint8_t smem_raw[];
  const uint32_t sb = smem_u32(smem_raw);
  const int tid = threadIdx.x, lane = tid & 31;
  const int warp = __shfl_sync(0xffffffffu, tid >> 5, 0);
  const int bid = blockIdx.x, j = bid >> 4, rt = bid & 15;
  const uint32_t bars = sb + SM_BAR;

  if (warp >= 8) {
    CK_(c0);
    asm volatile("setmaxnreg.dec.sync.aligned.u32 40;");
    CK_(c1);
    const int t = tid - 256;
    uint32_t tag;
    {
      uint32_t cb[4];
      if (t == 0) {
        mbar_init(bars + 80, 1);
        asm volatile("fence.mbarrier_init.release.cluster;" ::: "memory");
        mbar_expect(bars + 80, 8192);
        tma3d(sb + SM_PARK, &tmWm, bars + 80, 0, 0, bid);
        tma3d(sb + SM_PARK + 4096, &tmWm, bars + 80, 0, 256, bid);
        asm volatile("prefetch.tensormap [%0];" ::"l"(&tmWq) : "memory");
        for (int i = 0; i < NSLOT; i++) { mbar_init(bars + i * 8, 1); mbar_init(bars + 32 + i * 8, 8); }
        mbar_init(bars + 72, 2);
        asm volatile("fence.mbarrier_init.release.cluster;" ::: "memory");
      }
      __syncwarp();
      CK_(c2);
#pragma unroll
      for (int i = 0; i < 4; i++) cb[i] = ldg16(p.c + t + 128 * i);
      asm volatile("ld.relaxed.gpu.global.u32 %0, [%1];" : "=r"(tag) : "l"(&p.s->epoch) : "memory");
      bar_sync(5, 128);
      tag += 1;
      float a[8], sc[4];
#pragma unroll
      for (int i = 0; i < 4; i++) sc[i] = silu_c(cb[i]);
#pragma unroll
      for (int k = 0; k < 8; k++) a[k] = 0.f;
      mbar_wait(bars + 80, 0);
      CK_(c3);
#pragma unroll
      for (int i = 0; i < 4; i++) {
        uint32_t w[4];
        lds128(sb + SM_PARK + (t + 128 * i) * 16, w);
#pragma unroll
        for (int e = 0; e < 4; e++) {
          a[2 * e] = fmaf(sc[i], bf_lo(w[e]), a[2 * e]);
          a[2 * e + 1] = fmaf(sc[i], bf_hi(w[e]), a[2 * e + 1]);
        }
      }
      const bool h16 = lane & 16, h8 = lane & 8, h4 = lane & 4;
#pragma unroll
      for (int k = 0; k < 4; k++) {
        float send = h16 ? a[k] : a[k + 4], keep = h16 ? a[k + 4] : a[k];
        a[k] = keep + __shfl_xor_sync(0xffffffffu, send, 16);
      }
#pragma unroll
      for (int k = 0; k < 2; k++) {
        float send = h8 ? a[k] : a[k + 2], keep = h8 ? a[k + 2] : a[k];
        a[k] = keep + __shfl_xor_sync(0xffffffffu, send, 8);
      }
      {
        float send = h4 ? a[0] : a[1], keep = h4 ? a[1] : a[0];
        a[0] = keep + __shfl_xor_sync(0xffffffffu, send, 4);
      }
      a[0] += __shfl_xor_sync(0xffffffffu, a[0], 2);
      a[0] += __shfl_xor_sync(0xffffffffu, a[0], 1);
      float* red = (float*)(smem_raw + SM_RED);
      if ((lane & 3) == 0) red[(warp - 8) * 8 + (lane >> 2)] = a[0];
      if (t == 0) *(uint32_t*)(smem_raw + SM_BAR + 64) = tag;
      CK_(c4);
      bar_sync(5, 128);
      CK_(c5);
      if (t == 0) {
#pragma unroll
        for (int i = 0; i < EARLY_TILES; i++) {
          mbar_expect(bars + i * 8, SLOT);
          tma3d(sb + SM_RING + i * SLOT, &tmWq, bars + i * 8, 0, i * 128, (j * 4 + 1) * 2);
        }
      }
      if (warp == 9) {
        const int cl = lane & 7;
        float v = round_bf16(red[cl] + red[8 + cl] + red[16 + cl] + red[24 + cl]);
        if (bid >= 64) v = 1.f + v;
        float vn = __shfl_down_sync(0xffffffffu, v, 1);
        uint32_t wd = pack_bf16(v, vn);
        uint32_t w0 = __shfl_sync(0xffffffffu, wd, (lane & 1) * 4);
        uint32_t w1 = __shfl_sync(0xffffffffu, wd, (lane & 1) * 4 + 2);
        if (lane < 16) st_pkt(&p.s->mod1[(lane >> 1) * 256 + bid * 2 + (lane & 1)], w0, w1, tag, 0);
      }
      uint32_t r0[4], r1[4];
      const uint4* src = &p.s->mod1[j * 256 + t];
      CK_(c6);
      __nanosleep(MOD1_DELAY);
      CK_(c7);
      int spins = 0;
      do {
        ld_pkt(src, r0);
        ld_pkt(src + 128, r1);
      } while ((r0[2] != tag || r1[2] != tag) && ++spins < SPIN_LIMIT);
      const int g = t >> 2, pp = (t & 3) * 2;
      const uint32_t ad = sb + SM_TAB + (uint32_t)(g * 4 + (pp & 3)) * 16 + (pp >> 2) * 4;
      asm volatile("st.shared.b32 [%0], %1;" ::"r"(ad + 8), "r"(r0[0]) : "memory");
      asm volatile("st.shared.b32 [%0], %1;" ::"r"(ad + 24), "r"(r0[1]) : "memory");
      asm volatile("st.shared.b32 [%0], %1;" ::"r"(ad), "r"(r1[0]) : "memory");
      asm volatile("st.shared.b32 [%0], %1;" ::"r"(ad + 16), "r"(r1[1]) : "memory");
      bar_arrive(1, 384);
      CK_(c8);
      CKS(0, c0); CKS(1, c1); CKS(2, c2); CKS(3, c3); CKS(4, c4); CKS(5, c5); CKS(6, c6); CKS(7, c7); CKS(8, c8);
    }
    if (warp == 8) {
      if (lane == 0) {
        uint32_t s = EARLY_TILES & 3, ph = 1 ^ (EARLY_TILES >> 2);
#pragma unroll 1
        for (int tt = EARLY_TILES; tt < NTILES; tt++) {
          const CUtensorMap* tm;
          int c1, c2;
          uint32_t bytes = SLOT;
          if (tt < 16) {
            tm = &tmWq; c1 = (tt & 3) * 128; c2 = (j * 4 + (((tt >> 2) + 1) & 3)) * 2;
          } else if (tt < 48) {
            const int u = tt - 16;
            const bool isK = (u == 0) || ((u & 1) && u != 31);
            const int n = isK ? ((u + 1) >> 1) : (u == 31 ? 15 : (u >> 1) - 1);
            tm = isK ? &tmK : &tmV; c1 = j * SK + (SK - WIN) + (n & 3) * 128; c2 = 0;
          } else if (tt < 64) {
            const int u = tt - 48;
            tm = &tmWo; c1 = j * 512 + (u & 3) * 128; c2 = (u >> 2) * 2;
          } else if (tt < 72) {
            tm = &tmW1; c1 = (tt - 64) * 64; c2 = j * 7; bytes = 28672;
          } else {
            const int u = tt - 72;
            tm = &tmW2; c1 = j * FSL + (u & 1) * 112; c2 = (u >> 1) * 2; bytes = 28672;
          }
          mbar_wait(bars + 32 + s * 8, ph);
          mbar_expect(bars + s * 8, bytes);
          tma3d(sb + SM_RING + s * SLOT, tm, bars + s * 8, 0, c1, c2);
          if (++s == (tt < 48 ? 4u : 3u)) { s = 0; ph ^= 1; }
        }
      }
    } else if (warp >= 10) {
      const int t2 = tid - 320, hf = t2 & 1, r0 = t2 >> 1;
      bar_sync(6, 352);
      float a[8];
#pragma unroll
      for (int k = 0; k < 8; k++) a[k] = 0.f;
#pragma unroll 1
      for (int b = 0; b < 8; b++) {
        uint4 w[2];
        uint32_t cb[2];
#pragma unroll
        for (int i = 0; i < 2; i++) {
          w[i] = ldg128(p.wmod + (size_t)(r0 + 32 * (2 * b + i)) * 3072 + 1024 + bid * 16 + hf * 8);
          cb[i] = ldg16(p.c + r0 + 32 * (2 * b + i));
        }
#pragma unroll
        for (int i = 0; i < 2; i++) {
          const float s = silu_c(cb[i]);
          a[0] = fmaf(s, bf_lo(w[i].x), a[0]); a[1] = fmaf(s, bf_hi(w[i].x), a[1]);
          a[2] = fmaf(s, bf_lo(w[i].y), a[2]); a[3] = fmaf(s, bf_hi(w[i].y), a[3]);
          a[4] = fmaf(s, bf_lo(w[i].z), a[4]); a[5] = fmaf(s, bf_hi(w[i].z), a[5]);
          a[6] = fmaf(s, bf_lo(w[i].w), a[6]); a[7] = fmaf(s, bf_hi(w[i].w), a[7]);
        }
      }
      const bool h16 = lane & 16, h8 = lane & 8, h4 = lane & 4;
#pragma unroll
      for (int k = 0; k < 4; k++) {
        float send = h16 ? a[k] : a[k + 4], keep = h16 ? a[k + 4] : a[k];
        a[k] = keep + __shfl_xor_sync(0xffffffffu, send, 16);
      }
#pragma unroll
      for (int k = 0; k < 2; k++) {
        float send = h8 ? a[k] : a[k + 2], keep = h8 ? a[k + 2] : a[k];
        a[k] = keep + __shfl_xor_sync(0xffffffffu, send, 8);
      }
      {
        float send = h4 ? a[0] : a[1], keep = h4 ? a[1] : a[0];
        a[0] = keep + __shfl_xor_sync(0xffffffffu, send, 4);
      }
      a[0] += __shfl_xor_sync(0xffffffffu, a[0], 2);
      float* red = (float*)(smem_raw + SM_RED) + 32;
      if ((lane & 2) == 0) red[(warp - 10) * 16 + hf * 8 + (lane >> 2)] = a[0];
      bar_sync(4, 64);
      if (warp == 10) {
        const int cl = lane & 15;
        float v = round_bf16(red[cl] + red[16 + cl]);
        if ((bid >> 5) == 2) v = 1.f + v;
        float vn = __shfl_down_sync(0xffffffffu, v, 1);
        uint32_t wd = pack_bf16(v, vn);
        uint32_t w0 = __shfl_sync(0xffffffffu, wd, (lane & 3) * 2);
        uint32_t w1 = __shfl_sync(0xffffffffu, wd, (lane & 3) * 2 + 8);
        if (lane < 4) st_pkt(&p.s->mod2[bid * 4 + lane], w0, w1, tag, 0);
      }
      const int isv = warp - 10;
      if (bid < 112) {
        const int kk = lane >> 1;
        const uint4* mp = &p.s->mod2[(isv ? 1 : 2) * 128 + ((kk & 7) >> 1)];
#pragma unroll
        for (int k = 0; k < 8; k++) a[k] = 0.f;
#pragma unroll 1
        for (int g = 0; g < 32; g++) {
          const uint4 w = ldg128(p.w1 + (size_t)(g * 16 + kk) * FF + bid * 16 + (lane & 1) * 8);
          uint32_t m[4];
          ld_mod(mp + g * 4, tag, m);
          const uint32_t mw = (kk & 8) ? m[1] : m[0];
          const float s = (kk & 1) ? bf_hi(mw) : bf_lo(mw);
          a[0] = fmaf(s, bf_lo(w.x), a[0]); a[1] = fmaf(s, bf_hi(w.x), a[1]);
          a[2] = fmaf(s, bf_lo(w.y), a[2]); a[3] = fmaf(s, bf_hi(w.y), a[3]);
          a[4] = fmaf(s, bf_lo(w.z), a[4]); a[5] = fmaf(s, bf_hi(w.z), a[5]);
          a[6] = fmaf(s, bf_lo(w.w), a[6]); a[7] = fmaf(s, bf_hi(w.w), a[7]);
        }
#pragma unroll
        for (int k = 0; k < 4; k++) {
          float send = h16 ? a[k] : a[k + 4], keep = h16 ? a[k + 4] : a[k];
          a[k] = keep + __shfl_xor_sync(0xffffffffu, send, 16);
        }
#pragma unroll
        for (int o = 8; o > 1; o >>= 1) {
#pragma unroll
          for (int k = 0; k < 4; k++) a[k] += __shfl_xor_sync(0xffffffffu, a[k], o);
        }
        const float sc = isv ? 0.5f : 1.f;
        if ((lane & 14) == 0)
          st_pkt(&p.s->uv[isv * 448 + bid * 4 + (lane & 1) * 2 + (lane >> 4)],
                 (__float_as_uint(a[0] * sc) & ~1u) | (tag & 1u), __float_as_uint(a[1] * sc), __float_as_uint(a[2] * sc),
                 __float_as_uint(a[3] * sc));
      }
#pragma unroll 1
      for (int i = lane; i < 56; i += 32) {
        uint32_t m[4];
        int spins = 0;
        do { ld_pkt(&p.s->uv[isv * 448 + j * 56 + i], m); } while (((m[0] ^ tag) & 1u) && ++spins < SPIN_LIMIT);
        const uint32_t ad = sb + SM_TAB + i * 32 + isv * 8;
        asm volatile("st.shared.v2.b32 [%0], {%1,%2};" ::"r"(ad), "r"(m[0]), "r"(m[1]) : "memory");
        asm volatile("st.shared.v2.b32 [%0], {%1,%2};" ::"r"(ad + 16), "r"(m[2]), "r"(m[3]) : "memory");
      }
      __syncwarp();
      if (lane == 0) mbar_arrive(bars + 72);
    } else {
      bar_sync(6, 352);
      if (lane < 8) l2_prefetch((const char*)p.wo + (size_t)bid * 32768 + lane * 4096, 4096);
      else if (lane < 12) l2_prefetch((const char*)p.w1 + (size_t)bid * 14336 + (lane - 8) * 3584, 3584);
      else if (lane < 16) l2_prefetch((const char*)p.w2 + (size_t)bid * 14336 + (lane - 12) * 3584, 3584);
    }
  } else {
    const int wg = warp >> 2;
    const int q = lane & 3, gq = lane >> 2;
    const Ring ring{(sb + SM_RING) >> 4, bars};
    const uint32_t xoff = (uint32_t)(rt * 128 + 16 * j + warp) * 256 + gq * 8 + q;
    const uint32_t ooff = ((uint32_t)(rt * 8 + j) * 32 + gq) * 32 + warp * 4 + q;
    const uint32_t goff = (uint32_t)(rt * 8 + warp) * 1024 + lane;

    {
      const uint32_t* xo = (const uint32_t*)p.x + xoff;
      uint32_t xr[4][4];
      CK_(d0);
#pragma unroll
      for (int c = 0; c < 4; c++) {
        xr[c][0] = ldg32(xo + c * 64);
        xr[c][1] = ldg32(xo + c * 64 + 8 * 256);
        xr[c][2] = ldg32(xo + c * 64 + 4);
        xr[c][3] = ldg32(xo + c * 64 + 4 + 8 * 256);
      }
      CK_(d1);
      fence_regs(xr);
      CK_(d2);
      float s0 = 0.f, s1 = 0.f, v0 = 0.f, v1 = 0.f;
#pragma unroll
      for (int c = 0; c < 4; c++) {
#pragma unroll
        for (int e = 0; e < 4; e++) {
          const float a = bf_lo(xr[c][e]), b = bf_hi(xr[c][e]);
          if (e & 1) { s1 += a + b; v1 = fmaf(a, a, fmaf(b, b, v1)); }
          else { s0 += a + b; v0 = fmaf(a, a, fmaf(b, b, v0)); }
        }
      }
#pragma unroll
      for (int o = 16; o > 0; o >>= 1) {
        s0 += __shfl_xor_sync(0xffffffffu, s0, o);
        s1 += __shfl_xor_sync(0xffffffffu, s1, o);
        v0 += __shfl_xor_sync(0xffffffffu, v0, o);
        v1 += __shfl_xor_sync(0xffffffffu, v1, o);
      }
      const float m0 = s0 * (1.f / 512.f), m1 = s1 * (1.f / 512.f);
      const float r0 = rsqrtf(fmaxf(fmaf(-m0, m0, v0 * (1.f / 512.f)), 0.f) + 1e-5f);
      const float r1 = rsqrtf(fmaxf(fmaf(-m1, m1, v1 * (1.f / 512.f)), 0.f) + 1e-5f);
#pragma unroll
      for (int c = 0; c < 4; c++) {
        st_pkt(p.s->G + ooff + c * 256,
               pack_tag<1>((bf_lo(xr[c][0]) - m0) * r0, (bf_hi(xr[c][0]) - m0) * r0),
               pack_bf16((bf_lo(xr[c][1]) - m1) * r1, (bf_hi(xr[c][1]) - m1) * r1),
               pack_bf16((bf_lo(xr[c][2]) - m0) * r0, (bf_hi(xr[c][2]) - m0) * r0),
               pack_bf16((bf_lo(xr[c][3]) - m1) * r1, (bf_hi(xr[c][3]) - m1) * r1));
      }
      CK_(d3);
      CKS(16, d0); CKS(17, d1); CKS(18, d2); CKS(19, d3);

    }
    asm volatile("setmaxnreg.inc.sync.aligned.u32 232;");
    uint32_t qf[8][4];
    {
      uint32_t h[32][4];
      float acc[64];
      const uint4* Gin = p.s->G + goff;
      __nanosleep(G_DELAY);
      issue_pkts<1, 8>(Gin, 32, h);
      verify8_tag1<512>(Gin, h);
      issue_pkts<1, 8>(Gin + 256, 32, h + 8);
      TS(1);
      bar_sync(1, 384);
#pragma unroll
      for (int c = 0; c < 4; c++) {
        if (c > 0) verify8_tag1<512>(Gin + c * 256, h + c * 8);
        if (c > 0 && c < 3) issue_pkts<1, 8>(Gin + (c + 1) * 256, 32, h + (c + 1) * 8);
#pragma unroll
        for (int i = 0; i < 8; i++) {
          uint32_t m[4];
          lds128(sb + SM_TAB + (uint32_t)((c * 8 + i) * 4 + q) * 16, m);
          uint32_t* hh = h[c * 8 + i];
          hh[0] = hfma2_bf16(hh[0], m[0], m[2]);
          hh[1] = hfma2_bf16(hh[1], m[0], m[2]);
          hh[2] = hfma2_bf16(hh[2], m[1], m[3]);
          hh[3] = hfma2_bf16(hh[3], m[1], m[3]);
        }
        fence_frags<8>(h + c * 8);
        const uint32_t b = ring.wait_full(c, 0);
        if (c > 0) { wg_wait<0>(); ring.release(c - 1); }
        if (c == 0) TS(2);
        wg_fence();
        static_for<0, 8>([&](auto K) { wgmma_rs_n128_tb1<LB_MN128 + K * 128, HI128>(acc, h[c * 8 + K], b, (c | K) != 0); });
        wg_commit();
      }
      bar_arrive(6, 352);
#pragma unroll 1
      for (int ps = 1; ps < 4; ps++) {
        wg_wait<0>();
        ring.release(3);
        fence_regs(acc);
#pragma unroll
        for (int i = 0; i < 8; i++) {
          uint32_t o[4];
          pack8(o, acc + 8 * i);
          sts128(sb + SM_PARK + (ps - 1) * SLOT + i * 4096 + tid * 16, o[0], o[1], o[2], o[3]);
        }
#pragma unroll
        for (int c = 0; c < 4; c++) {
          const uint32_t b = ring.wait_full(c, ps & 1);
          if (c > 0) { wg_wait<0>(); ring.release(c - 1); }
          wg_fence();
          static_for<0, 8>([&](auto K) { wgmma_rs_n128_tb1<LB_MN128 + K * 128, HI128>(acc, h[c * 8 + K], b, (c | K) != 0); });
          wg_commit();
        }
      }
      wg_wait<0>();
      ring.release(3);
      fence_regs(acc);
#pragma unroll
      for (int i = 0; i < 8; i++) pack8(qf[i], acc + 8 * i);
    }
    fence_regs(qf);
    TS(3);

    float S[64];
    {
      float O[64];
      uint32_t P[8][4];
      const float cs = 0.08838834764831845f * 1.4426950408889634f;
      const int TAU = 0x41800000;
      float m0, m1, l0, l1;

      auto float_block_max = [&]() {
        float b0 = fmaxf(S[0], S[1]), b1 = fmaxf(S[2], S[3]);
#pragma unroll
        for (int i = 1; i < 16; i++) {
          b0 = fmaxf(b0, fmaxf(S[4 * i], S[4 * i + 1]));
          b1 = fmaxf(b1, fmaxf(S[4 * i + 2], S[4 * i + 3]));
        }
        b0 = fmaxf(b0, __shfl_xor_sync(0xffffffffu, b0, 1)); b1 = fmaxf(b1, __shfl_xor_sync(0xffffffffu, b1, 1));
        b0 = fmaxf(b0, __shfl_xor_sync(0xffffffffu, b0, 2)); b1 = fmaxf(b1, __shfl_xor_sync(0xffffffffu, b1, 2));
        m0 = b0 * cs; m1 = b1 * cs;
      };
      auto first_block_max = [&]() {
        int a0 = max(__float_as_int(S[0]), __float_as_int(S[1]));
        int a1 = max(__float_as_int(S[2]), __float_as_int(S[3]));
#pragma unroll
        for (int i = 1; i < 16; i++) {
          a0 = __vimax3_s32(a0, __float_as_int(S[4 * i]), __float_as_int(S[4 * i + 1]));
          a1 = __vimax3_s32(a1, __float_as_int(S[4 * i + 2]), __float_as_int(S[4 * i + 3]));
        }
        a0 = max(a0, __shfl_xor_sync(0xffffffffu, a0, 1)); a1 = max(a1, __shfl_xor_sync(0xffffffffu, a1, 1));
        a0 = max(a0, __shfl_xor_sync(0xffffffffu, a0, 2)); a1 = max(a1, __shfl_xor_sync(0xffffffffu, a1, 2));
        m0 = __int_as_float(a0) * cs; m1 = __int_as_float(a1) * cs;
        if (__any_sync(0xffffffffu, (a0 | a1) < 0)) float_block_max();
      };
      auto scale_sub = [&]() {
#pragma unroll
        for (int i = 0; i < 16; i++) {
          S[4 * i] = fmaf(S[4 * i], cs, -m0); S[4 * i + 1] = fmaf(S[4 * i + 1], cs, -m0);
          S[4 * i + 2] = fmaf(S[4 * i + 2], cs, -m1); S[4 * i + 3] = fmaf(S[4 * i + 3], cs, -m1);
        }
      };
      auto exps = [&](int i0, int i1) {
#pragma unroll
        for (int i = i0; i < i1; i++) {
          S[4 * i] = ex2(S[4 * i]); S[4 * i + 1] = ex2(S[4 * i + 1]);
          S[4 * i + 2] = ex2(S[4 * i + 2]); S[4 * i + 3] = ex2(S[4 * i + 3]);
          l0 += S[4 * i]; l1 += S[4 * i + 2]; l0 += S[4 * i + 1]; l1 += S[4 * i + 3];
        }
      };
      {
        const uint32_t b = ring.wait_full(0, 0);
        wg_fence();
        static_for<0, 8>([&](auto K) { wgmma_rs_n128_tb0<LB_K128 + (K >> 2) * 1024 + (K & 3) * 2, HI128>(S, qf[K], b, K != 0); });
        wg_commit();
        wg_wait<0>();
        fence_regs(S);
        ring.release(0);
        float_block_max();
        scale_sub();
        l0 = 0.f; l1 = 0.f;
        exps(0, 16);
#pragma unroll
        for (int i = 0; i < 8; i++) pack8(P[i], S + 8 * i);
      }
      fence_regs(P);
      if (wg == 1) bar_arrive(2, 256);
#pragma unroll 1
      for (int n = 1; n < 16; n++) {
        const uint32_t tk = 2 * n - 1, tv = 2 * n;
        const bool newhead = (n & 3) == 0;
        const uint32_t bk = ring.wait_full(tk & 3, (tk >> 2) & 1);
        const uint32_t bv = ring.wait_full(tv & 3, (tv >> 2) & 1);
        bar_sync(2 + wg, 256);
        wg_fence();
        static_for<0, 8>([&](auto K) { wgmma_rs_n128_tb0<LB_K128 + (K >> 2) * 1024 + (K & 3) * 2, HI128>(S, qf[K], bk, K != 0); });
        wg_commit();
        static_for<0, 8>([&](auto K) { wgmma_rs_n128_tb1<LB_MN128 + K * 128, HI128>(O, P[K], bv, K != 0 || (n & 3) != 1); });
        wg_commit();
        bar_arrive(2 + (wg ^ 1), 256);
        wg_wait<1>();
        fence_regs(S);
        ring.release(tk & 3);
        if ((n & 3) == 3 && n != 15) {
          fence_regs(qf);
#pragma unroll
          for (int i = 0; i < 8; i++) lds128(sb + SM_PARK + (n >> 2) * SLOT + i * 4096 + tid * 16, qf[i]);
        }
        float f0 = 1.f, f1 = 1.f;
        bool resc = newhead;
        if (newhead) {
          l0 += __shfl_xor_sync(0xffffffffu, l0, 1); l1 += __shfl_xor_sync(0xffffffffu, l1, 1);
          l0 += __shfl_xor_sync(0xffffffffu, l0, 2); l1 += __shfl_xor_sync(0xffffffffu, l1, 2);
          f0 = rcp_hw(l0); f1 = rcp_hw(l1);
          l0 = 0.f; l1 = 0.f;
          first_block_max();
          scale_sub();
        } else {
          scale_sub();
          int a0 = __vimax3_s32(__float_as_int(S[0]), __float_as_int(S[1]), __float_as_int(S[1]));
          int a1 = __vimax3_s32(__float_as_int(S[2]), __float_as_int(S[3]), __float_as_int(S[3]));
#pragma unroll
          for (int i = 1; i < 16; i++) {
            a0 = __vimax3_s32(a0, __float_as_int(S[4 * i]), __float_as_int(S[4 * i + 1]));
            a1 = __vimax3_s32(a1, __float_as_int(S[4 * i + 2]), __float_as_int(S[4 * i + 3]));
          }
          if (__any_sync(0xffffffffu, max(a0, a1) > TAU)) {
            a0 = max(a0, 0); a1 = max(a1, 0);
            a0 = max(a0, __shfl_xor_sync(0xffffffffu, a0, 1)); a1 = max(a1, __shfl_xor_sync(0xffffffffu, a1, 1));
            a0 = max(a0, __shfl_xor_sync(0xffffffffu, a0, 2)); a1 = max(a1, __shfl_xor_sync(0xffffffffu, a1, 2));
            const float d0 = __int_as_float(a0), d1 = __int_as_float(a1);
#pragma unroll
            for (int i = 0; i < 16; i++) { S[4 * i] -= d0; S[4 * i + 1] -= d0; S[4 * i + 2] -= d1; S[4 * i + 3] -= d1; }
            m0 += d0; m1 += d1;
            f0 = ex2(-d0); f1 = ex2(-d1);
            l0 *= f0; l1 *= f1;
            resc = true;
          }
        }
        exps(0, 4);
        wg_wait<0>();
        fence_regs(O);
        fence_regs(P);
        ring.release(tv & 3);
        if (resc) {
#pragma unroll
          for (int i = 0; i < 16; i++) {
            O[4 * i] *= f0; O[4 * i + 1] *= f0; O[4 * i + 2] *= f1; O[4 * i + 3] *= f1;
          }
          if (newhead) {
#pragma unroll
            for (int i = 0; i < 8; i++) {
              uint32_t o[4];
              pack8(o, O + 8 * i);
              sts128(sb + SM_PARK + ((n >> 2) - 1) * SLOT + i * 4096 + tid * 16, o[0], o[1], o[2], o[3]);
            }
          }
        }
        exps(4, 16);
#pragma unroll
        for (int i = 0; i < 8; i++) pack8(P[i], S + 8 * i);
        fence_regs(P);
        fence_regs(O);
      }
      {
        const uint32_t bv = ring.wait_full(3, 1);
        if (wg == 0) bar_sync(2, 256);
        wg_fence();
        static_for<0, 8>([&](auto K) { wgmma_rs_n128_tb1<LB_MN128 + K * 128, HI128>(O, P[K], bv, 1); });
        wg_commit();
        l0 += __shfl_xor_sync(0xffffffffu, l0, 1); l1 += __shfl_xor_sync(0xffffffffu, l1, 1);
        l0 += __shfl_xor_sync(0xffffffffu, l0, 2); l1 += __shfl_xor_sync(0xffffffffu, l1, 2);
        const float f0 = rcp_hw(l0), f1 = rcp_hw(l1);
        wg_wait<0>();
        fence_regs(O);
#pragma unroll
        for (int i = 0; i < 8; i++) {
          qf[i][0] = pack_bf16(O[8 * i] * f0, O[8 * i + 1] * f0); qf[i][1] = pack_bf16(O[8 * i + 2] * f1, O[8 * i + 3] * f1);
          qf[i][2] = pack_bf16(O[8 * i + 4] * f0, O[8 * i + 5] * f0); qf[i][3] = pack_bf16(O[8 * i + 6] * f1, O[8 * i + 7] * f1);
        }
      }
    }
    fence_regs(qf);
    TS(4);

    uint4* const Pout = p.s->P + ((size_t)(rt * 8 + warp) * 8 + j) * 1024;
    const uint32_t stage = sb + SM_RING + 3 * SLOT + warp * 4096;
    const uint32_t stoff = gq * 512 + (gq & 1) * 64 + q * 16;
    const uint32_t tag = *(volatile uint32_t*)(smem_raw + SM_BAR + 64);
    const uint4* const Pown = p.s->P + (size_t)(rt * 8 + j) * 8192 + warp * 32 + lane;
    const int go = gq ^ (warp & 1);
    const uint32_t xoff2 = (uint32_t)(rt * 128 + 16 * j + warp) * 256 + go * 8 + q;
    const uint32_t ooff2 = ((uint32_t)(rt * 8 + j) * 32 + go) * 32 + warp * 4 + q;
    const uint4* const mod2p = p.s->mod2 + go * 4 + q;

    auto store_partial = [&](auto TAGC, uint32_t stg, int c) {
#pragma unroll
      for (int i = 0; i < 8; i++)
        sts128(stg + (stoff ^ (i * 64)), pack_tag<TAGC>(S[8 * i], S[8 * i + 1]), pack_bf16(S[8 * i + 2], S[8 * i + 3]),
               pack_bf16(S[8 * i + 4], S[8 * i + 5]), pack_bf16(S[8 * i + 6], S[8 * i + 7]));
      warp_bulk_store(Pout + c * 256, stg, 4096);
    };
    uint32_t r[8][4], xr[4], ga[4], g2[4];
    float s0 = 0.f, s1 = 0.f, v0 = 0.f, v1 = 0.f;
    auto red1_issue = [&](int c) {
      issue_pkts<1, 8>(Pown + c * 256, 1024, r);
      const uint32_t* xo = (const uint32_t*)p.x + xoff2 + c * 64;
      xr[0] = ldg32(xo); xr[1] = ldg32(xo + 8 * 256); xr[2] = ldg32(xo + 4); xr[3] = ldg32(xo + 4 + 8 * 256);
      ld_pkt(mod2p + c * 32, ga);
      ld_pkt(mod2p + 256 + c * 32, g2);
    };
    auto red1_process = [&](int c, float (&x2)[8]) {
      if (ga[2] != tag) ld_mod(mod2p + c * 32, tag, ga);
      if (g2[2] != tag) ld_mod(mod2p + 256 + c * 32, tag, g2);
      verify8_tag1<16384>(Pown + c * 256, r);
      float hv[8];
#pragma unroll
      for (int e = 0; e < 4; e++) {
        float y0 = bf_lo(r[0][e]), y1 = bf_hi(r[0][e]);
#pragma unroll
        for (int s = 1; s < 8; s++) { y0 += bf_lo(r[s][e]); y1 += bf_hi(r[s][e]); }
        const float a = fmaf(bf_lo(ga[e >> 1]), y0, bf_lo(xr[e])), b = fmaf(bf_hi(ga[e >> 1]), y1, bf_hi(xr[e]));
        x2[2 * e] = a; x2[2 * e + 1] = b;
        hv[2 * e] = a * bf_lo(g2[e >> 1]); hv[2 * e + 1] = b * bf_hi(g2[e >> 1]);
        if (e & 1) { s1 += a + b; v1 = fmaf(a, a, fmaf(b, b, v1)); }
        else { s0 += a + b; v0 = fmaf(a, a, fmaf(b, b, v0)); }
      }
      st_pkt(p.s->G + ooff2 + c * 256, pack_tag<0>(hv[0], hv[1]), pack_bf16(hv[2], hv[3]), pack_bf16(hv[4], hv[5]),
             pack_bf16(hv[6], hv[7]));
    };
    auto park_x2 = [&](int c, const float (&x2)[8]) {
      sts128(sb + SM_PARK + (2 * c) * 4096 + tid * 16, __float_as_uint(x2[0]), __float_as_uint(x2[1]),
             __float_as_uint(x2[2]), __float_as_uint(x2[3]));
      sts128(sb + SM_PARK + (2 * c + 1) * 4096 + tid * 16, __float_as_uint(x2[4]), __float_as_uint(x2[5]),
             __float_as_uint(x2[6]), __float_as_uint(x2[7]));
    };

    const uint4* const Gin = p.s->G + goff;
    uint32_t fa[2][4][4];
    uint32_t rs = 0, rp = 0, b = ring.wait_full(0, 0);
    auto next_tile = [&]() {
      const uint32_t cur = rs;
      if (++rs == 3) { rs = 0; rp ^= 1; }
      b = ring.wait_full(rs, rp);
      wg_wait<0>();
      ring.release(cur);
    };
    {
      uint32_t a[8][4];
      float keep[8];
#pragma unroll
      for (int i = 0; i < 8; i++) lds128(sb + SM_PARK + i * 4096 + tid * 16, a[i]);
#pragma unroll 1
      for (int c = 0; c < 4; c++) {
        static_for<0, 4>([&](auto HH) {
          constexpr int hh = HH;
          wg_fence();
          static_for<0, 8>([&](auto K) {
            wgmma_rs_n128_tb1<LB_MN128 + K * 128, HI128>(S, hh == 3 ? qf[K] : a[K], b, (hh | K) != 0);
          });
          wg_commit();
          if constexpr (hh == 0) {
            if (c > 1) {
              if (c == 3) park_x2(0, keep);
              red1_process(c - 2, keep);
              if (c == 3) park_x2(1, keep);
            }
          }
          if constexpr (hh == 3) {
            if (c == 3) {
              issue_pkts<0, 4>(Gin, 32, a);
            } else {
              if (c > 0) red1_issue(c - 1);
#pragma unroll
              for (int i = 0; i < 8; i++) lds128(sb + SM_PARK + i * 4096 + tid * 16, a[i]);
            }
            warp_bulk_wait_read<0>();
          }
          next_tile();
          if constexpr (hh < 2) {
            fence_regs(a);
#pragma unroll
            for (int i = 0; i < 8; i++) lds128(sb + SM_PARK + (hh + 1) * SLOT + i * 4096 + tid * 16, a[i]);
          }
        });
        fence_regs(S);
        store_partial(IC<1>{}, stage, c);
      }
#pragma unroll
      for (int i = 0; i < 4; i++) { fa[0][i][0] = a[i][0]; fa[0][i][1] = a[i][1]; fa[0][i][2] = a[i][2]; fa[0][i][3] = a[i][3]; }
    }
    TS(5);

    uint32_t H[14][4];
    {
      float acc[112];
      uint32_t st[4];
      const uint4* const statp = &p.s->stat[((rt * 8 + warp) * 8 + gq) * 2];
#pragma unroll 1
      for (int it = 0; it < 4; it++) {
        verify4_tag0<512>(Gin + it * 256, fa[0]);
        if (it == 0) TS(6);
        if (it == 3) TS(7);
        wg_fence();
        static_for<0, 4>([&](auto K) { wgmma_rs_n224_tb1<LB_W1 + K * 64, HI64>(acc, fa[0][K], b, (it | K) != 0); });
        wg_commit();
        issue_pkts<0, 4>(Gin + it * 256 + 128, 32, fa[1]);
        next_tile();
        verify4_tag0<512>(Gin + it * 256 + 128, fa[1]);
        wg_fence();
        static_for<0, 4>([&](auto K) { wgmma_rs_n224_tb1<LB_W1 + K * 64, HI64>(acc, fa[1][K], b, 1); });
        wg_commit();
        if (it < 2) {
          float x2[8];
          red1_issue(2 + it);
          red1_process(2 + it, x2);
          park_x2(2 + it, x2);
          if (it == 1) {
#pragma unroll
            for (int o = 16; o > 0; o >>= 1) {
              s0 += __shfl_xor_sync(0xffffffffu, s0, o);
              s1 += __shfl_xor_sync(0xffffffffu, s1, o);
              v0 += __shfl_xor_sync(0xffffffffu, v0, o);
              v1 += __shfl_xor_sync(0xffffffffu, v1, o);
            }
            const float m0 = s0 * (1.f / 512.f), m1 = s1 * (1.f / 512.f);
            const float r0 = 0.5f * rsqrtf(fmaxf(fmaf(-m0, m0, v0 * (1.f / 512.f)), 0.f) + 1e-5f);
            const float r1 = 0.5f * rsqrtf(fmaxf(fmaf(-m1, m1, v1 * (1.f / 512.f)), 0.f) + 1e-5f);
            if (lane < 2)
              st_pkt(&p.s->stat[((rt * 8 + j) * 8 + warp) * 2 + lane], (__float_as_uint(r0) & ~1u) | (tag & 1u),
                     __float_as_uint(-m0 * r0), __float_as_uint(r1), __float_as_uint(-m1 * r1));
          }
        }
        if (it < 3) issue_pkts<0, 4>(Gin + it * 256 + 256, 32, fa[0]);
        else ld_pkt(statp, fa[0][0]);
        next_tile();
      }
      st[0] = fa[0][0][0]; st[1] = fa[0][0][1]; st[2] = fa[0][0][2]; st[3] = fa[0][0][3];
      fence_regs(acc);
      TS(9);
      mbar_wait(bars + 72, 0);
      {
        int spins = 0;
        while (((st[0] ^ tag) & 1u) && ++spins < SPIN_LIMIT) ld_pkt(statp, st);
      }
      const float ra0 = __uint_as_float(st[0]), rb0 = __uint_as_float(st[1]), ra1 = __uint_as_float(st[2]),
                  rb1 = __uint_as_float(st[3]);
#pragma unroll
      for (int i = 0; i < 28; i++) {
        uint32_t m[4];
        lds128(sb + SM_TAB + (i * 4 + q) * 16, m);
        const float u0 = __uint_as_float(m[0]), u1 = __uint_as_float(m[1]), w0 = __uint_as_float(m[2]), w1 = __uint_as_float(m[3]);
        const float z0 = fmaf(acc[4 * i], ra0, fmaf(u0, rb0, w0)), z1 = fmaf(acc[4 * i + 1], ra0, fmaf(u1, rb0, w1));
        const float z2 = fmaf(acc[4 * i + 2], ra1, fmaf(u0, rb1, w0)), z3 = fmaf(acc[4 * i + 3], ra1, fmaf(u1, rb1, w1));
        H[i >> 1][(i & 1) * 2] = pack_bf16(fmaf(z0, tanh_hw(z0), z0), fmaf(z1, tanh_hw(z1), z1));
        H[i >> 1][(i & 1) * 2 + 1] = pack_bf16(fmaf(z2, tanh_hw(z2), z2), fmaf(z3, tanh_hw(z3), z3));
      }
    }
    fence_regs(H);
    TS(10);
#pragma unroll 1
    for (int c = 0; c < 4; c++) {
      wg_fence();
      static_for<0, 7>([&](auto K) { wgmma_rs_n128_tb1<LB_W2 + K * 128, HI128>(S, H[K], b, K != 0); });
      wg_commit();
      if (c == 3) {
        issue_pkts<0, 8>(Pown, 1024, r);
        ld_pkt(mod2p + 384, ga);
      }
      next_tile();
      wg_fence();
      static_for<0, 7>([&](auto K) { wgmma_rs_n128_tb1<LB_W2 + K * 128, HI128>(S, H[7 + K], b, 1); });
      wg_commit();
      warp_bulk_wait_read<2>();
      if (c < 3) next_tile();
      wg_wait<0>();
      fence_regs(S);
      store_partial(IC<0>{}, c == 2 ? stage : sb + SM_PARK + (c == 1 ? 2 : 1) * SLOT + warp * 4096, c);
    }
    TS(11);
#pragma unroll 1
    for (int c = 0; c < 4; c++) {
      uint32_t* const oo = (uint32_t*)p.out + xoff2 + c * 64;
      uint32_t xa[2][4];
      if (c > 0) {
        issue_pkts<0, 8>(Pown + c * 256, 1024, r);
        ld_pkt(mod2p + 384 + c * 32, ga);
      }
      lds128(sb + SM_PARK + (2 * c) * 4096 + tid * 16, xa[0]);
      lds128(sb + SM_PARK + (2 * c + 1) * 4096 + tid * 16, xa[1]);
      if (ga[2] != tag) ld_mod(mod2p + 384 + c * 32, tag, ga);
      verify8_tag0<16384>(Pown + c * 256, r);
#pragma unroll
      for (int e = 0; e < 4; e++) {
        float y0 = bf_lo(r[0][e]), y1 = bf_hi(r[0][e]);
#pragma unroll
        for (int s = 1; s < 8; s++) { y0 += bf_lo(r[s][e]); y1 += bf_hi(r[s][e]); }
        oo[(e >> 1) * 4 + (e & 1) * 8 * 256] =
            pack_bf16(fmaf(bf_lo(ga[e >> 1]), y0, __uint_as_float(xa[e >> 1][(e & 1) * 2])),
                      fmaf(bf_hi(ga[e >> 1]), y1, __uint_as_float(xa[e >> 1][(e & 1) * 2 + 1])));
      }
      if (c == 1) TS(13);
      if (c == 2) TS(14);
    }
    warp_bulk_wait_read<0>();
    TS(12);
    if (bid == 0 && tid == 0) asm volatile("st.relaxed.gpu.global.u32 [%0], %1;" ::"l"(&p.s->epoch), "r"(tag) : "memory");
  }
}

typedef CUresult (*EncodeFn)(CUtensorMap*, CUtensorMapDataType, cuuint32_t, void*, const cuuint64_t*, const cuuint64_t*,
                             const cuuint32_t*, const cuuint32_t*, CUtensorMapInterleave, CUtensorMapSwizzle,
                             CUtensorMapL2promotion, CUtensorMapFloatOOBfill);

static void make_map(EncodeFn fn, CUtensorMap* tm, const void* ptr, int inner, int rows, int cols, int box_rows, int box_outer,
                     CUtensorMapSwizzle swz) {
  cuuint64_t gd[3] = {(cuuint64_t)inner, (cuuint64_t)rows, (cuuint64_t)(cols / inner)};
  cuuint64_t gs[2] = {(cuuint64_t)cols * 2, (cuuint64_t)inner * 2};
  cuuint32_t bx[3] = {(cuuint32_t)inner, (cuuint32_t)box_rows, (cuuint32_t)box_outer};
  cuuint32_t es[3] = {1, 1, 1};
  fn(tm, CU_TENSOR_MAP_DATA_TYPE_BFLOAT16, 3, const_cast<void*>(ptr), gd, gs, bx, es, CU_TENSOR_MAP_INTERLEAVE_NONE, swz,
     CU_TENSOR_MAP_L2_PROMOTION_L2_128B, CU_TENSOR_MAP_FLOAT_OOB_FILL_NONE);
}

extern "C" void kernel_launch(void* const* d_in, const int* in_sizes, int n_in, void* d_out, int out_size) {
  (void)in_sizes; (void)n_in; (void)out_size;
  void* fnp = nullptr;
  cudaDriverEntryPointQueryResult qr;
  cudaGetDriverEntryPoint("cuTensorMapEncodeTiled", &fnp, cudaEnableDefault, &qr);
  EncodeFn fn = (EncodeFn)fnp;
  CUtensorMap tmWq, tmK, tmV, tmWo, tmW1, tmW2, tmWm;
  make_map(fn, &tmWq, d_in[3], 64, 512, 4096, 128, 2, CU_TENSOR_MAP_SWIZZLE_128B);
  make_map(fn, &tmK, d_in[1], 64, 8 * SK, 128, 128, 2, CU_TENSOR_MAP_SWIZZLE_128B);
  make_map(fn, &tmV, d_in[2], 64, 8 * SK, 128, 128, 2, CU_TENSOR_MAP_SWIZZLE_128B);
  make_map(fn, &tmWo, d_in[4], 64, 4096, 512, 128, 2, CU_TENSOR_MAP_SWIZZLE_128B);
  make_map(fn, &tmW1, d_in[6], 32, 512, FF, 64, 7, CU_TENSOR_MAP_SWIZZLE_64B);
  make_map(fn, &tmW2, d_in[7], 64, FF, 512, 112, 2, CU_TENSOR_MAP_SWIZZLE_128B);
  make_map(fn, &tmWm, d_in[9], 8, 512, 3072, 256, 1, CU_TENSOR_MAP_SWIZZLE_NONE);
  Params p;
  p.x = (const __nv_bfloat16*)d_in[0];
  p.c = (const __nv_bfloat16*)d_in[8];
  p.wmod = (const __nv_bfloat16*)d_in[9];
  p.wo = (const __nv_bfloat16*)d_in[4];
  p.w1 = (const __nv_bfloat16*)d_in[6];
  p.w2 = (const __nv_bfloat16*)d_in[7];
  p.out = (__nv_bfloat16*)d_out;
  cudaGetSymbolAddress((void**)&p.s, g_scratch);
  cudaFuncSetAttribute(adaln_block_kernel, cudaFuncAttributeMaxDynamicSharedMemorySize, SM_TOTAL);
  adaln_block_kernel<<<128, 384, SM_TOTAL>>>(tmWq, tmK, tmV, tmWo, tmW1, tmW2, tmWm, p);
}
```

```cpp
#include <cuda_runtime.h>
#include <cuda_bf16.h>
#include <cuda.h>
#include <stdint.h>

template <int OFF, uint32_t HI>
__device__ __forceinline__ void wgmma_rs_n128_tb0(float (&d)[64], const uint32_t (&a)[4], uint32_t lo, int sd) {
  asm volatile("{\n.reg .pred p;\n.reg .b32 l;\n.reg .b64 db;\nsetp.ne.b32 p, %69, 0;\n"
    "add.u32 l, %68, %70;\nmov.b64 db, {l, %71};\n"
    "wgmma.mma_async.sync.aligned.m64n128k16.f32.bf16.bf16 "
    "{%0,%1,%2,%3,%4,%5,%6,%7,%8,%9,%10,%11,%12,%13,%14,%15,"
    "%16,%17,%18,%19,%20,%21,%22,%23,%24,%25,%26,%27,%28,%29,%30,%31,"
    "%32,%33,%34,%35,%36,%37,%38,%39,%40,%41,%42,%43,%44,%45,%46,%47,"
    "%48,%49,%50,%51,%52,%53,%54,%55,%56,%57,%58,%59,%60,%61,%62,%63}, "
    "{%64,%65,%66,%67}, db, p, 1, 1, 0;\n}\n"
    : "+f"(d[0]), "+f"(d[1]), "+f"(d[2]), "+f"(d[3]), "+f"(d[4]), "+f"(d[5]), "+f"(d[6]), "+f"(d[7]),
      "+f"(d[8]), "+f"(d[9]), "+f"(d[10]), "+f"(d[11]), "+f"(d[12]), "+f"(d[13]), "+f"(d[14]), "+f"(d[15]),
      "+f"(d[16]), "+f"(d[17]), "+f"(d[18]), "+f"(d[19]), "+f"(d[20]), "+f"(d[21]), "+f"(d[22]), "+f"(d[23]),
      "+f"(d[24]), "+f"(d[25]), "+f"(d[26]), "+f"(d[27]), "+f"(d[28]), "+f"(d[29]), "+f"(d[30]), "+f"(d[31]),
      "+f"(d[32]), "+f"(d[33]), "+f"(d[34]), "+f"(d[35]), "+f"(d[36]), "+f"(d[37]), "+f"(d[38]), "+f"(d[39]),
      "+f"(d[40]), "+f"(d[41]), "+f"(d[42]), "+f"(d[43]), "+f"(d[44]), "+f"(d[45]), "+f"(d[46]), "+f"(d[47]),
      "+f"(d[48]), "+f"(d[49]), "+f"(d[50]), "+f"(d[51]), "+f"(d[52]), "+f"(d[53]), "+f"(d[54]), "+f"(d[55]),
      "+f"(d[56]), "+f"(d[57]), "+f"(d[58]), "+f"(d[59]), "+f"(d[60]), "+f"(d[61]), "+f"(d[62]), "+f"(d[63])
    : "r"(a[0]), "r"(a[1]), "r"(a[2]), "r"(a[3]), "r"(lo), "r"(sd), "n"(OFF), "n"(HI));
}

template <int OFF, uint32_t HI>
__device__ __forceinline__ void wgmma_rs_n128_tb1(float (&d)[64], const uint32_t (&a)[4], uint32_t lo, int sd) {
  asm volatile("{\n.reg .pred p;\n.reg .b32 l;\n.reg .b64 db;\nsetp.ne.b32 p, %69, 0;\n"
    "add.u32 l, %68, %70;\nmov.b64 db, {l, %71};\n"
    "wgmma.mma_async.sync.aligned.m64n128k16.f32.bf16.bf16 "
    "{%0,%1,%2,%3,%4,%5,%6,%7,%8,%9,%10,%11,%12,%13,%14,%15,"
    "%16,%17,%18,%19,%20,%21,%22,%23,%24,%25,%26,%27,%28,%29,%30,%31,"
    "%32,%33,%34,%35,%36,%37,%38,%39,%40,%41,%42,%43,%44,%45,%46,%47,"
    "%48,%49,%50,%51,%52,%53,%54,%55,%56,%57,%58,%59,%60,%61,%62,%63}, "
    "{%64,%65,%66,%67}, db, p, 1, 1, 1;\n}\n"
    : "+f"(d[0]), "+f"(d[1]), "+f"(d[2]), "+f"(d[3]), "+f"(d[4]), "+f"(d[5]), "+f"(d[6]), "+f"(d[7]),
      "+f"(d[8]), "+f"(d[9]), "+f"(d[10]), "+f"(d[11]), "+f"(d[12]), "+f"(d[13]), "+f"(d[14]), "+f"(d[15]),
      "+f"(d[16]), "+f"(d[17]), "+f"(d[18]), "+f"(d[19]), "+f"(d[20]), "+f"(d[21]), "+f"(d[22]), "+f"(d[23]),
      "+f"(d[24]), "+f"(d[25]), "+f"(d[26]), "+f"(d[27]), "+f"(d[28]), "+f"(d[29]), "+f"(d[30]), "+f"(d[31]),
      "+f"(d[32]), "+f"(d[33]), "+f"(d[34]), "+f"(d[35]), "+f"(d[36]), "+f"(d[37]), "+f"(d[38]), "+f"(d[39]),
      "+f"(d[40]), "+f"(d[41]), "+f"(d[42]), "+f"(d[43]), "+f"(d[44]), "+f"(d[45]), "+f"(d[46]), "+f"(d[47]),
      "+f"(d[48]), "+f"(d[49]), "+f"(d[50]), "+f"(d[51]), "+f"(d[52]), "+f"(d[53]), "+f"(d[54]), "+f"(d[55]),
      "+f"(d[56]), "+f"(d[57]), "+f"(d[58]), "+f"(d[59]), "+f"(d[60]), "+f"(d[61]), "+f"(d[62]), "+f"(d[63])
    : "r"(a[0]), "r"(a[1]), "r"(a[2]), "r"(a[3]), "r"(lo), "r"(sd), "n"(OFF), "n"(HI));
}

template <int OFF, uint32_t HI>
__device__ __forceinline__ void wgmma_rs_n224_tb1(float (&d)[112], const uint32_t (&a)[4], uint32_t lo, int sd) {
  asm volatile("{\n.reg .pred p;\n.reg .b32 l;\n.reg .b64 db;\nsetp.ne.b32 p, %117, 0;\n"
    "add.u32 l, %116, %118;\nmov.b64 db, {l, %119};\n"
    "wgmma.mma_async.sync.aligned.m64n224k16.f32.bf16.bf16 "
    "{%0,%1,%2,%3,%4,%5,%6,%7,%8,%9,%10,%11,%12,%13,%14,%15,"
    "%16,%17,%18,%19,%20,%21,%22,%23,%24,%25,%26,%27,%28,%29,%30,%31,"
    "%32,%33,%34,%35,%36,%37,%38,%39,%40,%41,%42,%43,%44,%45,%46,%47,"
    "%48,%49,%50,%51,%52,%53,%54,%55,%56,%57,%58,%59,%60,%61,%62,%63,"
    "%64,%65,%66,%67,%68,%69,%70,%71,%72,%73,%74,%75,%76,%77,%78,%79,"
    "%80,%81,%82,%83,%84,%85,%86,%87,%88,%89,%90,%91,%92,%93,%94,%95,"
    "%96,%97,%98,%99,%100,%101,%102,%103,%104,%105,%106,%107,%108,%109,%110,%111}, "
    "{%112,%113,%114,%115}, db, p, 1, 1, 1;\n}\n"
    : "+f"(d[0]), "+f"(d[1]), "+f"(d[2]), "+f"(d[3]), "+f"(d[4]), "+f"(d[5]), "+f"(d[6]), "+f"(d[7]),
      "+f"(d[8]), "+f"(d[9]), "+f"(d[10]), "+f"(d[11]), "+f"(d[12]), "+f"(d[13]), "+f"(d[14]), "+f"(d[15]),
      "+f"(d[16]), "+f"(d[17]), "+f"(d[18]), "+f"(d[19]), "+f"(d[20]), "+f"(d[21]), "+f"(d[22]), "+f"(d[23]),
      "+f"(d[24]), "+f"(d[25]), "+f"(d[26]), "+f"(d[27]), "+f"(d[28]), "+f"(d[29]), "+f"(d[30]), "+f"(d[31]),
      "+f"(d[32]), "+f"(d[33]), "+f"(d[34]), "+f"(d[35]), "+f"(d[36]), "+f"(d[37]), "+f"(d[38]), "+f"(d[39]),
      "+f"(d[40]), "+f"(d[41]), "+f"(d[42]), "+f"(d[43]), "+f"(d[44]), "+f"(d[45]), "+f"(d[46]), "+f"(d[47]),
      "+f"(d[48]), "+f"(d[49]), "+f"(d[50]), "+f"(d[51]), "+f"(d[52]), "+f"(d[53]), "+f"(d[54]), "+f"(d[55]),
      "+f"(d[56]), "+f"(d[57]), "+f"(d[58]), "+f"(d[59]), "+f"(d[60]), "+f"(d[61]), "+f"(d[62]), "+f"(d[63]),
      "+f"(d[64]), "+f"(d[65]), "+f"(d[66]), "+f"(d[67]), "+f"(d[68]), "+f"(d[69]), "+f"(d[70]), "+f"(d[71]),
      "+f"(d[72]), "+f"(d[73]), "+f"(d[74]), "+f"(d[75]), "+f"(d[76]), "+f"(d[77]), "+f"(d[78]), "+f"(d[79]),
      "+f"(d[80]), "+f"(d[81]), "+f"(d[82]), "+f"(d[83]), "+f"(d[84]), "+f"(d[85]), "+f"(d[86]), "+f"(d[87]),
      "+f"(d[88]), "+f"(d[89]), "+f"(d[90]), "+f"(d[91]), "+f"(d[92]), "+f"(d[93]), "+f"(d[94]), "+f"(d[95]),
      "+f"(d[96]), "+f"(d[97]), "+f"(d[98]), "+f"(d[99]), "+f"(d[100]), "+f"(d[101]), "+f"(d[102]), "+f"(d[103]),
      "+f"(d[104]), "+f"(d[105]), "+f"(d[106]), "+f"(d[107]), "+f"(d[108]), "+f"(d[109]), "+f"(d[110]), "+f"(d[111])
    : "r"(a[0]), "r"(a[1]), "r"(a[2]), "r"(a[3]), "r"(lo), "r"(sd), "n"(OFF), "n"(HI));
}

template <int STR>
__device__ __forceinline__ void verify8_tag1(const uint4* p, uint32_t (*r)[4]) {
  asm volatile("{\n.reg .pred p, q;\n.reg .b32 a, n;\nmov.u32 n, 0;\n"
    "LAB_CHK:\n"
    "and.b32 a, %0, %4;\n"
    "and.b32 a, a, %8;\n"
    "and.b32 a, a, %12;\n"
    "and.b32 a, a, %16;\n"
    "and.b32 a, a, %20;\n"
    "and.b32 a, a, %24;\n"
    "and.b32 a, a, %28;\n"
    "and.b32 a, a, 1;\nsetp.eq.u32 p, a, 1;\nvote.sync.all.pred p, p, 0xffffffff;\n"
    "@p bra.uni LAB_OK;\n"
    "and.b32 a, %0, 1;\nsetp.ne.u32 q, a, 1;\n"
    "@q ld.relaxed.gpu.global.v4.b32 {%0,%1,%2,%3}, [%32+%33];\n"
    "and.b32 a, %4, 1;\nsetp.ne.u32 q, a, 1;\n"
    "@q ld.relaxed.gpu.global.v4.b32 {%4,%5,%6,%7}, [%32+%34];\n"
    "and.b32 a, %8, 1;\nsetp.ne.u32 q, a, 1;\n"
    "@q ld.relaxed.gpu.global.v4.b32 {%8,%9,%10,%11}, [%32+%35];\n"
    "and.b32 a, %12, 1;\nsetp.ne.u32 q, a, 1;\n"
    "@q ld.relaxed.gpu.global.v4.b32 {%12,%13,%14,%15}, [%32+%36];\n"
    "and.b32 a, %16, 1;\nsetp.ne.u32 q, a, 1;\n"
    "@q ld.relaxed.gpu.global.v4.b32 {%16,%17,%18,%19}, [%32+%37];\n"
    "and.b32 a, %20, 1;\nsetp.ne.u32 q, a, 1;\n"
    "@q ld.relaxed.gpu.global.v4.b32 {%20,%21,%22,%23}, [%32+%38];\n"
    "and.b32 a, %24, 1;\nsetp.ne.u32 q, a, 1;\n"
    "@q ld.relaxed.gpu.global.v4.b32 {%24,%25,%26,%27}, [%32+%39];\n"
    "and.b32 a, %28, 1;\nsetp.ne.u32 q, a, 1;\n"
    "@q ld.relaxed.gpu.global.v4.b32 {%28,%29,%30,%31}, [%32+%40];\n"
    "add.u32 n, n, 1;\nsetp.lt.u32 q, n, 262144;\n@q bra.uni LAB_CHK;\n"
    "LAB_OK:\n"
    "}\n"
    : "+r"(r[0][0]), "+r"(r[0][1]), "+r"(r[0][2]), "+r"(r[0][3]), "+r"(r[1][0]), "+r"(r[1][1]), "+r"(r[1][2]), "+r"(r[1][3]),
      "+r"(r[2][0]), "+r"(r[2][1]), "+r"(r[2][2]), "+r"(r[2][3]), "+r"(r[3][0]), "+r"(r[3][1]), "+r"(r[3][2]), "+r"(r[3][3]),
      "+r"(r[4][0]), "+r"(r[4][1]), "+r"(r[4][2]), "+r"(r[4][3]), "+r"(r[5][0]), "+r"(r[5][1]), "+r"(r[5][2]), "+r"(r[5][3]),
      "+r"(r[6][0]), "+r"(r[6][1]), "+r"(r[6][2]), "+r"(r[6][3]), "+r"(r[7][0]), "+r"(r[7][1]), "+r"(r[7][2]), "+r"(r[7][3])
    : "l"(p), "n"(0 * STR), "n"(1 * STR), "n"(2 * STR), "n"(3 * STR), "n"(4 * STR), "n"(5 * STR), "n"(6 * STR), "n"(7 * STR)
    : "memory");
}

template <int STR>
__device__ __forceinline__ void verify8_tag0(const uint4* p, uint32_t (*r)[4]) {
  asm volatile("{\n.reg .pred p, q;\n.reg .b32 a, n;\nmov.u32 n, 0;\n"
    "LAB_CHK:\n"
    "or.b32 a, %0, %4;\n"
    "or.b32 a, a, %8;\n"
    "or.b32 a, a, %12;\n"
    "or.b32 a, a, %16;\n"
    "or.b32 a, a, %20;\n"
    "or.b32 a, a, %24;\n"
    "or.b32 a, a, %28;\n"
    "and.b32 a, a, 1;\nsetp.eq.u32 p, a, 0;\nvote.sync.all.pred p, p, 0xffffffff;\n"
    "@p bra.uni LAB_OK;\n"
    "and.b32 a, %0, 1;\nsetp.ne.u32 q, a, 0;\n"
    "@q ld.relaxed.gpu.global.v4.b32 {%0,%1,%2,%3}, [%32+%33];\n"
    "and.b32 a, %4, 1;\nsetp.ne.u32 q, a, 0;\n"
    "@q ld.relaxed.gpu.global.v4.b32 {%4,%5,%6,%7}, [%32+%34];\n"
    "and.b32 a, %8, 1;\nsetp.ne.u32 q, a, 0;\n"
    "@q ld.relaxed.gpu.global.v4.b32 {%8,%9,%10,%11}, [%32+%35];\n"
    "and.b32 a, %12, 1;\nsetp.ne.u32 q, a, 0;\n"
    "@q ld.relaxed.gpu.global.v4.b32 {%12,%13,%14,%15}, [%32+%36];\n"
    "and.b32 a, %16, 1;\nsetp.ne.u32 q, a, 0;\n"
    "@q ld.relaxed.gpu.global.v4.b32 {%16,%17,%18,%19}, [%32+%37];\n"
    "and.b32 a, %20, 1;\nsetp.ne.u32 q, a, 0;\n"
    "@q ld.relaxed.gpu.global.v4.b32 {%20,%21,%22,%23}, [%32+%38];\n"
    "and.b32 a, %24, 1;\nsetp.ne.u32 q, a, 0;\n"
    "@q ld.relaxed.gpu.global.v4.b32 {%24,%25,%26,%27}, [%32+%39];\n"
    "and.b32 a, %28, 1;\nsetp.ne.u32 q, a, 0;\n"
    "@q ld.relaxed.gpu.global.v4.b32 {%28,%29,%30,%31}, [%32+%40];\n"
    "add.u32 n, n, 1;\nsetp.lt.u32 q, n, 262144;\n@q bra.uni LAB_CHK;\n"
    "LAB_OK:\n"
    "or.b32 %0, %0, 1;\n"
    "or.b32 %4, %4, 1;\n"
    "or.b32 %8, %8, 1;\n"
    "or.b32 %12, %12, 1;\n"
    "or.b32 %16, %16, 1;\n"
    "or.b32 %20, %20, 1;\n"
    "or.b32 %24, %24, 1;\n"
    "or.b32 %28, %28, 1;\n"
    "}\n"
    : "+r"(r[0][0]), "+r"(r[0][1]), "+r"(r[0][2]), "+r"(r[0][3]), "+r"(r[1][0]), "+r"(r[1][1]), "+r"(r[1][2]), "+r"(r[1][3]),
      "+r"(r[2][0]), "+r"(r[2][1]), "+r"(r[2][2]), "+r"(r[2][3]), "+r"(r[3][0]), "+r"(r[3][1]), "+r"(r[3][2]), "+r"(r[3][3]),
      "+r"(r[4][0]), "+r"(r[4][1]), "+r"(r[4][2]), "+r"(r[4][3]), "+r"(r[5][0]), "+r"(r[5][1]), "+r"(r[5][2]), "+r"(r[5][3]),
      "+r"(r[6][0]), "+r"(r[6][1]), "+r"(r[6][2]), "+r"(r[6][3]), "+r"(r[7][0]), "+r"(r[7][1]), "+r"(r[7][2]), "+r"(r[7][3])
    : "l"(p), "n"(0 * STR), "n"(1 * STR), "n"(2 * STR), "n"(3 * STR), "n"(4 * STR), "n"(5 * STR), "n"(6 * STR), "n"(7 * STR)
    : "memory");
}

template <int STR>
__device__ __forceinline__ void verify4_tag0(const uint4* p, uint32_t (*r)[4]) {
  asm volatile("{\n.reg .pred p, q;\n.reg .b32 a, n;\nmov.u32 n, 0;\n"
    "LAB_CHK:\n"
    "or.b32 a, %0, %4;\n"
    "or.b32 a, a, %8;\n"
    "or.b32 a, a, %12;\n"
    "and.b32 a, a, 1;\nsetp.eq.u32 p, a, 0;\nvote.sync.all.pred p, p, 0xffffffff;\n"
    "@p bra.uni LAB_OK;\n"
    "and.b32 a, %0, 1;\nsetp.ne.u32 q, a, 0;\n"
    "@q ld.relaxed.gpu.global.v4.b32 {%0,%1,%2,%3}, [%16+%17];\n"
    "and.b32 a, %4, 1;\nsetp.ne.u32 q, a, 0;\n"
    "@q ld.relaxed.gpu.global.v4.b32 {%4,%5,%6,%7}, [%16+%18];\n"
    "and.b32 a, %8, 1;\nsetp.ne.u32 q, a, 0;\n"
    "@q ld.relaxed.gpu.global.v4.b32 {%8,%9,%10,%11}, [%16+%19];\n"
    "and.b32 a, %12, 1;\nsetp.ne.u32 q, a, 0;\n"
    "@q ld.relaxed.gpu.global.v4.b32 {%12,%13,%14,%15}, [%16+%20];\n"
    "add.u32 n, n, 1;\nsetp.lt.u32 q, n, 262144;\n@q bra.uni LAB_CHK;\n"
    "LAB_OK:\n"
    "or.b32 %0, %0, 1;\n"
    "or.b32 %4, %4, 1;\n"
    "or.b32 %8, %8, 1;\n"
    "or.b32 %12, %12, 1;\n"
    "}\n"
    : "+r"(r[0][0]), "+r"(r[0][1]), "+r"(r[0][2]), "+r"(r[0][3]), "+r"(r[1][0]), "+r"(r[1][1]), "+r"(r[1][2]), "+r"(r[1][3]),
      "+r"(r[2][0]), "+r"(r[2][1]), "+r"(r[2][2]), "+r"(r[2][3]), "+r"(r[3][0]), "+r"(r[3][1]), "+r"(r[3][2]), "+r"(r[3][3])
    : "l"(p), "n"(0 * STR), "n"(1 * STR), "n"(2 * STR), "n"(3 * STR)
    : "memory");
}

#define SPIN_LIMIT (1 << 18)

__device__ __forceinline__ uint32_t smem_u32(const void* p) { return (uint32_t)__cvta_generic_to_shared(p); }
__device__ __forceinline__ void mbar_init(uint32_t a, uint32_t c) {
  asm volatile("mbarrier.init.shared::cta.b64 [%0], %1;" ::"r"(a), "r"(c) : "memory");
}
__device__ __forceinline__ void mbar_expect(uint32_t a, uint32_t b) {
  asm volatile("mbarrier.arrive.expect_tx.shared::cta.b64 _, [%0], %1;" ::"r"(a), "r"(b) : "memory");
}
__device__ __forceinline__ void mbar_arrive(uint32_t a) {
  asm volatile("mbarrier.arrive.shared::cta.b64 _, [%0];" ::"r"(a) : "memory");
}
__device__ __forceinline__ void mbar_wait(uint32_t a, uint32_t parity) {
  asm volatile(
      "{\n.reg .pred p;\n.reg .u32 n;\nmov.u32 n, 0;\n"
      "LAB_WAIT:\n"
      "mbarrier.try_wait.parity.shared::cta.b64 p, [%0], %1;\n"
      "@p bra LAB_DONE;\n"
      "add.u32 n, n, 1;\n"
      "setp.lt.u32 p, n, 262144;\n"
      "@p bra LAB_WAIT;\n"
      "LAB_DONE:\n}\n" ::"r"(a), "r"(parity) : "memory");
}
__device__ __forceinline__ void tma3d(uint32_t dst, const CUtensorMap* tm, uint32_t bar, int c0, int c1, int c2) {
  asm volatile(
      "cp.async.bulk.tensor.3d.shared::cluster.global.mbarrier::complete_tx::bytes [%0], [%1, {%3,%4,%5}], [%2];"
      ::"r"(dst), "l"(tm), "r"(bar), "r"(c0), "r"(c1), "r"(c2) : "memory");
}
__device__ __forceinline__ void wg_fence() { asm volatile("wgmma.fence.sync.aligned;" ::: "memory"); }
__device__ __forceinline__ void wg_commit() { asm volatile("wgmma.commit_group.sync.aligned;" ::: "memory"); }
template <int N> __device__ __forceinline__ void wg_wait() {
  asm volatile("wgmma.wait_group.sync.aligned %0;" ::"n"(N) : "memory");
}
template <int N> __device__ __forceinline__ void fence_regs(float (&d)[N]) {
#pragma unroll
  for (int i = 0; i < N; i++) asm volatile("" : "+f"(d[i])::"memory");
}
template <int N> __device__ __forceinline__ void fence_regs(uint32_t (&d)[N][4]) {
#pragma unroll
  for (int i = 0; i < N; i++) asm volatile("" : "+r"(d[i][0]), "+r"(d[i][1]), "+r"(d[i][2]), "+r"(d[i][3])::"memory");
}
template <int N> __device__ __forceinline__ void fence_frags(uint32_t (*d)[4]) {
#pragma unroll
  for (int i = 0; i < N; i++) asm volatile("" : "+r"(d[i][0]), "+r"(d[i][1]), "+r"(d[i][2]), "+r"(d[i][3])::"memory");
}
__device__ __forceinline__ void bar_sync(int id, int n) { asm volatile("bar.sync %0, %1;" ::"r"(id), "r"(n) : "memory"); }
__device__ __forceinline__ void bar_arrive(int id, int n) { asm volatile("bar.arrive %0, %1;" ::"r"(id), "r"(n) : "memory"); }

__device__ __forceinline__ uint32_t pack_bf16(float lo, float hi) {
  uint32_t r;
  asm("cvt.rn.bf16x2.f32 %0, %1, %2;" : "=r"(r) : "f"(hi), "f"(lo));
  return r;
}
__device__ __forceinline__ float bf_lo(uint32_t w) { return __uint_as_float(w << 16); }
__device__ __forceinline__ float bf_hi(uint32_t w) { return __uint_as_float(w & 0xFFFF0000u); }
__device__ __forceinline__ float round_bf16(float x) { return bf_lo(pack_bf16(x, 0.f)); }
__device__ __forceinline__ uint32_t hfma2_bf16(uint32_t a, uint32_t b, uint32_t c) {
  uint32_t r;
  asm("fma.rn.bf16x2 %0, %1, %2, %3;" : "=r"(r) : "r"(a), "r"(b), "r"(c));
  return r;
}
__device__ __forceinline__ float ex2(float x) {
  float r;
  asm("ex2.approx.ftz.f32 %0, %1;" : "=f"(r) : "f"(x));
  return r;
}
__device__ __forceinline__ float tanh_hw(float x) {
  float r;
  asm("tanh.approx.f32 %0, %1;" : "=f"(r) : "f"(x));
  return r;
}
template <int TAG> __device__ __forceinline__ uint32_t pack_tag(float lo, float hi) {
  uint32_t w = __byte_perm(__float_as_uint(lo), pack_bf16(lo, hi), 0x7632);
  return TAG ? (w | 1u) : (w & ~1u);
}
__device__ __forceinline__ void st_pkt(uint4* p, uint32_t a, uint32_t b, uint32_t c, uint32_t d) {
  asm volatile(
      "st.relaxed.gpu.global.v4.b32 [%0], {%1,%2,%3,%4};" ::"l"(p), "r"(a), "r"(b), "r"(c), "r"(d) : "memory");
}
__device__ __forceinline__ void ld_pkt(const uint4* p, uint32_t (&r)[4]) {
  asm volatile(
      "ld.relaxed.gpu.global.v4.b32 {%0,%1,%2,%3}, [%4];"
      : "=r"(r[0]), "=r"(r[1]), "=r"(r[2]), "=r"(r[3]) : "l"(p) : "memory");
}
__device__ __forceinline__ uint32_t ldg32(const void* p) {
  uint32_t r;
  asm volatile("ld.global.nc.b32 %0, [%1];" : "=r"(r) : "l"(p));
  return r;
}
__device__ __forceinline__ uint32_t ldg16(const void* p) {
  uint16_t r;
  asm volatile("ld.global.nc.b16 %0, [%1];" : "=h"(r) : "l"(p));
  return r;
}
__device__ __forceinline__ uint4 ldg128(const void* p) {
  uint4 r;
  asm volatile("ld.global.nc.v4.b32 {%0,%1,%2,%3}, [%4];" : "=r"(r.x), "=r"(r.y), "=r"(r.z), "=r"(r.w) : "l"(p));
  return r;
}
__device__ __forceinline__ void l2_prefetch(const void* p, uint32_t bytes) {
  asm volatile("cp.async.bulk.prefetch.L2.global [%0], %1;" ::"l"(p), "r"(bytes) : "memory");
}
__device__ __forceinline__ float rcp_hw(float x) {
  float r;
  asm("rcp.approx.ftz.f32 %0, %1;" : "=f"(r) : "f"(x));
  return r;
}
__device__ __forceinline__ void warp_bulk_store(void* gdst, uint32_t ssrc, uint32_t bytes) {
  asm volatile("fence.proxy.async.shared::cta;" ::: "memory");
  __syncwarp();
  if ((threadIdx.x & 31) == 0) {
    asm volatile("cp.async.bulk.global.shared::cta.bulk_group [%0], [%1], %2;" ::"l"(gdst), "r"(ssrc), "r"(bytes) : "memory");
    asm volatile("cp.async.bulk.commit_group;" ::: "memory");
  }
}
__device__ __forceinline__ void warp_bulk_load(uint32_t sdst, const void* gsrc, uint32_t bytes, uint32_t bar) {
  if ((threadIdx.x & 31) == 0) {
    mbar_expect(bar, bytes);
    asm volatile("cp.async.bulk.shared::cluster.global.mbarrier::complete_tx::bytes [%0], [%1], %2, [%3];"
                 ::"r"(sdst), "l"(gsrc), "r"(bytes), "r"(bar) : "memory");
  }
}
__device__ __forceinline__ void spin_cycles(uint32_t n) {
  uint32_t t0, t;
  asm volatile("mov.u32 %0, %%clock;" : "=r"(t0));
  do { asm volatile("mov.u32 %0, %%clock;" : "=r"(t)); } while (t - t0 < n);
}
template <int N> __device__ __forceinline__ void warp_bulk_wait_read() {
  if ((threadIdx.x & 31) == 0) asm volatile("cp.async.bulk.wait_group.read %0;" ::"n"(N) : "memory");
  __syncwarp();
}
__device__ __forceinline__ void sts128(uint32_t a, uint32_t x, uint32_t y, uint32_t z, uint32_t w) {
  asm volatile("st.shared.v4.b32 [%0], {%1,%2,%3,%4};" ::"r"(a), "r"(x), "r"(y), "r"(z), "r"(w) : "memory");
}
__device__ __forceinline__ void lds128(uint32_t a, uint32_t (&r)[4]) {
  asm volatile("ld.shared.v4.b32 {%0,%1,%2,%3}, [%4];" : "=r"(r[0]), "=r"(r[1]), "=r"(r[2]), "=r"(r[3]) : "r"(a) : "memory");
}

constexpr int SK = 2048, WIN = 512;
constexpr int FF = 1792, FSL = 224;
constexpr int NTILES = 80;
constexpr int NSLOT = 4;
constexpr uint32_t SLOT = 32768;
constexpr uint32_t SM_PARK = 0;
constexpr uint32_t SM_RING = 3 * SLOT;
constexpr uint32_t SM_TAB = 7 * SLOT;
constexpr uint32_t SM_RED = SM_TAB + 2048;
constexpr uint32_t SM_BAR = SM_RED + 256;
constexpr uint32_t SM_WBAR = SM_BAR + 128;
constexpr uint32_t SM_TOTAL = SM_WBAR + 192;

struct Scratch {
  uint4 P[16 * 8 * 8 * 1024];
  uint4 G[16 * 8 * 32 * 32];
  uint4 mod1[8 * 256];
  uint4 mod2[512];
  uint4 uv[2 * 448];
  uint4 stat[16 * 8 * 8 * 2];
  uint32_t epoch;
};
__device__ Scratch g_scratch;

#define TS(i) do { } while (0)
#define TR(code)
#define CK_(v)
#define CKS(i, v)

struct Params {
  const __nv_bfloat16* x;
  const __nv_bfloat16* c;
  const __nv_bfloat16* wmod;
  const __nv_bfloat16* wo;
  const __nv_bfloat16* w1;
  const __nv_bfloat16* w2;
  __nv_bfloat16* out;
  Scratch* s;
};

constexpr uint32_t HI128 = (1024 >> 4) | (1u << 30);
constexpr uint32_t HI64 = (512 >> 4) | (2u << 30);
constexpr int LB_MN128 = (16384 >> 4) << 16;
constexpr int LB_K128 = 1 << 16;
constexpr int LB_W1 = (4096 >> 4) << 16;
constexpr int LB_W2 = (14336 >> 4) << 16;

template <int I> struct IC {
  __host__ __device__ constexpr operator int() const { return I; }
};
template <int I, int N, typename F> __device__ __forceinline__ void static_for(F&& f) {
  if constexpr (I < N) {
    f(IC<I>{});
    static_for<I + 1, N>(f);
  }
}

struct Ring {
  uint32_t base16, bars;
  __device__ __forceinline__ uint32_t wait_full(uint32_t slot, uint32_t parity) const {
    mbar_wait(bars + slot * 8, parity);
    return base16 + slot * (SLOT >> 4);
  }
  __device__ __forceinline__ void release(uint32_t slot) const {
    if ((threadIdx.x & 31) == 0) mbar_arrive(bars + 32 + slot * 8);
  }
};

__device__ __forceinline__ float silu_c(uint32_t bits) {
  float x = bf_lo(bits);
  return round_bf16(x * rcp_hw(1.f + ex2(-1.4426950408889634f * x)));
}
__device__ __forceinline__ void pack8(uint32_t (&o)[4], const float* v) {
  o[0] = pack_bf16(v[0], v[1]); o[1] = pack_bf16(v[2], v[3]); o[2] = pack_bf16(v[4], v[5]); o[3] = pack_bf16(v[6], v[7]);
}

template <int TAG, int N>
__device__ __forceinline__ void issue_pkts(const uint4* p, int stride, uint32_t (*r)[4]) {
#pragma unroll
  for (int i = 0; i < N; i++) ld_pkt(p + i * stride, r[i]);
}
__device__ __forceinline__ void ld_mod(const uint4* p, uint32_t tag, uint32_t (&r)[4]) {
  int spins = 0;
  ld_pkt(p, r);
  while (r[2] != tag && ++spins < SPIN_LIMIT) ld_pkt(p, r);
}

#define EARLY_TILES 2
#define PF_WMOD 1
#define MOD1_DELAY 500
#define RED3_UNIT 3
#define JLO 2
#define G_DELAY 0

__global__ void __launch_bounds__(384, 1)
adaln_block_kernel(const __grid_constant__ CUtensorMap tmWq, const __grid_constant__ CUtensorMap tmK,
                   const __grid_constant__ CUtensorMap tmV, const __grid_constant__ CUtensorMap tmWo,
                   const __grid_constant__ CUtensorMap tmW1, const __grid_constant__ CUtensorMap tmW2,
                   const __grid_constant__ CUtensorMap tmWm, const __grid_constant__ CUtensorMap tmP, const Params p) {
  extern __shared__ __align__(1024) uint8_t smem_raw[];
  const uint32_t sb = smem_u32(smem_raw);
  const int tid = threadIdx.x, lane = tid & 31;
  const int warp = __shfl_sync(0xffffffffu, tid >> 5, 0);
  const int bid = blockIdx.x;
  const int j = ((bid >> (4 + JLO)) << JLO) | (bid & ((1 << JLO) - 1)), rt = (bid >> JLO) & 15;
  const uint32_t bars = sb + SM_BAR;

  if (warp >= 8) {
    CK_(c0);
    asm volatile("setmaxnreg.dec.sync.aligned.u32 40;");
    CK_(c1);
    const int t = tid - 256;
    uint32_t tag;
    {
      uint32_t cb[4];
      if (t == 0) {
        mbar_init(bars + 80, 1);
        asm volatile("fence.mbarrier_init.release.cluster;" ::: "memory");
        mbar_expect(bars + 80, 8192);
        tma3d(sb + SM_RING + 3 * SLOT, &tmWm, bars + 80, 0, 0, bid);
        tma3d(sb + SM_RING + 3 * SLOT + 4096, &tmWm, bars + 80, 0, 256, bid);
        asm volatile("prefetch.tensormap [%0];" ::"l"(&tmWq) : "memory");
        for (int i = 0; i < NSLOT; i++) { mbar_init(bars + i * 8, 1); mbar_init(bars + 32 + i * 8, 8); }
        mbar_init(bars + 72, 2);
        for (int i = 0; i < 24; i++) mbar_init(sb + SM_WBAR + i * 8, 1);
        asm volatile("fence.mbarrier_init.release.cluster;" ::: "memory");
      }
      __syncwarp();
      CK_(c2);
#pragma unroll
      for (int i = 0; i < 4; i++) cb[i] = ldg16(p.c + t + 128 * i);
      asm volatile("ld.relaxed.gpu.global.u32 %0, [%1];" : "=r"(tag) : "l"(&p.s->epoch) : "memory");
      bar_sync(5, 128);
      tag += 1;
      float a[8], sc[4];
#pragma unroll
      for (int i = 0; i < 4; i++) sc[i] = silu_c(cb[i]);
#pragma unroll
      for (int k = 0; k < 8; k++) a[k] = 0.f;
      mbar_wait(bars + 80, 0);
      CK_(c3);
#pragma unroll
      for (int i = 0; i < 4; i++) {
        uint32_t w[4];
        lds128(sb + SM_RING + 3 * SLOT + (t + 128 * i) * 16, w);
#pragma unroll
        for (int e = 0; e < 4; e++) {
          a[2 * e] = fmaf(sc[i], bf_lo(w[e]), a[2 * e]);
          a[2 * e + 1] = fmaf(sc[i], bf_hi(w[e]), a[2 * e + 1]);
        }
      }
      const bool h16 = lane & 16, h8 = lane & 8, h4 = lane & 4;
#pragma unroll
      for (int k = 0; k < 4; k++) {
        float send = h16 ? a[k] : a[k + 4], keep = h16 ? a[k + 4] : a[k];
        a[k] = keep + __shfl_xor_sync(0xffffffffu, send, 16);
      }
#pragma unroll
      for (int k = 0; k < 2; k++) {
        float send = h8 ? a[k] : a[k + 2], keep = h8 ? a[k + 2] : a[k];
        a[k] = keep + __shfl_xor_sync(0xffffffffu, send, 8);
      }
      {
        float send = h4 ? a[0] : a[1], keep = h4 ? a[1] : a[0];
        a[0] = keep + __shfl_xor_sync(0xffffffffu, send, 4);
      }
      a[0] += __shfl_xor_sync(0xffffffffu, a[0], 2);
      a[0] += __shfl_xor_sync(0xffffffffu, a[0], 1);
      float* red = (float*)(smem_raw + SM_RED);
      if ((lane & 3) == 0) red[(warp - 8) * 8 + (lane >> 2)] = a[0];
      if (t == 0) *(uint32_t*)(smem_raw + SM_BAR + 64) = tag;
      CK_(c4);
      bar_sync(5, 128);
      bar_arrive(7, 384);
      CK_(c5);
      if (t == 0) {
#pragma unroll
        for (int i = 0; i < EARLY_TILES; i++) {
          mbar_expect(bars + i * 8, SLOT);
          tma3d(sb + SM_RING + i * SLOT, &tmWq, bars + i * 8, 0, i * 128, (j * 4 + 1) * 2);
        }
      }
      if (warp == 9) {
        const int cl = lane & 7;
        float v = round_bf16(red[cl] + red[8 + cl] + red[16 + cl] + red[24 + cl]);
        if (bid >= 64) v = 1.f + v;
        float vn = __shfl_down_sync(0xffffffffu, v, 1);
        uint32_t wd = pack_bf16(v, vn);
        uint32_t w0 = __shfl_sync(0xffffffffu, wd, (lane & 1) * 4);
        uint32_t w1 = __shfl_sync(0xffffffffu, wd, (lane & 1) * 4 + 2);
        if (lane < 16) st_pkt(&p.s->mod1[(lane >> 1) * 256 + bid * 2 + (lane & 1)], w0, w1, tag, 0);
      }
      uint32_t r0[4], r1[4];
      const uint4* src = &p.s->mod1[j * 256 + t];
      CK_(c6);
      spin_cycles(MOD1_DELAY);
      CK_(c7);
      int spins = 0;
      do {
        ld_pkt(src, r0);
        ld_pkt(src + 128, r1);
      } while ((r0[2] != tag || r1[2] != tag) && ++spins < SPIN_LIMIT);
      const int g = t >> 2, pp = (t & 3) * 2;
      const uint32_t ad = sb + SM_TAB + (uint32_t)(g * 4 + (pp & 3)) * 16 + (pp >> 2) * 4;
      asm volatile("st.shared.b32 [%0], %1;" ::"r"(ad + 8), "r"(r0[0]) : "memory");
      asm volatile("st.shared.b32 [%0], %1;" ::"r"(ad + 24), "r"(r0[1]) : "memory");
      asm volatile("st.shared.b32 [%0], %1;" ::"r"(ad), "r"(r1[0]) : "memory");
      asm volatile("st.shared.b32 [%0], %1;" ::"r"(ad + 16), "r"(r1[1]) : "memory");
      bar_arrive(1, 384);
      CK_(c8);
      CKS(0, c0); CKS(1, c1); CKS(2, c2); CKS(3, c3); CKS(4, c4); CKS(5, c5); CKS(6, c6); CKS(7, c7); CKS(8, c8);
    }
    if (warp == 8) {
      if (lane == 0) {
        uint32_t s = EARLY_TILES & 3, ph = 1 ^ (EARLY_TILES >> 2);
#pragma unroll 1
        for (int tt = EARLY_TILES; tt < NTILES; tt++) {
          const CUtensorMap* tm;
          int c1, c2;
          uint32_t bytes = SLOT;
          if (tt < 16) {
            tm = &tmWq; c1 = (tt & 3) * 128; c2 = (j * 4 + (((tt >> 2) + 1) & 3)) * 2;
          } else if (tt < 48) {
            const int u = tt - 16;
            const bool isK = (u == 0) || ((u & 1) && u != 31);
            const int n = isK ? ((u + 1) >> 1) : (u == 31 ? 15 : (u >> 1) - 1);
            tm = isK ? &tmK : &tmV; c1 = j * SK + (SK - WIN) + (n & 3) * 128; c2 = 0;
          } else if (tt < 64) {
            const int u = tt - 48;
            tm = &tmWo; c1 = j * 512 + (u & 3) * 128; c2 = (u >> 2) * 2;
          } else if (tt < 72) {
            tm = &tmW1; c1 = (tt - 64) * 64; c2 = j * 7; bytes = 28672;
          } else {
            const int u = tt - 72;
            tm = &tmW2; c1 = j * FSL + (u & 1) * 112; c2 = (u >> 1) * 2; bytes = 28672;
          }
          mbar_wait(bars + 32 + s * 8, ph);
          mbar_expect(bars + s * 8, bytes);
          tma3d(sb + SM_RING + s * SLOT, tm, bars + s * 8, 0, c1, c2);
          if (++s == (tt < 48 ? 4u : 3u)) { s = 0; ph ^= 1; }
        }
      }
    } else if (warp >= 10) {
      const int t2 = tid - 320, hf = t2 & 1, r0 = t2 >> 1;
      bar_sync(6, 352);
      float a[8];
#pragma unroll
      for (int k = 0; k < 8; k++) a[k] = 0.f;
#pragma unroll 1
      for (int b = 0; b < 8; b++) {
        uint4 w[2];
        uint32_t cb[2];
#pragma unroll
        for (int i = 0; i < 2; i++) {
          w[i] = ldg128(p.wmod + (size_t)(r0 + 32 * (2 * b + i)) * 3072 + 1024 + bid * 16 + hf * 8);
          cb[i] = ldg16(p.c + r0 + 32 * (2 * b + i));
        }
#pragma unroll
        for (int i = 0; i < 2; i++) {
          const float s = silu_c(cb[i]);
          a[0] = fmaf(s, bf_lo(w[i].x), a[0]); a[1] = fmaf(s, bf_hi(w[i].x), a[1]);
          a[2] = fmaf(s, bf_lo(w[i].y), a[2]); a[3] = fmaf(s, bf_hi(w[i].y), a[3]);
          a[4] = fmaf(s, bf_lo(w[i].z), a[4]); a[5] = fmaf(s, bf_hi(w[i].z), a[5]);
          a[6] = fmaf(s, bf_lo(w[i].w), a[6]); a[7] = fmaf(s, bf_hi(w[i].w), a[7]);
        }
      }
      const bool h16 = lane & 16, h8 = lane & 8, h4 = lane & 4;
#pragma unroll
      for (int k = 0; k < 4; k++) {
        float send = h16 ? a[k] : a[k + 4], keep = h16 ? a[k + 4] : a[k];
        a[k] = keep + __shfl_xor_sync(0xffffffffu, send, 16);
      }
#pragma unroll
      for (int k = 0; k < 2; k++) {
        float send = h8 ? a[k] : a[k + 2], keep = h8 ? a[k + 2] : a[k];
        a[k] = keep + __shfl_xor_sync(0xffffffffu, send, 8);
      }
      {
        float send = h4 ? a[0] : a[1], keep = h4 ? a[1] : a[0];
        a[0] = keep + __shfl_xor_sync(0xffffffffu, send, 4);
      }
      a[0] += __shfl_xor_sync(0xffffffffu, a[0], 2);
      float* red = (float*)(smem_raw + SM_RED) + 32;
      if ((lane & 2) == 0) red[(warp - 10) * 16 + hf * 8 + (lane >> 2)] = a[0];
      bar_sync(4, 64);
      if (warp == 10) {
        const int cl = lane & 15;
        float v = round_bf16(red[cl] + red[16 + cl]);
        if ((bid >> 5) == 2) v = 1.f + v;
        float vn = __shfl_down_sync(0xffffffffu, v, 1);
        uint32_t wd = pack_bf16(v, vn);
        uint32_t w0 = __shfl_sync(0xffffffffu, wd, (lane & 3) * 2);
        uint32_t w1 = __shfl_sync(0xffffffffu, wd, (lane & 3) * 2 + 8);
        if (lane < 4) st_pkt(&p.s->mod2[bid * 4 + lane], w0, w1, tag, 0);
      }
      const int isv = warp - 10;
      if (bid < 112) {
        const int kk = lane >> 1;
        const uint4* mp = &p.s->mod2[(isv ? 1 : 2) * 128 + ((kk & 7) >> 1)];
#pragma unroll
        for (int k = 0; k < 8; k++) a[k] = 0.f;
#pragma unroll 1
        for (int g = 0; g < 32; g++) {
          const uint4 w = ldg128(p.w1 + (size_t)(g * 16 + kk) * FF + bid * 16 + (lane & 1) * 8);
          uint32_t m[4];
          ld_mod(mp + g * 4, tag, m);
          const uint32_t mw = (kk & 8) ? m[1] : m[0];
          const float s = (kk & 1) ? bf_hi(mw) : bf_lo(mw);
          a[0] = fmaf(s, bf_lo(w.x), a[0]); a[1] = fmaf(s, bf_hi(w.x), a[1]);
          a[2] = fmaf(s, bf_lo(w.y), a[2]); a[3] = fmaf(s, bf_hi(w.y), a[3]);
          a[4] = fmaf(s, bf_lo(w.z), a[4]); a[5] = fmaf(s, bf_hi(w.z), a[5]);
          a[6] = fmaf(s, bf_lo(w.w), a[6]); a[7] = fmaf(s, bf_hi(w.w), a[7]);
        }
#pragma unroll
        for (int k = 0; k < 4; k++) {
          float send = h16 ? a[k] : a[k + 4], keep = h16 ? a[k + 4] : a[k];
          a[k] = keep + __shfl_xor_sync(0xffffffffu, send, 16);
        }
#pragma unroll
        for (int o = 8; o > 1; o >>= 1) {
#pragma unroll
          for (int k = 0; k < 4; k++) a[k] += __shfl_xor_sync(0xffffffffu, a[k], o);
        }
        const float sc = isv ? 0.5f : 1.f;
        if ((lane & 14) == 0)
          st_pkt(&p.s->uv[isv * 448 + bid * 4 + (lane & 1) * 2 + (lane >> 4)],
                 (__float_as_uint(a[0] * sc) & ~1u) | (tag & 1u), __float_as_uint(a[1] * sc), __float_as_uint(a[2] * sc),
                 __float_as_uint(a[3] * sc));
      }
#pragma unroll 1
      for (int i = lane; i < 56; i += 32) {
        uint32_t m[4];
        int spins = 0;
        do { ld_pkt(&p.s->uv[isv * 448 + j * 56 + i], m); } while (((m[0] ^ tag) & 1u) && ++spins < SPIN_LIMIT);
        const uint32_t ad = sb + SM_TAB + i * 32 + isv * 8;
        asm volatile("st.shared.v2.b32 [%0], {%1,%2};" ::"r"(ad), "r"(m[0]), "r"(m[1]) : "memory");
        asm volatile("st.shared.v2.b32 [%0], {%1,%2};" ::"r"(ad + 16), "r"(m[2]), "r"(m[3]) : "memory");
      }
      __syncwarp();
      if (lane == 0) mbar_arrive(bars + 72);
    } else {
      bar_sync(6, 352);
      if (lane < 8) l2_prefetch((const char*)p.wo + (size_t)bid * 32768 + lane * 4096, 4096);
      else if (lane < 12) l2_prefetch((const char*)p.w1 + (size_t)bid * 14336 + (lane - 8) * 3584, 3584);
      else if (lane < 16) l2_prefetch((const char*)p.w2 + (size_t)bid * 14336 + (lane - 12) * 3584, 3584);
    }
  } else {
    const int wg = warp >> 2;
    const int q = lane & 3, gq = lane >> 2;
    const Ring ring{(sb + SM_RING) >> 4, bars};
    const uint32_t xoff = (uint32_t)(rt * 128 + 16 * j + warp) * 256 + gq * 8 + q;
    const uint32_t ooff = ((uint32_t)(rt * 8 + j) * 32 + gq) * 32 + warp * 4 + q;
    const uint32_t wblk = sb + SM_PARK + warp * 4096, wprv = wblk + lane * 16;
    const uint32_t wbar = sb + SM_WBAR + warp * 24;
    const uint32_t goff = (uint32_t)(rt * 8 + warp) * 1024 + lane;

    {
      const uint32_t* xo = (const uint32_t*)p.x + xoff;
      uint32_t xr[4][4];
      CK_(d0);
#pragma unroll
      for (int c = 0; c < 4; c++) {
        xr[c][0] = ldg32(xo + c * 64);
        xr[c][1] = ldg32(xo + c * 64 + 8 * 256);
        xr[c][2] = ldg32(xo + c * 64 + 4);
        xr[c][3] = ldg32(xo + c * 64 + 4 + 8 * 256);
      }
      CK_(d1);
      fence_regs(xr);
      CK_(d2);
      float s0 = 0.f, s1 = 0.f, v0 = 0.f, v1 = 0.f;
#pragma unroll
      for (int c = 0; c < 4; c++) {
#pragma unroll
        for (int e = 0; e < 4; e++) {
          const float a = bf_lo(xr[c][e]), b = bf_hi(xr[c][e]);
          if (e & 1) { s1 += a + b; v1 = fmaf(a, a, fmaf(b, b, v1)); }
          else { s0 += a + b; v0 = fmaf(a, a, fmaf(b, b, v0)); }
        }
      }
#pragma unroll
      for (int o = 16; o > 0; o >>= 1) {
        s0 += __shfl_xor_sync(0xffffffffu, s0, o);
        s1 += __shfl_xor_sync(0xffffffffu, s1, o);
        v0 += __shfl_xor_sync(0xffffffffu, v0, o);
        v1 += __shfl_xor_sync(0xffffffffu, v1, o);
      }
      const float m0 = s0 * (1.f / 512.f), m1 = s1 * (1.f / 512.f);
      const float r0 = rsqrtf(fmaxf(fmaf(-m0, m0, v0 * (1.f / 512.f)), 0.f) + 1e-5f);
      const float r1 = rsqrtf(fmaxf(fmaf(-m1, m1, v1 * (1.f / 512.f)), 0.f) + 1e-5f);
#pragma unroll
      for (int c = 0; c < 4; c++) {
        st_pkt(p.s->G + ooff + c * 256,
               pack_tag<1>((bf_lo(xr[c][0]) - m0) * r0, (bf_hi(xr[c][0]) - m0) * r0),
               pack_bf16((bf_lo(xr[c][1]) - m1) * r1, (bf_hi(xr[c][1]) - m1) * r1),
               pack_bf16((bf_lo(xr[c][2]) - m0) * r0, (bf_hi(xr[c][2]) - m0) * r0),
               pack_bf16((bf_lo(xr[c][3]) - m1) * r1, (bf_hi(xr[c][3]) - m1) * r1));
      }
      CK_(d3);
      CKS(16, d0); CKS(17, d1); CKS(18, d2); CKS(19, d3);

    }
    asm volatile("setmaxnreg.inc.sync.aligned.u32 232;");
    uint32_t qf[8][4];
    {
      uint32_t h[32][4];
      float acc[64];
      const uint4* Gin = p.s->G + goff;
      bar_sync(7, 384);
      if (G_DELAY) spin_cycles(G_DELAY);
#pragma unroll
      for (int c = 0; c < 3; c++) warp_bulk_load(wblk + c * SLOT, Gin + c * 256, 4096, wbar + c * 8);
#pragma unroll
      for (int c = 0; c < 4; c++) {
        mbar_wait(wbar + (c % 3) * 8, c / 3);
#pragma unroll
        for (int i = 0; i < 8; i++) lds128(wprv + (c % 3) * SLOT + i * 512, h[c * 8 + i]);
        verify8_tag1<512>(Gin + c * 256, h + c * 8);
        if (c == 0) {
          warp_bulk_load(wblk, Gin + 768, 4096, wbar);
          TS(1);
          bar_sync(1, 384);
        }
#pragma unroll
        for (int i = 0; i < 8; i++) {
          uint32_t m[4];
          lds128(sb + SM_TAB + (uint32_t)((c * 8 + i) * 4 + q) * 16, m);
          uint32_t* hh = h[c * 8 + i];
          hh[0] = hfma2_bf16(hh[0], m[0], m[2]);
          hh[1] = hfma2_bf16(hh[1], m[0], m[2]);
          hh[2] = hfma2_bf16(hh[2], m[1], m[3]);
          hh[3] = hfma2_bf16(hh[3], m[1], m[3]);
        }
        fence_frags<8>(h + c * 8);
        const uint32_t b = ring.wait_full(c, 0);
        if (c > 0) { wg_wait<0>(); ring.release(c - 1); }
        if (c == 0) TS(2);
        wg_fence();
        static_for<0, 8>([&](auto K) { wgmma_rs_n128_tb1<LB_MN128 + K * 128, HI128>(acc, h[c * 8 + K], b, (c | K) != 0); });
        wg_commit();
      }
      bar_arrive(6, 352);
#pragma unroll 1
      for (int ps = 1; ps < 4; ps++) {
        wg_wait<0>();
        ring.release(3);
        fence_regs(acc);
#pragma unroll
        for (int i = 0; i < 8; i++) {
          uint32_t o[4];
          pack8(o, acc + 8 * i);
          sts128(wprv + (ps - 1) * SLOT + i * 512, o[0], o[1], o[2], o[3]);
        }
#pragma unroll
        for (int c = 0; c < 4; c++) {
          const uint32_t b = ring.wait_full(c, ps & 1);
          if (c > 0) { wg_wait<0>(); ring.release(c - 1); }
          wg_fence();
          static_for<0, 8>([&](auto K) { wgmma_rs_n128_tb1<LB_MN128 + K * 128, HI128>(acc, h[c * 8 + K], b, (c | K) != 0); });
          wg_commit();
        }
      }
      wg_wait<0>();
      ring.release(3);
      fence_regs(acc);
#pragma unroll
      for (int i = 0; i < 8; i++) pack8(qf[i], acc + 8 * i);
    }
    fence_regs(qf);
    TS(3);

    float S[64];
    {
      float O[64];
      uint32_t P[8][4];
      const float cs = 0.08838834764831845f * 1.4426950408889634f;
      const int TAU = 0x41800000;
      float m0, m1, l0, l1;

      auto float_block_max = [&]() {
        float b0 = fmaxf(S[0], S[1]), b1 = fmaxf(S[2], S[3]);
#pragma unroll
        for (int i = 1; i < 16; i++) {
          b0 = fmaxf(b0, fmaxf(S[4 * i], S[4 * i + 1]));
          b1 = fmaxf(b1, fmaxf(S[4 * i + 2], S[4 * i + 3]));
        }
        b0 = fmaxf(b0, __shfl_xor_sync(0xffffffffu, b0, 1)); b1 = fmaxf(b1, __shfl_xor_sync(0xffffffffu, b1, 1));
        b0 = fmaxf(b0, __shfl_xor_sync(0xffffffffu, b0, 2)); b1 = fmaxf(b1, __shfl_xor_sync(0xffffffffu, b1, 2));
        m0 = b0 * cs; m1 = b1 * cs;
      };
      auto first_block_max = [&]() {
        int a0 = max(__float_as_int(S[0]), __float_as_int(S[1]));
        int a1 = max(__float_as_int(S[2]), __float_as_int(S[3]));
#pragma unroll
        for (int i = 1; i < 16; i++) {
          a0 = __vimax3_s32(a0, __float_as_int(S[4 * i]), __float_as_int(S[4 * i + 1]));
          a1 = __vimax3_s32(a1, __float_as_int(S[4 * i + 2]), __float_as_int(S[4 * i + 3]));
        }
        a0 = max(a0, __shfl_xor_sync(0xffffffffu, a0, 1)); a1 = max(a1, __shfl_xor_sync(0xffffffffu, a1, 1));
        a0 = max(a0, __shfl_xor_sync(0xffffffffu, a0, 2)); a1 = max(a1, __shfl_xor_sync(0xffffffffu, a1, 2));
        m0 = __int_as_float(a0) * cs; m1 = __int_as_float(a1) * cs;
        if (__any_sync(0xffffffffu, (a0 | a1) < 0)) float_block_max();
      };
      auto scale_sub = [&]() {
#pragma unroll
        for (int i = 0; i < 16; i++) {
          S[4 * i] = fmaf(S[4 * i], cs, -m0); S[4 * i + 1] = fmaf(S[4 * i + 1], cs, -m0);
          S[4 * i + 2] = fmaf(S[4 * i + 2], cs, -m1); S[4 * i + 3] = fmaf(S[4 * i + 3], cs, -m1);
        }
      };
      auto exps = [&](int i0, int i1) {
#pragma unroll
        for (int i = i0; i < i1; i++) {
          S[4 * i] = ex2(S[4 * i]); S[4 * i + 1] = ex2(S[4 * i + 1]);
          S[4 * i + 2] = ex2(S[4 * i + 2]); S[4 * i + 3] = ex2(S[4 * i + 3]);
          l0 += S[4 * i]; l1 += S[4 * i + 2]; l0 += S[4 * i + 1]; l1 += S[4 * i + 3];
        }
      };
      {
        const uint32_t b = ring.wait_full(0, 0);
        wg_fence();
        static_for<0, 8>([&](auto K) { wgmma_rs_n128_tb0<LB_K128 + (K >> 2) * 1024 + (K & 3) * 2, HI128>(S, qf[K], b, K != 0); });
        wg_commit();
        wg_wait<0>();
        fence_regs(S);
        ring.release(0);
        float_block_max();
        scale_sub();
        l0 = 0.f; l1 = 0.f;
        exps(0, 16);
#pragma unroll
        for (int i = 0; i < 8; i++) pack8(P[i], S + 8 * i);
      }
      fence_regs(P);
      if (wg == 1) bar_arrive(2, 256);
#pragma unroll 1
      for (int n = 1; n < 16; n++) {
        const uint32_t tk = 2 * n - 1, tv = 2 * n;
        const bool newhead = (n & 3) == 0;
        const uint32_t bk = ring.wait_full(tk & 3, (tk >> 2) & 1);
        const uint32_t bv = ring.wait_full(tv & 3, (tv >> 2) & 1);
        bar_sync(2 + wg, 256);
        wg_fence();
        static_for<0, 8>([&](auto K) { wgmma_rs_n128_tb0<LB_K128 + (K >> 2) * 1024 + (K & 3) * 2, HI128>(S, qf[K], bk, K != 0); });
        wg_commit();
        static_for<0, 8>([&](auto K) { wgmma_rs_n128_tb1<LB_MN128 + K * 128, HI128>(O, P[K], bv, K != 0 || (n & 3) != 1); });
        wg_commit();
        bar_arrive(2 + (wg ^ 1), 256);
        wg_wait<1>();
        fence_regs(S);
        ring.release(tk & 3);
        if ((n & 3) == 3 && n != 15) {
          fence_regs(qf);
#pragma unroll
          for (int i = 0; i < 8; i++) lds128(wprv + (n >> 2) * SLOT + i * 512, qf[i]);
        }
        float f0 = 1.f, f1 = 1.f;
        bool resc = newhead;
        if (newhead) {
          l0 += __shfl_xor_sync(0xffffffffu, l0, 1); l1 += __shfl_xor_sync(0xffffffffu, l1, 1);
          l0 += __shfl_xor_sync(0xffffffffu, l0, 2); l1 += __shfl_xor_sync(0xffffffffu, l1, 2);
          f0 = rcp_hw(l0); f1 = rcp_hw(l1);
          l0 = 0.f; l1 = 0.f;
          first_block_max();
          scale_sub();
        } else {
          scale_sub();
          int a0 = __vimax3_s32(__float_as_int(S[0]), __float_as_int(S[1]), __float_as_int(S[1]));
          int a1 = __vimax3_s32(__float_as_int(S[2]), __float_as_int(S[3]), __float_as_int(S[3]));
#pragma unroll
          for (int i = 1; i < 16; i++) {
            a0 = __vimax3_s32(a0, __float_as_int(S[4 * i]), __float_as_int(S[4 * i + 1]));
            a1 = __vimax3_s32(a1, __float_as_int(S[4 * i + 2]), __float_as_int(S[4 * i + 3]));
          }
          if (__any_sync(0xffffffffu, max(a0, a1) > TAU)) {
            a0 = max(a0, 0); a1 = max(a1, 0);
            a0 = max(a0, __shfl_xor_sync(0xffffffffu, a0, 1)); a1 = max(a1, __shfl_xor_sync(0xffffffffu, a1, 1));
            a0 = max(a0, __shfl_xor_sync(0xffffffffu, a0, 2)); a1 = max(a1, __shfl_xor_sync(0xffffffffu, a1, 2));
            const float d0 = __int_as_float(a0), d1 = __int_as_float(a1);
#pragma unroll
            for (int i = 0; i < 16; i++) { S[4 * i] -= d0; S[4 * i + 1] -= d0; S[4 * i + 2] -= d1; S[4 * i + 3] -= d1; }
            m0 += d0; m1 += d1;
            f0 = ex2(-d0); f1 = ex2(-d1);
            l0 *= f0; l1 *= f1;
            resc = true;
          }
        }
        exps(0, 4);
        wg_wait<0>();
        fence_regs(O);
        fence_regs(P);
        ring.release(tv & 3);
        if (resc) {
#pragma unroll
          for (int i = 0; i < 16; i++) {
            O[4 * i] *= f0; O[4 * i + 1] *= f0; O[4 * i + 2] *= f1; O[4 * i + 3] *= f1;
          }
          if (newhead) {
#pragma unroll
            for (int i = 0; i < 8; i++) {
              uint32_t o[4];
              pack8(o, O + 8 * i);
              sts128(wprv + ((n >> 2) - 1) * SLOT + i * 512, o[0], o[1], o[2], o[3]);
            }
          }
        }
        exps(4, 16);
#pragma unroll
        for (int i = 0; i < 8; i++) pack8(P[i], S + 8 * i);
        fence_regs(P);
        fence_regs(O);
      }
      {
        const uint32_t bv = ring.wait_full(3, 1);
        if (wg == 0) bar_sync(2, 256);
        wg_fence();
        static_for<0, 8>([&](auto K) { wgmma_rs_n128_tb1<LB_MN128 + K * 128, HI128>(O, P[K], bv, 1); });
        wg_commit();
        l0 += __shfl_xor_sync(0xffffffffu, l0, 1); l1 += __shfl_xor_sync(0xffffffffu, l1, 1);
        l0 += __shfl_xor_sync(0xffffffffu, l0, 2); l1 += __shfl_xor_sync(0xffffffffu, l1, 2);
        const float f0 = rcp_hw(l0), f1 = rcp_hw(l1);
        wg_wait<0>();
        fence_regs(O);
#pragma unroll
        for (int i = 0; i < 8; i++) {
          qf[i][0] = pack_bf16(O[8 * i] * f0, O[8 * i + 1] * f0); qf[i][1] = pack_bf16(O[8 * i + 2] * f1, O[8 * i + 3] * f1);
          qf[i][2] = pack_bf16(O[8 * i + 4] * f0, O[8 * i + 5] * f0); qf[i][3] = pack_bf16(O[8 * i + 6] * f1, O[8 * i + 7] * f1);
        }
      }
    }
    fence_regs(qf);
    TS(4);

    uint4* const Pout = p.s->P + ((size_t)(rt * 8 + warp) * 8 + j) * 1024;
    const uint32_t stage = sb + SM_RING + 3 * SLOT + warp * 4096;
    const uint32_t stoff = gq * 512 + (gq & 1) * 64 + q * 16;
    const uint32_t tag = *(volatile uint32_t*)(smem_raw + SM_BAR + 64);
    const uint4* const Pown = p.s->P + (size_t)(rt * 8 + j) * 8192 + warp * 32 + lane;
    const int go = gq ^ (warp & 1);
    const uint32_t xoff2 = (uint32_t)(rt * 128 + 16 * j + warp) * 256 + go * 8 + q;
    const uint32_t ooff2 = ((uint32_t)(rt * 8 + j) * 32 + go) * 32 + warp * 4 + q;
    const uint4* const mod2p = p.s->mod2 + go * 4 + q;

    auto store_partial = [&](auto TAGC, uint32_t stg, int c) {
#pragma unroll
      for (int i = 0; i < 8; i++)
        sts128(stg + (stoff ^ (i * 64)), pack_tag<TAGC>(S[8 * i], S[8 * i + 1]), pack_bf16(S[8 * i + 2], S[8 * i + 3]),
               pack_bf16(S[8 * i + 4], S[8 * i + 5]), pack_bf16(S[8 * i + 6], S[8 * i + 7]));
      warp_bulk_store(Pout + c * 256, stg, 4096);
    };
    uint32_t xr[4], ga[4], g2[4];
    float s0 = 0.f, s1 = 0.f, v0 = 0.f, v1 = 0.f;
    auto red_issue = [&](int c) {
      if (lane == 0) {
        mbar_expect(wbar + 16, 4096);
        tma3d(wblk, &tmP, wbar + 16, 0, c * 8 + warp, (rt * 8 + j) * 8);
      }
    };
    auto red1_issue = [&](int c) {
      red_issue(c);
      const uint32_t* xo = (const uint32_t*)p.x + xoff2 + c * 64;
      xr[0] = ldg32(xo); xr[1] = ldg32(xo + 8 * 256); xr[2] = ldg32(xo + 4); xr[3] = ldg32(xo + 4 + 8 * 256);
      ld_pkt(mod2p + c * 32, ga);
      ld_pkt(mod2p + 256 + c * 32, g2);
    };
    auto red1_process = [&](int c, float (&x2)[8]) {
      uint32_t r[8][4];
      if (ga[2] != tag) ld_mod(mod2p + c * 32, tag, ga);
      if (g2[2] != tag) ld_mod(mod2p + 256 + c * 32, tag, g2);
      mbar_wait(wbar + 16, (c + 1) & 1);
#pragma unroll
      for (int i = 0; i < 8; i++) lds128(wprv + i * 512, r[i]);
      verify8_tag1<16384>(Pown + c * 256, r);
      float hv[8];
#pragma unroll
      for (int e = 0; e < 4; e++) {
        float y0 = bf_lo(r[0][e]), y1 = bf_hi(r[0][e]);
#pragma unroll
        for (int s = 1; s < 8; s++) { y0 += bf_lo(r[s][e]); y1 += bf_hi(r[s][e]); }
        const float a = fmaf(bf_lo(ga[e >> 1]), y0, bf_lo(xr[e])), b = fmaf(bf_hi(ga[e >> 1]), y1, bf_hi(xr[e]));
        x2[2 * e] = a; x2[2 * e + 1] = b;
        hv[2 * e] = a * bf_lo(g2[e >> 1]); hv[2 * e + 1] = b * bf_hi(g2[e >> 1]);
        if (e & 1) { s1 += a + b; v1 = fmaf(a, a, fmaf(b, b, v1)); }
        else { s0 += a + b; v0 = fmaf(a, a, fmaf(b, b, v0)); }
      }
      st_pkt(p.s->G + ooff2 + c * 256, pack_tag<0>(hv[0], hv[1]), pack_bf16(hv[2], hv[3]), pack_bf16(hv[4], hv[5]),
             pack_bf16(hv[6], hv[7]));
    };
    auto park_x2 = [&](int c, const float (&x2)[8]) {
      sts128(wprv + SLOT + c * 1024, __float_as_uint(x2[0]), __float_as_uint(x2[1]), __float_as_uint(x2[2]),
             __float_as_uint(x2[3]));
      sts128(wprv + SLOT + c * 1024 + 512, __float_as_uint(x2[4]), __float_as_uint(x2[5]), __float_as_uint(x2[6]),
             __float_as_uint(x2[7]));
    };
    const uint4* const Gin = p.s->G + goff;
    auto g_issue = [&](int u) { warp_bulk_load(wblk + 2 * SLOT + (u & 1) * 2048, Gin + u * 128, 2048, wbar + (u & 1) * 8); };

    uint32_t rs = 0, rp = 0, b = ring.wait_full(0, 0);
    auto next_tile = [&]() {
      const uint32_t cur = rs;
      if (++rs == 3) { rs = 0; rp ^= 1; }
      b = ring.wait_full(rs, rp);
      wg_wait<0>();
      TR(4);
      ring.release(cur);
    };
    {
      uint32_t o0[8][4], a[8][4];
      float keep[8];
#pragma unroll
      for (int i = 0; i < 8; i++) lds128(wprv + i * 512, o0[i]);
#pragma unroll 1
      for (int c = 0; c < 4; c++) {
        static_for<0, 4>([&](auto HH) {
          constexpr int hh = HH;
          wg_fence();
          static_for<0, 8>([&](auto K) {
            wgmma_rs_n128_tb1<LB_MN128 + K * 128, HI128>(S, hh == 0 ? o0[K] : hh == 3 ? qf[K] : a[K], b, (hh | K) != 0);
          });
          wg_commit();
          if constexpr (hh == 0) {
#pragma unroll
            for (int i = 0; i < 8; i++) lds128(wprv + SLOT + i * 512, a[i]);
          }
          if constexpr (hh == 1) {
            if (c > 1) {
              if (c == 3) park_x2(0, keep);
              red1_process(c - 2, keep);
              if (c == 3) park_x2(1, keep);
            }
          }
          if constexpr (hh == 2) {
            if (c == 3) { g_issue(0); g_issue(1); }
          }
          if constexpr (hh == 3) {
            if (c > 0) red1_issue(c - 1);
            warp_bulk_wait_read<0>();
          }
          next_tile();
          if constexpr (hh == 1) {
            fence_regs(a);
#pragma unroll
            for (int i = 0; i < 8; i++) lds128(wprv + 2 * SLOT + i * 512, a[i]);
          }
        });
        fence_regs(S);
        store_partial(IC<1>{}, stage, c);
      }
    }
    TS(5);

    uint32_t H[14][4];
    {
      float acc[112];
      const uint4* const statp = &p.s->stat[((rt * 8 + warp) * 8 + gq) * 2];
#pragma unroll 1
      for (int u = 0; u < 8; u++) {
        uint32_t fa[4][4];
        mbar_wait(wbar + (u & 1) * 8, ((u >> 1) + (u & 1)) & 1);
#pragma unroll
        for (int i = 0; i < 4; i++) lds128(wprv + 2 * SLOT + (u & 1) * 2048 + i * 512, fa[i]);
        verify4_tag0<512>(Gin + u * 128, fa);
        TR(13);
        wg_fence();
        static_for<0, 4>([&](auto K) { wgmma_rs_n224_tb1<LB_W1 + K * 64, HI64>(acc, fa[K], b, (u | K) != 0); });
        wg_commit();
        if (u < 4) g_issue(u + 2);
        if (u == 3 && wg == 0) red1_issue(3);
        if (u == 0 || u == 4 - wg) {
          float x2[8];
          const int c = u ? 3 : 2;
          red1_process(c, x2);
          park_x2(c, x2);
          if (u) {
#pragma unroll
            for (int o = 16; o > 0; o >>= 1) {
              s0 += __shfl_xor_sync(0xffffffffu, s0, o);
              s1 += __shfl_xor_sync(0xffffffffu, s1, o);
              v0 += __shfl_xor_sync(0xffffffffu, v0, o);
              v1 += __shfl_xor_sync(0xffffffffu, v1, o);
            }
            const float m0 = s0 * (1.f / 512.f), m1 = s1 * (1.f / 512.f);
            const float r0 = 0.5f * rsqrtf(fmaxf(fmaf(-m0, m0, v0 * (1.f / 512.f)), 0.f) + 1e-5f);
            const float r1 = 0.5f * rsqrtf(fmaxf(fmaf(-m1, m1, v1 * (1.f / 512.f)), 0.f) + 1e-5f);
            if (lane < 2)
              st_pkt(&p.s->stat[((rt * 8 + j) * 8 + warp) * 2 + lane], (__float_as_uint(r0) & ~1u) | (tag & 1u),
                     __float_as_uint(-m0 * r0), __float_as_uint(r1), __float_as_uint(-m1 * r1));
          }
        }
        if (u == 7) ld_pkt(statp, xr);
        next_tile();
        if (u == 2 && wg == 1) red1_issue(3);
        if (u == 5) { g_issue(6); g_issue(7); }
      }
      fence_regs(acc);
      TS(9);
      mbar_wait(bars + 72, 0);
      {
        int spins = 0;
        while (((xr[0] ^ tag) & 1u) && ++spins < SPIN_LIMIT) ld_pkt(statp, xr);
      }
      const float ra0 = __uint_as_float(xr[0]), rb0 = __uint_as_float(xr[1]), ra1 = __uint_as_float(xr[2]),
                  rb1 = __uint_as_float(xr[3]);
#pragma unroll
      for (int i = 0; i < 28; i++) {
        uint32_t m[4];
        lds128(sb + SM_TAB + (i * 4 + q) * 16, m);
        const float u0 = __uint_as_float(m[0]), u1 = __uint_as_float(m[1]), w0 = __uint_as_float(m[2]), w1 = __uint_as_float(m[3]);
        const float z0 = fmaf(acc[4 * i], ra0, fmaf(u0, rb0, w0)), z1 = fmaf(acc[4 * i + 1], ra0, fmaf(u1, rb0, w1));
        const float z2 = fmaf(acc[4 * i + 2], ra1, fmaf(u0, rb1, w0)), z3 = fmaf(acc[4 * i + 3], ra1, fmaf(u1, rb1, w1));
        H[i >> 1][(i & 1) * 2] = pack_bf16(fmaf(z0, tanh_hw(z0), z0), fmaf(z1, tanh_hw(z1), z1));
        H[i >> 1][(i & 1) * 2 + 1] = pack_bf16(fmaf(z2, tanh_hw(z2), z2), fmaf(z3, tanh_hw(z3), z3));
      }
    }
    fence_regs(H);
    TS(10);
#pragma unroll 1
    for (int c = 0; c < 4; c++) {
      wg_fence();
      static_for<0, 7>([&](auto K) { wgmma_rs_n128_tb1<LB_W2 + K * 128, HI128>(S, H[K], b, K != 0); });
      wg_commit();
      if (c == 3) {
        red_issue(0);
        ld_pkt(mod2p + 384, ga);
      }
      next_tile();
      wg_fence();
      static_for<0, 7>([&](auto K) { wgmma_rs_n128_tb1<LB_W2 + K * 128, HI128>(S, H[7 + K], b, 1); });
      wg_commit();
      warp_bulk_wait_read<1>();
      if (c < 3) next_tile();
      wg_wait<0>();
      fence_regs(S);
      store_partial(IC<0>{}, (c & 1) ? stage : wblk + 2 * SLOT, c);
    }
    TS(11);
#pragma unroll 1
    for (int c = 0; c < 4; c++) {
      uint32_t* const oo = (uint32_t*)p.out + xoff2 + c * 64;
      uint32_t xa[2][4], r[8][4], gb[2];
      if (ga[2] != tag) ld_mod(mod2p + 384 + c * 32, tag, ga);
      gb[0] = ga[0]; gb[1] = ga[1];
      lds128(wprv + SLOT + c * 1024, xa[0]);
      lds128(wprv + SLOT + c * 1024 + 512, xa[1]);
      mbar_wait(wbar + 16, (c + 1) & 1);
#pragma unroll
      for (int i = 0; i < 8; i++) lds128(wprv + i * 512, r[i]);
      verify8_tag0<16384>(Pown + c * 256, r);
      if (c < 3) {
        red_issue(c + 1);
        ld_pkt(mod2p + 384 + (c + 1) * 32, ga);
      }
#pragma unroll
      for (int e = 0; e < 4; e++) {
        float y0 = bf_lo(r[0][e]), y1 = bf_hi(r[0][e]);
#pragma unroll
        for (int s = 1; s < 8; s++) { y0 += bf_lo(r[s][e]); y1 += bf_hi(r[s][e]); }
        oo[(e >> 1) * 4 + (e & 1) * 8 * 256] =
            pack_bf16(fmaf(bf_lo(gb[e >> 1]), y0, __uint_as_float(xa[e >> 1][(e & 1) * 2])),
                      fmaf(bf_hi(gb[e >> 1]), y1, __uint_as_float(xa[e >> 1][(e & 1) * 2 + 1])));
      }
      if (c == 1) TS(13);
      if (c == 2) TS(14);
    }
    warp_bulk_wait_read<0>();
    TS(12);
    if (bid == 0 && tid == 0) asm volatile("st.relaxed.gpu.global.u32 [%0], %1;" ::"l"(&p.s->epoch), "r"(tag) : "memory");
  }
}

typedef CUresult (*EncodeFn)(CUtensorMap*, CUtensorMapDataType, cuuint32_t, void*, const cuuint64_t*, const cuuint64_t*,
                             const cuuint32_t*, const cuuint32_t*, CUtensorMapInterleave, CUtensorMapSwizzle,
                             CUtensorMapL2promotion, CUtensorMapFloatOOBfill);

static void make_map(EncodeFn fn, CUtensorMap* tm, const void* ptr, int inner, int rows, int cols, int box_rows, int box_outer,
                     CUtensorMapSwizzle swz) {
  cuuint64_t gd[3] = {(cuuint64_t)inner, (cuuint64_t)rows, (cuuint64_t)(cols / inner)};
  cuuint64_t gs[2] = {(cuuint64_t)cols * 2, (cuuint64_t)inner * 2};
  cuuint32_t bx[3] = {(cuuint32_t)inner, (cuuint32_t)box_rows, (cuuint32_t)box_outer};
  cuuint32_t es[3] = {1, 1, 1};
  fn(tm, CU_TENSOR_MAP_DATA_TYPE_BFLOAT16, 3, const_cast<void*>(ptr), gd, gs, bx, es, CU_TENSOR_MAP_INTERLEAVE_NONE, swz,
     CU_TENSOR_MAP_L2_PROMOTION_L2_128B, CU_TENSOR_MAP_FLOAT_OOB_FILL_NONE);
}

extern "C" void kernel_launch(void* const* d_in, const int* in_sizes, int n_in, void* d_out, int out_size) {
  (void)in_sizes; (void)n_in; (void)out_size;
  void* fnp = nullptr;
  cudaDriverEntryPointQueryResult qr;
  cudaGetDriverEntryPoint("cuTensorMapEncodeTiled", &fnp, cudaEnableDefault, &qr);
  EncodeFn fn = (EncodeFn)fnp;
  CUtensorMap tmWq, tmK, tmV, tmWo, tmW1, tmW2, tmWm, tmP;
  make_map(fn, &tmWq, d_in[3], 64, 512, 4096, 128, 2, CU_TENSOR_MAP_SWIZZLE_128B);
  make_map(fn, &tmK, d_in[1], 64, 8 * SK, 128, 128, 2, CU_TENSOR_MAP_SWIZZLE_128B);
  make_map(fn, &tmV, d_in[2], 64, 8 * SK, 128, 128, 2, CU_TENSOR_MAP_SWIZZLE_128B);
  make_map(fn, &tmWo, d_in[4], 64, 4096, 512, 128, 2, CU_TENSOR_MAP_SWIZZLE_128B);
  make_map(fn, &tmW1, d_in[6], 32, 512, FF, 64, 7, CU_TENSOR_MAP_SWIZZLE_64B);
  make_map(fn, &tmW2, d_in[7], 64, FF, 512, 112, 2, CU_TENSOR_MAP_SWIZZLE_128B);
  make_map(fn, &tmWm, d_in[9], 8, 512, 3072, 256, 1, CU_TENSOR_MAP_SWIZZLE_NONE);
  Params p;
  p.x = (const __nv_bfloat16*)d_in[0];
  p.c = (const __nv_bfloat16*)d_in[8];
  p.wmod = (const __nv_bfloat16*)d_in[9];
  p.wo = (const __nv_bfloat16*)d_in[4];
  p.w1 = (const __nv_bfloat16*)d_in[6];
  p.w2 = (const __nv_bfloat16*)d_in[7];
  p.out = (__nv_bfloat16*)d_out;
  cudaGetSymbolAddress((void**)&p.s, g_scratch);
  {
    cuuint64_t gd[3] = {256, 32, 1024};
    cuuint64_t gs[2] = {512, 16384};
    cuuint32_t bx[3] = {256, 1, 8};
    cuuint32_t es[3] = {1, 1, 1};
    fn(&tmP, CU_TENSOR_MAP_DATA_TYPE_BFLOAT16, 3, (void*)p.s->P, gd, gs, bx, es, CU_TENSOR_MAP_INTERLEAVE_NONE,
       CU_TENSOR_MAP_SWIZZLE_NONE, CU_TENSOR_MAP_L2_PROMOTION_NONE, CU_TENSOR_MAP_FLOAT_OOB_FILL_NONE);
  }
  cudaFuncSetAttribute(adaln_block_kernel, cudaFuncAttributeMaxDynamicSharedMemorySize, SM_TOTAL);
  adaln_block_kernel<<<128, 384, SM_TOTAL>>>(tmWq, tmK, tmV, tmWo, tmW1, tmW2, tmWm, tmP, p);
}
```

```cpp
#include <cuda_runtime.h>
#include <cuda_bf16.h>
#include <cuda.h>
#include <stdint.h>

template <int OFF, uint32_t HI>
__device__ __forceinline__ void wgmma_rs_n128_tb0(float (&d)[64], const uint32_t (&a)[4], uint32_t lo, int sd) {
  asm volatile("{\n.reg .pred p;\n.reg .b32 l;\n.reg .b64 db;\nsetp.ne.b32 p, %69, 0;\n"
    "add.u32 l, %68, %70;\nmov.b64 db, {l, %71};\n"
    "wgmma.mma_async.sync.aligned.m64n128k16.f32.bf16.bf16 "
    "{%0,%1,%2,%3,%4,%5,%6,%7,%8,%9,%10,%11,%12,%13,%14,%15,"
    "%16,%17,%18,%19,%20,%21,%22,%23,%24,%25,%26,%27,%28,%29,%30,%31,"
    "%32,%33,%34,%35,%36,%37,%38,%39,%40,%41,%42,%43,%44,%45,%46,%47,"
    "%48,%49,%50,%51,%52,%53,%54,%55,%56,%57,%58,%59,%60,%61,%62,%63}, "
    "{%64,%65,%66,%67}, db, p, 1, 1, 0;\n}\n"
    : "+f"(d[0]), "+f"(d[1]), "+f"(d[2]), "+f"(d[3]), "+f"(d[4]), "+f"(d[5]), "+f"(d[6]), "+f"(d[7]),
      "+f"(d[8]), "+f"(d[9]), "+f"(d[10]), "+f"(d[11]), "+f"(d[12]), "+f"(d[13]), "+f"(d[14]), "+f"(d[15]),
      "+f"(d[16]), "+f"(d[17]), "+f"(d[18]), "+f"(d[19]), "+f"(d[20]), "+f"(d[21]), "+f"(d[22]), "+f"(d[23]),
      "+f"(d[24]), "+f"(d[25]), "+f"(d[26]), "+f"(d[27]), "+f"(d[28]), "+f"(d[29]), "+f"(d[30]), "+f"(d[31]),
      "+f"(d[32]), "+f"(d[33]), "+f"(d[34]), "+f"(d[35]), "+f"(d[36]), "+f"(d[37]), "+f"(d[38]), "+f"(d[39]),
      "+f"(d[40]), "+f"(d[41]), "+f"(d[42]), "+f"(d[43]), "+f"(d[44]), "+f"(d[45]), "+f"(d[46]), "+f"(d[47]),
      "+f"(d[48]), "+f"(d[49]), "+f"(d[50]), "+f"(d[51]), "+f"(d[52]), "+f"(d[53]), "+f"(d[54]), "+f"(d[55]),
      "+f"(d[56]), "+f"(d[57]), "+f"(d[58]), "+f"(d[59]), "+f"(d[60]), "+f"(d[61]), "+f"(d[62]), "+f"(d[63])
    : "r"(a[0]), "r"(a[1]), "r"(a[2]), "r"(a[3]), "r"(lo), "r"(sd), "n"(OFF), "n"(HI));
}

template <int OFF, uint32_t HI>
__device__ __forceinline__ void wgmma_rs_n128_tb1(float (&d)[64], const uint32_t (&a)[4], uint32_t lo, int sd) {
  asm volatile("{\n.reg .pred p;\n.reg .b32 l;\n.reg .b64 db;\nsetp.ne.b32 p, %69, 0;\n"
    "add.u32 l, %68, %70;\nmov.b64 db, {l, %71};\n"
    "wgmma.mma_async.sync.aligned.m64n128k16.f32.bf16.bf16 "
    "{%0,%1,%2,%3,%4,%5,%6,%7,%8,%9,%10,%11,%12,%13,%14,%15,"
    "%16,%17,%18,%19,%20,%21,%22,%23,%24,%25,%26,%27,%28,%29,%30,%31,"
    "%32,%33,%34,%35,%36,%37,%38,%39,%40,%41,%42,%43,%44,%45,%46,%47,"
    "%48,%49,%50,%51,%52,%53,%54,%55,%56,%57,%58,%59,%60,%61,%62,%63}, "
    "{%64,%65,%66,%67}, db, p, 1, 1, 1;\n}\n"
    : "+f"(d[0]), "+f"(d[1]), "+f"(d[2]), "+f"(d[3]), "+f"(d[4]), "+f"(d[5]), "+f"(d[6]), "+f"(d[7]),
      "+f"(d[8]), "+f"(d[9]), "+f"(d[10]), "+f"(d[11]), "+f"(d[12]), "+f"(d[13]), "+f"(d[14]), "+f"(d[15]),
      "+f"(d[16]), "+f"(d[17]), "+f"(d[18]), "+f"(d[19]), "+f"(d[20]), "+f"(d[21]), "+f"(d[22]), "+f"(d[23]),
      "+f"(d[24]), "+f"(d[25]), "+f"(d[26]), "+f"(d[27]), "+f"(d[28]), "+f"(d[29]), "+f"(d[30]), "+f"(d[31]),
      "+f"(d[32]), "+f"(d[33]), "+f"(d[34]), "+f"(d[35]), "+f"(d[36]), "+f"(d[37]), "+f"(d[38]), "+f"(d[39]),
      "+f"(d[40]), "+f"(d[41]), "+f"(d[42]), "+f"(d[43]), "+f"(d[44]), "+f"(d[45]), "+f"(d[46]), "+f"(d[47]),
      "+f"(d[48]), "+f"(d[49]), "+f"(d[50]), "+f"(d[51]), "+f"(d[52]), "+f"(d[53]), "+f"(d[54]), "+f"(d[55]),
      "+f"(d[56]), "+f"(d[57]), "+f"(d[58]), "+f"(d[59]), "+f"(d[60]), "+f"(d[61]), "+f"(d[62]), "+f"(d[63])
    : "r"(a[0]), "r"(a[1]), "r"(a[2]), "r"(a[3]), "r"(lo), "r"(sd), "n"(OFF), "n"(HI));
}

template <int OFF, uint32_t HI>
__device__ __forceinline__ void wgmma_rs_n224_tb1(float (&d)[112], const uint32_t (&a)[4], uint32_t lo, int sd) {
  asm volatile("{\n.reg .pred p;\n.reg .b32 l;\n.reg .b64 db;\nsetp.ne.b32 p, %117, 0;\n"
    "add.u32 l, %116, %118;\nmov.b64 db, {l, %119};\n"
    "wgmma.mma_async.sync.aligned.m64n224k16.f32.bf16.bf16 "
    "{%0,%1,%2,%3,%4,%5,%6,%7,%8,%9,%10,%11,%12,%13,%14,%15,"
    "%16,%17,%18,%19,%20,%21,%22,%23,%24,%25,%26,%27,%28,%29,%30,%31,"
    "%32,%33,%34,%35,%36,%37,%38,%39,%40,%41,%42,%43,%44,%45,%46,%47,"
    "%48,%49,%50,%51,%52,%53,%54,%55,%56,%57,%58,%59,%60,%61,%62,%63,"
    "%64,%65,%66,%67,%68,%69,%70,%71,%72,%73,%74,%75,%76,%77,%78,%79,"
    "%80,%81,%82,%83,%84,%85,%86,%87,%88,%89,%90,%91,%92,%93,%94,%95,"
    "%96,%97,%98,%99,%100,%101,%102,%103,%104,%105,%106,%107,%108,%109,%110,%111}, "
    "{%112,%113,%114,%115}, db, p, 1, 1, 1;\n}\n"
    : "+f"(d[0]), "+f"(d[1]), "+f"(d[2]), "+f"(d[3]), "+f"(d[4]), "+f"(d[5]), "+f"(d[6]), "+f"(d[7]),
      "+f"(d[8]), "+f"(d[9]), "+f"(d[10]), "+f"(d[11]), "+f"(d[12]), "+f"(d[13]), "+f"(d[14]), "+f"(d[15]),
      "+f"(d[16]), "+f"(d[17]), "+f"(d[18]), "+f"(d[19]), "+f"(d[20]), "+f"(d[21]), "+f"(d[22]), "+f"(d[23]),
      "+f"(d[24]), "+f"(d[25]), "+f"(d[26]), "+f"(d[27]), "+f"(d[28]), "+f"(d[29]), "+f"(d[30]), "+f"(d[31]),
      "+f"(d[32]), "+f"(d[33]), "+f"(d[34]), "+f"(d[35]), "+f"(d[36]), "+f"(d[37]), "+f"(d[38]), "+f"(d[39]),
      "+f"(d[40]), "+f"(d[41]), "+f"(d[42]), "+f"(d[43]), "+f"(d[44]), "+f"(d[45]), "+f"(d[46]), "+f"(d[47]),
      "+f"(d[48]), "+f"(d[49]), "+f"(d[50]), "+f"(d[51]), "+f"(d[52]), "+f"(d[53]), "+f"(d[54]), "+f"(d[55]),
      "+f"(d[56]), "+f"(d[57]), "+f"(d[58]), "+f"(d[59]), "+f"(d[60]), "+f"(d[61]), "+f"(d[62]), "+f"(d[63]),
      "+f"(d[64]), "+f"(d[65]), "+f"(d[66]), "+f"(d[67]), "+f"(d[68]), "+f"(d[69]), "+f"(d[70]), "+f"(d[71]),
      "+f"(d[72]), "+f"(d[73]), "+f"(d[74]), "+f"(d[75]), "+f"(d[76]), "+f"(d[77]), "+f"(d[78]), "+f"(d[79]),
      "+f"(d[80]), "+f"(d[81]), "+f"(d[82]), "+f"(d[83]), "+f"(d[84]), "+f"(d[85]), "+f"(d[86]), "+f"(d[87]),
      "+f"(d[88]), "+f"(d[89]), "+f"(d[90]), "+f"(d[91]), "+f"(d[92]), "+f"(d[93]), "+f"(d[94]), "+f"(d[95]),
      "+f"(d[96]), "+f"(d[97]), "+f"(d[98]), "+f"(d[99]), "+f"(d[100]), "+f"(d[101]), "+f"(d[102]), "+f"(d[103]),
      "+f"(d[104]), "+f"(d[105]), "+f"(d[106]), "+f"(d[107]), "+f"(d[108]), "+f"(d[109]), "+f"(d[110]), "+f"(d[111])
    : "r"(a[0]), "r"(a[1]), "r"(a[2]), "r"(a[3]), "r"(lo), "r"(sd), "n"(OFF), "n"(HI));
}

template <int OFF, uint32_t HI>
__device__ __forceinline__ void wgmma_rs_n64_tb1(float (&d)[32], const uint32_t (&a)[4], uint32_t lo, int sd) {
  asm volatile("{\n.reg .pred p;\n.reg .b32 l;\n.reg .b64 db;\nsetp.ne.b32 p, %37, 0;\n"
    "add.u32 l, %36, %38;\nmov.b64 db, {l, %39};\n"
    "wgmma.mma_async.sync.aligned.m64n64k16.f32.bf16.bf16 "
    "{%0,%1,%2,%3,%4,%5,%6,%7,%8,%9,%10,%11,%12,%13,%14,%15,"
    "%16,%17,%18,%19,%20,%21,%22,%23,%24,%25,%26,%27,%28,%29,%30,%31}, "
    "{%32,%33,%34,%35}, db, p, 1, 1, 1;\n}\n"
    : "+f"(d[0]), "+f"(d[1]), "+f"(d[2]), "+f"(d[3]), "+f"(d[4]), "+f"(d[5]), "+f"(d[6]), "+f"(d[7]),
      "+f"(d[8]), "+f"(d[9]), "+f"(d[10]), "+f"(d[11]), "+f"(d[12]), "+f"(d[13]), "+f"(d[14]), "+f"(d[15]),
      "+f"(d[16]), "+f"(d[17]), "+f"(d[18]), "+f"(d[19]), "+f"(d[20]), "+f"(d[21]), "+f"(d[22]), "+f"(d[23]),
      "+f"(d[24]), "+f"(d[25]), "+f"(d[26]), "+f"(d[27]), "+f"(d[28]), "+f"(d[29]), "+f"(d[30]), "+f"(d[31])
    : "r"(a[0]), "r"(a[1]), "r"(a[2]), "r"(a[3]), "r"(lo), "r"(sd), "n"(OFF), "n"(HI));
}

template <int STR>
__device__ __forceinline__ void verify8_tag1(const uint4* p, uint32_t (*r)[4]) {
  asm volatile("{\n.reg .pred p, q;\n.reg .b32 a, n;\nmov.u32 n, 0;\n"
    "LAB_CHK:\n"
    "and.b32 a, %0, %4;\n"
    "and.b32 a, a, %8;\n"
    "and.b32 a, a, %12;\n"
    "and.b32 a, a, %16;\n"
    "and.b32 a, a, %20;\n"
    "and.b32 a, a, %24;\n"
    "and.b32 a, a, %28;\n"
    "and.b32 a, a, 1;\nsetp.eq.u32 p, a, 1;\nvote.sync.all.pred p, p, 0xffffffff;\n"
    "@p bra.uni LAB_OK;\n"
    "and.b32 a, %0, 1;\nsetp.ne.u32 q, a, 1;\n"
    "@q ld.relaxed.gpu.global.v4.b32 {%0,%1,%2,%3}, [%32+%33];\n"
    "and.b32 a, %4, 1;\nsetp.ne.u32 q, a, 1;\n"
    "@q ld.relaxed.gpu.global.v4.b32 {%4,%5,%6,%7}, [%32+%34];\n"
    "and.b32 a, %8, 1;\nsetp.ne.u32 q, a, 1;\n"
    "@q ld.relaxed.gpu.global.v4.b32 {%8,%9,%10,%11}, [%32+%35];\n"
    "and.b32 a, %12, 1;\nsetp.ne.u32 q, a, 1;\n"
    "@q ld.relaxed.gpu.global.v4.b32 {%12,%13,%14,%15}, [%32+%36];\n"
    "and.b32 a, %16, 1;\nsetp.ne.u32 q, a, 1;\n"
    "@q ld.relaxed.gpu.global.v4.b32 {%16,%17,%18,%19}, [%32+%37];\n"
    "and.b32 a, %20, 1;\nsetp.ne.u32 q, a, 1;\n"
    "@q ld.relaxed.gpu.global.v4.b32 {%20,%21,%22,%23}, [%32+%38];\n"
    "and.b32 a, %24, 1;\nsetp.ne.u32 q, a, 1;\n"
    "@q ld.relaxed.gpu.global.v4.b32 {%24,%25,%26,%27}, [%32+%39];\n"
    "and.b32 a, %28, 1;\nsetp.ne.u32 q, a, 1;\n"
    "@q ld.relaxed.gpu.global.v4.b32 {%28,%29,%30,%31}, [%32+%40];\n"
    "add.u32 n, n, 1;\nsetp.lt.u32 q, n, 262144;\n@q bra.uni LAB_CHK;\n"
    "LAB_OK:\n"
    "}\n"
    : "+r"(r[0][0]), "+r"(r[0][1]), "+r"(r[0][2]), "+r"(r[0][3]), "+r"(r[1][0]), "+r"(r[1][1]), "+r"(r[1][2]), "+r"(r[1][3]),
      "+r"(r[2][0]), "+r"(r[2][1]), "+r"(r[2][2]), "+r"(r[2][3]), "+r"(r[3][0]), "+r"(r[3][1]), "+r"(r[3][2]), "+r"(r[3][3]),
      "+r"(r[4][0]), "+r"(r[4][1]), "+r"(r[4][2]), "+r"(r[4][3]), "+r"(r[5][0]), "+r"(r[5][1]), "+r"(r[5][2]), "+r"(r[5][3]),
      "+r"(r[6][0]), "+r"(r[6][1]), "+r"(r[6][2]), "+r"(r[6][3]), "+r"(r[7][0]), "+r"(r[7][1]), "+r"(r[7][2]), "+r"(r[7][3])
    : "l"(p), "n"(0 * STR), "n"(1 * STR), "n"(2 * STR), "n"(3 * STR), "n"(4 * STR), "n"(5 * STR), "n"(6 * STR), "n"(7 * STR)
    : "memory");
}

template <int STR>
__device__ __forceinline__ void verify4_tag1(const uint4* p, uint32_t (*r)[4]) {
  asm volatile("{\n.reg .pred p, q;\n.reg .b32 a, n;\nmov.u32 n, 0;\n"
    "LAB_CHK:\n"
    "and.b32 a, %0, %4;\n"
    "and.b32 a, a, %8;\n"
    "and.b32 a, a, %12;\n"
    "and.b32 a, a, 1;\nsetp.eq.u32 p, a, 1;\nvote.sync.all.pred p, p, 0xffffffff;\n"
    "@p bra.uni LAB_OK;\n"
    "and.b32 a, %0, 1;\nsetp.ne.u32 q, a, 1;\n"
    "@q ld.relaxed.gpu.global.v4.b32 {%0,%1,%2,%3}, [%16+%17];\n"
    "and.b32 a, %4, 1;\nsetp.ne.u32 q, a, 1;\n"
    "@q ld.relaxed.gpu.global.v4.b32 {%4,%5,%6,%7}, [%16+%18];\n"
    "and.b32 a, %8, 1;\nsetp.ne.u32 q, a, 1;\n"
    "@q ld.relaxed.gpu.global.v4.b32 {%8,%9,%10,%11}, [%16+%19];\n"
    "and.b32 a, %12, 1;\nsetp.ne.u32 q, a, 1;\n"
    "@q ld.relaxed.gpu.global.v4.b32 {%12,%13,%14,%15}, [%16+%20];\n"
    "add.u32 n, n, 1;\nsetp.lt.u32 q, n, 262144;\n@q bra.uni LAB_CHK;\n"
    "LAB_OK:\n"
    "}\n"
    : "+r"(r[0][0]), "+r"(r[0][1]), "+r"(r[0][2]), "+r"(r[0][3]), "+r"(r[1][0]), "+r"(r[1][1]), "+r"(r[1][2]), "+r"(r[1][3]),
      "+r"(r[2][0]), "+r"(r[2][1]), "+r"(r[2][2]), "+r"(r[2][3]), "+r"(r[3][0]), "+r"(r[3][1]), "+r"(r[3][2]), "+r"(r[3][3])
    : "l"(p), "n"(0 * STR), "n"(1 * STR), "n"(2 * STR), "n"(3 * STR)
    : "memory");
}

template <int STR>
__device__ __forceinline__ void verify4_tag0(const uint4* p, uint32_t (*r)[4]) {
  asm volatile("{\n.reg .pred p, q;\n.reg .b32 a, n;\nmov.u32 n, 0;\n"
    "LAB_CHK:\n"
    "or.b32 a, %0, %4;\n"
    "or.b32 a, a, %8;\n"
    "or.b32 a, a, %12;\n"
    "and.b32 a, a, 1;\nsetp.eq.u32 p, a, 0;\nvote.sync.all.pred p, p, 0xffffffff;\n"
    "@p bra.uni LAB_OK;\n"
    "and.b32 a, %0, 1;\nsetp.ne.u32 q, a, 0;\n"
    "@q ld.relaxed.gpu.global.v4.b32 {%0,%1,%2,%3}, [%16+%17];\n"
    "and.b32 a, %4, 1;\nsetp.ne.u32 q, a, 0;\n"
    "@q ld.relaxed.gpu.global.v4.b32 {%4,%5,%6,%7}, [%16+%18];\n"
    "and.b32 a, %8, 1;\nsetp.ne.u32 q, a, 0;\n"
    "@q ld.relaxed.gpu.global.v4.b32 {%8,%9,%10,%11}, [%16+%19];\n"
    "and.b32 a, %12, 1;\nsetp.ne.u32 q, a, 0;\n"
    "@q ld.relaxed.gpu.global.v4.b32 {%12,%13,%14,%15}, [%16+%20];\n"
    "add.u32 n, n, 1;\nsetp.lt.u32 q, n, 262144;\n@q bra.uni LAB_CHK;\n"
    "LAB_OK:\n"
    "or.b32 %0, %0, 1;\n"
    "or.b32 %4, %4, 1;\n"
    "or.b32 %8, %8, 1;\n"
    "or.b32 %12, %12, 1;\n"
    "}\n"
    : "+r"(r[0][0]), "+r"(r[0][1]), "+r"(r[0][2]), "+r"(r[0][3]), "+r"(r[1][0]), "+r"(r[1][1]), "+r"(r[1][2]), "+r"(r[1][3]),
      "+r"(r[2][0]), "+r"(r[2][1]), "+r"(r[2][2]), "+r"(r[2][3]), "+r"(r[3][0]), "+r"(r[3][1]), "+r"(r[3][2]), "+r"(r[3][3])
    : "l"(p), "n"(0 * STR), "n"(1 * STR), "n"(2 * STR), "n"(3 * STR)
    : "memory");
}

#define SPIN_LIMIT (1 << 18)

__device__ __forceinline__ uint32_t smem_u32(const void* p) { return (uint32_t)__cvta_generic_to_shared(p); }
__device__ __forceinline__ void mbar_init(uint32_t a, uint32_t c) {
  asm volatile("mbarrier.init.shared::cta.b64 [%0], %1;" ::"r"(a), "r"(c) : "memory");
}
__device__ __forceinline__ void mbar_expect(uint32_t a, uint32_t b) {
  asm volatile("mbarrier.arrive.expect_tx.shared::cta.b64 _, [%0], %1;" ::"r"(a), "r"(b) : "memory");
}
__device__ __forceinline__ void mbar_arrive(uint32_t a) {
  asm volatile("mbarrier.arrive.shared::cta.b64 _, [%0];" ::"r"(a) : "memory");
}
__device__ __forceinline__ void mbar_wait(uint32_t a, uint32_t parity) {
  asm volatile(
      "{\n.reg .pred p;\n.reg .u32 n;\nmov.u32 n, 0;\n"
      "LAB_WAIT:\n"
      "mbarrier.try_wait.parity.shared::cta.b64 p, [%0], %1;\n"
      "@p bra LAB_DONE;\n"
      "add.u32 n, n, 1;\n"
      "setp.lt.u32 p, n, 262144;\n"
      "@p bra LAB_WAIT;\n"
      "LAB_DONE:\n}\n" ::"r"(a), "r"(parity) : "memory");
}
__device__ __forceinline__ bool mbar_test(uint32_t a, uint32_t parity) {
  uint32_t ok;
  asm volatile("{\n.reg .pred p;\nmbarrier.test_wait.parity.shared::cta.b64 p, [%1], %2;\nselp.u32 %0, 1, 0, p;\n}\n"
               : "=r"(ok) : "r"(a), "r"(parity) : "memory");
  return ok;
}
__device__ __forceinline__ void tma3d(uint32_t dst, const CUtensorMap* tm, uint32_t bar, int c0, int c1, int c2) {
  asm volatile(
      "cp.async.bulk.tensor.3d.shared::cluster.global.mbarrier::complete_tx::bytes [%0], [%1, {%3,%4,%5}], [%2];"
      ::"r"(dst), "l"(tm), "r"(bar), "r"(c0), "r"(c1), "r"(c2) : "memory");
}
__device__ __forceinline__ void wg_fence() { asm volatile("wgmma.fence.sync.aligned;" ::: "memory"); }
__device__ __forceinline__ void wg_commit() { asm volatile("wgmma.commit_group.sync.aligned;" ::: "memory"); }
template <int N> __device__ __forceinline__ void wg_wait() {
  asm volatile("wgmma.wait_group.sync.aligned %0;" ::"n"(N) : "memory");
}
template <int N> __device__ __forceinline__ void fence_regs(float (&d)[N]) {
#pragma unroll
  for (int i = 0; i < N; i++) asm volatile("" : "+f"(d[i])::"memory");
}
template <int N> __device__ __forceinline__ void fence_regs(uint32_t (&d)[N][4]) {
#pragma unroll
  for (int i = 0; i < N; i++) asm volatile("" : "+r"(d[i][0]), "+r"(d[i][1]), "+r"(d[i][2]), "+r"(d[i][3])::"memory");
}
template <int N> __device__ __forceinline__ void fence_frags(uint32_t (*d)[4]) {
#pragma unroll
  for (int i = 0; i < N; i++) asm volatile("" : "+r"(d[i][0]), "+r"(d[i][1]), "+r"(d[i][2]), "+r"(d[i][3])::"memory");
}
__device__ __forceinline__ void bar_sync(int id, int n) { asm volatile("bar.sync %0, %1;" ::"r"(id), "r"(n) : "memory"); }
__device__ __forceinline__ void bar_arrive(int id, int n) { asm volatile("bar.arrive %0, %1;" ::"r"(id), "r"(n) : "memory"); }

__device__ __forceinline__ uint32_t pack_bf16(float lo, float hi) {
  uint32_t r;
  asm("cvt.rn.bf16x2.f32 %0, %1, %2;" : "=r"(r) : "f"(hi), "f"(lo));
  return r;
}
__device__ __forceinline__ float bf_lo(uint32_t w) { return __uint_as_float(w << 16); }
__device__ __forceinline__ float bf_hi(uint32_t w) { return __uint_as_float(w & 0xFFFF0000u); }
__device__ __forceinline__ float round_bf16(float x) { return bf_lo(pack_bf16(x, 0.f)); }
__device__ __forceinline__ uint32_t hfma2_bf16(uint32_t a, uint32_t b, uint32_t c) {
  uint32_t r;
  asm("fma.rn.bf16x2 %0, %1, %2, %3;" : "=r"(r) : "r"(a), "r"(b), "r"(c));
  return r;
}
__device__ __forceinline__ float ex2(float x) {
  float r;
  asm("ex2.approx.ftz.f32 %0, %1;" : "=f"(r) : "f"(x));
  return r;
}
__device__ __forceinline__ float tanh_hw(float x) {
  float r;
  asm("tanh.approx.f32 %0, %1;" : "=f"(r) : "f"(x));
  return r;
}
template <int TAG> __device__ __forceinline__ uint32_t pack_tag(float lo, float hi) {
  uint32_t w = __byte_perm(__float_as_uint(lo), pack_bf16(lo, hi), 0x7632);
  return TAG ? (w | 1u) : (w & ~1u);
}
__device__ __forceinline__ void st_pkt(uint4* p, uint32_t a, uint32_t b, uint32_t c, uint32_t d) {
  asm volatile(
      "st.relaxed.gpu.global.v4.b32 [%0], {%1,%2,%3,%4};" ::"l"(p), "r"(a), "r"(b), "r"(c), "r"(d) : "memory");
}
__device__ __forceinline__ void ld_pkt(const uint4* p, uint32_t (&r)[4]) {
  asm volatile(
      "ld.relaxed.gpu.global.v4.b32 {%0,%1,%2,%3}, [%4];"
      : "=r"(r[0]), "=r"(r[1]), "=r"(r[2]), "=r"(r[3]) : "l"(p) : "memory");
}
__device__ __forceinline__ uint32_t ldg32(const void* p) {
  uint32_t r;
  asm volatile("ld.global.nc.b32 %0, [%1];" : "=r"(r) : "l"(p));
  return r;
}
__device__ __forceinline__ uint32_t ldg16(const void* p) {
  uint16_t r;
  asm volatile("ld.global.nc.b16 %0, [%1];" : "=h"(r) : "l"(p));
  return r;
}
__device__ __forceinline__ uint4 ldg128(const void* p) {
  uint4 r;
  asm volatile("ld.global.nc.v4.b32 {%0,%1,%2,%3}, [%4];" : "=r"(r.x), "=r"(r.y), "=r"(r.z), "=r"(r.w) : "l"(p));
  return r;
}
__device__ __forceinline__ void l2_prefetch(const void* p, uint32_t bytes) {
  asm volatile("cp.async.bulk.prefetch.L2.global [%0], %1;" ::"l"(p), "r"(bytes) : "memory");
}
__device__ __forceinline__ float rcp_hw(float x) {
  float r;
  asm("rcp.approx.ftz.f32 %0, %1;" : "=f"(r) : "f"(x));
  return r;
}
__device__ __forceinline__ void warp_bulk_load(uint32_t sdst, const void* gsrc, uint32_t bytes, uint32_t bar) {
  if ((threadIdx.x & 31) == 0) {
    mbar_expect(bar, bytes);
    asm volatile("cp.async.bulk.shared::cluster.global.mbarrier::complete_tx::bytes [%0], [%1], %2, [%3];"
                 ::"r"(sdst), "l"(gsrc), "r"(bytes), "r"(bar) : "memory");
  }
}
__device__ __forceinline__ void spin_cycles(uint32_t n) {
  uint32_t t0, t;
  asm volatile("mov.u32 %0, %%clock;" : "=r"(t0));
  do { asm volatile("mov.u32 %0, %%clock;" : "=r"(t)); } while (t - t0 < n);
}
__device__ __forceinline__ void sts128(uint32_t a, uint32_t x, uint32_t y, uint32_t z, uint32_t w) {
  asm volatile("st.shared.v4.b32 [%0], {%1,%2,%3,%4};" ::"r"(a), "r"(x), "r"(y), "r"(z), "r"(w) : "memory");
}
__device__ __forceinline__ void lds128(uint32_t a, uint32_t (&r)[4]) {
  asm volatile("ld.shared.v4.b32 {%0,%1,%2,%3}, [%4];" : "=r"(r[0]), "=r"(r[1]), "=r"(r[2]), "=r"(r[3]) : "r"(a) : "memory");
}

constexpr int SK = 2048, WIN = 512;
constexpr int FF = 1792, FSL = 224;
constexpr int NTILES = 80;
constexpr int NSLOT = 4;
constexpr uint32_t SLOT = 32768;
constexpr uint32_t SM_PARK = 0;
constexpr uint32_t SM_RING = 3 * SLOT;
constexpr uint32_t SM_TAB = 7 * SLOT;
constexpr uint32_t SM_RED = SM_TAB + 2048;
constexpr uint32_t SM_BAR = SM_RED + 256;
constexpr uint32_t SM_WBAR = SM_BAR + 128;
constexpr uint32_t SM_TOTAL = SM_WBAR + 192;

struct Scratch {
  uint4 P[16 * 8 * 8 * 1024];
  uint4 G[16 * 8 * 32 * 32];
  uint4 mod1[8 * 256];
  uint4 mod2[512];
  uint4 uv[2 * 448];
  uint4 stat[16 * 8 * 8];
  uint32_t epoch;
};
__device__ Scratch g_scratch;

#define TS(i) do { } while (0)
#define TR(code)
#define CK_(v)
#define CKS(i, v)

struct Params {
  const __nv_bfloat16* x;
  const __nv_bfloat16* c;
  const __nv_bfloat16* wmod;
  const __nv_bfloat16* wo;
  const __nv_bfloat16* w1;
  const __nv_bfloat16* w2;
  __nv_bfloat16* out;
  Scratch* s;
};

constexpr uint32_t HI128 = (1024 >> 4) | (1u << 30);
constexpr uint32_t HI64 = (512 >> 4) | (2u << 30);
constexpr int LB_MN128 = (16384 >> 4) << 16;
constexpr int LB_K128 = 1 << 16;
constexpr int LB_W1 = (4096 >> 4) << 16;

template <int I> struct IC {
  __host__ __device__ constexpr operator int() const { return I; }
};
template <int I, int N, typename F> __device__ __forceinline__ void static_for(F&& f) {
  if constexpr (I < N) {
    f(IC<I>{});
    static_for<I + 1, N>(f);
  }
}

struct Ring {
  uint32_t base16, bars;
  __device__ __forceinline__ uint32_t wait_full(uint32_t slot, uint32_t parity) const {
    mbar_wait(bars + slot * 8, parity);
    return base16 + slot * (SLOT >> 4);
  }
  __device__ __forceinline__ void release(uint32_t slot) const {
    if ((threadIdx.x & 31) == 0) mbar_arrive(bars + 32 + slot * 8);
  }
};

__device__ __forceinline__ float silu_c(uint32_t bits) {
  float x = bf_lo(bits);
  return round_bf16(x * rcp_hw(1.f + ex2(-1.4426950408889634f * x)));
}
__device__ __forceinline__ void pack8(uint32_t (&o)[4], const float* v) {
  o[0] = pack_bf16(v[0], v[1]); o[1] = pack_bf16(v[2], v[3]); o[2] = pack_bf16(v[4], v[5]); o[3] = pack_bf16(v[6], v[7]);
}

template <int TAG, int N>
__device__ __forceinline__ void issue_pkts(const uint4* p, int stride, uint32_t (*r)[4]) {
#pragma unroll
  for (int i = 0; i < N; i++) ld_pkt(p + i * stride, r[i]);
}
__device__ __forceinline__ void ld_mod(const uint4* p, uint32_t tag, uint32_t (&r)[4]) {
  int spins = 0;
  ld_pkt(p, r);
  while (r[2] != tag && ++spins < SPIN_LIMIT) ld_pkt(p, r);
}

#define EARLY_TILES 2
#define PF_WMOD 1
#define MOD1_DELAY 500
#define RED3_UNIT 3
#define JLO 2
#define G_DELAY 0

__global__ void __launch_bounds__(384, 1)
adaln_block_kernel(const __grid_constant__ CUtensorMap tmWq, const __grid_constant__ CUtensorMap tmK,
                   const __grid_constant__ CUtensorMap tmV, const __grid_constant__ CUtensorMap tmWo,
                   const __grid_constant__ CUtensorMap tmW1, const __grid_constant__ CUtensorMap tmW2,
                   const __grid_constant__ CUtensorMap tmWm, const __grid_constant__ CUtensorMap tmP, const Params p) {
  extern __shared__ __align__(1024) uint8_t smem_raw[];
  const uint32_t sb = smem_u32(smem_raw);
  const int tid = threadIdx.x, lane = tid & 31;
  const int warp = __shfl_sync(0xffffffffu, tid >> 5, 0);
  const int bid = blockIdx.x;
  const int j = ((bid >> (4 + JLO)) << JLO) | (bid & ((1 << JLO) - 1)), rt = (bid >> JLO) & 15;
  const uint32_t bars = sb + SM_BAR;

  if (warp >= 8) {
    CK_(c0);
    asm volatile("setmaxnreg.dec.sync.aligned.u32 40;");
    CK_(c1);
    const int t = tid - 256;
    uint32_t tag;
    {
      uint32_t cb[4];
      if (t == 0) {
        mbar_init(bars + 80, 1);
        asm volatile("fence.mbarrier_init.release.cluster;" ::: "memory");
        mbar_expect(bars + 80, 8192);
        tma3d(sb + SM_RING + 3 * SLOT, &tmWm, bars + 80, 0, 0, bid);
        tma3d(sb + SM_RING + 3 * SLOT + 4096, &tmWm, bars + 80, 0, 256, bid);
        asm volatile("prefetch.tensormap [%0];" ::"l"(&tmWq) : "memory");
        for (int i = 0; i < NSLOT; i++) { mbar_init(bars + i * 8, 1); mbar_init(bars + 32 + i * 8, 8); }
        mbar_init(bars + 72, 2);
        mbar_init(bars + 88, 8);
        for (int i = 0; i < 24; i++) mbar_init(sb + SM_WBAR + i * 8, 1);
        asm volatile("fence.mbarrier_init.release.cluster;" ::: "memory");
      }
      __syncwarp();
      CK_(c2);
#pragma unroll
      for (int i = 0; i < 4; i++) cb[i] = ldg16(p.c + t + 128 * i);
      asm volatile("ld.relaxed.gpu.global.u32 %0, [%1];" : "=r"(tag) : "l"(&p.s->epoch) : "memory");
      bar_sync(5, 128);
      tag += 1;
      float a[8], sc[4];
#pragma unroll
      for (int i = 0; i < 4; i++) sc[i] = silu_c(cb[i]);
#pragma unroll
      for (int k = 0; k < 8; k++) a[k] = 0.f;
      mbar_wait(bars + 80, 0);
      CK_(c3);
#pragma unroll
      for (int i = 0; i < 4; i++) {
        uint32_t w[4];
        lds128(sb + SM_RING + 3 * SLOT + (t + 128 * i) * 16, w);
#pragma unroll
        for (int e = 0; e < 4; e++) {
          a[2 * e] = fmaf(sc[i], bf_lo(w[e]), a[2 * e]);
          a[2 * e + 1] = fmaf(sc[i], bf_hi(w[e]), a[2 * e + 1]);
        }
      }
      const bool h16 = lane & 16, h8 = lane & 8, h4 = lane & 4;
#pragma unroll
      for (int k = 0; k < 4; k++) {
        float send = h16 ? a[k] : a[k + 4], keep = h16 ? a[k + 4] : a[k];
        a[k] = keep + __shfl_xor_sync(0xffffffffu, send, 16);
      }
#pragma unroll
      for (int k = 0; k < 2; k++) {
        float send = h8 ? a[k] : a[k + 2], keep = h8 ? a[k + 2] : a[k];
        a[k] = keep + __shfl_xor_sync(0xffffffffu, send, 8);
      }
      {
        float send = h4 ? a[0] : a[1], keep = h4 ? a[1] : a[0];
        a[0] = keep + __shfl_xor_sync(0xffffffffu, send, 4);
      }
      a[0] += __shfl_xor_sync(0xffffffffu, a[0], 2);
      a[0] += __shfl_xor_sync(0xffffffffu, a[0], 1);
      float* red = (float*)(smem_raw + SM_RED);
      if ((lane & 3) == 0) red[(warp - 8) * 8 + (lane >> 2)] = a[0];
      if (t == 0) *(uint32_t*)(smem_raw + SM_BAR + 64) = tag;
      CK_(c4);
      bar_sync(5, 128);
      bar_arrive(7, 384);
      CK_(c5);
      if (t == 0) {
#pragma unroll
        for (int i = 0; i < EARLY_TILES; i++) {
          mbar_expect(bars + i * 8, SLOT);
          tma3d(sb + SM_RING + i * SLOT, &tmWq, bars + i * 8, 0, i * 128, (j * 4 + 1) * 2);
        }
      }
      if (warp == 9) {
        const int cl = lane & 7;
        float v = round_bf16(red[cl] + red[8 + cl] + red[16 + cl] + red[24 + cl]);
        if (bid >= 64) v = 1.f + v;
        float vn = __shfl_down_sync(0xffffffffu, v, 1);
        uint32_t wd = pack_bf16(v, vn);
        uint32_t w0 = __shfl_sync(0xffffffffu, wd, (lane & 1) * 4);
        uint32_t w1 = __shfl_sync(0xffffffffu, wd, (lane & 1) * 4 + 2);
        if (lane < 16) st_pkt(&p.s->mod1[(lane >> 1) * 256 + bid * 2 + (lane & 1)], w0, w1, tag, 0);
      }
      uint32_t r0[4], r1[4];
      const uint4* src = &p.s->mod1[j * 256 + t];
      CK_(c6);
      spin_cycles(MOD1_DELAY);
      CK_(c7);
      int spins = 0;
      do {
        ld_pkt(src, r0);
        ld_pkt(src + 128, r1);
      } while ((r0[2] != tag || r1[2] != tag) && ++spins < SPIN_LIMIT);
      const int g = t >> 2, pp = (t & 3) * 2;
      const uint32_t ad = sb + SM_TAB + (uint32_t)(g * 4 + (pp & 3)) * 16 + (pp >> 2) * 4;
      asm volatile("st.shared.b32 [%0], %1;" ::"r"(ad + 8), "r"(r0[0]) : "memory");
      asm volatile("st.shared.b32 [%0], %1;" ::"r"(ad + 24), "r"(r0[1]) : "memory");
      asm volatile("st.shared.b32 [%0], %1;" ::"r"(ad), "r"(r1[0]) : "memory");
      asm volatile("st.shared.b32 [%0], %1;" ::"r"(ad + 16), "r"(r1[1]) : "memory");
      bar_arrive(1, 384);
      CK_(c8);
      CKS(0, c0); CKS(1, c1); CKS(2, c2); CKS(3, c3); CKS(4, c4); CKS(5, c5); CKS(6, c6); CKS(7, c7); CKS(8, c8);
    }
    if (warp == 8) {
      if (lane == 0) {
        uint32_t s = EARLY_TILES & 3, ph = 1 ^ (EARLY_TILES >> 2);
#pragma unroll 1
        for (int tt = EARLY_TILES; tt < NTILES; tt++) {
          const CUtensorMap* tm;
          int c1, c2;
          uint32_t bytes = SLOT;
          if (tt < 16) {
            tm = &tmWq; c1 = (tt & 3) * 128; c2 = (j * 4 + (((tt >> 2) + 1) & 3)) * 2;
          } else if (tt < 48) {
            const int u = tt - 16;
            const bool isK = (u == 0) || ((u & 1) && u != 31);
            const int n = isK ? ((u + 1) >> 1) : (u == 31 ? 15 : (u >> 1) - 1);
            tm = isK ? &tmK : &tmV; c1 = j * SK + (SK - WIN) + (n & 3) * 128; c2 = 0;
          } else if (tt < 64) {
            const int u = tt - 48;
            tm = &tmWo; c1 = j * 512 + (u & 1) * 256; c2 = u >> 1;
          } else if (tt < 72) {
            tm = &tmW1; c1 = (tt - 64) * 64; c2 = j * 7; bytes = 28672;
          } else {
            tm = &tmW2; c1 = j * FSL; c2 = tt - 72; bytes = 28672;
          }
          mbar_wait(bars + 32 + s * 8, ph);
          mbar_expect(bars + s * 8, bytes);
          tma3d(sb + SM_RING + s * SLOT, tm, bars + s * 8, 0, c1, c2);
          if (++s == 4) { s = 0; ph ^= 1; }
        }
      }
    } else if (warp >= 10) {
      const int t2 = tid - 320, hf = t2 & 1, r0 = t2 >> 1;
      bar_sync(6, 352);
      float a[8];
#pragma unroll
      for (int k = 0; k < 8; k++) a[k] = 0.f;
#pragma unroll 1
      for (int b = 0; b < 8; b++) {
        uint4 w[2];
        uint32_t cb[2];
#pragma unroll
        for (int i = 0; i < 2; i++) {
          w[i] = ldg128(p.wmod + (size_t)(r0 + 32 * (2 * b + i)) * 3072 + 1024 + bid * 16 + hf * 8);
          cb[i] = ldg16(p.c + r0 + 32 * (2 * b + i));
        }
#pragma unroll
        for (int i = 0; i < 2; i++) {
          const float s = silu_c(cb[i]);
          a[0] = fmaf(s, bf_lo(w[i].x), a[0]); a[1] = fmaf(s, bf_hi(w[i].x), a[1]);
          a[2] = fmaf(s, bf_lo(w[i].y), a[2]); a[3] = fmaf(s, bf_hi(w[i].y), a[3]);
          a[4] = fmaf(s, bf_lo(w[i].z), a[4]); a[5] = fmaf(s, bf_hi(w[i].z), a[5]);
          a[6] = fmaf(s, bf_lo(w[i].w), a[6]); a[7] = fmaf(s, bf_hi(w[i].w), a[7]);
        }
      }
      const bool h16 = lane & 16, h8 = lane & 8, h4 = lane & 4;
#pragma unroll
      for (int k = 0; k < 4; k++) {
        float send = h16 ? a[k] : a[k + 4], keep = h16 ? a[k + 4] : a[k];
        a[k] = keep + __shfl_xor_sync(0xffffffffu, send, 16);
      }
#pragma unroll
      for (int k = 0; k < 2; k++) {
        float send = h8 ? a[k] : a[k + 2], keep = h8 ? a[k + 2] : a[k];
        a[k] = keep + __shfl_xor_sync(0xffffffffu, send, 8);
      }
      {
        float send = h4 ? a[0] : a[1], keep = h4 ? a[1] : a[0];
        a[0] = keep + __shfl_xor_sync(0xffffffffu, send, 4);
      }
      a[0] += __shfl_xor_sync(0xffffffffu, a[0], 2);
      float* red = (float*)(smem_raw + SM_RED) + 32;
      if ((lane & 2) == 0) red[(warp - 10) * 16 + hf * 8 + (lane >> 2)] = a[0];
      bar_sync(4, 64);
      if (warp == 10) {
        const int cl = lane & 15;
        float v = round_bf16(red[cl] + red[16 + cl]);
        if ((bid >> 5) == 2) v = 1.f + v;
        float vn = __shfl_down_sync(0xffffffffu, v, 1);
        uint32_t wd = pack_bf16(v, vn);
        uint32_t w0 = __shfl_sync(0xffffffffu, wd, (lane & 3) * 2);
        uint32_t w1 = __shfl_sync(0xffffffffu, wd, (lane & 3) * 2 + 8);
        if (lane < 4) st_pkt(&p.s->mod2[bid * 4 + lane], w0, w1, tag, 0);
      }
      const int isv = warp - 10;
      if (bid < 112) {
        const int kk = lane >> 1;
        const uint4* mp = &p.s->mod2[(isv ? 1 : 2) * 128 + ((kk & 7) >> 1)];
#pragma unroll
        for (int k = 0; k < 8; k++) a[k] = 0.f;
#pragma unroll 1
        for (int g = 0; g < 32; g++) {
          const uint4 w = ldg128(p.w1 + (size_t)(g * 16 + kk) * FF + bid * 16 + (lane & 1) * 8);
          uint32_t m[4];
          ld_mod(mp + g * 4, tag, m);
          const uint32_t mw = (kk & 8) ? m[1] : m[0];
          const float s = (kk & 1) ? bf_hi(mw) : bf_lo(mw);
          a[0] = fmaf(s, bf_lo(w.x), a[0]); a[1] = fmaf(s, bf_hi(w.x), a[1]);
          a[2] = fmaf(s, bf_lo(w.y), a[2]); a[3] = fmaf(s, bf_hi(w.y), a[3]);
          a[4] = fmaf(s, bf_lo(w.z), a[4]); a[5] = fmaf(s, bf_hi(w.z), a[5]);
          a[6] = fmaf(s, bf_lo(w.w), a[6]); a[7] = fmaf(s, bf_hi(w.w), a[7]);
        }
#pragma unroll
        for (int k = 0; k < 4; k++) {
          float send = h16 ? a[k] : a[k + 4], keep = h16 ? a[k + 4] : a[k];
          a[k] = keep + __shfl_xor_sync(0xffffffffu, send, 16);
        }
#pragma unroll
        for (int o = 8; o > 1; o >>= 1) {
#pragma unroll
          for (int k = 0; k < 4; k++) a[k] += __shfl_xor_sync(0xffffffffu, a[k], o);
        }
        const float sc = isv ? 0.5f : 1.f;
        if ((lane & 14) == 0)
          st_pkt(&p.s->uv[isv * 448 + bid * 4 + (lane & 1) * 2 + (lane >> 4)],
                 (__float_as_uint(a[0] * sc) & ~1u) | (tag & 1u), __float_as_uint(a[1] * sc), __float_as_uint(a[2] * sc),
                 __float_as_uint(a[3] * sc));
      }
#pragma unroll 1
      for (int i = lane; i < 56; i += 32) {
        uint32_t m[4];
        int spins = 0;
        do { ld_pkt(&p.s->uv[isv * 448 + j * 56 + i], m); } while (((m[0] ^ tag) & 1u) && ++spins < SPIN_LIMIT);
        const uint32_t ad = sb + SM_TAB + i * 32 + isv * 8;
        asm volatile("st.shared.v2.b32 [%0], {%1,%2};" ::"r"(ad), "r"(m[0]), "r"(m[1]) : "memory");
        asm volatile("st.shared.v2.b32 [%0], {%1,%2};" ::"r"(ad + 16), "r"(m[2]), "r"(m[3]) : "memory");
      }
      __syncwarp();
      if (lane == 0) mbar_arrive(bars + 72);
    } else {
      bar_sync(6, 352);
      if (lane < 8) l2_prefetch((const char*)p.wo + (size_t)bid * 32768 + lane * 4096, 4096);
      else if (lane < 12) l2_prefetch((const char*)p.w1 + (size_t)bid * 14336 + (lane - 8) * 3584, 3584);
      else if (lane < 16) l2_prefetch((const char*)p.w2 + (size_t)bid * 14336 + (lane - 12) * 3584, 3584);
      {
        int spins = 0;
        while (!mbar_test(bars + 88, 0) && ++spins < SPIN_LIMIT) __nanosleep(100);
      }
      float a = 0.f;
#pragma unroll
      for (int w = 0; w < 8; w++) a += *(const float*)(smem_raw + SM_PARK + w * 4096 + lane * 4);
      a *= (1.f / 512.f);
      const float mean = __shfl_sync(0xffffffffu, a, lane & ~1), sq = __shfl_sync(0xffffffffu, a, lane | 1);
      const float rs = 0.5f * rsqrtf(fmaxf(fmaf(-mean, mean, sq), 0.f) + 1e-5f), mr = -mean * rs;
      const float rs0 = __shfl_sync(0xffffffffu, rs, lane & ~3), mr0 = __shfl_sync(0xffffffffu, mr, lane & ~3);
      const float rs1 = __shfl_sync(0xffffffffu, rs, lane | 2), mr1 = __shfl_sync(0xffffffffu, mr, lane | 2);
      if ((lane & 3) == 0)
        st_pkt(&p.s->stat[(rt * 8 + j) * 8 + (lane >> 2)], (__float_as_uint(rs0) & ~1u) | (tag & 1u), __float_as_uint(mr0),
               __float_as_uint(rs1), __float_as_uint(mr1));
    }
  } else {
    const int wg = warp >> 2;
    const int q = lane & 3, gq = lane >> 2;
    const Ring ring{(sb + SM_RING) >> 4, bars};
    const uint32_t xoff = (uint32_t)(rt * 128 + 16 * j + warp) * 256 + gq * 8 + q;
    const uint32_t ooff = ((uint32_t)(rt * 8 + j) * 32 + gq) * 32 + warp * 4 + q;
    const uint32_t wblk = sb + SM_PARK + warp * 4096, wprv = wblk + lane * 16;
    const uint32_t wbar = sb + SM_WBAR + warp * 24;
    const uint32_t goff = (uint32_t)(rt * 8 + warp) * 1024 + lane;

    {
      const uint32_t* xo = (const uint32_t*)p.x + xoff;
      uint32_t xr[4][4];
      CK_(d0);
#pragma unroll
      for (int c = 0; c < 4; c++) {
        xr[c][0] = ldg32(xo + c * 64);
        xr[c][1] = ldg32(xo + c * 64 + 8 * 256);
        xr[c][2] = ldg32(xo + c * 64 + 4);
        xr[c][3] = ldg32(xo + c * 64 + 4 + 8 * 256);
      }
      CK_(d1);
      fence_regs(xr);
      CK_(d2);
      float s0 = 0.f, s1 = 0.f, v0 = 0.f, v1 = 0.f;
#pragma unroll
      for (int c = 0; c < 4; c++) {
#pragma unroll
        for (int e = 0; e < 4; e++) {
          const float a = bf_lo(xr[c][e]), b = bf_hi(xr[c][e]);
          if (e & 1) { s1 += a + b; v1 = fmaf(a, a, fmaf(b, b, v1)); }
          else { s0 += a + b; v0 = fmaf(a, a, fmaf(b, b, v0)); }
        }
      }
#pragma unroll
      for (int o = 16; o > 0; o >>= 1) {
        s0 += __shfl_xor_sync(0xffffffffu, s0, o);
        s1 += __shfl_xor_sync(0xffffffffu, s1, o);
        v0 += __shfl_xor_sync(0xffffffffu, v0, o);
        v1 += __shfl_xor_sync(0xffffffffu, v1, o);
      }
      const float m0 = s0 * (1.f / 512.f), m1 = s1 * (1.f / 512.f);
      const float r0 = rsqrtf(fmaxf(fmaf(-m0, m0, v0 * (1.f / 512.f)), 0.f) + 1e-5f);
      const float r1 = rsqrtf(fmaxf(fmaf(-m1, m1, v1 * (1.f / 512.f)), 0.f) + 1e-5f);
#pragma unroll
      for (int c = 0; c < 4; c++) {
        st_pkt(p.s->G + ooff + c * 256,
               pack_tag<1>((bf_lo(xr[c][0]) - m0) * r0, (bf_hi(xr[c][0]) - m0) * r0),
               pack_bf16((bf_lo(xr[c][1]) - m1) * r1, (bf_hi(xr[c][1]) - m1) * r1),
               pack_bf16((bf_lo(xr[c][2]) - m0) * r0, (bf_hi(xr[c][2]) - m0) * r0),
               pack_bf16((bf_lo(xr[c][3]) - m1) * r1, (bf_hi(xr[c][3]) - m1) * r1));
      }
      CK_(d3);
      CKS(16, d0); CKS(17, d1); CKS(18, d2); CKS(19, d3);

    }
    asm volatile("setmaxnreg.inc.sync.aligned.u32 232;");
    uint32_t qf[8][4];
    {
      uint32_t h[32][4];
      float acc[64];
      const uint4* Gin = p.s->G + goff;
      bar_sync(7, 384);
      if (G_DELAY) spin_cycles(G_DELAY);
#pragma unroll
      for (int c = 0; c < 3; c++) warp_bulk_load(wblk + c * SLOT, Gin + c * 256, 4096, wbar + c * 8);
#pragma unroll
      for (int c = 0; c < 4; c++) {
        mbar_wait(wbar + (c % 3) * 8, c / 3);
#pragma unroll
        for (int i = 0; i < 8; i++) lds128(wprv + (c % 3) * SLOT + i * 512, h[c * 8 + i]);
        verify8_tag1<512>(Gin + c * 256, h + c * 8);
        if (c == 0) {
          warp_bulk_load(wblk, Gin + 768, 4096, wbar);
          TS(1);
          bar_sync(1, 384);
        }
#pragma unroll
        for (int i = 0; i < 8; i++) {
          uint32_t m[4];
          lds128(sb + SM_TAB + (uint32_t)((c * 8 + i) * 4 + q) * 16, m);
          uint32_t* hh = h[c * 8 + i];
          hh[0] = hfma2_bf16(hh[0], m[0], m[2]);
          hh[1] = hfma2_bf16(hh[1], m[0], m[2]);
          hh[2] = hfma2_bf16(hh[2], m[1], m[3]);
          hh[3] = hfma2_bf16(hh[3], m[1], m[3]);
        }
        fence_frags<8>(h + c * 8);
        const uint32_t b = ring.wait_full(c, 0);
        if (c > 0) { wg_wait<0>(); ring.release(c - 1); }
        if (c == 0) TS(2);
        wg_fence();
        static_for<0, 8>([&](auto K) { wgmma_rs_n128_tb1<LB_MN128 + K * 128, HI128>(acc, h[c * 8 + K], b, (c | K) != 0); });
        wg_commit();
      }
      bar_arrive(6, 352);
#pragma unroll 1
      for (int ps = 1; ps < 4; ps++) {
        wg_wait<0>();
        ring.release(3);
        fence_regs(acc);
#pragma unroll
        for (int i = 0; i < 8; i++) {
          uint32_t o[4];
          pack8(o, acc + 8 * i);
          sts128(wprv + (ps - 1) * SLOT + i * 512, o[0], o[1], o[2], o[3]);
        }
#pragma unroll
        for (int c = 0; c < 4; c++) {
          const uint32_t b = ring.wait_full(c, ps & 1);
          if (c > 0) { wg_wait<0>(); ring.release(c - 1); }
          wg_fence();
          static_for<0, 8>([&](auto K) { wgmma_rs_n128_tb1<LB_MN128 + K * 128, HI128>(acc, h[c * 8 + K], b, (c | K) != 0); });
          wg_commit();
        }
      }
      wg_wait<0>();
      ring.release(3);
      fence_regs(acc);
#pragma unroll
      for (int i = 0; i < 8; i++) pack8(qf[i], acc + 8 * i);
    }
    fence_regs(qf);
    TS(3);

    float S[64];
    {
      float O[64];
      uint32_t P[8][4];
      const float cs = 0.08838834764831845f * 1.4426950408889634f;
      const int TAU = 0x41800000;
      float m0, m1, l0, l1;

      auto float_block_max = [&]() {
        float b0 = fmaxf(S[0], S[1]), b1 = fmaxf(S[2], S[3]);
#pragma unroll
        for (int i = 1; i < 16; i++) {
          b0 = fmaxf(b0, fmaxf(S[4 * i], S[4 * i + 1]));
          b1 = fmaxf(b1, fmaxf(S[4 * i + 2], S[4 * i + 3]));
        }
        b0 = fmaxf(b0, __shfl_xor_sync(0xffffffffu, b0, 1)); b1 = fmaxf(b1, __shfl_xor_sync(0xffffffffu, b1, 1));
        b0 = fmaxf(b0, __shfl_xor_sync(0xffffffffu, b0, 2)); b1 = fmaxf(b1, __shfl_xor_sync(0xffffffffu, b1, 2));
        m0 = b0 * cs; m1 = b1 * cs;
      };
      auto first_block_max = [&]() {
        int a0 = max(__float_as_int(S[0]), __float_as_int(S[1]));
        int a1 = max(__float_as_int(S[2]), __float_as_int(S[3]));
#pragma unroll
        for (int i = 1; i < 16; i++) {
          a0 = __vimax3_s32(a0, __float_as_int(S[4 * i]), __float_as_int(S[4 * i + 1]));
          a1 = __vimax3_s32(a1, __float_as_int(S[4 * i + 2]), __float_as_int(S[4 * i + 3]));
        }
        a0 = max(a0, __shfl_xor_sync(0xffffffffu, a0, 1)); a1 = max(a1, __shfl_xor_sync(0xffffffffu, a1, 1));
        a0 = max(a0, __shfl_xor_sync(0xffffffffu, a0, 2)); a1 = max(a1, __shfl_xor_sync(0xffffffffu, a1, 2));
        m0 = __int_as_float(a0) * cs; m1 = __int_as_float(a1) * cs;
        if (__any_sync(0xffffffffu, (a0 | a1) < 0)) float_block_max();
      };
      auto scale_sub = [&]() {
#pragma unroll
        for (int i = 0; i < 16; i++) {
          S[4 * i] = fmaf(S[4 * i], cs, -m0); S[4 * i + 1] = fmaf(S[4 * i + 1], cs, -m0);
          S[4 * i + 2] = fmaf(S[4 * i + 2], cs, -m1); S[4 * i + 3] = fmaf(S[4 * i + 3], cs, -m1);
        }
      };
      auto exps = [&](int i0, int i1) {
#pragma unroll
        for (int i = i0; i < i1; i++) {
          S[4 * i] = ex2(S[4 * i]); S[4 * i + 1] = ex2(S[4 * i + 1]);
          S[4 * i + 2] = ex2(S[4 * i + 2]); S[4 * i + 3] = ex2(S[4 * i + 3]);
          l0 += S[4 * i]; l1 += S[4 * i + 2]; l0 += S[4 * i + 1]; l1 += S[4 * i + 3];
        }
      };
      {
        const uint32_t b = ring.wait_full(0, 0);
        wg_fence();
        static_for<0, 8>([&](auto K) { wgmma_rs_n128_tb0<LB_K128 + (K >> 2) * 1024 + (K & 3) * 2, HI128>(S, qf[K], b, K != 0); });
        wg_commit();
        wg_wait<0>();
        fence_regs(S);
        ring.release(0);
        float_block_max();
        scale_sub();
        l0 = 0.f; l1 = 0.f;
        exps(0, 16);
#pragma unroll
        for (int i = 0; i < 8; i++) pack8(P[i], S + 8 * i);
      }
      fence_regs(P);
      if (wg == 1) bar_arrive(2, 256);
#pragma unroll 1
      for (int n = 1; n < 16; n++) {
        const uint32_t tk = 2 * n - 1, tv = 2 * n;
        const bool newhead = (n & 3) == 0;
        const uint32_t bk = ring.wait_full(tk & 3, (tk >> 2) & 1);
        const uint32_t bv = ring.wait_full(tv & 3, (tv >> 2) & 1);
        bar_sync(2 + wg, 256);
        wg_fence();
        static_for<0, 8>([&](auto K) { wgmma_rs_n128_tb0<LB_K128 + (K >> 2) * 1024 + (K & 3) * 2, HI128>(S, qf[K], bk, K != 0); });
        wg_commit();
        static_for<0, 8>([&](auto K) { wgmma_rs_n128_tb1<LB_MN128 + K * 128, HI128>(O, P[K], bv, K != 0 || (n & 3) != 1); });
        wg_commit();
        bar_arrive(2 + (wg ^ 1), 256);
        wg_wait<1>();
        fence_regs(S);
        ring.release(tk & 3);
        if ((n & 3) == 3 && n != 15) {
          fence_regs(qf);
#pragma unroll
          for (int i = 0; i < 8; i++) lds128(wprv + (n >> 2) * SLOT + i * 512, qf[i]);
        }
        float f0 = 1.f, f1 = 1.f;
        bool resc = newhead;
        if (newhead) {
          l0 += __shfl_xor_sync(0xffffffffu, l0, 1); l1 += __shfl_xor_sync(0xffffffffu, l1, 1);
          l0 += __shfl_xor_sync(0xffffffffu, l0, 2); l1 += __shfl_xor_sync(0xffffffffu, l1, 2);
          f0 = rcp_hw(l0); f1 = rcp_hw(l1);
          l0 = 0.f; l1 = 0.f;
          first_block_max();
          scale_sub();
        } else {
          scale_sub();
          int a0 = __vimax3_s32(__float_as_int(S[0]), __float_as_int(S[1]), __float_as_int(S[1]));
          int a1 = __vimax3_s32(__float_as_int(S[2]), __float_as_int(S[3]), __float_as_int(S[3]));
#pragma unroll
          for (int i = 1; i < 16; i++) {
            a0 = __vimax3_s32(a0, __float_as_int(S[4 * i]), __float_as_int(S[4 * i + 1]));
            a1 = __vimax3_s32(a1, __float_as_int(S[4 * i + 2]), __float_as_int(S[4 * i + 3]));
          }
          if (__any_sync(0xffffffffu, max(a0, a1) > TAU)) {
            a0 = max(a0, 0); a1 = max(a1, 0);
            a0 = max(a0, __shfl_xor_sync(0xffffffffu, a0, 1)); a1 = max(a1, __shfl_xor_sync(0xffffffffu, a1, 1));
            a0 = max(a0, __shfl_xor_sync(0xffffffffu, a0, 2)); a1 = max(a1, __shfl_xor_sync(0xffffffffu, a1, 2));
            const float d0 = __int_as_float(a0), d1 = __int_as_float(a1);
#pragma unroll
            for (int i = 0; i < 16; i++) { S[4 * i] -= d0; S[4 * i + 1] -= d0; S[4 * i + 2] -= d1; S[4 * i + 3] -= d1; }
            m0 += d0; m1 += d1;
            f0 = ex2(-d0); f1 = ex2(-d1);
            l0 *= f0; l1 *= f1;
            resc = true;
          }
        }
        exps(0, 4);
        wg_wait<0>();
        fence_regs(O);
        fence_regs(P);
        ring.release(tv & 3);
        if (resc) {
#pragma unroll
          for (int i = 0; i < 16; i++) {
            O[4 * i] *= f0; O[4 * i + 1] *= f0; O[4 * i + 2] *= f1; O[4 * i + 3] *= f1;
          }
          if (newhead) {
#pragma unroll
            for (int i = 0; i < 8; i++) {
              uint32_t o[4];
              pack8(o, O + 8 * i);
              sts128(wprv + ((n >> 2) - 1) * SLOT + i * 512, o[0], o[1], o[2], o[3]);
            }
          }
        }
        exps(4, 16);
#pragma unroll
        for (int i = 0; i < 8; i++) pack8(P[i], S + 8 * i);
        fence_regs(P);
        fence_regs(O);
      }
      {
        const uint32_t bv = ring.wait_full(3, 1);
        if (wg == 0) bar_sync(2, 256);
        wg_fence();
        static_for<0, 8>([&](auto K) { wgmma_rs_n128_tb1<LB_MN128 + K * 128, HI128>(O, P[K], bv, 1); });
        wg_commit();
        l0 += __shfl_xor_sync(0xffffffffu, l0, 1); l1 += __shfl_xor_sync(0xffffffffu, l1, 1);
        l0 += __shfl_xor_sync(0xffffffffu, l0, 2); l1 += __shfl_xor_sync(0xffffffffu, l1, 2);
        const float f0 = rcp_hw(l0), f1 = rcp_hw(l1);
        wg_wait<0>();
        fence_regs(O);
        ring.release(3);
#pragma unroll
        for (int i = 0; i < 8; i++) {
          qf[i][0] = pack_bf16(O[8 * i] * f0, O[8 * i + 1] * f0); qf[i][1] = pack_bf16(O[8 * i + 2] * f1, O[8 * i + 3] * f1);
          qf[i][2] = pack_bf16(O[8 * i + 4] * f0, O[8 * i + 5] * f0); qf[i][3] = pack_bf16(O[8 * i + 6] * f1, O[8 * i + 7] * f1);
        }
      }
    }
    fence_regs(qf);
    TS(4);

    uint4* const Pout = p.s->P + ((size_t)(rt * 8 + warp) * 8 + j) * 1024 + lane;
    const uint32_t tag = *(volatile uint32_t*)(smem_raw + SM_BAR + 64);
    const int go = warp ^ 4;
    const uint4* const Pown = p.s->P + (size_t)(rt * 8 + j) * 8192 + go * 32 + lane;
    const uint32_t xoff2 = (uint32_t)(rt * 128 + 16 * j + gq) * 256 + go * 8 + q;
    const uint4* const mod2p = p.s->mod2 + go * 4 + q;

    float acc2[32];
    uint32_t pk[4][4];
    auto pack_partial = [&](auto TAGC) {
      fence_regs(acc2);
#pragma unroll
      for (int i = 0; i < 4; i++) {
        pack8(pk[i], acc2 + 8 * i);
        pk[i][0] = pack_tag<TAGC>(acc2[8 * i], acc2[8 * i + 1]);
      }
      fence_regs(pk);
    };
    auto store_partial = [&](int cc) {
#pragma unroll
      for (int i = 0; i < 4; i++) st_pkt(Pout + (cc * 4 + i) * 32, pk[i][0], pk[i][1], pk[i][2], pk[i][3]);
    };
    auto red_issue = [&](int c, uint32_t slot, uint32_t bar) {
      if (lane == 0) {
        mbar_expect(bar, 4096);
        tma3d(wblk + slot * SLOT, &tmP, bar, 0, c * 8 + go, (rt * 8 + j) * 8);
      }
    };
    auto red_sum = [&](auto TAGC, int c, uint32_t src, float (&y)[8]) {
#pragma unroll
      for (int hf = 0; hf < 2; hf++) {
        uint32_t r[4][4];
#pragma unroll
        for (int i = 0; i < 4; i++) lds128(src + (hf * 4 + i) * 512, r[i]);
        if constexpr (TAGC) verify4_tag1<16384>(Pown + c * 256 + hf * 4096, r);
        else verify4_tag0<16384>(Pown + c * 256 + hf * 4096, r);
#pragma unroll
        for (int e = 0; e < 4; e++) {
          const float a = (bf_lo(r[0][e]) + bf_lo(r[1][e])) + (bf_lo(r[2][e]) + bf_lo(r[3][e]));
          const float b = (bf_hi(r[0][e]) + bf_hi(r[1][e])) + (bf_hi(r[2][e]) + bf_hi(r[3][e]));
          y[2 * e] = hf ? y[2 * e] + a : a;
          y[2 * e + 1] = hf ? y[2 * e + 1] + b : b;
        }
      }
    };
    uint32_t xr[4], ga[4], g2[4];
    float s0 = 0.f, s1 = 0.f, v0 = 0.f, v1 = 0.f;
    auto red1_issue = [&](int c) {
      red_issue(c, 0, wbar + 16);
      const uint32_t* xo = (const uint32_t*)p.x + xoff2 + c * 64;
      xr[0] = ldg32(xo); xr[1] = ldg32(xo + 8 * 256); xr[2] = ldg32(xo + 4); xr[3] = ldg32(xo + 4 + 8 * 256);
      ld_pkt(mod2p + c * 32, ga);
      ld_pkt(mod2p + 256 + c * 32, g2);
    };
    auto red1_process = [&](int c) {
      float y[8];
      if (ga[2] != tag) ld_mod(mod2p + c * 32, tag, ga);
      if (g2[2] != tag) ld_mod(mod2p + 256 + c * 32, tag, g2);
      mbar_wait(wbar + 16, (c + 1) & 1);
      red_sum(IC<1>{}, c, wprv, y);
#pragma unroll
      for (int e = 0; e < 4; e++) {
        const float a = fmaf(bf_lo(ga[e >> 1]), y[2 * e], bf_lo(xr[e])), b = fmaf(bf_hi(ga[e >> 1]), y[2 * e + 1], bf_hi(xr[e]));
        y[2 * e] = a; y[2 * e + 1] = b;
        if (e & 1) { s1 += a + b; v1 = fmaf(a, a, fmaf(b, b, v1)); }
        else { s0 += a + b; v0 = fmaf(a, a, fmaf(b, b, v0)); }
      }
      st_pkt(p.s->G + ((rt * 8 + j) * 32 + c * 8 + go) * 32 + lane, pack_tag<0>(y[0] * bf_lo(g2[0]), y[1] * bf_hi(g2[0])),
             pack_bf16(y[2] * bf_lo(g2[0]), y[3] * bf_hi(g2[0])), pack_bf16(y[4] * bf_lo(g2[1]), y[5] * bf_hi(g2[1])),
             pack_bf16(y[6] * bf_lo(g2[1]), y[7] * bf_hi(g2[1])));
      sts128(wprv + SLOT + c * 1024, __float_as_uint(y[0]), __float_as_uint(y[1]), __float_as_uint(y[2]), __float_as_uint(y[3]));
      sts128(wprv + SLOT + c * 1024 + 512, __float_as_uint(y[4]), __float_as_uint(y[5]), __float_as_uint(y[6]),
             __float_as_uint(y[7]));
    };
    const uint4* const Gin = p.s->G + goff;
    auto g_issue = [&](int u) { warp_bulk_load(wblk + 2 * SLOT + (u & 1) * 2048, Gin + u * 128, 2048, wbar + (u & 1) * 8); };

    uint32_t tl = 0, b = ring.wait_full(0, 0);
    auto next_tile = [&]() {
      const uint32_t cur = tl & 3;
      tl++;
      b = ring.wait_full(tl & 3, (tl >> 2) & 1);
      wg_wait<0>();
      TR(4);
      ring.release(cur);
    };
    {
      uint32_t o[24][4];
#pragma unroll
      for (int i = 0; i < 24; i++) lds128(wprv + (i >> 3) * SLOT + (i & 7) * 512, o[i]);
#pragma unroll 1
      for (int cc = 0; cc < 8; cc++) {
        wg_fence();
        static_for<0, 16>([&](auto K) { wgmma_rs_n64_tb1<K * 128, HI128>(acc2, o[K], b, K != 0); });
        wg_commit();
        if (cc > 0) store_partial(cc - 1);
        if (cc >= 3 && (cc & 1) == wg) red1_process((cc - 3) >> 1);
        next_tile();
        wg_fence();
        static_for<0, 16>([&](auto K) { wgmma_rs_n64_tb1<K * 128, HI128>(acc2, K < 8 ? o[16 + (K & 7)] : qf[K & 7], b, 1); });
        wg_commit();
        if (cc >= 2 && (cc & 1) != wg) red1_issue((cc - 2) >> 1);
        if (cc == 6) { g_issue(0); g_issue(1); }
        next_tile();
        pack_partial(IC<1>{});
      }
    }
    TS(5);

    uint32_t H[14][4];
    {
      float acc[112];
      const uint4* const statp = &p.s->stat[(rt * 8 + warp) * 8 + gq];
#pragma unroll 1
      for (int u = 0; u < 8; u++) {
        uint32_t fa[4][4];
        mbar_wait(wbar + (u & 1) * 8, ((u >> 1) + (u & 1)) & 1);
#pragma unroll
        for (int i = 0; i < 4; i++) lds128(wprv + 2 * SLOT + (u & 1) * 2048 + i * 512, fa[i]);
        verify4_tag0<512>(Gin + u * 128, fa);
        wg_fence();
        static_for<0, 4>([&](auto K) { wgmma_rs_n224_tb1<LB_W1 + K * 64, HI64>(acc, fa[K], b, (u | K) != 0); });
        wg_commit();
        if (u == 0) store_partial(7);
        if (u < 5) g_issue(u + 2);
        if (u == (wg ? 0 : RED3_UNIT)) red1_issue(3);
        if (wg ? u == 1 : (u == 0 || u == RED3_UNIT + 1)) {
          red1_process(u ? 3 : 2);
          if (u) {
#pragma unroll
            for (int o = 1; o < 4; o <<= 1) {
              s0 += __shfl_xor_sync(0xffffffffu, s0, o);
              s1 += __shfl_xor_sync(0xffffffffu, s1, o);
              v0 += __shfl_xor_sync(0xffffffffu, v0, o);
              v1 += __shfl_xor_sync(0xffffffffu, v1, o);
            }
            if (q == 0) sts128(wblk + gq * 16, __float_as_uint(s0), __float_as_uint(v0), __float_as_uint(s1), __float_as_uint(v1));
            __syncwarp();
            if (lane == 0) mbar_arrive(bars + 88);
          }
        }
        if (u == 7) ld_pkt(statp, xr);
        next_tile();
        if (u == 5) g_issue(7);
      }
      fence_regs(acc);
      TS(9);
      mbar_wait(bars + 72, 0);
      {
        int spins = 0;
        while (((xr[0] ^ tag) & 1u) && ++spins < SPIN_LIMIT) ld_pkt(statp, xr);
      }
      const float ra0 = __uint_as_float(xr[0]), rb0 = __uint_as_float(xr[1]), ra1 = __uint_as_float(xr[2]),
                  rb1 = __uint_as_float(xr[3]);
#pragma unroll
      for (int i = 0; i < 28; i++) {
        uint32_t m[4];
        lds128(sb + SM_TAB + (i * 4 + q) * 16, m);
        const float u0 = __uint_as_float(m[0]), u1 = __uint_as_float(m[1]), w0 = __uint_as_float(m[2]), w1 = __uint_as_float(m[3]);
        const float z0 = fmaf(acc[4 * i], ra0, fmaf(u0, rb0, w0)), z1 = fmaf(acc[4 * i + 1], ra0, fmaf(u1, rb0, w1));
        const float z2 = fmaf(acc[4 * i + 2], ra1, fmaf(u0, rb1, w0)), z3 = fmaf(acc[4 * i + 3], ra1, fmaf(u1, rb1, w1));
        H[i >> 1][(i & 1) * 2] = pack_bf16(fmaf(z0, tanh_hw(z0), z0), fmaf(z1, tanh_hw(z1), z1));
        H[i >> 1][(i & 1) * 2 + 1] = pack_bf16(fmaf(z2, tanh_hw(z2), z2), fmaf(z3, tanh_hw(z3), z3));
      }
    }
    fence_regs(H);
    TS(10);
#pragma unroll 1
    for (int cc = 0; cc < 8; cc++) {
      wg_fence();
      static_for<0, 14>([&](auto K) { wgmma_rs_n64_tb1<K * 128, HI128>(acc2, H[K], b, K != 0); });
      wg_commit();
      if (cc == 5) red_issue(0, 0, wbar + 16);
      if (cc == 7) {
        red_issue(1, 2, wbar);
        ld_pkt(mod2p + 384, ga);
      }
      if (cc > 0) store_partial(cc - 1);
      if (cc < 7) next_tile();
      wg_wait<0>();
      pack_partial(IC<0>{});
    }
    store_partial(7);
    TS(11);
#pragma unroll 1
    for (int c = 0; c < 4; c++) {
      uint32_t* const oo = (uint32_t*)p.out + xoff2 + c * 64;
      uint32_t xa[2][4], gb[2];
      float y[8];
      if (ga[2] != tag) ld_mod(mod2p + 384 + c * 32, tag, ga);
      gb[0] = ga[0]; gb[1] = ga[1];
      if (c < 3) ld_pkt(mod2p + 384 + (c + 1) * 32, ga);
      lds128(wprv + SLOT + c * 1024, xa[0]);
      lds128(wprv + SLOT + c * 1024 + 512, xa[1]);
      const uint32_t slot = (c & 1) * 2, bar = wbar + 16 - (c & 1) * 16;
      mbar_wait(bar, ((c >> 1) + 1 - (c & 1)) & 1);
      red_sum(IC<0>{}, c, wprv + slot * SLOT, y);
      if (c < 2) red_issue(c + 2, slot, bar);
#pragma unroll
      for (int e = 0; e < 4; e++)
        oo[(e >> 1) * 4 + (e & 1) * 8 * 256] =
            pack_bf16(fmaf(bf_lo(gb[e >> 1]), y[2 * e], __uint_as_float(xa[e >> 1][(e & 1) * 2])),
                      fmaf(bf_hi(gb[e >> 1]), y[2 * e + 1], __uint_as_float(xa[e >> 1][(e & 1) * 2 + 1])));
      if (c == 1) TS(13);
      if (c == 2) TS(14);
    }
    TS(12);
    if (bid == 0 && tid == 0) asm volatile("st.relaxed.gpu.global.u32 [%0], %1;" ::"l"(&p.s->epoch), "r"(tag) : "memory");
  }
}

typedef CUresult (*EncodeFn)(CUtensorMap*, CUtensorMapDataType, cuuint32_t, void*, const cuuint64_t*, const cuuint64_t*,
                             const cuuint32_t*, const cuuint32_t*, CUtensorMapInterleave, CUtensorMapSwizzle,
                             CUtensorMapL2promotion, CUtensorMapFloatOOBfill);

static void make_map(EncodeFn fn, CUtensorMap* tm, const void* ptr, int inner, int rows, int cols, int box_rows, int box_outer,
                     CUtensorMapSwizzle swz) {
  cuuint64_t gd[3] = {(cuuint64_t)inner, (cuuint64_t)rows, (cuuint64_t)(cols / inner)};
  cuuint64_t gs[2] = {(cuuint64_t)cols * 2, (cuuint64_t)inner * 2};
  cuuint32_t bx[3] = {(cuuint32_t)inner, (cuuint32_t)box_rows, (cuuint32_t)box_outer};
  cuuint32_t es[3] = {1, 1, 1};
  fn(tm, CU_TENSOR_MAP_DATA_TYPE_BFLOAT16, 3, const_cast<void*>(ptr), gd, gs, bx, es, CU_TENSOR_MAP_INTERLEAVE_NONE, swz,
     CU_TENSOR_MAP_L2_PROMOTION_L2_128B, CU_TENSOR_MAP_FLOAT_OOB_FILL_NONE);
}

extern "C" void kernel_launch(void* const* d_in, const int* in_sizes, int n_in, void* d_out, int out_size) {
  (void)in_sizes; (void)n_in; (void)out_size;
  void* fnp = nullptr;
  cudaDriverEntryPointQueryResult qr;
  cudaGetDriverEntryPoint("cuTensorMapEncodeTiled", &fnp, cudaEnableDefault, &qr);
  EncodeFn fn = (EncodeFn)fnp;
  CUtensorMap tmWq, tmK, tmV, tmWo, tmW1, tmW2, tmWm, tmP;
  make_map(fn, &tmWq, d_in[3], 64, 512, 4096, 128, 2, CU_TENSOR_MAP_SWIZZLE_128B);
  make_map(fn, &tmK, d_in[1], 64, 8 * SK, 128, 128, 2, CU_TENSOR_MAP_SWIZZLE_128B);
  make_map(fn, &tmV, d_in[2], 64, 8 * SK, 128, 128, 2, CU_TENSOR_MAP_SWIZZLE_128B);
  make_map(fn, &tmWo, d_in[4], 64, 4096, 512, 256, 1, CU_TENSOR_MAP_SWIZZLE_128B);
  make_map(fn, &tmW1, d_in[6], 32, 512, FF, 64, 7, CU_TENSOR_MAP_SWIZZLE_64B);
  make_map(fn, &tmW2, d_in[7], 64, FF, 512, 224, 1, CU_TENSOR_MAP_SWIZZLE_128B);
  make_map(fn, &tmWm, d_in[9], 8, 512, 3072, 256, 1, CU_TENSOR_MAP_SWIZZLE_NONE);
  Params p;
  p.x = (const __nv_bfloat16*)d_in[0];
  p.c = (const __nv_bfloat16*)d_in[8];
  p.wmod = (const __nv_bfloat16*)d_in[9];
  p.wo = (const __nv_bfloat16*)d_in[4];
  p.w1 = (const __nv_bfloat16*)d_in[6];
  p.w2 = (const __nv_bfloat16*)d_in[7];
  p.out = (__nv_bfloat16*)d_out;
  cudaGetSymbolAddress((void**)&p.s, g_scratch);
  {
    cuuint64_t gd[3] = {256, 32, 1024};
    cuuint64_t gs[2] = {512, 16384};
    cuuint32_t bx[3] = {256, 1, 8};
    cuuint32_t es[3] = {1, 1, 1};
    fn(&tmP, CU_TENSOR_MAP_DATA_TYPE_BFLOAT16, 3, (void*)p.s->P, gd, gs, bx, es, CU_TENSOR_MAP_INTERLEAVE_NONE,
       CU_TENSOR_MAP_SWIZZLE_NONE, CU_TENSOR_MAP_L2_PROMOTION_NONE, CU_TENSOR_MAP_FLOAT_OOB_FILL_NONE);
  }
  cudaFuncSetAttribute(adaln_block_kernel, cudaFuncAttributeMaxDynamicSharedMemorySize, SM_TOTAL);
  adaln_block_kernel<<<128, 384, SM_TOTAL>>>(tmWq, tmK, tmV, tmWo, tmW1, tmW2, tmWm, tmP, p);
}
```

```cpp
#include <cuda_runtime.h>
#include <cuda_bf16.h>
#include <cuda.h>
#include <stdint.h>

template <int OFF, uint32_t HI>
__device__ __forceinline__ void wgmma_rs_n128_tb0(float (&d)[64], const uint32_t (&a)[4], uint32_t lo, int sd) {
  asm volatile("{\n.reg .pred p;\n.reg .b32 l;\n.reg .b64 db;\nsetp.ne.b32 p, %69, 0;\n"
    "add.u32 l, %68, %70;\nmov.b64 db, {l, %71};\n"
    "wgmma.mma_async.sync.aligned.m64n128k16.f32.bf16.bf16 "
    "{%0,%1,%2,%3,%4,%5,%6,%7,%8,%9,%10,%11,%12,%13,%14,%15,"
    "%16,%17,%18,%19,%20,%21,%22,%23,%24,%25,%26,%27,%28,%29,%30,%31,"
    "%32,%33,%34,%35,%36,%37,%38,%39,%40,%41,%42,%43,%44,%45,%46,%47,"
    "%48,%49,%50,%51,%52,%53,%54,%55,%56,%57,%58,%59,%60,%61,%62,%63}, "
    "{%64,%65,%66,%67}, db, p, 1, 1, 0;\n}\n"
    : "+f"(d[0]), "+f"(d[1]), "+f"(d[2]), "+f"(d[3]), "+f"(d[4]), "+f"(d[5]), "+f"(d[6]), "+f"(d[7]),
      "+f"(d[8]), "+f"(d[9]), "+f"(d[10]), "+f"(d[11]), "+f"(d[12]), "+f"(d[13]), "+f"(d[14]), "+f"(d[15]),
      "+f"(d[16]), "+f"(d[17]), "+f"(d[18]), "+f"(d[19]), "+f"(d[20]), "+f"(d[21]), "+f"(d[22]), "+f"(d[23]),
      "+f"(d[24]), "+f"(d[25]), "+f"(d[26]), "+f"(d[27]), "+f"(d[28]), "+f"(d[29]), "+f"(d[30]), "+f"(d[31]),
      "+f"(d[32]), "+f"(d[33]), "+f"(d[34]), "+f"(d[35]), "+f"(d[36]), "+f"(d[37]), "+f"(d[38]), "+f"(d[39]),
      "+f"(d[40]), "+f"(d[41]), "+f"(d[42]), "+f"(d[43]), "+f"(d[44]), "+f"(d[45]), "+f"(d[46]), "+f"(d[47]),
      "+f"(d[48]), "+f"(d[49]), "+f"(d[50]), "+f"(d[51]), "+f"(d[52]), "+f"(d[53]), "+f"(d[54]), "+f"(d[55]),
      "+f"(d[56]), "+f"(d[57]), "+f"(d[58]), "+f"(d[59]), "+f"(d[60]), "+f"(d[61]), "+f"(d[62]), "+f"(d[63])
    : "r"(a[0]), "r"(a[1]), "r"(a[2]), "r"(a[3]), "r"(lo), "r"(sd), "n"(OFF), "n"(HI));
}

template <int OFF, uint32_t HI>
__device__ __forceinline__ void wgmma_rs_n128_tb1(float (&d)[64], const uint32_t (&a)[4], uint32_t lo, int sd) {
  asm volatile("{\n.reg .pred p;\n.reg .b32 l;\n.reg .b64 db;\nsetp.ne.b32 p, %69, 0;\n"
    "add.u32 l, %68, %70;\nmov.b64 db, {l, %71};\n"
    "wgmma.mma_async.sync.aligned.m64n128k16.f32.bf16.bf16 "
    "{%0,%1,%2,%3,%4,%5,%6,%7,%8,%9,%10,%11,%12,%13,%14,%15,"
    "%16,%17,%18,%19,%20,%21,%22,%23,%24,%25,%26,%27,%28,%29,%30,%31,"
    "%32,%33,%34,%35,%36,%37,%38,%39,%40,%41,%42,%43,%44,%45,%46,%47,"
    "%48,%49,%50,%51,%52,%53,%54,%55,%56,%57,%58,%59,%60,%61,%62,%63}, "
    "{%64,%65,%66,%67}, db, p, 1, 1, 1;\n}\n"
    : "+f"(d[0]), "+f"(d[1]), "+f"(d[2]), "+f"(d[3]), "+f"(d[4]), "+f"(d[5]), "+f"(d[6]), "+f"(d[7]),
      "+f"(d[8]), "+f"(d[9]), "+f"(d[10]), "+f"(d[11]), "+f"(d[12]), "+f"(d[13]), "+f"(d[14]), "+f"(d[15]),
      "+f"(d[16]), "+f"(d[17]), "+f"(d[18]), "+f"(d[19]), "+f"(d[20]), "+f"(d[21]), "+f"(d[22]), "+f"(d[23]),
      "+f"(d[24]), "+f"(d[25]), "+f"(d[26]), "+f"(d[27]), "+f"(d[28]), "+f"(d[29]), "+f"(d[30]), "+f"(d[31]),
      "+f"(d[32]), "+f"(d[33]), "+f"(d[34]), "+f"(d[35]), "+f"(d[36]), "+f"(d[37]), "+f"(d[38]), "+f"(d[39]),
      "+f"(d[40]), "+f"(d[41]), "+f"(d[42]), "+f"(d[43]), "+f"(d[44]), "+f"(d[45]), "+f"(d[46]), "+f"(d[47]),
      "+f"(d[48]), "+f"(d[49]), "+f"(d[50]), "+f"(d[51]), "+f"(d[52]), "+f"(d[53]), "+f"(d[54]), "+f"(d[55]),
      "+f"(d[56]), "+f"(d[57]), "+f"(d[58]), "+f"(d[59]), "+f"(d[60]), "+f"(d[61]), "+f"(d[62]), "+f"(d[63])
    : "r"(a[0]), "r"(a[1]), "r"(a[2]), "r"(a[3]), "r"(lo), "r"(sd), "n"(OFF), "n"(HI));
}

template <int OFF, uint32_t HI>
__device__ __forceinline__ void wgmma_rs_n224_tb1(float (&d)[112], const uint32_t (&a)[4], uint32_t lo, int sd) {
  asm volatile("{\n.reg .pred p;\n.reg .b32 l;\n.reg .b64 db;\nsetp.ne.b32 p, %117, 0;\n"
    "add.u32 l, %116, %118;\nmov.b64 db, {l, %119};\n"
    "wgmma.mma_async.sync.aligned.m64n224k16.f32.bf16.bf16 "
    "{%0,%1,%2,%3,%4,%5,%6,%7,%8,%9,%10,%11,%12,%13,%14,%15,"
    "%16,%17,%18,%19,%20,%21,%22,%23,%24,%25,%26,%27,%28,%29,%30,%31,"
    "%32,%33,%34,%35,%36,%37,%38,%39,%40,%41,%42,%43,%44,%45,%46,%47,"
    "%48,%49,%50,%51,%52,%53,%54,%55,%56,%57,%58,%59,%60,%61,%62,%63,"
    "%64,%65,%66,%67,%68,%69,%70,%71,%72,%73,%74,%75,%76,%77,%78,%79,"
    "%80,%81,%82,%83,%84,%85,%86,%87,%88,%89,%90,%91,%92,%93,%94,%95,"
    "%96,%97,%98,%99,%100,%101,%102,%103,%104,%105,%106,%107,%108,%109,%110,%111}, "
    "{%112,%113,%114,%115}, db, p, 1, 1, 1;\n}\n"
    : "+f"(d[0]), "+f"(d[1]), "+f"(d[2]), "+f"(d[3]), "+f"(d[4]), "+f"(d[5]), "+f"(d[6]), "+f"(d[7]),
      "+f"(d[8]), "+f"(d[9]), "+f"(d[10]), "+f"(d[11]), "+f"(d[12]), "+f"(d[13]), "+f"(d[14]), "+f"(d[15]),
      "+f"(d[16]), "+f"(d[17]), "+f"(d[18]), "+f"(d[19]), "+f"(d[20]), "+f"(d[21]), "+f"(d[22]), "+f"(d[23]),
      "+f"(d[24]), "+f"(d[25]), "+f"(d[26]), "+f"(d[27]), "+f"(d[28]), "+f"(d[29]), "+f"(d[30]), "+f"(d[31]),
      "+f"(d[32]), "+f"(d[33]), "+f"(d[34]), "+f"(d[35]), "+f"(d[36]), "+f"(d[37]), "+f"(d[38]), "+f"(d[39]),
      "+f"(d[40]), "+f"(d[41]), "+f"(d[42]), "+f"(d[43]), "+f"(d[44]), "+f"(d[45]), "+f"(d[46]), "+f"(d[47]),
      "+f"(d[48]), "+f"(d[49]), "+f"(d[50]), "+f"(d[51]), "+f"(d[52]), "+f"(d[53]), "+f"(d[54]), "+f"(d[55]),
      "+f"(d[56]), "+f"(d[57]), "+f"(d[58]), "+f"(d[59]), "+f"(d[60]), "+f"(d[61]), "+f"(d[62]), "+f"(d[63]),
      "+f"(d[64]), "+f"(d[65]), "+f"(d[66]), "+f"(d[67]), "+f"(d[68]), "+f"(d[69]), "+f"(d[70]), "+f"(d[71]),
      "+f"(d[72]), "+f"(d[73]), "+f"(d[74]), "+f"(d[75]), "+f"(d[76]), "+f"(d[77]), "+f"(d[78]), "+f"(d[79]),
      "+f"(d[80]), "+f"(d[81]), "+f"(d[82]), "+f"(d[83]), "+f"(d[84]), "+f"(d[85]), "+f"(d[86]), "+f"(d[87]),
      "+f"(d[88]), "+f"(d[89]), "+f"(d[90]), "+f"(d[91]), "+f"(d[92]), "+f"(d[93]), "+f"(d[94]), "+f"(d[95]),
      "+f"(d[96]), "+f"(d[97]), "+f"(d[98]), "+f"(d[99]), "+f"(d[100]), "+f"(d[101]), "+f"(d[102]), "+f"(d[103]),
      "+f"(d[104]), "+f"(d[105]), "+f"(d[106]), "+f"(d[107]), "+f"(d[108]), "+f"(d[109]), "+f"(d[110]), "+f"(d[111])
    : "r"(a[0]), "r"(a[1]), "r"(a[2]), "r"(a[3]), "r"(lo), "r"(sd), "n"(OFF), "n"(HI));
}

template <int OFF, uint32_t HI>
__device__ __forceinline__ void wgmma_rs_n64_tb1(float (&d)[32], const uint32_t (&a)[4], uint32_t lo, int sd) {
  asm volatile("{\n.reg .pred p;\n.reg .b32 l;\n.reg .b64 db;\nsetp.ne.b32 p, %37, 0;\n"
    "add.u32 l, %36, %38;\nmov.b64 db, {l, %39};\n"
    "wgmma.mma_async.sync.aligned.m64n64k16.f32.bf16.bf16 "
    "{%0,%1,%2,%3,%4,%5,%6,%7,%8,%9,%10,%11,%12,%13,%14,%15,"
    "%16,%17,%18,%19,%20,%21,%22,%23,%24,%25,%26,%27,%28,%29,%30,%31}, "
    "{%32,%33,%34,%35}, db, p, 1, 1, 1;\n}\n"
    : "+f"(d[0]), "+f"(d[1]), "+f"(d[2]), "+f"(d[3]), "+f"(d[4]), "+f"(d[5]), "+f"(d[6]), "+f"(d[7]),
      "+f"(d[8]), "+f"(d[9]), "+f"(d[10]), "+f"(d[11]), "+f"(d[12]), "+f"(d[13]), "+f"(d[14]), "+f"(d[15]),
      "+f"(d[16]), "+f"(d[17]), "+f"(d[18]), "+f"(d[19]), "+f"(d[20]), "+f"(d[21]), "+f"(d[22]), "+f"(d[23]),
      "+f"(d[24]), "+f"(d[25]), "+f"(d[26]), "+f"(d[27]), "+f"(d[28]), "+f"(d[29]), "+f"(d[30]), "+f"(d[31])
    : "r"(a[0]), "r"(a[1]), "r"(a[2]), "r"(a[3]), "r"(lo), "r"(sd), "n"(OFF), "n"(HI));
}

template <int STR>
__device__ __forceinline__ void verify8_tag1(const uint4* p, uint32_t (*r)[4]) {
  asm volatile("{\n.reg .pred p, q;\n.reg .b32 a, n;\nmov.u32 n, 0;\n"
    "LAB_CHK:\n"
    "and.b32 a, %0, %4;\n"
    "and.b32 a, a, %8;\n"
    "and.b32 a, a, %12;\n"
    "and.b32 a, a, %16;\n"
    "and.b32 a, a, %20;\n"
    "and.b32 a, a, %24;\n"
    "and.b32 a, a, %28;\n"
    "and.b32 a, a, 1;\nsetp.eq.u32 p, a, 1;\nvote.sync.all.pred p, p, 0xffffffff;\n"
    "@p bra.uni LAB_OK;\n"
    "and.b32 a, %0, 1;\nsetp.ne.u32 q, a, 1;\n"
    "@q ld.relaxed.gpu.global.v4.b32 {%0,%1,%2,%3}, [%32+%33];\n"
    "and.b32 a, %4, 1;\nsetp.ne.u32 q, a, 1;\n"
    "@q ld.relaxed.gpu.global.v4.b32 {%4,%5,%6,%7}, [%32+%34];\n"
    "and.b32 a, %8, 1;\nsetp.ne.u32 q, a, 1;\n"
    "@q ld.relaxed.gpu.global.v4.b32 {%8,%9,%10,%11}, [%32+%35];\n"
    "and.b32 a, %12, 1;\nsetp.ne.u32 q, a, 1;\n"
    "@q ld.relaxed.gpu.global.v4.b32 {%12,%13,%14,%15}, [%32+%36];\n"
    "and.b32 a, %16, 1;\nsetp.ne.u32 q, a, 1;\n"
    "@q ld.relaxed.gpu.global.v4.b32 {%16,%17,%18,%19}, [%32+%37];\n"
    "and.b32 a, %20, 1;\nsetp.ne.u32 q, a, 1;\n"
    "@q ld.relaxed.gpu.global.v4.b32 {%20,%21,%22,%23}, [%32+%38];\n"
    "and.b32 a, %24, 1;\nsetp.ne.u32 q, a, 1;\n"
    "@q ld.relaxed.gpu.global.v4.b32 {%24,%25,%26,%27}, [%32+%39];\n"
    "and.b32 a, %28, 1;\nsetp.ne.u32 q, a, 1;\n"
    "@q ld.relaxed.gpu.global.v4.b32 {%28,%29,%30,%31}, [%32+%40];\n"
    "add.u32 n, n, 1;\nsetp.lt.u32 q, n, 262144;\n@q bra.uni LAB_CHK;\n"
    "LAB_OK:\n"
    "}\n"
    : "+r"(r[0][0]), "+r"(r[0][1]), "+r"(r[0][2]), "+r"(r[0][3]), "+r"(r[1][0]), "+r"(r[1][1]), "+r"(r[1][2]), "+r"(r[1][3]),
      "+r"(r[2][0]), "+r"(r[2][1]), "+r"(r[2][2]), "+r"(r[2][3]), "+r"(r[3][0]), "+r"(r[3][1]), "+r"(r[3][2]), "+r"(r[3][3]),
      "+r"(r[4][0]), "+r"(r[4][1]), "+r"(r[4][2]), "+r"(r[4][3]), "+r"(r[5][0]), "+r"(r[5][1]), "+r"(r[5][2]), "+r"(r[5][3]),
      "+r"(r[6][0]), "+r"(r[6][1]), "+r"(r[6][2]), "+r"(r[6][3]), "+r"(r[7][0]), "+r"(r[7][1]), "+r"(r[7][2]), "+r"(r[7][3])
    : "l"(p), "n"(0 * STR), "n"(1 * STR), "n"(2 * STR), "n"(3 * STR), "n"(4 * STR), "n"(5 * STR), "n"(6 * STR), "n"(7 * STR)
    : "memory");
}

template <int STR>
__device__ __forceinline__ void verify8_tag0(const uint4* p, uint32_t (*r)[4]) {
  asm volatile("{\n.reg .pred p, q;\n.reg .b32 a, n;\nmov.u32 n, 0;\n"
    "LAB_CHK:\n"
    "or.b32 a, %0, %4;\n"
    "or.b32 a, a, %8;\n"
    "or.b32 a, a, %12;\n"
    "or.b32 a, a, %16;\n"
    "or.b32 a, a, %20;\n"
    "or.b32 a, a, %24;\n"
    "or.b32 a, a, %28;\n"
    "and.b32 a, a, 1;\nsetp.eq.u32 p, a, 0;\nvote.sync.all.pred p, p, 0xffffffff;\n"
    "@p bra.uni LAB_OK;\n"
    "and.b32 a, %0, 1;\nsetp.ne.u32 q, a, 0;\n"
    "@q ld.relaxed.gpu.global.v4.b32 {%0,%1,%2,%3}, [%32+%33];\n"
    "and.b32 a, %4, 1;\nsetp.ne.u32 q, a, 0;\n"
    "@q ld.relaxed.gpu.global.v4.b32 {%4,%5,%6,%7}, [%32+%34];\n"
    "and.b32 a, %8, 1;\nsetp.ne.u32 q, a, 0;\n"
    "@q ld.relaxed.gpu.global.v4.b32 {%8,%9,%10,%11}, [%32+%35];\n"
    "and.b32 a, %12, 1;\nsetp.ne.u32 q, a, 0;\n"
    "@q ld.relaxed.gpu.global.v4.b32 {%12,%13,%14,%15}, [%32+%36];\n"
    "and.b32 a, %16, 1;\nsetp.ne.u32 q, a, 0;\n"
    "@q ld.relaxed.gpu.global.v4.b32 {%16,%17,%18,%19}, [%32+%37];\n"
    "and.b32 a, %20, 1;\nsetp.ne.u32 q, a, 0;\n"
    "@q ld.relaxed.gpu.global.v4.b32 {%20,%21,%22,%23}, [%32+%38];\n"
    "and.b32 a, %24, 1;\nsetp.ne.u32 q, a, 0;\n"
    "@q ld.relaxed.gpu.global.v4.b32 {%24,%25,%26,%27}, [%32+%39];\n"
    "and.b32 a, %28, 1;\nsetp.ne.u32 q, a, 0;\n"
    "@q ld.relaxed.gpu.global.v4.b32 {%28,%29,%30,%31}, [%32+%40];\n"
    "add.u32 n, n, 1;\nsetp.lt.u32 q, n, 262144;\n@q bra.uni LAB_CHK;\n"
    "LAB_OK:\n"
    "or.b32 %0, %0, 1;\n"
    "or.b32 %4, %4, 1;\n"
    "or.b32 %8, %8, 1;\n"
    "or.b32 %12, %12, 1;\n"
    "or.b32 %16, %16, 1;\n"
    "or.b32 %20, %20, 1;\n"
    "or.b32 %24, %24, 1;\n"
    "or.b32 %28, %28, 1;\n"
    "}\n"
    : "+r"(r[0][0]), "+r"(r[0][1]), "+r"(r[0][2]), "+r"(r[0][3]), "+r"(r[1][0]), "+r"(r[1][1]), "+r"(r[1][2]), "+r"(r[1][3]),
      "+r"(r[2][0]), "+r"(r[2][1]), "+r"(r[2][2]), "+r"(r[2][3]), "+r"(r[3][0]), "+r"(r[3][1]), "+r"(r[3][2]), "+r"(r[3][3]),
      "+r"(r[4][0]), "+r"(r[4][1]), "+r"(r[4][2]), "+r"(r[4][3]), "+r"(r[5][0]), "+r"(r[5][1]), "+r"(r[5][2]), "+r"(r[5][3]),
      "+r"(r[6][0]), "+r"(r[6][1]), "+r"(r[6][2]), "+r"(r[6][3]), "+r"(r[7][0]), "+r"(r[7][1]), "+r"(r[7][2]), "+r"(r[7][3])
    : "l"(p), "n"(0 * STR), "n"(1 * STR), "n"(2 * STR), "n"(3 * STR), "n"(4 * STR), "n"(5 * STR), "n"(6 * STR), "n"(7 * STR)
    : "memory");
}

template <int STR>
__device__ __forceinline__ void verify4_tag0(const uint4* p, uint32_t (*r)[4]) {
  asm volatile("{\n.reg .pred p, q;\n.reg .b32 a, n;\nmov.u32 n, 0;\n"
    "LAB_CHK:\n"
    "or.b32 a, %0, %4;\n"
    "or.b32 a, a, %8;\n"
    "or.b32 a, a, %12;\n"
    "and.b32 a, a, 1;\nsetp.eq.u32 p, a, 0;\nvote.sync.all.pred p, p, 0xffffffff;\n"
    "@p bra.uni LAB_OK;\n"
    "and.b32 a, %0, 1;\nsetp.ne.u32 q, a, 0;\n"
    "@q ld.relaxed.gpu.global.v4.b32 {%0,%1,%2,%3}, [%16+%17];\n"
    "and.b32 a, %4, 1;\nsetp.ne.u32 q, a, 0;\n"
    "@q ld.relaxed.gpu.global.v4.b32 {%4,%5,%6,%7}, [%16+%18];\n"
    "and.b32 a, %8, 1;\nsetp.ne.u32 q, a, 0;\n"
    "@q ld.relaxed.gpu.global.v4.b32 {%8,%9,%10,%11}, [%16+%19];\n"
    "and.b32 a, %12, 1;\nsetp.ne.u32 q, a, 0;\n"
    "@q ld.relaxed.gpu.global.v4.b32 {%12,%13,%14,%15}, [%16+%20];\n"
    "add.u32 n, n, 1;\nsetp.lt.u32 q, n, 262144;\n@q bra.uni LAB_CHK;\n"
    "LAB_OK:\n"
    "or.b32 %0, %0, 1;\n"
    "or.b32 %4, %4, 1;\n"
    "or.b32 %8, %8, 1;\n"
    "or.b32 %12, %12, 1;\n"
    "}\n"
    : "+r"(r[0][0]), "+r"(r[0][1]), "+r"(r[0][2]), "+r"(r[0][3]), "+r"(r[1][0]), "+r"(r[1][1]), "+r"(r[1][2]), "+r"(r[1][3]),
      "+r"(r[2][0]), "+r"(r[2][1]), "+r"(r[2][2]), "+r"(r[2][3]), "+r"(r[3][0]), "+r"(r[3][1]), "+r"(r[3][2]), "+r"(r[3][3])
    : "l"(p), "n"(0 * STR), "n"(1 * STR), "n"(2 * STR), "n"(3 * STR)
    : "memory");
}

#define SPIN_LIMIT (1 << 18)

__device__ __forceinline__ uint32_t smem_u32(const void* p) { return (uint32_t)__cvta_generic_to_shared(p); }
__device__ __forceinline__ void mbar_init(uint32_t a, uint32_t c) {
  asm volatile("mbarrier.init.shared::cta.b64 [%0], %1;" ::"r"(a), "r"(c) : "memory");
}
__device__ __forceinline__ void mbar_expect(uint32_t a, uint32_t b) {
  asm volatile("mbarrier.arrive.expect_tx.shared::cta.b64 _, [%0], %1;" ::"r"(a), "r"(b) : "memory");
}
__device__ __forceinline__ void mbar_arrive(uint32_t a) {
  asm volatile("mbarrier.arrive.shared::cta.b64 _, [%0];" ::"r"(a) : "memory");
}
__device__ __forceinline__ void mbar_wait(uint32_t a, uint32_t parity) {
  asm volatile(
      "{\n.reg .pred p;\n.reg .u32 n;\nmov.u32 n, 0;\n"
      "LAB_WAIT:\n"
      "mbarrier.try_wait.parity.shared::cta.b64 p, [%0], %1;\n"
      "@p bra LAB_DONE;\n"
      "add.u32 n, n, 1;\n"
      "setp.lt.u32 p, n, 262144;\n"
      "@p bra LAB_WAIT;\n"
      "LAB_DONE:\n}\n" ::"r"(a), "r"(parity) : "memory");
}
__device__ __forceinline__ bool mbar_test(uint32_t a, uint32_t parity) {
  uint32_t ok;
  asm volatile("{\n.reg .pred p;\nmbarrier.test_wait.parity.shared::cta.b64 p, [%1], %2;\nselp.u32 %0, 1, 0, p;\n}\n"
               : "=r"(ok) : "r"(a), "r"(parity) : "memory");
  return ok;
}
__device__ __forceinline__ void tma3d(uint32_t dst, const CUtensorMap* tm, uint32_t bar, int c0, int c1, int c2) {
  asm volatile(
      "cp.async.bulk.tensor.3d.shared::cluster.global.mbarrier::complete_tx::bytes [%0], [%1, {%3,%4,%5}], [%2];"
      ::"r"(dst), "l"(tm), "r"(bar), "r"(c0), "r"(c1), "r"(c2) : "memory");
}
__device__ __forceinline__ void wg_fence() { asm volatile("wgmma.fence.sync.aligned;" ::: "memory"); }
__device__ __forceinline__ void wg_commit() { asm volatile("wgmma.commit_group.sync.aligned;" ::: "memory"); }
template <int N> __device__ __forceinline__ void wg_wait() {
  asm volatile("wgmma.wait_group.sync.aligned %0;" ::"n"(N) : "memory");
}
template <int N> __device__ __forceinline__ void fence_regs(float (&d)[N]) {
#pragma unroll
  for (int i = 0; i < N; i++) asm volatile("" : "+f"(d[i])::"memory");
}
template <int N> __device__ __forceinline__ void fence_regs(uint32_t (&d)[N][4]) {
#pragma unroll
  for (int i = 0; i < N; i++) asm volatile("" : "+r"(d[i][0]), "+r"(d[i][1]), "+r"(d[i][2]), "+r"(d[i][3])::"memory");
}
template <int N> __device__ __forceinline__ void fence_frags(uint32_t (*d)[4]) {
#pragma unroll
  for (int i = 0; i < N; i++) asm volatile("" : "+r"(d[i][0]), "+r"(d[i][1]), "+r"(d[i][2]), "+r"(d[i][3])::"memory");
}
__device__ __forceinline__ void bar_sync(int id, int n) { asm volatile("bar.sync %0, %1;" ::"r"(id), "r"(n) : "memory"); }
__device__ __forceinline__ void bar_arrive(int id, int n) { asm volatile("bar.arrive %0, %1;" ::"r"(id), "r"(n) : "memory"); }

__device__ __forceinline__ uint32_t pack_bf16(float lo, float hi) {
  uint32_t r;
  asm("cvt.rn.bf16x2.f32 %0, %1, %2;" : "=r"(r) : "f"(hi), "f"(lo));
  return r;
}
__device__ __forceinline__ float bf_lo(uint32_t w) { return __uint_as_float(w << 16); }
__device__ __forceinline__ float bf_hi(uint32_t w) { return __uint_as_float(w & 0xFFFF0000u); }
__device__ __forceinline__ float round_bf16(float x) { return bf_lo(pack_bf16(x, 0.f)); }
__device__ __forceinline__ uint32_t hfma2_bf16(uint32_t a, uint32_t b, uint32_t c) {
  uint32_t r;
  asm("fma.rn.bf16x2 %0, %1, %2, %3;" : "=r"(r) : "r"(a), "r"(b), "r"(c));
  return r;
}
__device__ __forceinline__ float ex2(float x) {
  float r;
  asm("ex2.approx.ftz.f32 %0, %1;" : "=f"(r) : "f"(x));
  return r;
}
__device__ __forceinline__ float tanh_hw(float x) {
  float r;
  asm("tanh.approx.f32 %0, %1;" : "=f"(r) : "f"(x));
  return r;
}
template <int TAG> __device__ __forceinline__ uint32_t pack_tag(float lo, float hi) {
  uint32_t w = __byte_perm(__float_as_uint(lo), pack_bf16(lo, hi), 0x7632);
  return TAG ? (w | 1u) : (w & ~1u);
}
__device__ __forceinline__ void st_pkt(uint4* p, uint32_t a, uint32_t b, uint32_t c, uint32_t d) {
  asm volatile(
      "st.relaxed.gpu.global.v4.b32 [%0], {%1,%2,%3,%4};" ::"l"(p), "r"(a), "r"(b), "r"(c), "r"(d) : "memory");
}
__device__ __forceinline__ void ld_pkt(const uint4* p, uint32_t (&r)[4]) {
  asm volatile(
      "ld.relaxed.gpu.global.v4.b32 {%0,%1,%2,%3}, [%4];"
      : "=r"(r[0]), "=r"(r[1]), "=r"(r[2]), "=r"(r[3]) : "l"(p) : "memory");
}
__device__ __forceinline__ uint32_t ldg32(const void* p) {
  uint32_t r;
  asm volatile("ld.global.nc.b32 %0, [%1];" : "=r"(r) : "l"(p));
  return r;
}
__device__ __forceinline__ uint32_t ldg16(const void* p) {
  uint16_t r;
  asm volatile("ld.global.nc.b16 %0, [%1];" : "=h"(r) : "l"(p));
  return r;
}
__device__ __forceinline__ uint4 ldg128(const void* p) {
  uint4 r;
  asm volatile("ld.global.nc.v4.b32 {%0,%1,%2,%3}, [%4];" : "=r"(r.x), "=r"(r.y), "=r"(r.z), "=r"(r.w) : "l"(p));
  return r;
}
__device__ __forceinline__ void l2_prefetch(const void* p, uint32_t bytes) {
  asm volatile("cp.async.bulk.prefetch.L2.global [%0], %1;" ::"l"(p), "r"(bytes) : "memory");
}
__device__ __forceinline__ float rcp_hw(float x) {
  float r;
  asm("rcp.approx.ftz.f32 %0, %1;" : "=f"(r) : "f"(x));
  return r;
}
__device__ __forceinline__ void warp_bulk_load(uint32_t sdst, const void* gsrc, uint32_t bytes, uint32_t bar) {
  if ((threadIdx.x & 31) == 0) {
    mbar_expect(bar, bytes);
    asm volatile("cp.async.bulk.shared::cluster.global.mbarrier::complete_tx::bytes [%0], [%1], %2, [%3];"
                 ::"r"(sdst), "l"(gsrc), "r"(bytes), "r"(bar) : "memory");
  }
}
__device__ __forceinline__ void spin_cycles(uint32_t n) {
  uint32_t t0, t;
  asm volatile("mov.u32 %0, %%clock;" : "=r"(t0));
  do { asm volatile("mov.u32 %0, %%clock;" : "=r"(t)); } while (t - t0 < n);
}
__device__ __forceinline__ void sts128(uint32_t a, uint32_t x, uint32_t y, uint32_t z, uint32_t w) {
  asm volatile("st.shared.v4.b32 [%0], {%1,%2,%3,%4};" ::"r"(a), "r"(x), "r"(y), "r"(z), "r"(w) : "memory");
}
__device__ __forceinline__ void lds128(uint32_t a, uint32_t (&r)[4]) {
  asm volatile("ld.shared.v4.b32 {%0,%1,%2,%3}, [%4];" : "=r"(r[0]), "=r"(r[1]), "=r"(r[2]), "=r"(r[3]) : "r"(a) : "memory");
}

__device__ __forceinline__ uint32_t lds32(uint32_t a) {
  uint32_t r;
  asm volatile("ld.shared.b32 %0, [%1];" : "=r"(r) : "r"(a) : "memory");
  return r;
}
__device__ __forceinline__ void store_out(__nv_bfloat16* out, uint32_t woff, uint32_t x2s, const uint32_t (&gb)[4],
                                          const float (&y)[8]) {
  uint32_t xa[2][4];
  lds128(x2s, xa[0]);
  lds128(x2s + 512, xa[1]);
  uint32_t* const oo = (uint32_t*)out + woff;
#pragma unroll
  for (int e = 0; e < 4; e++)
    oo[(e >> 1) * 4 + (e & 1) * 8 * 256] =
        pack_bf16(fmaf(bf_lo(gb[e >> 1]), y[2 * e], __uint_as_float(xa[e >> 1][(e & 1) * 2])),
                  fmaf(bf_hi(gb[e >> 1]), y[2 * e + 1], __uint_as_float(xa[e >> 1][(e & 1) * 2 + 1])));
}

constexpr int SK = 2048, WIN = 512;
constexpr int FF = 1792, FSL = 224;
constexpr int NTILES = 80;
constexpr int NSLOT = 4;
constexpr uint32_t SLOT = 32768;
constexpr uint32_t SM_PARK = 0;
constexpr uint32_t SM_RING = 3 * SLOT;
constexpr uint32_t SM_TAB = 7 * SLOT;
constexpr uint32_t SM_RED = SM_TAB + 2048;
constexpr uint32_t SM_BAR = SM_RED + 256;
constexpr uint32_t SM_WBAR = SM_BAR + 128;
constexpr uint32_t SM_SBAR = SM_WBAR + 224;
constexpr uint32_t SM_TOTAL = SM_SBAR + 112;

struct Scratch {
  uint4 P[16 * 8 * 8 * 1024];
  uint4 G[16 * 8 * 32 * 32];
  uint4 mod1[8 * 256];
  uint4 mod2[512];
  uint4 uv[2 * 448];
  uint4 stat[16 * 8 * 8];
  uint32_t epoch;
};
__device__ Scratch g_scratch;

#define TS(i) do { } while (0)
#define TR(code)
#define CK_(v)
#define CKS(i, v)

struct Params {
  const __nv_bfloat16* x;
  const __nv_bfloat16* c;
  const __nv_bfloat16* wmod;
  const __nv_bfloat16* wo;
  const __nv_bfloat16* w1;
  const __nv_bfloat16* w2;
  __nv_bfloat16* out;
  Scratch* s;
};

constexpr uint32_t HI128 = (1024 >> 4) | (1u << 30);
constexpr uint32_t HI64 = (512 >> 4) | (2u << 30);
constexpr int LB_MN128 = (16384 >> 4) << 16;
constexpr int LB_K128 = 1 << 16;
constexpr int LB_W1 = (4096 >> 4) << 16;

template <int I> struct IC {
  __host__ __device__ constexpr operator int() const { return I; }
};
template <int I, int N, typename F> __device__ __forceinline__ void static_for(F&& f) {
  if constexpr (I < N) {
    f(IC<I>{});
    static_for<I + 1, N>(f);
  }
}

struct Ring {
  uint32_t base16, bars;
  __device__ __forceinline__ uint32_t wait_full(uint32_t slot, uint32_t parity) const {
    mbar_wait(bars + slot * 8, parity);
    return base16 + slot * (SLOT >> 4);
  }
  __device__ __forceinline__ void release(uint32_t slot) const {
    if ((threadIdx.x & 31) == 0) mbar_arrive(bars + 32 + slot * 8);
  }
};

__device__ __forceinline__ float silu_c(uint32_t bits) {
  float x = bf_lo(bits);
  return round_bf16(x * rcp_hw(1.f + ex2(-1.4426950408889634f * x)));
}
__device__ __forceinline__ void pack8(uint32_t (&o)[4], const float* v) {
  o[0] = pack_bf16(v[0], v[1]); o[1] = pack_bf16(v[2], v[3]); o[2] = pack_bf16(v[4], v[5]); o[3] = pack_bf16(v[6], v[7]);
}

template <int TAG, int N>
__device__ __forceinline__ void issue_pkts(const uint4* p, int stride, uint32_t (*r)[4]) {
#pragma unroll
  for (int i = 0; i < N; i++) ld_pkt(p + i * stride, r[i]);
}
__device__ __forceinline__ void ld_mod(const uint4* p, uint32_t tag, uint32_t (&r)[4]) {
  int spins = 0;
  ld_pkt(p, r);
  while (r[2] != tag && ++spins < SPIN_LIMIT) ld_pkt(p, r);
}

#define EARLY_TILES 2
#define PF_WMOD 1
#define MOD1_DELAY 500
#define RED3_UNIT 3
#define JLO 2
#define RED_DELAY 700
#define FIN_DELAY0 800
#define FIN_DELAY1 0
#define G_DELAY 0

__global__ void __launch_bounds__(384, 1)
adaln_block_kernel(const __grid_constant__ CUtensorMap tmWq, const __grid_constant__ CUtensorMap tmK,
                   const __grid_constant__ CUtensorMap tmV, const __grid_constant__ CUtensorMap tmWo,
                   const __grid_constant__ CUtensorMap tmW1, const __grid_constant__ CUtensorMap tmW2,
                   const __grid_constant__ CUtensorMap tmWm, const __grid_constant__ CUtensorMap tmP,
                   const __grid_constant__ CUtensorMap tmX, const Params p) {
  extern __shared__ __align__(1024) uint8_t smem_raw[];
  const uint32_t sb = smem_u32(smem_raw);
  const int tid = threadIdx.x, lane = tid & 31;
  const int warp = __shfl_sync(0xffffffffu, tid >> 5, 0);
  const int bid = blockIdx.x;
  const int j = ((bid >> (4 + JLO)) << JLO) | (bid & ((1 << JLO) - 1)), rt = (bid >> JLO) & 15;
  const uint32_t bars = sb + SM_BAR;

  if (warp >= 8) {
    CK_(c0);
    asm volatile("setmaxnreg.dec.sync.aligned.u32 56;");
    CK_(c1);
    const int t = tid - 256;
    uint32_t tag;
    {
      uint32_t cb[4];
      if (t == 0) {
        mbar_init(bars + 80, 1);
        asm volatile("fence.mbarrier_init.release.cluster;" ::: "memory");
        mbar_expect(bars + 80, 8192);
        tma3d(sb + SM_RING + 3 * SLOT, &tmWm, bars + 80, 0, 0, bid);
        tma3d(sb + SM_RING + 3 * SLOT + 4096, &tmWm, bars + 80, 0, 256, bid);
        asm volatile("prefetch.tensormap [%0];" ::"l"(&tmWq) : "memory");
        for (int i = 0; i < NSLOT; i++) { mbar_init(bars + i * 8, 1); mbar_init(bars + 32 + i * 8, 8); }
        mbar_init(bars + 72, 2);
        mbar_init(bars + 88, 2);
        for (int i = 0; i < 28; i++) mbar_init(sb + SM_WBAR + i * 8, 1);
        for (int i = 0; i < 14; i++) mbar_init(sb + SM_SBAR + i * 8, 8);
        asm volatile("fence.mbarrier_init.release.cluster;" ::: "memory");
      }
      __syncwarp();
      CK_(c2);
#pragma unroll
      for (int i = 0; i < 4; i++) cb[i] = ldg16(p.c + t + 128 * i);
      asm volatile("ld.relaxed.gpu.global.u32 %0, [%1];" : "=r"(tag) : "l"(&p.s->epoch) : "memory");
      bar_sync(5, 128);
      tag += 1;
      float a[8], sc[4];
#pragma unroll
      for (int i = 0; i < 4; i++) sc[i] = silu_c(cb[i]);
#pragma unroll
      for (int k = 0; k < 8; k++) a[k] = 0.f;
      mbar_wait(bars + 80, 0);
      CK_(c3);
#pragma unroll
      for (int i = 0; i < 4; i++) {
        uint32_t w[4];
        lds128(sb + SM_RING + 3 * SLOT + (t + 128 * i) * 16, w);
#pragma unroll
        for (int e = 0; e < 4; e++) {
          a[2 * e] = fmaf(sc[i], bf_lo(w[e]), a[2 * e]);
          a[2 * e + 1] = fmaf(sc[i], bf_hi(w[e]), a[2 * e + 1]);
        }
      }
      const bool h16 = lane & 16, h8 = lane & 8, h4 = lane & 4;
#pragma unroll
      for (int k = 0; k < 4; k++) {
        float send = h16 ? a[k] : a[k + 4], keep = h16 ? a[k + 4] : a[k];
        a[k] = keep + __shfl_xor_sync(0xffffffffu, send, 16);
      }
#pragma unroll
      for (int k = 0; k < 2; k++) {
        float send = h8 ? a[k] : a[k + 2], keep = h8 ? a[k + 2] : a[k];
        a[k] = keep + __shfl_xor_sync(0xffffffffu, send, 8);
      }
      {
        float send = h4 ? a[0] : a[1], keep = h4 ? a[1] : a[0];
        a[0] = keep + __shfl_xor_sync(0xffffffffu, send, 4);
      }
      a[0] += __shfl_xor_sync(0xffffffffu, a[0], 2);
      a[0] += __shfl_xor_sync(0xffffffffu, a[0], 1);
      float* red = (float*)(smem_raw + SM_RED);
      if ((lane & 3) == 0) red[(warp - 8) * 8 + (lane >> 2)] = a[0];
      if (t == 0) *(uint32_t*)(smem_raw + SM_BAR + 64) = tag;
      CK_(c4);
      bar_sync(5, 128);
      bar_arrive(7, 384);
      CK_(c5);
      if (t == 0) {
#pragma unroll
        for (int i = 0; i < EARLY_TILES; i++) {
          mbar_expect(bars + i * 8, SLOT);
          tma3d(sb + SM_RING + i * SLOT, &tmWq, bars + i * 8, 0, i * 128, (j * 4 + 1) * 2);
        }
      }
      if (warp == 9) {
        const int cl = lane & 7;
        float v = round_bf16(red[cl] + red[8 + cl] + red[16 + cl] + red[24 + cl]);
        if (bid >= 64) v = 1.f + v;
        float vn = __shfl_down_sync(0xffffffffu, v, 1);
        uint32_t wd = pack_bf16(v, vn);
        uint32_t w0 = __shfl_sync(0xffffffffu, wd, (lane & 1) * 4);
        uint32_t w1 = __shfl_sync(0xffffffffu, wd, (lane & 1) * 4 + 2);
        if (lane < 16) st_pkt(&p.s->mod1[(lane >> 1) * 256 + bid * 2 + (lane & 1)], w0, w1, tag, 0);
      }
      uint32_t r0[4], r1[4];
      const uint4* src = &p.s->mod1[j * 256 + t];
      CK_(c6);
      spin_cycles(MOD1_DELAY);
      CK_(c7);
      int spins = 0;
      do {
        ld_pkt(src, r0);
        ld_pkt(src + 128, r1);
      } while ((r0[2] != tag || r1[2] != tag) && ++spins < SPIN_LIMIT);
      const int g = t >> 2, pp = (t & 3) * 2;
      const uint32_t ad = sb + SM_TAB + (uint32_t)(g * 4 + (pp & 3)) * 16 + (pp >> 2) * 4;
      asm volatile("st.shared.b32 [%0], %1;" ::"r"(ad + 8), "r"(r0[0]) : "memory");
      asm volatile("st.shared.b32 [%0], %1;" ::"r"(ad + 24), "r"(r0[1]) : "memory");
      asm volatile("st.shared.b32 [%0], %1;" ::"r"(ad), "r"(r1[0]) : "memory");
      asm volatile("st.shared.b32 [%0], %1;" ::"r"(ad + 16), "r"(r1[1]) : "memory");
      bar_arrive(1, 384);
      CK_(c8);
      CKS(0, c0); CKS(1, c1); CKS(2, c2); CKS(3, c3); CKS(4, c4); CKS(5, c5); CKS(6, c6); CKS(7, c7); CKS(8, c8);
    }
    if (warp == 8) {
      if (lane == 0) {
        uint32_t s = EARLY_TILES & 3, ph = 1 ^ (EARLY_TILES >> 2);
#pragma unroll 1
        for (int tt = EARLY_TILES; tt < NTILES; tt++) {
          const CUtensorMap* tm;
          int c1, c2;
          uint32_t bytes = SLOT;
          if (tt < 16) {
            tm = &tmWq; c1 = (tt & 3) * 128; c2 = (j * 4 + (((tt >> 2) + 1) & 3)) * 2;
          } else if (tt < 48) {
            const int u = tt - 16;
            const bool isK = (u == 0) || ((u & 1) && u != 31);
            const int n = isK ? ((u + 1) >> 1) : (u == 31 ? 15 : (u >> 1) - 1);
            tm = isK ? &tmK : &tmV; c1 = j * SK + (SK - WIN) + (n & 3) * 128; c2 = 0;
          } else if (tt < 64) {
            const int u = tt - 48;
            tm = &tmWo; c1 = j * 512 + (u & 1) * 256; c2 = u >> 1;
          } else if (tt < 72) {
            tm = &tmW1; c1 = (tt - 64) * 64; c2 = j * 7; bytes = 28672;
          } else {
            tm = &tmW2; c1 = j * FSL; c2 = tt - 72; bytes = 28672;
          }
          mbar_wait(bars + 32 + s * 8, ph);
          mbar_expect(bars + s * 8, bytes);
          tma3d(sb + SM_RING + s * SLOT, tm, bars + s * 8, 0, c1, c2);
          if (++s == 4) { s = 0; ph ^= 1; }
        }
      }
    } else if (warp >= 10) {
      const int t2 = tid - 320, hf = t2 & 1, r0 = t2 >> 1;
      bar_sync(6, 352);
      float a[8];
#pragma unroll
      for (int k = 0; k < 8; k++) a[k] = 0.f;
#pragma unroll 1
      for (int b = 0; b < 8; b++) {
        uint4 w[2];
        uint32_t cb[2];
#pragma unroll
        for (int i = 0; i < 2; i++) {
          w[i] = ldg128(p.wmod + (size_t)(r0 + 32 * (2 * b + i)) * 3072 + 1024 + bid * 16 + hf * 8);
          cb[i] = ldg16(p.c + r0 + 32 * (2 * b + i));
        }
#pragma unroll
        for (int i = 0; i < 2; i++) {
          const float s = silu_c(cb[i]);
          a[0] = fmaf(s, bf_lo(w[i].x), a[0]); a[1] = fmaf(s, bf_hi(w[i].x), a[1]);
          a[2] = fmaf(s, bf_lo(w[i].y), a[2]); a[3] = fmaf(s, bf_hi(w[i].y), a[3]);
          a[4] = fmaf(s, bf_lo(w[i].z), a[4]); a[5] = fmaf(s, bf_hi(w[i].z), a[5]);
          a[6] = fmaf(s, bf_lo(w[i].w), a[6]); a[7] = fmaf(s, bf_hi(w[i].w), a[7]);
        }
      }
      const bool h16 = lane & 16, h8 = lane & 8, h4 = lane & 4;
#pragma unroll
      for (int k = 0; k < 4; k++) {
        float send = h16 ? a[k] : a[k + 4], keep = h16 ? a[k + 4] : a[k];
        a[k] = keep + __shfl_xor_sync(0xffffffffu, send, 16);
      }
#pragma unroll
      for (int k = 0; k < 2; k++) {
        float send = h8 ? a[k] : a[k + 2], keep = h8 ? a[k + 2] : a[k];
        a[k] = keep + __shfl_xor_sync(0xffffffffu, send, 8);
      }
      {
        float send = h4 ? a[0] : a[1], keep = h4 ? a[1] : a[0];
        a[0] = keep + __shfl_xor_sync(0xffffffffu, send, 4);
      }
      a[0] += __shfl_xor_sync(0xffffffffu, a[0], 2);
      float* red = (float*)(smem_raw + SM_RED) + 32;
      if ((lane & 2) == 0) red[(warp - 10) * 16 + hf * 8 + (lane >> 2)] = a[0];
      bar_sync(4, 64);
      if (warp == 10) {
        const int cl = lane & 15;
        float v = round_bf16(red[cl] + red[16 + cl]);
        if ((bid >> 5) == 2) v = 1.f + v;
        float vn = __shfl_down_sync(0xffffffffu, v, 1);
        uint32_t wd = pack_bf16(v, vn);
        uint32_t w0 = __shfl_sync(0xffffffffu, wd, (lane & 3) * 2);
        uint32_t w1 = __shfl_sync(0xffffffffu, wd, (lane & 3) * 2 + 8);
        const int vec = (0x2130 >> ((bid >> 5) * 4)) & 3;
        if (lane < 4) st_pkt(&p.s->mod2[((bid & 31) * 4 + vec) * 4 + lane], w0, w1, tag, 0);
      }
      const int isv = warp - 10;
      if (bid < 112) {
        const int kk = lane >> 1;
        const uint4* mp = &p.s->mod2[(isv ? 3 : 1) * 4 + ((kk & 7) >> 1)];
#pragma unroll
        for (int k = 0; k < 8; k++) a[k] = 0.f;
#pragma unroll 1
        for (int g = 0; g < 32; g++) {
          const uint4 w = ldg128(p.w1 + (size_t)(g * 16 + kk) * FF + bid * 16 + (lane & 1) * 8);
          uint32_t m[4];
          ld_mod(mp + g * 16, tag, m);
          const uint32_t mw = (kk & 8) ? m[1] : m[0];
          const float s = (kk & 1) ? bf_hi(mw) : bf_lo(mw);
          a[0] = fmaf(s, bf_lo(w.x), a[0]); a[1] = fmaf(s, bf_hi(w.x), a[1]);
          a[2] = fmaf(s, bf_lo(w.y), a[2]); a[3] = fmaf(s, bf_hi(w.y), a[3]);
          a[4] = fmaf(s, bf_lo(w.z), a[4]); a[5] = fmaf(s, bf_hi(w.z), a[5]);
          a[6] = fmaf(s, bf_lo(w.w), a[6]); a[7] = fmaf(s, bf_hi(w.w), a[7]);
        }
#pragma unroll
        for (int k = 0; k < 4; k++) {
          float send = h16 ? a[k] : a[k + 4], keep = h16 ? a[k + 4] : a[k];
          a[k] = keep + __shfl_xor_sync(0xffffffffu, send, 16);
        }
#pragma unroll
        for (int o = 8; o > 1; o >>= 1) {
#pragma unroll
          for (int k = 0; k < 4; k++) a[k] += __shfl_xor_sync(0xffffffffu, a[k], o);
        }
        const float sc = isv ? 0.5f : 1.f;
        if ((lane & 14) == 0)
          st_pkt(&p.s->uv[isv * 448 + bid * 4 + (lane & 1) * 2 + (lane >> 4)],
                 (__float_as_uint(a[0] * sc) & ~1u) | (tag & 1u), __float_as_uint(a[1] * sc), __float_as_uint(a[2] * sc),
                 __float_as_uint(a[3] * sc));
      }
#pragma unroll 1
      for (int i = lane; i < 56; i += 32) {
        uint32_t m[4];
        int spins = 0;
        do { ld_pkt(&p.s->uv[isv * 448 + j * 56 + i], m); } while (((m[0] ^ tag) & 1u) && ++spins < SPIN_LIMIT);
        const uint32_t ad = sb + SM_TAB + i * 32 + isv * 8;
        asm volatile("st.shared.v2.b32 [%0], {%1,%2};" ::"r"(ad), "r"(m[0]), "r"(m[1]) : "memory");
        asm volatile("st.shared.v2.b32 [%0], {%1,%2};" ::"r"(ad + 16), "r"(m[2]), "r"(m[3]) : "memory");
      }
      __syncwarp();
      if (lane == 0) mbar_arrive(bars + 72);

      const int q = lane & 3;
      float s0 = 0.f, s1 = 0.f, v0 = 0.f, v1 = 0.f;
      uint32_t ph = 0;
#pragma unroll 1
      for (int step = 0; step < 14; step++) {
        const bool ex1 = step < 8;
        const int cc = step & 7;
        auto item_issue = [&](int k2) {
          const int g = cc * 4 + isv * 2 + k2;
          const uint32_t bar = sb + SM_WBAR + 192 + (isv * 2 + k2) * 8;
          const uint32_t xs = sb + SM_PARK + SLOT + ((g & 7) ^ 4) * 4096 + (g >> 3) * 1024;
          if (lane == 0) {
            mbar_expect(bar, ex1 ? 4096 + 512 + 128 : 4096 + 64);
            tma3d(sb + SM_PARK + (g & 7) * 4096, &tmP, bar, 0, g, (rt * 8 + j) * 8);
            if (ex1) tma3d(xs, &tmX, bar, 0, rt * 128 + j * 16, g);
            asm volatile("cp.async.bulk.shared::cluster.global.mbarrier::complete_tx::bytes [%0], [%1], %2, [%3];"
                         ::"r"(ex1 ? xs + 512 : sb + SM_RED + (isv * 2 + k2) * 64), "l"(&p.s->mod2[g * 16 + (ex1 ? 0 : 8)]),
                           "r"(ex1 ? 128 : 64), "r"(bar) : "memory");
          }
        };
        mbar_wait(sb + SM_SBAR + step * 8, 0);
        spin_cycles(RED_DELAY);
        item_issue(0);
        item_issue(1);
#pragma unroll 1
        for (int k2 = 0; k2 < 2; k2++) {
          const int g = cc * 4 + isv * 2 + k2;
          const uint32_t bar = sb + SM_WBAR + 192 + (isv * 2 + k2) * 8;
          const uint32_t ls = sb + SM_PARK + (g & 7) * 4096 + lane * 16;
          const uint32_t xs = sb + SM_PARK + SLOT + ((g & 7) ^ 4) * 4096 + (g >> 3) * 1024;
          const uint32_t ms = ex1 ? xs + 512 : sb + SM_RED + (isv * 2 + k2) * 64;
          uint32_t m1[4], m2[4];
          for (int spins = 0; spins < SPIN_LIMIT; spins++) {
            mbar_wait(bar, (ph >> k2) & 1);
            ph ^= 1u << k2;
            uint32_t bad = 0;
#pragma unroll
            for (int i = 0; i < 8; i++) bad |= lds32(ls + i * 512) ^ (uint32_t)ex1;
            lds128(ms + q * 16, m1);
            lds128(ms + (ex1 ? 64 : 0) + q * 16, m2);
            if (!__any_sync(0xffffffffu, (bad & 1u) || m1[2] != tag || m2[2] != tag)) break;
            item_issue(k2);
          }
          float y[8];
#pragma unroll
          for (int i = 0; i < 8; i++) {
            uint32_t r[4];
            lds128(ls + i * 512, r);
            r[0] |= 1u;
#pragma unroll
            for (int e = 0; e < 4; e++) {
              y[2 * e] = i ? y[2 * e] + bf_lo(r[e]) : bf_lo(r[e]);
              y[2 * e + 1] = i ? y[2 * e + 1] + bf_hi(r[e]) : bf_hi(r[e]);
            }
          }
          if (ex1) {
            uint32_t xr[4];
            asm volatile("ldmatrix.sync.aligned.m8n8.x4.shared.b16 {%0,%1,%2,%3}, [%4];"
                         : "=r"(xr[0]), "=r"(xr[1]), "=r"(xr[2]), "=r"(xr[3]) : "r"(xs + (lane & 15) * 32 + (lane >> 4) * 16) : "memory");
#pragma unroll
            for (int e = 0; e < 4; e++) {
              const float a = fmaf(bf_lo(m1[e >> 1]), y[2 * e], bf_lo(xr[e])), b = fmaf(bf_hi(m1[e >> 1]), y[2 * e + 1], bf_hi(xr[e]));
              y[2 * e] = a; y[2 * e + 1] = b;
              if (e & 1) { s1 += a + b; v1 = fmaf(a, a, fmaf(b, b, v1)); }
              else { s0 += a + b; v0 = fmaf(a, a, fmaf(b, b, v0)); }
            }
            st_pkt(p.s->G + ((rt * 8 + j) * 32 + g) * 32 + lane, pack_tag<0>(y[0] * bf_lo(m2[0]), y[1] * bf_hi(m2[0])),
                   pack_bf16(y[2] * bf_lo(m2[0]), y[3] * bf_hi(m2[0])), pack_bf16(y[4] * bf_lo(m2[1]), y[5] * bf_hi(m2[1])),
                   pack_bf16(y[6] * bf_lo(m2[1]), y[7] * bf_hi(m2[1])));
            __syncwarp();
            sts128(xs + lane * 16, __float_as_uint(y[0]), __float_as_uint(y[1]), __float_as_uint(y[2]), __float_as_uint(y[3]));
            sts128(xs + 512 + lane * 16, __float_as_uint(y[4]), __float_as_uint(y[5]), __float_as_uint(y[6]), __float_as_uint(y[7]));
          } else {
            store_out(p.out, (uint32_t)(rt * 128 + 16 * j + (lane >> 2)) * 256 + g * 8 + q, xs + lane * 16, m1, y);
          }
        }
        if (step == 7) {
#pragma unroll
          for (int o = 1; o < 4; o <<= 1) {
            s0 += __shfl_xor_sync(0xffffffffu, s0, o);
            s1 += __shfl_xor_sync(0xffffffffu, s1, o);
            v0 += __shfl_xor_sync(0xffffffffu, v0, o);
            v1 += __shfl_xor_sync(0xffffffffu, v1, o);
          }
          if (isv && q == 0) sts128(sb + SM_RED + (lane >> 2) * 16, __float_as_uint(s0), __float_as_uint(v0), __float_as_uint(s1), __float_as_uint(v1));
          bar_sync(4, 64);
          if (!isv) {
            uint32_t o[4];
            lds128(sb + SM_RED + (lane >> 2) * 16, o);
            const float m0 = (s0 + __uint_as_float(o[0])) * (1.f / 512.f), m1 = (s1 + __uint_as_float(o[2])) * (1.f / 512.f);
            const float r0 = 0.5f * rsqrtf(fmaxf(fmaf(-m0, m0, (v0 + __uint_as_float(o[1])) * (1.f / 512.f)), 0.f) + 1e-5f);
            const float r1 = 0.5f * rsqrtf(fmaxf(fmaf(-m1, m1, (v1 + __uint_as_float(o[3])) * (1.f / 512.f)), 0.f) + 1e-5f);
            if (q == 0)
              st_pkt(&p.s->stat[(rt * 8 + j) * 8 + (lane >> 2)], (__float_as_uint(r0) & ~1u) | (tag & 1u),
                     __float_as_uint(-m0 * r0), __float_as_uint(r1), __float_as_uint(-m1 * r1));
          }
          __syncwarp();
          if (lane == 0) mbar_arrive(bars + 88);
        }
      }
    } else {
      bar_sync(6, 352);
      if (lane < 8) l2_prefetch((const char*)p.wo + (size_t)bid * 32768 + lane * 4096, 4096);
      else if (lane < 12) l2_prefetch((const char*)p.w1 + (size_t)bid * 14336 + (lane - 8) * 3584, 3584);
      else if (lane < 16) l2_prefetch((const char*)p.w2 + (size_t)bid * 14336 + (lane - 12) * 3584, 3584);
    }
  } else {
    const int wg = warp >> 2;
    const int q = lane & 3, gq = lane >> 2;
    const Ring ring{(sb + SM_RING) >> 4, bars};
    const uint32_t xoff = (uint32_t)(rt * 128 + 16 * j + warp) * 256 + gq * 8 + q;
    const uint32_t ooff = ((uint32_t)(rt * 8 + j) * 32 + gq) * 32 + warp * 4 + q;
    const uint32_t wblk = sb + SM_PARK + warp * 4096, wprv = wblk + lane * 16;
    const uint32_t wbar = sb + SM_WBAR + warp * 24;
    const uint32_t goff = (uint32_t)(rt * 8 + warp) * 1024 + lane;

    {
      const uint32_t* xo = (const uint32_t*)p.x + xoff;
      uint32_t xr[4][4];
      CK_(d0);
#pragma unroll
      for (int c = 0; c < 4; c++) {
        xr[c][0] = ldg32(xo + c * 64);
        xr[c][1] = ldg32(xo + c * 64 + 8 * 256);
        xr[c][2] = ldg32(xo + c * 64 + 4);
        xr[c][3] = ldg32(xo + c * 64 + 4 + 8 * 256);
      }
      CK_(d1);
      fence_regs(xr);
      CK_(d2);
      float s0 = 0.f, s1 = 0.f, v0 = 0.f, v1 = 0.f;
#pragma unroll
      for (int c = 0; c < 4; c++) {
#pragma unroll
        for (int e = 0; e < 4; e++) {
          const float a = bf_lo(xr[c][e]), b = bf_hi(xr[c][e]);
          if (e & 1) { s1 += a + b; v1 = fmaf(a, a, fmaf(b, b, v1)); }
          else { s0 += a + b; v0 = fmaf(a, a, fmaf(b, b, v0)); }
        }
      }
#pragma unroll
      for (int o = 16; o > 0; o >>= 1) {
        s0 += __shfl_xor_sync(0xffffffffu, s0, o);
        s1 += __shfl_xor_sync(0xffffffffu, s1, o);
        v0 += __shfl_xor_sync(0xffffffffu, v0, o);
        v1 += __shfl_xor_sync(0xffffffffu, v1, o);
      }
      const float m0 = s0 * (1.f / 512.f), m1 = s1 * (1.f / 512.f);
      const float r0 = rsqrtf(fmaxf(fmaf(-m0, m0, v0 * (1.f / 512.f)), 0.f) + 1e-5f);
      const float r1 = rsqrtf(fmaxf(fmaf(-m1, m1, v1 * (1.f / 512.f)), 0.f) + 1e-5f);
#pragma unroll
      for (int c = 0; c < 4; c++) {
        st_pkt(p.s->G + ooff + c * 256,
               pack_tag<1>((bf_lo(xr[c][0]) - m0) * r0, (bf_hi(xr[c][0]) - m0) * r0),
               pack_bf16((bf_lo(xr[c][1]) - m1) * r1, (bf_hi(xr[c][1]) - m1) * r1),
               pack_bf16((bf_lo(xr[c][2]) - m0) * r0, (bf_hi(xr[c][2]) - m0) * r0),
               pack_bf16((bf_lo(xr[c][3]) - m1) * r1, (bf_hi(xr[c][3]) - m1) * r1));
      }
      CK_(d3);
      CKS(16, d0); CKS(17, d1); CKS(18, d2); CKS(19, d3);

    }
    asm volatile("setmaxnreg.inc.sync.aligned.u32 224;");
    uint32_t qf[8][4];
    {
      uint32_t h[32][4];
      float acc[64];
      const uint4* Gin = p.s->G + goff;
      bar_sync(7, 384);
      if (G_DELAY) spin_cycles(G_DELAY);
#pragma unroll
      for (int c = 0; c < 3; c++) warp_bulk_load(wblk + c * SLOT, Gin + c * 256, 4096, wbar + c * 8);
#pragma unroll
      for (int c = 0; c < 4; c++) {
        mbar_wait(wbar + (c % 3) * 8, c / 3);
#pragma unroll
        for (int i = 0; i < 8; i++) lds128(wprv + (c % 3) * SLOT + i * 512, h[c * 8 + i]);
        verify8_tag1<512>(Gin + c * 256, h + c * 8);
        if (c == 0) {
          warp_bulk_load(wblk, Gin + 768, 4096, wbar);
          TS(1);
          bar_sync(1, 384);
        }
#pragma unroll
        for (int i = 0; i < 8; i++) {
          uint32_t m[4];
          lds128(sb + SM_TAB + (uint32_t)((c * 8 + i) * 4 + q) * 16, m);
          uint32_t* hh = h[c * 8 + i];
          hh[0] = hfma2_bf16(hh[0], m[0], m[2]);
          hh[1] = hfma2_bf16(hh[1], m[0], m[2]);
          hh[2] = hfma2_bf16(hh[2], m[1], m[3]);
          hh[3] = hfma2_bf16(hh[3], m[1], m[3]);
        }
        fence_frags<8>(h + c * 8);
        const uint32_t b = ring.wait_full(c, 0);
        if (c > 0) { wg_wait<0>(); ring.release(c - 1); }
        if (c == 0) TS(2);
        wg_fence();
        static_for<0, 8>([&](auto K) { wgmma_rs_n128_tb1<LB_MN128 + K * 128, HI128>(acc, h[c * 8 + K], b, (c | K) != 0); });
        wg_commit();
      }
      bar_arrive(6, 352);
#pragma unroll 1
      for (int ps = 1; ps < 4; ps++) {
        wg_wait<0>();
        ring.release(3);
        fence_regs(acc);
#pragma unroll
        for (int i = 0; i < 8; i++) {
          uint32_t o[4];
          pack8(o, acc + 8 * i);
          sts128(wprv + (ps - 1) * SLOT + i * 512, o[0], o[1], o[2], o[3]);
        }
#pragma unroll
        for (int c = 0; c < 4; c++) {
          const uint32_t b = ring.wait_full(c, ps & 1);
          if (c > 0) { wg_wait<0>(); ring.release(c - 1); }
          wg_fence();
          static_for<0, 8>([&](auto K) { wgmma_rs_n128_tb1<LB_MN128 + K * 128, HI128>(acc, h[c * 8 + K], b, (c | K) != 0); });
          wg_commit();
        }
      }
      wg_wait<0>();
      ring.release(3);
      fence_regs(acc);
#pragma unroll
      for (int i = 0; i < 8; i++) pack8(qf[i], acc + 8 * i);
    }
    fence_regs(qf);
    TS(3);

    float S[64];
    {
      float O[64];
      uint32_t P[8][4];
      const float cs = 0.08838834764831845f * 1.4426950408889634f;
      const int TAU = 0x41800000;
      float m0, m1, l0, l1;

      auto float_block_max = [&]() {
        float b0 = fmaxf(S[0], S[1]), b1 = fmaxf(S[2], S[3]);
#pragma unroll
        for (int i = 1; i < 16; i++) {
          b0 = fmaxf(b0, fmaxf(S[4 * i], S[4 * i + 1]));
          b1 = fmaxf(b1, fmaxf(S[4 * i + 2], S[4 * i + 3]));
        }
        b0 = fmaxf(b0, __shfl_xor_sync(0xffffffffu, b0, 1)); b1 = fmaxf(b1, __shfl_xor_sync(0xffffffffu, b1, 1));
        b0 = fmaxf(b0, __shfl_xor_sync(0xffffffffu, b0, 2)); b1 = fmaxf(b1, __shfl_xor_sync(0xffffffffu, b1, 2));
        m0 = b0 * cs; m1 = b1 * cs;
      };
      auto first_block_max = [&]() {
        int a0 = max(__float_as_int(S[0]), __float_as_int(S[1]));
        int a1 = max(__float_as_int(S[2]), __float_as_int(S[3]));
#pragma unroll
        for (int i = 1; i < 16; i++) {
          a0 = __vimax3_s32(a0, __float_as_int(S[4 * i]), __float_as_int(S[4 * i + 1]));
          a1 = __vimax3_s32(a1, __float_as_int(S[4 * i + 2]), __float_as_int(S[4 * i + 3]));
        }
        a0 = max(a0, __shfl_xor_sync(0xffffffffu, a0, 1)); a1 = max(a1, __shfl_xor_sync(0xffffffffu, a1, 1));
        a0 = max(a0, __shfl_xor_sync(0xffffffffu, a0, 2)); a1 = max(a1, __shfl_xor_sync(0xffffffffu, a1, 2));
        m0 = __int_as_float(a0) * cs; m1 = __int_as_float(a1) * cs;
        if (__any_sync(0xffffffffu, (a0 | a1) < 0)) float_block_max();
      };
      auto scale_sub = [&]() {
#pragma unroll
        for (int i = 0; i < 16; i++) {
          S[4 * i] = fmaf(S[4 * i], cs, -m0); S[4 * i + 1] = fmaf(S[4 * i + 1], cs, -m0);
          S[4 * i + 2] = fmaf(S[4 * i + 2], cs, -m1); S[4 * i + 3] = fmaf(S[4 * i + 3], cs, -m1);
        }
      };
      auto exps = [&](int i0, int i1) {
#pragma unroll
        for (int i = i0; i < i1; i++) {
          S[4 * i] = ex2(S[4 * i]); S[4 * i + 1] = ex2(S[4 * i + 1]);
          S[4 * i + 2] = ex2(S[4 * i + 2]); S[4 * i + 3] = ex2(S[4 * i + 3]);
          l0 += S[4 * i]; l1 += S[4 * i + 2]; l0 += S[4 * i + 1]; l1 += S[4 * i + 3];
        }
      };
      {
        const uint32_t b = ring.wait_full(0, 0);
        wg_fence();
        static_for<0, 8>([&](auto K) { wgmma_rs_n128_tb0<LB_K128 + (K >> 2) * 1024 + (K & 3) * 2, HI128>(S, qf[K], b, K != 0); });
        wg_commit();
        wg_wait<0>();
        fence_regs(S);
        ring.release(0);
        float_block_max();
        scale_sub();
        l0 = 0.f; l1 = 0.f;
        exps(0, 16);
#pragma unroll
        for (int i = 0; i < 8; i++) pack8(P[i], S + 8 * i);
      }
      fence_regs(P);
      if (wg == 1) bar_arrive(2, 256);
#pragma unroll 1
      for (int n = 1; n < 16; n++) {
        const uint32_t tk = 2 * n - 1, tv = 2 * n;
        const bool newhead = (n & 3) == 0;
        const uint32_t bk = ring.wait_full(tk & 3, (tk >> 2) & 1);
        const uint32_t bv = ring.wait_full(tv & 3, (tv >> 2) & 1);
        bar_sync(2 + wg, 256);
        wg_fence();
        static_for<0, 8>([&](auto K) { wgmma_rs_n128_tb0<LB_K128 + (K >> 2) * 1024 + (K & 3) * 2, HI128>(S, qf[K], bk, K != 0); });
        wg_commit();
        static_for<0, 8>([&](auto K) { wgmma_rs_n128_tb1<LB_MN128 + K * 128, HI128>(O, P[K], bv, K != 0 || (n & 3) != 1); });
        wg_commit();
        bar_arrive(2 + (wg ^ 1), 256);
        wg_wait<1>();
        fence_regs(S);
        ring.release(tk & 3);
        if ((n & 3) == 3 && n != 15) {
          fence_regs(qf);
#pragma unroll
          for (int i = 0; i < 8; i++) lds128(wprv + (n >> 2) * SLOT + i * 512, qf[i]);
        }
        float f0 = 1.f, f1 = 1.f;
        bool resc = newhead;
        if (newhead) {
          l0 += __shfl_xor_sync(0xffffffffu, l0, 1); l1 += __shfl_xor_sync(0xffffffffu, l1, 1);
          l0 += __shfl_xor_sync(0xffffffffu, l0, 2); l1 += __shfl_xor_sync(0xffffffffu, l1, 2);
          f0 = rcp_hw(l0); f1 = rcp_hw(l1);
          l0 = 0.f; l1 = 0.f;
          first_block_max();
          scale_sub();
        } else {
          scale_sub();
          int a0 = __vimax3_s32(__float_as_int(S[0]), __float_as_int(S[1]), __float_as_int(S[1]));
          int a1 = __vimax3_s32(__float_as_int(S[2]), __float_as_int(S[3]), __float_as_int(S[3]));
#pragma unroll
          for (int i = 1; i < 16; i++) {
            a0 = __vimax3_s32(a0, __float_as_int(S[4 * i]), __float_as_int(S[4 * i + 1]));
            a1 = __vimax3_s32(a1, __float_as_int(S[4 * i + 2]), __float_as_int(S[4 * i + 3]));
          }
          if (__any_sync(0xffffffffu, max(a0, a1) > TAU)) {
            a0 = max(a0, 0); a1 = max(a1, 0);
            a0 = max(a0, __shfl_xor_sync(0xffffffffu, a0, 1)); a1 = max(a1, __shfl_xor_sync(0xffffffffu, a1, 1));
            a0 = max(a0, __shfl_xor_sync(0xffffffffu, a0, 2)); a1 = max(a1, __shfl_xor_sync(0xffffffffu, a1, 2));
            const float d0 = __int_as_float(a0), d1 = __int_as_float(a1);
#pragma unroll
            for (int i = 0; i < 16; i++) { S[4 * i] -= d0; S[4 * i + 1] -= d0; S[4 * i + 2] -= d1; S[4 * i + 3] -= d1; }
            m0 += d0; m1 += d1;
            f0 = ex2(-d0); f1 = ex2(-d1);
            l0 *= f0; l1 *= f1;
            resc = true;
          }
        }
        exps(0, 4);
        wg_wait<0>();
        fence_regs(O);
        fence_regs(P);
        ring.release(tv & 3);
        if (resc) {
#pragma unroll
          for (int i = 0; i < 16; i++) {
            O[4 * i] *= f0; O[4 * i + 1] *= f0; O[4 * i + 2] *= f1; O[4 * i + 3] *= f1;
          }
          if (newhead) {
#pragma unroll
            for (int i = 0; i < 8; i++) {
              uint32_t o[4];
              pack8(o, O + 8 * i);
              sts128(wprv + ((n >> 2) - 1) * SLOT + i * 512, o[0], o[1], o[2], o[3]);
            }
          }
        }
        exps(4, 16);
#pragma unroll
        for (int i = 0; i < 8; i++) pack8(P[i], S + 8 * i);
        fence_regs(P);
        fence_regs(O);
      }
      {
        const uint32_t bv = ring.wait_full(3, 1);
        if (wg == 0) bar_sync(2, 256);
        wg_fence();
        static_for<0, 8>([&](auto K) { wgmma_rs_n128_tb1<LB_MN128 + K * 128, HI128>(O, P[K], bv, 1); });
        wg_commit();
        l0 += __shfl_xor_sync(0xffffffffu, l0, 1); l1 += __shfl_xor_sync(0xffffffffu, l1, 1);
        l0 += __shfl_xor_sync(0xffffffffu, l0, 2); l1 += __shfl_xor_sync(0xffffffffu, l1, 2);
        const float f0 = rcp_hw(l0), f1 = rcp_hw(l1);
        wg_wait<0>();
        fence_regs(O);
        ring.release(3);
#pragma unroll
        for (int i = 0; i < 8; i++) {
          qf[i][0] = pack_bf16(O[8 * i] * f0, O[8 * i + 1] * f0); qf[i][1] = pack_bf16(O[8 * i + 2] * f1, O[8 * i + 3] * f1);
          qf[i][2] = pack_bf16(O[8 * i + 4] * f0, O[8 * i + 5] * f0); qf[i][3] = pack_bf16(O[8 * i + 6] * f1, O[8 * i + 7] * f1);
        }
      }
    }
    fence_regs(qf);
    TS(4);

    uint4* const Pout = p.s->P + ((size_t)(rt * 8 + warp) * 8 + j) * 1024 + lane;
    const uint32_t tag = *(volatile uint32_t*)(smem_raw + SM_BAR + 64);

    float acc2[32];
    uint32_t pk[4][4];
    auto pack_partial = [&](auto TAGC) {
      fence_regs(acc2);
#pragma unroll
      for (int i = 0; i < 4; i++) {
        pack8(pk[i], acc2 + 8 * i);
        pk[i][0] = pack_tag<TAGC>(acc2[8 * i], acc2[8 * i + 1]);
      }
      fence_regs(pk);
    };
    auto store_partial = [&](int step) {
#pragma unroll
      for (int i = 0; i < 4; i++) st_pkt(Pout + ((step & 7) * 4 + i) * 32, pk[i][0], pk[i][1], pk[i][2], pk[i][3]);
      if (lane == 0 && step < 14) mbar_arrive(sb + SM_SBAR + step * 8);
    };
    const uint4* const Gin = p.s->G + goff;
    auto g_issue = [&](int u) { warp_bulk_load(wblk + 2 * SLOT + (u & 1) * 2048, Gin + u * 128, 2048, wbar + (u & 1) * 8); };

    uint32_t tl = 0, b = ring.wait_full(0, 0);
    auto next_tile = [&]() {
      const uint32_t cur = tl & 3;
      tl++;
      b = ring.wait_full(tl & 3, (tl >> 2) & 1);
      wg_wait<0>();
      TR(4);
      ring.release(cur);
    };
    {
      uint32_t o[24][4];
#pragma unroll
      for (int i = 0; i < 24; i++) lds128(wprv + (i >> 3) * SLOT + (i & 7) * 512, o[i]);
#pragma unroll 1
      for (int cc = 0; cc < 8; cc++) {
        wg_fence();
        static_for<0, 16>([&](auto K) { wgmma_rs_n64_tb1<K * 128, HI128>(acc2, o[K], b, K != 0); });
        wg_commit();
        if (cc > 0) store_partial(cc - 1);
        next_tile();
        wg_fence();
        static_for<0, 16>([&](auto K) { wgmma_rs_n64_tb1<K * 128, HI128>(acc2, K < 8 ? o[16 + (K & 7)] : qf[K & 7], b, 1); });
        wg_commit();
        if (cc == 6) { g_issue(0); g_issue(1); }
        next_tile();
        pack_partial(IC<1>{});
      }
    }
    TS(5);

    uint32_t H[14][4];
    {
      float acc[112];
      const uint4* const statp = &p.s->stat[(rt * 8 + warp) * 8];
#pragma unroll 1
      for (int u = 0; u < 8; u++) {
        uint32_t fa[4][4];
        mbar_wait(wbar + (u & 1) * 8, ((u >> 1) + (u & 1)) & 1);
#pragma unroll
        for (int i = 0; i < 4; i++) lds128(wprv + 2 * SLOT + (u & 1) * 2048 + i * 512, fa[i]);
        verify4_tag0<512>(Gin + u * 128, fa);
        wg_fence();
        static_for<0, 4>([&](auto K) { wgmma_rs_n224_tb1<LB_W1 + K * 64, HI64>(acc, fa[K], b, (u | K) != 0); });
        wg_commit();
        if (u == 0) store_partial(7);
        if (u < 5) g_issue(u + 2);
        if (u == 7) warp_bulk_load(wblk + 2 * SLOT, statp, 128, wbar + 16);
        next_tile();
        if (u == 5) g_issue(7);
      }
      fence_regs(acc);
      TS(9);
      mbar_wait(bars + 72, 0);
      uint32_t xr[4];
      mbar_wait(wbar + 16, 1);
      lds128(wblk + 2 * SLOT + gq * 16, xr);
      {
        int spins = 0;
        while (((xr[0] ^ tag) & 1u) && ++spins < SPIN_LIMIT) ld_pkt(statp + gq, xr);
      }
      const float ra0 = __uint_as_float(xr[0]), rb0 = __uint_as_float(xr[1]), ra1 = __uint_as_float(xr[2]),
                  rb1 = __uint_as_float(xr[3]);
#pragma unroll
      for (int i = 0; i < 28; i++) {
        uint32_t m[4];
        lds128(sb + SM_TAB + (i * 4 + q) * 16, m);
        const float u0 = __uint_as_float(m[0]), u1 = __uint_as_float(m[1]), w0 = __uint_as_float(m[2]), w1 = __uint_as_float(m[3]);
        const float z0 = fmaf(acc[4 * i], ra0, fmaf(u0, rb0, w0)), z1 = fmaf(acc[4 * i + 1], ra0, fmaf(u1, rb0, w1));
        const float z2 = fmaf(acc[4 * i + 2], ra1, fmaf(u0, rb1, w0)), z3 = fmaf(acc[4 * i + 3], ra1, fmaf(u1, rb1, w1));
        H[i >> 1][(i & 1) * 2] = pack_bf16(fmaf(z0, tanh_hw(z0), z0), fmaf(z1, tanh_hw(z1), z1));
        H[i >> 1][(i & 1) * 2 + 1] = pack_bf16(fmaf(z2, tanh_hw(z2), z2), fmaf(z3, tanh_hw(z3), z3));
      }
    }
    fence_regs(H);
    TS(10);
    const int go = 24 + (warp ^ 4);
    uint32_t gb[4];
    ld_pkt(p.s->mod2 + go * 16 + 8 + q, gb);
#pragma unroll 1
    for (int cc = 0; cc < 8; cc++) {
      wg_fence();
      static_for<0, 14>([&](auto K) { wgmma_rs_n64_tb1<K * 128, HI128>(acc2, H[K], b, K != 0); });
      wg_commit();
      if (cc > 0) store_partial(8 + cc - 1);
      if (cc < 7) next_tile();
      wg_wait<0>();
      pack_partial(IC<0>{});
    }
    store_partial(15);
    TS(11);
    {
      const uint4* const Pown = p.s->P + (size_t)(rt * 8 + j) * 8192 + go * 32 + lane;
      uint32_t r[8][4];
      float y[8];
      if (gb[2] != tag) ld_mod(p.s->mod2 + go * 16 + 8 + q, tag, gb);
      mbar_wait(bars + 88, 0);
      spin_cycles(wg ? FIN_DELAY1 : FIN_DELAY0);
      issue_pkts<0, 8>(Pown, 1024, r);
      verify8_tag0<16384>(Pown, r);
      TS(13);
#pragma unroll
      for (int e = 0; e < 4; e++) {
        y[2 * e] = bf_lo(r[0][e]); y[2 * e + 1] = bf_hi(r[0][e]);
#pragma unroll
        for (int s = 1; s < 8; s++) { y[2 * e] += bf_lo(r[s][e]); y[2 * e + 1] += bf_hi(r[s][e]); }
      }
      store_out(p.out, (uint32_t)(rt * 128 + 16 * j + gq) * 256 + go * 8 + q, wprv + SLOT + 3 * 1024, gb, y);
    }
    TS(12);
    if (bid == 0 && tid == 0) asm volatile("st.relaxed.gpu.global.u32 [%0], %1;" ::"l"(&p.s->epoch), "r"(tag) : "memory");
  }
}

typedef CUresult (*EncodeFn)(CUtensorMap*, CUtensorMapDataType, cuuint32_t, void*, const cuuint64_t*, const cuuint64_t*,
                             const cuuint32_t*, const cuuint32_t*, CUtensorMapInterleave, CUtensorMapSwizzle,
                             CUtensorMapL2promotion, CUtensorMapFloatOOBfill);

static void make_map(EncodeFn fn, CUtensorMap* tm, const void* ptr, int inner, int rows, int cols, int box_rows, int box_outer,
                     CUtensorMapSwizzle swz) {
  cuuint64_t gd[3] = {(cuuint64_t)inner, (cuuint64_t)rows, (cuuint64_t)(cols / inner)};
  cuuint64_t gs[2] = {(cuuint64_t)cols * 2, (cuuint64_t)inner * 2};
  cuuint32_t bx[3] = {(cuuint32_t)inner, (cuuint32_t)box_rows, (cuuint32_t)box_outer};
  cuuint32_t es[3] = {1, 1, 1};
  fn(tm, CU_TENSOR_MAP_DATA_TYPE_BFLOAT16, 3, const_cast<void*>(ptr), gd, gs, bx, es, CU_TENSOR_MAP_INTERLEAVE_NONE, swz,
     CU_TENSOR_MAP_L2_PROMOTION_L2_128B, CU_TENSOR_MAP_FLOAT_OOB_FILL_NONE);
}

extern "C" void kernel_launch(void* const* d_in, const int* in_sizes, int n_in, void* d_out, int out_size) {
  (void)in_sizes; (void)n_in; (void)out_size;
  void* fnp = nullptr;
  cudaDriverEntryPointQueryResult qr;
  cudaGetDriverEntryPoint("cuTensorMapEncodeTiled", &fnp, cudaEnableDefault, &qr);
  EncodeFn fn = (EncodeFn)fnp;
  CUtensorMap tmWq, tmK, tmV, tmWo, tmW1, tmW2, tmWm, tmP, tmX;
  make_map(fn, &tmWq, d_in[3], 64, 512, 4096, 128, 2, CU_TENSOR_MAP_SWIZZLE_128B);
  make_map(fn, &tmK, d_in[1], 64, 8 * SK, 128, 128, 2, CU_TENSOR_MAP_SWIZZLE_128B);
  make_map(fn, &tmV, d_in[2], 64, 8 * SK, 128, 128, 2, CU_TENSOR_MAP_SWIZZLE_128B);
  make_map(fn, &tmWo, d_in[4], 64, 4096, 512, 256, 1, CU_TENSOR_MAP_SWIZZLE_128B);
  make_map(fn, &tmW1, d_in[6], 32, 512, FF, 64, 7, CU_TENSOR_MAP_SWIZZLE_64B);
  make_map(fn, &tmW2, d_in[7], 64, FF, 512, 224, 1, CU_TENSOR_MAP_SWIZZLE_128B);
  make_map(fn, &tmWm, d_in[9], 8, 512, 3072, 256, 1, CU_TENSOR_MAP_SWIZZLE_NONE);
  make_map(fn, &tmX, d_in[0], 16, 2048, 512, 16, 1, CU_TENSOR_MAP_SWIZZLE_NONE);
  Params p;
  p.x = (const __nv_bfloat16*)d_in[0];
  p.c = (const __nv_bfloat16*)d_in[8];
  p.wmod = (const __nv_bfloat16*)d_in[9];
  p.wo = (const __nv_bfloat16*)d_in[4];
  p.w1 = (const __nv_bfloat16*)d_in[6];
  p.w2 = (const __nv_bfloat16*)d_in[7];
  p.out = (__nv_bfloat16*)d_out;
  cudaGetSymbolAddress((void**)&p.s, g_scratch);
  {
    cuuint64_t gd[3] = {256, 32, 1024};
    cuuint64_t gs[2] = {512, 16384};
    cuuint32_t bx[3] = {256, 1, 8};
    cuuint32_t es[3] = {1, 1, 1};
    fn(&tmP, CU_TENSOR_MAP_DATA_TYPE_BFLOAT16, 3, (void*)p.s->P, gd, gs, bx, es, CU_TENSOR_MAP_INTERLEAVE_NONE,
       CU_TENSOR_MAP_SWIZZLE_NONE, CU_TENSOR_MAP_L2_PROMOTION_NONE, CU_TENSOR_MAP_FLOAT_OOB_FILL_NONE);
  }
  cudaFuncSetAttribute(adaln_block_kernel, cudaFuncAttributeMaxDynamicSharedMemorySize, SM_TOTAL);
  adaln_block_kernel<<<128, 384, SM_TOTAL>>>(tmWq, tmK, tmV, tmWo, tmW1, tmW2, tmWm, tmP, tmX, p);
}
```

```cpp
#include <cuda_runtime.h>
#include <cuda_bf16.h>
#include <cuda.h>
#include <stdint.h>

template <int OFF, uint32_t HI>
__device__ __forceinline__ void wgmma_rs_n128_tb0(float (&d)[64], const uint32_t (&a)[4], uint32_t lo, int sd) {
  asm volatile("{\n.reg .pred p;\n.reg .b32 l;\n.reg .b64 db;\nsetp.ne.b32 p, %69, 0;\n"
    "add.u32 l, %68, %70;\nmov.b64 db, {l, %71};\n"
    "wgmma.mma_async.sync.aligned.m64n128k16.f32.bf16.bf16 "
    "{%0,%1,%2,%3,%4,%5,%6,%7,%8,%9,%10,%11,%12,%13,%14,%15,"
    "%16,%17,%18,%19,%20,%21,%22,%23,%24,%25,%26,%27,%28,%29,%30,%31,"
    "%32,%33,%34,%35,%36,%37,%38,%39,%40,%41,%42,%43,%44,%45,%46,%47,"
    "%48,%49,%50,%51,%52,%53,%54,%55,%56,%57,%58,%59,%60,%61,%62,%63}, "
    "{%64,%65,%66,%67}, db, p, 1, 1, 0;\n}\n"
    : "+f"(d[0]), "+f"(d[1]), "+f"(d[2]), "+f"(d[3]), "+f"(d[4]), "+f"(d[5]), "+f"(d[6]), "+f"(d[7]),
      "+f"(d[8]), "+f"(d[9]), "+f"(d[10]), "+f"(d[11]), "+f"(d[12]), "+f"(d[13]), "+f"(d[14]), "+f"(d[15]),
      "+f"(d[16]), "+f"(d[17]), "+f"(d[18]), "+f"(d[19]), "+f"(d[20]), "+f"(d[21]), "+f"(d[22]), "+f"(d[23]),
      "+f"(d[24]), "+f"(d[25]), "+f"(d[26]), "+f"(d[27]), "+f"(d[28]), "+f"(d[29]), "+f"(d[30]), "+f"(d[31]),
      "+f"(d[32]), "+f"(d[33]), "+f"(d[34]), "+f"(d[35]), "+f"(d[36]), "+f"(d[37]), "+f"(d[38]), "+f"(d[39]),
      "+f"(d[40]), "+f"(d[41]), "+f"(d[42]), "+f"(d[43]), "+f"(d[44]), "+f"(d[45]), "+f"(d[46]), "+f"(d[47]),
      "+f"(d[48]), "+f"(d[49]), "+f"(d[50]), "+f"(d[51]), "+f"(d[52]), "+f"(d[53]), "+f"(d[54]), "+f"(d[55]),
      "+f"(d[56]), "+f"(d[57]), "+f"(d[58]), "+f"(d[59]), "+f"(d[60]), "+f"(d[61]), "+f"(d[62]), "+f"(d[63])
    : "r"(a[0]), "r"(a[1]), "r"(a[2]), "r"(a[3]), "r"(lo), "r"(sd), "n"(OFF), "n"(HI));
}

template <int OFF, uint32_t HI>
__device__ __forceinline__ void wgmma_rs_n128_tb1(float (&d)[64], const uint32_t (&a)[4], uint32_t lo, int sd) {
  asm volatile("{\n.reg .pred p;\n.reg .b32 l;\n.reg .b64 db;\nsetp.ne.b32 p, %69, 0;\n"
    "add.u32 l, %68, %70;\nmov.b64 db, {l, %71};\n"
    "wgmma.mma_async.sync.aligned.m64n128k16.f32.bf16.bf16 "
    "{%0,%1,%2,%3,%4,%5,%6,%7,%8,%9,%10,%11,%12,%13,%14,%15,"
    "%16,%17,%18,%19,%20,%21,%22,%23,%24,%25,%26,%27,%28,%29,%30,%31,"
    "%32,%33,%34,%35,%36,%37,%38,%39,%40,%41,%42,%43,%44,%45,%46,%47,"
    "%48,%49,%50,%51,%52,%53,%54,%55,%56,%57,%58,%59,%60,%61,%62,%63}, "
    "{%64,%65,%66,%67}, db, p, 1, 1, 1;\n}\n"
    : "+f"(d[0]), "+f"(d[1]), "+f"(d[2]), "+f"(d[3]), "+f"(d[4]), "+f"(d[5]), "+f"(d[6]), "+f"(d[7]),
      "+f"(d[8]), "+f"(d[9]), "+f"(d[10]), "+f"(d[11]), "+f"(d[12]), "+f"(d[13]), "+f"(d[14]), "+f"(d[15]),
      "+f"(d[16]), "+f"(d[17]), "+f"(d[18]), "+f"(d[19]), "+f"(d[20]), "+f"(d[21]), "+f"(d[22]), "+f"(d[23]),
      "+f"(d[24]), "+f"(d[25]), "+f"(d[26]), "+f"(d[27]), "+f"(d[28]), "+f"(d[29]), "+f"(d[30]), "+f"(d[31]),
      "+f"(d[32]), "+f"(d[33]), "+f"(d[34]), "+f"(d[35]), "+f"(d[36]), "+f"(d[37]), "+f"(d[38]), "+f"(d[39]),
      "+f"(d[40]), "+f"(d[41]), "+f"(d[42]), "+f"(d[43]), "+f"(d[44]), "+f"(d[45]), "+f"(d[46]), "+f"(d[47]),
      "+f"(d[48]), "+f"(d[49]), "+f"(d[50]), "+f"(d[51]), "+f"(d[52]), "+f"(d[53]), "+f"(d[54]), "+f"(d[55]),
      "+f"(d[56]), "+f"(d[57]), "+f"(d[58]), "+f"(d[59]), "+f"(d[60]), "+f"(d[61]), "+f"(d[62]), "+f"(d[63])
    : "r"(a[0]), "r"(a[1]), "r"(a[2]), "r"(a[3]), "r"(lo), "r"(sd), "n"(OFF), "n"(HI));
}

template <int OFF, uint32_t HI>
__device__ __forceinline__ void wgmma_rs_n224_tb1(float (&d)[112], const uint32_t (&a)[4], uint32_t lo, int sd) {
  asm volatile("{\n.reg .pred p;\n.reg .b32 l;\n.reg .b64 db;\nsetp.ne.b32 p, %117, 0;\n"
    "add.u32 l, %116, %118;\nmov.b64 db, {l, %119};\n"
    "wgmma.mma_async.sync.aligned.m64n224k16.f32.bf16.bf16 "
    "{%0,%1,%2,%3,%4,%5,%6,%7,%8,%9,%10,%11,%12,%13,%14,%15,"
    "%16,%17,%18,%19,%20,%21,%22,%23,%24,%25,%26,%27,%28,%29,%30,%31,"
    "%32,%33,%34,%35,%36,%37,%38,%39,%40,%41,%42,%43,%44,%45,%46,%47,"
    "%48,%49,%50,%51,%52,%53,%54,%55,%56,%57,%58,%59,%60,%61,%62,%63,"
    "%64,%65,%66,%67,%68,%69,%70,%71,%72,%73,%74,%75,%76,%77,%78,%79,"
    "%80,%81,%82,%83,%84,%85,%86,%87,%88,%89,%90,%91,%92,%93,%94,%95,"
    "%96,%97,%98,%99,%100,%101,%102,%103,%104,%105,%106,%107,%108,%109,%110,%111}, "
    "{%112,%113,%114,%115}, db, p, 1, 1, 1;\n}\n"
    : "+f"(d[0]), "+f"(d[1]), "+f"(d[2]), "+f"(d[3]), "+f"(d[4]), "+f"(d[5]), "+f"(d[6]), "+f"(d[7]),
      "+f"(d[8]), "+f"(d[9]), "+f"(d[10]), "+f"(d[11]), "+f"(d[12]), "+f"(d[13]), "+f"(d[14]), "+f"(d[15]),
      "+f"(d[16]), "+f"(d[17]), "+f"(d[18]), "+f"(d[19]), "+f"(d[20]), "+f"(d[21]), "+f"(d[22]), "+f"(d[23]),
      "+f"(d[24]), "+f"(d[25]), "+f"(d[26]), "+f"(d[27]), "+f"(d[28]), "+f"(d[29]), "+f"(d[30]), "+f"(d[31]),
      "+f"(d[32]), "+f"(d[33]), "+f"(d[34]), "+f"(d[35]), "+f"(d[36]), "+f"(d[37]), "+f"(d[38]), "+f"(d[39]),
      "+f"(d[40]), "+f"(d[41]), "+f"(d[42]), "+f"(d[43]), "+f"(d[44]), "+f"(d[45]), "+f"(d[46]), "+f"(d[47]),
      "+f"(d[48]), "+f"(d[49]), "+f"(d[50]), "+f"(d[51]), "+f"(d[52]), "+f"(d[53]), "+f"(d[54]), "+f"(d[55]),
      "+f"(d[56]), "+f"(d[57]), "+f"(d[58]), "+f"(d[59]), "+f"(d[60]), "+f"(d[61]), "+f"(d[62]), "+f"(d[63]),
      "+f"(d[64]), "+f"(d[65]), "+f"(d[66]), "+f"(d[67]), "+f"(d[68]), "+f"(d[69]), "+f"(d[70]), "+f"(d[71]),
      "+f"(d[72]), "+f"(d[73]), "+f"(d[74]), "+f"(d[75]), "+f"(d[76]), "+f"(d[77]), "+f"(d[78]), "+f"(d[79]),
      "+f"(d[80]), "+f"(d[81]), "+f"(d[82]), "+f"(d[83]), "+f"(d[84]), "+f"(d[85]), "+f"(d[86]), "+f"(d[87]),
      "+f"(d[88]), "+f"(d[89]), "+f"(d[90]), "+f"(d[91]), "+f"(d[92]), "+f"(d[93]), "+f"(d[94]), "+f"(d[95]),
      "+f"(d[96]), "+f"(d[97]), "+f"(d[98]), "+f"(d[99]), "+f"(d[100]), "+f"(d[101]), "+f"(d[102]), "+f"(d[103]),
      "+f"(d[104]), "+f"(d[105]), "+f"(d[106]), "+f"(d[107]), "+f"(d[108]), "+f"(d[109]), "+f"(d[110]), "+f"(d[111])
    : "r"(a[0]), "r"(a[1]), "r"(a[2]), "r"(a[3]), "r"(lo), "r"(sd), "n"(OFF), "n"(HI));
}

template <int OFF, uint32_t HI>
__device__ __forceinline__ void wgmma_rs_n64_tb1(float (&d)[32], const uint32_t (&a)[4], uint32_t lo, int sd) {
  asm volatile("{\n.reg .pred p;\n.reg .b32 l;\n.reg .b64 db;\nsetp.ne.b32 p, %37, 0;\n"
    "add.u32 l, %36, %38;\nmov.b64 db, {l, %39};\n"
    "wgmma.mma_async.sync.aligned.m64n64k16.f32.bf16.bf16 "
    "{%0,%1,%2,%3,%4,%5,%6,%7,%8,%9,%10,%11,%12,%13,%14,%15,"
    "%16,%17,%18,%19,%20,%21,%22,%23,%24,%25,%26,%27,%28,%29,%30,%31}, "
    "{%32,%33,%34,%35}, db, p, 1, 1, 1;\n}\n"
    : "+f"(d[0]), "+f"(d[1]), "+f"(d[2]), "+f"(d[3]), "+f"(d[4]), "+f"(d[5]), "+f"(d[6]), "+f"(d[7]),
      "+f"(d[8]), "+f"(d[9]), "+f"(d[10]), "+f"(d[11]), "+f"(d[12]), "+f"(d[13]), "+f"(d[14]), "+f"(d[15]),
      "+f"(d[16]), "+f"(d[17]), "+f"(d[18]), "+f"(d[19]), "+f"(d[20]), "+f"(d[21]), "+f"(d[22]), "+f"(d[23]),
      "+f"(d[24]), "+f"(d[25]), "+f"(d[26]), "+f"(d[27]), "+f"(d[28]), "+f"(d[29]), "+f"(d[30]), "+f"(d[31])
    : "r"(a[0]), "r"(a[1]), "r"(a[2]), "r"(a[3]), "r"(lo), "r"(sd), "n"(OFF), "n"(HI));
}

template <int STR>
__device__ __forceinline__ void verify8_tag1(const uint4* p, uint32_t (*r)[4]) {
  asm volatile("{\n.reg .pred p, q;\n.reg .b32 a, n;\nmov.u32 n, 0;\n"
    "LAB_CHK:\n"
    "and.b32 a, %0, %4;\n"
    "and.b32 a, a, %8;\n"
    "and.b32 a, a, %12;\n"
    "and.b32 a, a, %16;\n"
    "and.b32 a, a, %20;\n"
    "and.b32 a, a, %24;\n"
    "and.b32 a, a, %28;\n"
    "and.b32 a, a, 1;\nsetp.eq.u32 p, a, 1;\nvote.sync.all.pred p, p, 0xffffffff;\n"
    "@p bra.uni LAB_OK;\n"
    "and.b32 a, %0, 1;\nsetp.ne.u32 q, a, 1;\n"
    "@q ld.relaxed.gpu.global.v4.b32 {%0,%1,%2,%3}, [%32+%33];\n"
    "and.b32 a, %4, 1;\nsetp.ne.u32 q, a, 1;\n"
    "@q ld.relaxed.gpu.global.v4.b32 {%4,%5,%6,%7}, [%32+%34];\n"
    "and.b32 a, %8, 1;\nsetp.ne.u32 q, a, 1;\n"
    "@q ld.relaxed.gpu.global.v4.b32 {%8,%9,%10,%11}, [%32+%35];\n"
    "and.b32 a, %12, 1;\nsetp.ne.u32 q, a, 1;\n"
    "@q ld.relaxed.gpu.global.v4.b32 {%12,%13,%14,%15}, [%32+%36];\n"
    "and.b32 a, %16, 1;\nsetp.ne.u32 q, a, 1;\n"
    "@q ld.relaxed.gpu.global.v4.b32 {%16,%17,%18,%19}, [%32+%37];\n"
    "and.b32 a, %20, 1;\nsetp.ne.u32 q, a, 1;\n"
    "@q ld.relaxed.gpu.global.v4.b32 {%20,%21,%22,%23}, [%32+%38];\n"
    "and.b32 a, %24, 1;\nsetp.ne.u32 q, a, 1;\n"
    "@q ld.relaxed.gpu.global.v4.b32 {%24,%25,%26,%27}, [%32+%39];\n"
    "and.b32 a, %28, 1;\nsetp.ne.u32 q, a, 1;\n"
    "@q ld.relaxed.gpu.global.v4.b32 {%28,%29,%30,%31}, [%32+%40];\n"
    "add.u32 n, n, 1;\nsetp.lt.u32 q, n, 262144;\n@q bra.uni LAB_CHK;\n"
    "LAB_OK:\n"
    "}\n"
    : "+r"(r[0][0]), "+r"(r[0][1]), "+r"(r[0][2]), "+r"(r[0][3]), "+r"(r[1][0]), "+r"(r[1][1]), "+r"(r[1][2]), "+r"(r[1][3]),
      "+r"(r[2][0]), "+r"(r[2][1]), "+r"(r[2][2]), "+r"(r[2][3]), "+r"(r[3][0]), "+r"(r[3][1]), "+r"(r[3][2]), "+r"(r[3][3]),
      "+r"(r[4][0]), "+r"(r[4][1]), "+r"(r[4][2]), "+r"(r[4][3]), "+r"(r[5][0]), "+r"(r[5][1]), "+r"(r[5][2]), "+r"(r[5][3]),
      "+r"(r[6][0]), "+r"(r[6][1]), "+r"(r[6][2]), "+r"(r[6][3]), "+r"(r[7][0]), "+r"(r[7][1]), "+r"(r[7][2]), "+r"(r[7][3])
    : "l"(p), "n"(0 * STR), "n"(1 * STR), "n"(2 * STR), "n"(3 * STR), "n"(4 * STR), "n"(5 * STR), "n"(6 * STR), "n"(7 * STR)
    : "memory");
}

template <int STR>
__device__ __forceinline__ void verify8_tag0(const uint4* p, uint32_t (*r)[4]) {
  asm volatile("{\n.reg .pred p, q;\n.reg .b32 a, n;\nmov.u32 n, 0;\n"
    "LAB_CHK:\n"
    "or.b32 a, %0, %4;\n"
    "or.b32 a, a, %8;\n"
    "or.b32 a, a, %12;\n"
    "or.b32 a, a, %16;\n"
    "or.b32 a, a, %20;\n"
    "or.b32 a, a, %24;\n"
    "or.b32 a, a, %28;\n"
    "and.b32 a, a, 1;\nsetp.eq.u32 p, a, 0;\nvote.sync.all.pred p, p, 0xffffffff;\n"
    "@p bra.uni LAB_OK;\n"
    "and.b32 a, %0, 1;\nsetp.ne.u32 q, a, 0;\n"
    "@q ld.relaxed.gpu.global.v4.b32 {%0,%1,%2,%3}, [%32+%33];\n"
    "and.b32 a, %4, 1;\nsetp.ne.u32 q, a, 0;\n"
    "@q ld.relaxed.gpu.global.v4.b32 {%4,%5,%6,%7}, [%32+%34];\n"
    "and.b32 a, %8, 1;\nsetp.ne.u32 q, a, 0;\n"
    "@q ld.relaxed.gpu.global.v4.b32 {%8,%9,%10,%11}, [%32+%35];\n"
    "and.b32 a, %12, 1;\nsetp.ne.u32 q, a, 0;\n"
    "@q ld.relaxed.gpu.global.v4.b32 {%12,%13,%14,%15}, [%32+%36];\n"
    "and.b32 a, %16, 1;\nsetp.ne.u32 q, a, 0;\n"
    "@q ld.relaxed.gpu.global.v4.b32 {%16,%17,%18,%19}, [%32+%37];\n"
    "and.b32 a, %20, 1;\nsetp.ne.u32 q, a, 0;\n"
    "@q ld.relaxed.gpu.global.v4.b32 {%20,%21,%22,%23}, [%32+%38];\n"
    "and.b32 a, %24, 1;\nsetp.ne.u32 q, a, 0;\n"
    "@q ld.relaxed.gpu.global.v4.b32 {%24,%25,%26,%27}, [%32+%39];\n"
    "and.b32 a, %28, 1;\nsetp.ne.u32 q, a, 0;\n"
    "@q ld.relaxed.gpu.global.v4.b32 {%28,%29,%30,%31}, [%32+%40];\n"
    "add.u32 n, n, 1;\nsetp.lt.u32 q, n, 262144;\n@q bra.uni LAB_CHK;\n"
    "LAB_OK:\n"
    "or.b32 %0, %0, 1;\n"
    "or.b32 %4, %4, 1;\n"
    "or.b32 %8, %8, 1;\n"
    "or.b32 %12, %12, 1;\n"
    "or.b32 %16, %16, 1;\n"
    "or.b32 %20, %20, 1;\n"
    "or.b32 %24, %24, 1;\n"
    "or.b32 %28, %28, 1;\n"
    "}\n"
    : "+r"(r[0][0]), "+r"(r[0][1]), "+r"(r[0][2]), "+r"(r[0][3]), "+r"(r[1][0]), "+r"(r[1][1]), "+r"(r[1][2]), "+r"(r[1][3]),
      "+r"(r[2][0]), "+r"(r[2][1]), "+r"(r[2][2]), "+r"(r[2][3]), "+r"(r[3][0]), "+r"(r[3][1]), "+r"(r[3][2]), "+r"(r[3][3]),
      "+r"(r[4][0]), "+r"(r[4][1]), "+r"(r[4][2]), "+r"(r[4][3]), "+r"(r[5][0]), "+r"(r[5][1]), "+r"(r[5][2]), "+r"(r[5][3]),
      "+r"(r[6][0]), "+r"(r[6][1]), "+r"(r[6][2]), "+r"(r[6][3]), "+r"(r[7][0]), "+r"(r[7][1]), "+r"(r[7][2]), "+r"(r[7][3])
    : "l"(p), "n"(0 * STR), "n"(1 * STR), "n"(2 * STR), "n"(3 * STR), "n"(4 * STR), "n"(5 * STR), "n"(6 * STR), "n"(7 * STR)
    : "memory");
}

template <int STR>
__device__ __forceinline__ void verify4_tag0(const uint4* p, uint32_t (*r)[4]) {
  asm volatile("{\n.reg .pred p, q;\n.reg .b32 a, n;\nmov.u32 n, 0;\n"
    "LAB_CHK:\n"
    "or.b32 a, %0, %4;\n"
    "or.b32 a, a, %8;\n"
    "or.b32 a, a, %12;\n"
    "and.b32 a, a, 1;\nsetp.eq.u32 p, a, 0;\nvote.sync.all.pred p, p, 0xffffffff;\n"
    "@p bra.uni LAB_OK;\n"
    "and.b32 a, %0, 1;\nsetp.ne.u32 q, a, 0;\n"
    "@q ld.relaxed.gpu.global.v4.b32 {%0,%1,%2,%3}, [%16+%17];\n"
    "and.b32 a, %4, 1;\nsetp.ne.u32 q, a, 0;\n"
    "@q ld.relaxed.gpu.global.v4.b32 {%4,%5,%6,%7}, [%16+%18];\n"
    "and.b32 a, %8, 1;\nsetp.ne.u32 q, a, 0;\n"
    "@q ld.relaxed.gpu.global.v4.b32 {%8,%9,%10,%11}, [%16+%19];\n"
    "and.b32 a, %12, 1;\nsetp.ne.u32 q, a, 0;\n"
    "@q ld.relaxed.gpu.global.v4.b32 {%12,%13,%14,%15}, [%16+%20];\n"
    "add.u32 n, n, 1;\nsetp.lt.u32 q, n, 262144;\n@q bra.uni LAB_CHK;\n"
    "LAB_OK:\n"
    "or.b32 %0, %0, 1;\n"
    "or.b32 %4, %4, 1;\n"
    "or.b32 %8, %8, 1;\n"
    "or.b32 %12, %12, 1;\n"
    "}\n"
    : "+r"(r[0][0]), "+r"(r[0][1]), "+r"(r[0][2]), "+r"(r[0][3]), "+r"(r[1][0]), "+r"(r[1][1]), "+r"(r[1][2]), "+r"(r[1][3]),
      "+r"(r[2][0]), "+r"(r[2][1]), "+r"(r[2][2]), "+r"(r[2][3]), "+r"(r[3][0]), "+r"(r[3][1]), "+r"(r[3][2]), "+r"(r[3][3])
    : "l"(p), "n"(0 * STR), "n"(1 * STR), "n"(2 * STR), "n"(3 * STR)
    : "memory");
}

#define SPIN_LIMIT (1 << 18)

__device__ __forceinline__ uint32_t smem_u32(const void* p) { return (uint32_t)__cvta_generic_to_shared(p); }
__device__ __forceinline__ void mbar_init(uint32_t a, uint32_t c) {
  asm volatile("mbarrier.init.shared::cta.b64 [%0], %1;" ::"r"(a), "r"(c) : "memory");
}
__device__ __forceinline__ void mbar_expect(uint32_t a, uint32_t b) {
  asm volatile("mbarrier.arrive.expect_tx.shared::cta.b64 _, [%0], %1;" ::"r"(a), "r"(b) : "memory");
}
__device__ __forceinline__ void mbar_arrive(uint32_t a) {
  asm volatile("mbarrier.arrive.shared::cta.b64 _, [%0];" ::"r"(a) : "memory");
}
__device__ __forceinline__ void mbar_wait(uint32_t a, uint32_t parity) {
  asm volatile(
      "{\n.reg .pred p;\n.reg .u32 n;\nmov.u32 n, 0;\n"
      "LAB_WAIT:\n"
      "mbarrier.try_wait.parity.shared::cta.b64 p, [%0], %1;\n"
      "@p bra LAB_DONE;\n"
      "add.u32 n, n, 1;\n"
      "setp.lt.u32 p, n, 262144;\n"
      "@p bra LAB_WAIT;\n"
      "LAB_DONE:\n}\n" ::"r"(a), "r"(parity) : "memory");
}
__device__ __forceinline__ bool mbar_test(uint32_t a, uint32_t parity) {
  uint32_t ok;
  asm volatile("{\n.reg .pred p;\nmbarrier.test_wait.parity.shared::cta.b64 p, [%1], %2;\nselp.u32 %0, 1, 0, p;\n}\n"
               : "=r"(ok) : "r"(a), "r"(parity) : "memory");
  return ok;
}
__device__ __forceinline__ void tma3d(uint32_t dst, const CUtensorMap* tm, uint32_t bar, int c0, int c1, int c2) {
  asm volatile(
      "cp.async.bulk.tensor.3d.shared::cluster.global.mbarrier::complete_tx::bytes [%0], [%1, {%3,%4,%5}], [%2];"
      ::"r"(dst), "l"(tm), "r"(bar), "r"(c0), "r"(c1), "r"(c2) : "memory");
}
__device__ __forceinline__ void wg_fence() { asm volatile("wgmma.fence.sync.aligned;" ::: "memory"); }
__device__ __forceinline__ void wg_commit() { asm volatile("wgmma.commit_group.sync.aligned;" ::: "memory"); }
template <int N> __device__ __forceinline__ void wg_wait() {
  asm volatile("wgmma.wait_group.sync.aligned %0;" ::"n"(N) : "memory");
}
template <int N> __device__ __forceinline__ void fence_regs(float (&d)[N]) {
#pragma unroll
  for (int i = 0; i < N; i++) asm volatile("" : "+f"(d[i])::"memory");
}
template <int N> __device__ __forceinline__ void fence_regs(uint32_t (&d)[N][4]) {
#pragma unroll
  for (int i = 0; i < N; i++) asm volatile("" : "+r"(d[i][0]), "+r"(d[i][1]), "+r"(d[i][2]), "+r"(d[i][3])::"memory");
}
template <int N> __device__ __forceinline__ void fence_frags(uint32_t (*d)[4]) {
#pragma unroll
  for (int i = 0; i < N; i++) asm volatile("" : "+r"(d[i][0]), "+r"(d[i][1]), "+r"(d[i][2]), "+r"(d[i][3])::"memory");
}
__device__ __forceinline__ void bar_sync(int id, int n) { asm volatile("bar.sync %0, %1;" ::"r"(id), "r"(n) : "memory"); }
__device__ __forceinline__ void bar_arrive(int id, int n) { asm volatile("bar.arrive %0, %1;" ::"r"(id), "r"(n) : "memory"); }

__device__ __forceinline__ uint32_t pack_bf16(float lo, float hi) {
  uint32_t r;
  asm("cvt.rn.bf16x2.f32 %0, %1, %2;" : "=r"(r) : "f"(hi), "f"(lo));
  return r;
}
__device__ __forceinline__ float bf_lo(uint32_t w) { return __uint_as_float(w << 16); }
__device__ __forceinline__ float bf_hi(uint32_t w) { return __uint_as_float(w & 0xFFFF0000u); }
__device__ __forceinline__ float round_bf16(float x) { return bf_lo(pack_bf16(x, 0.f)); }
__device__ __forceinline__ uint32_t hfma2_bf16(uint32_t a, uint32_t b, uint32_t c) {
  uint32_t r;
  asm("fma.rn.bf16x2 %0, %1, %2, %3;" : "=r"(r) : "r"(a), "r"(b), "r"(c));
  return r;
}
__device__ __forceinline__ float ex2(float x) {
  float r;
  asm("ex2.approx.ftz.f32 %0, %1;" : "=f"(r) : "f"(x));
  return r;
}
__device__ __forceinline__ float tanh_hw(float x) {
  float r;
  asm("tanh.approx.f32 %0, %1;" : "=f"(r) : "f"(x));
  return r;
}
template <int TAG> __device__ __forceinline__ uint32_t pack_tag(float lo, float hi) {
  uint32_t w = __byte_perm(__float_as_uint(lo), pack_bf16(lo, hi), 0x7632);
  return TAG ? (w | 1u) : (w & ~1u);
}
__device__ __forceinline__ void st_pkt(uint4* p, uint32_t a, uint32_t b, uint32_t c, uint32_t d) {
  asm volatile(
      "st.relaxed.gpu.global.v4.b32 [%0], {%1,%2,%3,%4};" ::"l"(p), "r"(a), "r"(b), "r"(c), "r"(d) : "memory");
}
__device__ __forceinline__ void ld_pkt(const uint4* p, uint32_t (&r)[4]) {
  asm volatile(
      "ld.relaxed.gpu.global.v4.b32 {%0,%1,%2,%3}, [%4];"
      : "=r"(r[0]), "=r"(r[1]), "=r"(r[2]), "=r"(r[3]) : "l"(p) : "memory");
}
__device__ __forceinline__ uint32_t ldg32(const void* p) {
  uint32_t r;
  asm volatile("ld.global.nc.b32 %0, [%1];" : "=r"(r) : "l"(p));
  return r;
}
__device__ __forceinline__ uint32_t ldg16(const void* p) {
  uint16_t r;
  asm volatile("ld.global.nc.b16 %0, [%1];" : "=h"(r) : "l"(p));
  return r;
}
__device__ __forceinline__ uint4 ldg128(const void* p) {
  uint4 r;
  asm volatile("ld.global.nc.v4.b32 {%0,%1,%2,%3}, [%4];" : "=r"(r.x), "=r"(r.y), "=r"(r.z), "=r"(r.w) : "l"(p));
  return r;
}
__device__ __forceinline__ void l2_prefetch(const void* p, uint32_t bytes) {
  asm volatile("cp.async.bulk.prefetch.L2.global [%0], %1;" ::"l"(p), "r"(bytes) : "memory");
}
__device__ __forceinline__ float rcp_hw(float x) {
  float r;
  asm("rcp.approx.ftz.f32 %0, %1;" : "=f"(r) : "f"(x));
  return r;
}
__device__ __forceinline__ void warp_bulk_load(uint32_t sdst, const void* gsrc, uint32_t bytes, uint32_t bar) {
  if ((threadIdx.x & 31) == 0) {
    mbar_expect(bar, bytes);
    asm volatile("cp.async.bulk.shared::cluster.global.mbarrier::complete_tx::bytes [%0], [%1], %2, [%3];"
                 ::"r"(sdst), "l"(gsrc), "r"(bytes), "r"(bar) : "memory");
  }
}
__device__ __forceinline__ void spin_cycles(uint32_t n) {
  uint32_t t0, t;
  asm volatile("mov.u32 %0, %%clock;" : "=r"(t0));
  do { asm volatile("mov.u32 %0, %%clock;" : "=r"(t)); } while (t - t0 < n);
}
__device__ __forceinline__ void sts128(uint32_t a, uint32_t x, uint32_t y, uint32_t z, uint32_t w) {
  asm volatile("st.shared.v4.b32 [%0], {%1,%2,%3,%4};" ::"r"(a), "r"(x), "r"(y), "r"(z), "r"(w) : "memory");
}
__device__ __forceinline__ void lds128(uint32_t a, uint32_t (&r)[4]) {
  asm volatile("ld.shared.v4.b32 {%0,%1,%2,%3}, [%4];" : "=r"(r[0]), "=r"(r[1]), "=r"(r[2]), "=r"(r[3]) : "r"(a) : "memory");
}

__device__ __forceinline__ uint32_t lds32(uint32_t a) {
  uint32_t r;
  asm volatile("ld.shared.b32 %0, [%1];" : "=r"(r) : "r"(a) : "memory");
  return r;
}
__device__ __forceinline__ void store_out(__nv_bfloat16* out, uint32_t woff, uint32_t x2s, const uint32_t (&gb)[4],
                                          const float (&y)[8]) {
  uint32_t xa[2][4];
  lds128(x2s, xa[0]);
  lds128(x2s + 512, xa[1]);
  uint32_t* const oo = (uint32_t*)out + woff;
#pragma unroll
  for (int e = 0; e < 4; e++)
    oo[(e >> 1) * 4 + (e & 1) * 8 * 256] =
        pack_bf16(fmaf(bf_lo(gb[e >> 1]), y[2 * e], __uint_as_float(xa[e >> 1][(e & 1) * 2])),
                  fmaf(bf_hi(gb[e >> 1]), y[2 * e + 1], __uint_as_float(xa[e >> 1][(e & 1) * 2 + 1])));
}

constexpr int SK = 2048, WIN = 512;
constexpr int FF = 1792, FSL = 224;
constexpr int NTILES = 80;
constexpr int NSLOT = 4;
constexpr uint32_t SLOT = 32768;
constexpr uint32_t SM_PARK = 0;
constexpr uint32_t SM_RING = 3 * SLOT;
constexpr uint32_t SM_TAB = 7 * SLOT;
constexpr uint32_t SM_RED = SM_TAB + 2048;
constexpr uint32_t SM_BAR = SM_RED + 256;
constexpr uint32_t SM_WBAR = SM_BAR + 128;
constexpr uint32_t SM_SBAR = SM_WBAR + 240;
constexpr uint32_t SM_TOTAL = SM_SBAR + 112;

struct Scratch {
  uint4 P[16 * 8 * 8 * 1024];
  uint4 G[16 * 8 * 32 * 32];
  uint4 mod1[8 * 256];
  uint4 mod2[512];
  uint4 uv[2 * 448];
  uint4 stat[16 * 8 * 8];
  uint32_t epoch;
};
__device__ Scratch g_scratch;

#define TS(i) do { } while (0)
#define TR(code)
#define CK_(v)
#define CKS(i, v)

struct Params {
  const __nv_bfloat16* x;
  const __nv_bfloat16* c;
  const __nv_bfloat16* wmod;
  const __nv_bfloat16* wo;
  const __nv_bfloat16* w1;
  const __nv_bfloat16* w2;
  __nv_bfloat16* out;
  Scratch* s;
};

constexpr uint32_t HI128 = (1024 >> 4) | (1u << 30);
constexpr uint32_t HI64 = (512 >> 4) | (2u << 30);
constexpr int LB_MN128 = (16384 >> 4) << 16;
constexpr int LB_K128 = 1 << 16;
constexpr int LB_W1 = (4096 >> 4) << 16;

template <int I> struct IC {
  __host__ __device__ constexpr operator int() const { return I; }
};
template <int I, int N, typename F> __device__ __forceinline__ void static_for(F&& f) {
  if constexpr (I < N) {
    f(IC<I>{});
    static_for<I + 1, N>(f);
  }
}

struct Ring {
  uint32_t base16, bars;
  __device__ __forceinline__ uint32_t wait_full(uint32_t slot, uint32_t parity) const {
    mbar_wait(bars + slot * 8, parity);
    return base16 + slot * (SLOT >> 4);
  }
  __device__ __forceinline__ void release(uint32_t slot) const {
    if ((threadIdx.x & 31) == 0) mbar_arrive(bars + 32 + slot * 8);
  }
};

__device__ __forceinline__ float silu_c(uint32_t bits) {
  float x = bf_lo(bits);
  return round_bf16(x * rcp_hw(1.f + ex2(-1.4426950408889634f * x)));
}
__device__ __forceinline__ void pack8(uint32_t (&o)[4], const float* v) {
  o[0] = pack_bf16(v[0], v[1]); o[1] = pack_bf16(v[2], v[3]); o[2] = pack_bf16(v[4], v[5]); o[3] = pack_bf16(v[6], v[7]);
}

template <int TAG, int N>
__device__ __forceinline__ void issue_pkts(const uint4* p, int stride, uint32_t (*r)[4]) {
#pragma unroll
  for (int i = 0; i < N; i++) ld_pkt(p + i * stride, r[i]);
}
__device__ __forceinline__ void ld_mod(const uint4* p, uint32_t tag, uint32_t (&r)[4]) {
  int spins = 0;
  ld_pkt(p, r);
  while (r[2] != tag && ++spins < SPIN_LIMIT) ld_pkt(p, r);
}

#define EARLY_TILES 2
#define PF_WMOD 1
#define MOD1_DELAY 500
#define RED3_UNIT 3
#define JLO 2
#define NITEM2 24
#define FIN_DELAY0 800
#define FIN_DELAY1 0
#define G_DELAY 0

__global__ void __launch_bounds__(384, 1)
adaln_block_kernel(const __grid_constant__ CUtensorMap tmWq, const __grid_constant__ CUtensorMap tmK,
                   const __grid_constant__ CUtensorMap tmV, const __grid_constant__ CUtensorMap tmWo,
                   const __grid_constant__ CUtensorMap tmW1, const __grid_constant__ CUtensorMap tmW2,
                   const __grid_constant__ CUtensorMap tmWm, const __grid_constant__ CUtensorMap tmP,
                   const __grid_constant__ CUtensorMap tmX, const Params p) {
  extern __shared__ __align__(1024) uint8_t smem_raw[];
  const uint32_t sb = smem_u32(smem_raw);
  const int tid = threadIdx.x, lane = tid & 31;
  const int warp = __shfl_sync(0xffffffffu, tid >> 5, 0);
  const int bid = blockIdx.x;
  const int j = ((bid >> (4 + JLO)) << JLO) | (bid & ((1 << JLO) - 1)), rt = (bid >> JLO) & 15;
  const uint32_t bars = sb + SM_BAR;

  if (warp >= 8) {
    CK_(c0);
    asm volatile("setmaxnreg.dec.sync.aligned.u32 56;");
    CK_(c1);
    const int t = tid - 256;
    uint32_t tag;
    {
      uint32_t cb[4];
      if (t == 0) {
        mbar_init(bars + 80, 1);
        asm volatile("fence.mbarrier_init.release.cluster;" ::: "memory");
        mbar_expect(bars + 80, 8192);
        tma3d(sb + SM_RING + 3 * SLOT, &tmWm, bars + 80, 0, 0, bid);
        tma3d(sb + SM_RING + 3 * SLOT + 4096, &tmWm, bars + 80, 0, 256, bid);
        asm volatile("prefetch.tensormap [%0];" ::"l"(&tmWq) : "memory");
        for (int i = 0; i < NSLOT; i++) { mbar_init(bars + i * 8, 1); mbar_init(bars + 32 + i * 8, 8); }
        mbar_init(bars + 72, 2);
        mbar_init(bars + 88, 1);
        for (int i = 0; i < 30; i++) mbar_init(sb + SM_WBAR + i * 8, 1);
        for (int i = 0; i < 14; i++) mbar_init(sb + SM_SBAR + i * 8, 8);
        asm volatile("fence.mbarrier_init.release.cluster;" ::: "memory");
      }
      __syncwarp();
      CK_(c2);
#pragma unroll
      for (int i = 0; i < 4; i++) cb[i] = ldg16(p.c + t + 128 * i);
      asm volatile("ld.relaxed.gpu.global.u32 %0, [%1];" : "=r"(tag) : "l"(&p.s->epoch) : "memory");
      bar_sync(5, 128);
      tag += 1;
      float a[8], sc[4];
#pragma unroll
      for (int i = 0; i < 4; i++) sc[i] = silu_c(cb[i]);
#pragma unroll
      for (int k = 0; k < 8; k++) a[k] = 0.f;
      mbar_wait(bars + 80, 0);
      CK_(c3);
#pragma unroll
      for (int i = 0; i < 4; i++) {
        uint32_t w[4];
        lds128(sb + SM_RING + 3 * SLOT + (t + 128 * i) * 16, w);
#pragma unroll
        for (int e = 0; e < 4; e++) {
          a[2 * e] = fmaf(sc[i], bf_lo(w[e]), a[2 * e]);
          a[2 * e + 1] = fmaf(sc[i], bf_hi(w[e]), a[2 * e + 1]);
        }
      }
      const bool h16 = lane & 16, h8 = lane & 8, h4 = lane & 4;
#pragma unroll
      for (int k = 0; k < 4; k++) {
        float send = h16 ? a[k] : a[k + 4], keep = h16 ? a[k + 4] : a[k];
        a[k] = keep + __shfl_xor_sync(0xffffffffu, send, 16);
      }
#pragma unroll
      for (int k = 0; k < 2; k++) {
        float send = h8 ? a[k] : a[k + 2], keep = h8 ? a[k + 2] : a[k];
        a[k] = keep + __shfl_xor_sync(0xffffffffu, send, 8);
      }
      {
        float send = h4 ? a[0] : a[1], keep = h4 ? a[1] : a[0];
        a[0] = keep + __shfl_xor_sync(0xffffffffu, send, 4);
      }
      a[0] += __shfl_xor_sync(0xffffffffu, a[0], 2);
      a[0] += __shfl_xor_sync(0xffffffffu, a[0], 1);
      float* red = (float*)(smem_raw + SM_RED);
      if ((lane & 3) == 0) red[(warp - 8) * 8 + (lane >> 2)] = a[0];
      if (t == 0) *(uint32_t*)(smem_raw + SM_BAR + 64) = tag;
      CK_(c4);
      bar_sync(5, 128);
      bar_arrive(7, 384);
      CK_(c5);
      if (t == 0) {
#pragma unroll
        for (int i = 0; i < EARLY_TILES; i++) {
          mbar_expect(bars + i * 8, SLOT);
          tma3d(sb + SM_RING + i * SLOT, &tmWq, bars + i * 8, 0, i * 128, (j * 4 + 1) * 2);
        }
      }
      if (warp == 9) {
        const int cl = lane & 7;
        float v = round_bf16(red[cl] + red[8 + cl] + red[16 + cl] + red[24 + cl]);
        if (bid >= 64) v = 1.f + v;
        float vn = __shfl_down_sync(0xffffffffu, v, 1);
        uint32_t wd = pack_bf16(v, vn);
        uint32_t w0 = __shfl_sync(0xffffffffu, wd, (lane & 1) * 4);
        uint32_t w1 = __shfl_sync(0xffffffffu, wd, (lane & 1) * 4 + 2);
        if (lane < 16) st_pkt(&p.s->mod1[(lane >> 1) * 256 + bid * 2 + (lane & 1)], w0, w1, tag, 0);
      }
      uint32_t r0[4], r1[4];
      const uint4* src = &p.s->mod1[j * 256 + t];
      CK_(c6);
      spin_cycles(MOD1_DELAY);
      CK_(c7);
      int spins = 0;
      do {
        ld_pkt(src, r0);
        ld_pkt(src + 128, r1);
      } while ((r0[2] != tag || r1[2] != tag) && ++spins < SPIN_LIMIT);
      const int g = t >> 2, pp = (t & 3) * 2;
      const uint32_t ad = sb + SM_TAB + (uint32_t)(g * 4 + (pp & 3)) * 16 + (pp >> 2) * 4;
      asm volatile("st.shared.b32 [%0], %1;" ::"r"(ad + 8), "r"(r0[0]) : "memory");
      asm volatile("st.shared.b32 [%0], %1;" ::"r"(ad + 24), "r"(r0[1]) : "memory");
      asm volatile("st.shared.b32 [%0], %1;" ::"r"(ad), "r"(r1[0]) : "memory");
      asm volatile("st.shared.b32 [%0], %1;" ::"r"(ad + 16), "r"(r1[1]) : "memory");
      bar_arrive(1, 384);
      CK_(c8);
      CKS(0, c0); CKS(1, c1); CKS(2, c2); CKS(3, c3); CKS(4, c4); CKS(5, c5); CKS(6, c6); CKS(7, c7); CKS(8, c8);
    }
    if (warp == 8) {
      if (lane == 0) {
        uint32_t s = EARLY_TILES & 3, ph = 1 ^ (EARLY_TILES >> 2);
#pragma unroll 1
        for (int tt = EARLY_TILES; tt < NTILES; tt++) {
          const CUtensorMap* tm;
          int c1, c2;
          uint32_t bytes = SLOT;
          if (tt < 16) {
            tm = &tmWq; c1 = (tt & 3) * 128; c2 = (j * 4 + (((tt >> 2) + 1) & 3)) * 2;
          } else if (tt < 48) {
            const int u = tt - 16;
            const bool isK = (u == 0) || ((u & 1) && u != 31);
            const int n = isK ? ((u + 1) >> 1) : (u == 31 ? 15 : (u >> 1) - 1);
            tm = isK ? &tmK : &tmV; c1 = j * SK + (SK - WIN) + (n & 3) * 128; c2 = 0;
          } else if (tt < 64) {
            const int u = tt - 48;
            tm = &tmWo; c1 = j * 512 + (u & 1) * 256; c2 = u >> 1;
          } else if (tt < 72) {
            tm = &tmW1; c1 = (tt - 64) * 64; c2 = j * 7; bytes = 28672;
          } else {
            tm = &tmW2; c1 = j * FSL; c2 = tt - 72; bytes = 28672;
          }
          mbar_wait(bars + 32 + s * 8, ph);
          mbar_expect(bars + s * 8, bytes);
          tma3d(sb + SM_RING + s * SLOT, tm, bars + s * 8, 0, c1, c2);
          if (++s == 4) { s = 0; ph ^= 1; }
        }
      }
    } else if (warp >= 10) {
      const int t2 = tid - 320, hf = t2 & 1, r0 = t2 >> 1;
      bar_sync(6, 352);
      float a[8];
#pragma unroll
      for (int k = 0; k < 8; k++) a[k] = 0.f;
#pragma unroll 1
      for (int b = 0; b < 8; b++) {
        uint4 w[2];
        uint32_t cb[2];
#pragma unroll
        for (int i = 0; i < 2; i++) {
          w[i] = ldg128(p.wmod + (size_t)(r0 + 32 * (2 * b + i)) * 3072 + 1024 + bid * 16 + hf * 8);
          cb[i] = ldg16(p.c + r0 + 32 * (2 * b + i));
        }
#pragma unroll
        for (int i = 0; i < 2; i++) {
          const float s = silu_c(cb[i]);
          a[0] = fmaf(s, bf_lo(w[i].x), a[0]); a[1] = fmaf(s, bf_hi(w[i].x), a[1]);
          a[2] = fmaf(s, bf_lo(w[i].y), a[2]); a[3] = fmaf(s, bf_hi(w[i].y), a[3]);
          a[4] = fmaf(s, bf_lo(w[i].z), a[4]); a[5] = fmaf(s, bf_hi(w[i].z), a[5]);
          a[6] = fmaf(s, bf_lo(w[i].w), a[6]); a[7] = fmaf(s, bf_hi(w[i].w), a[7]);
        }
      }
      const bool h16 = lane & 16, h8 = lane & 8, h4 = lane & 4;
#pragma unroll
      for (int k = 0; k < 4; k++) {
        float send = h16 ? a[k] : a[k + 4], keep = h16 ? a[k + 4] : a[k];
        a[k] = keep + __shfl_xor_sync(0xffffffffu, send, 16);
      }
#pragma unroll
      for (int k = 0; k < 2; k++) {
        float send = h8 ? a[k] : a[k + 2], keep = h8 ? a[k + 2] : a[k];
        a[k] = keep + __shfl_xor_sync(0xffffffffu, send, 8);
      }
      {
        float send = h4 ? a[0] : a[1], keep = h4 ? a[1] : a[0];
        a[0] = keep + __shfl_xor_sync(0xffffffffu, send, 4);
      }
      a[0] += __shfl_xor_sync(0xffffffffu, a[0], 2);
      float* red = (float*)(smem_raw + SM_RED) + 32;
      if ((lane & 2) == 0) red[(warp - 10) * 16 + hf * 8 + (lane >> 2)] = a[0];
      bar_sync(4, 64);
      if (warp == 10) {
        const int cl = lane & 15;
        float v = round_bf16(red[cl] + red[16 + cl]);
        if ((bid >> 5) == 2) v = 1.f + v;
        float vn = __shfl_down_sync(0xffffffffu, v, 1);
        uint32_t wd = pack_bf16(v, vn);
        uint32_t w0 = __shfl_sync(0xffffffffu, wd, (lane & 3) * 2);
        uint32_t w1 = __shfl_sync(0xffffffffu, wd, (lane & 3) * 2 + 8);
        const int vec = (0x2130 >> ((bid >> 5) * 4)) & 3;
        if (lane < 4) st_pkt(&p.s->mod2[((bid & 31) * 4 + vec) * 4 + lane], w0, w1, tag, 0);
      }
      const int isv = warp - 10;
      if (bid < 112) {
        const int kk = lane >> 1;
        const uint4* mp = &p.s->mod2[(isv ? 3 : 1) * 4 + ((kk & 7) >> 1)];
#pragma unroll
        for (int k = 0; k < 8; k++) a[k] = 0.f;
#pragma unroll 1
        for (int g = 0; g < 32; g++) {
          const uint4 w = ldg128(p.w1 + (size_t)(g * 16 + kk) * FF + bid * 16 + (lane & 1) * 8);
          uint32_t m[4];
          ld_mod(mp + g * 16, tag, m);
          const uint32_t mw = (kk & 8) ? m[1] : m[0];
          const float s = (kk & 1) ? bf_hi(mw) : bf_lo(mw);
          a[0] = fmaf(s, bf_lo(w.x), a[0]); a[1] = fmaf(s, bf_hi(w.x), a[1]);
          a[2] = fmaf(s, bf_lo(w.y), a[2]); a[3] = fmaf(s, bf_hi(w.y), a[3]);
          a[4] = fmaf(s, bf_lo(w.z), a[4]); a[5] = fmaf(s, bf_hi(w.z), a[5]);
          a[6] = fmaf(s, bf_lo(w.w), a[6]); a[7] = fmaf(s, bf_hi(w.w), a[7]);
        }
#pragma unroll
        for (int k = 0; k < 4; k++) {
          float send = h16 ? a[k] : a[k + 4], keep = h16 ? a[k + 4] : a[k];
          a[k] = keep + __shfl_xor_sync(0xffffffffu, send, 16);
        }
#pragma unroll
        for (int o = 8; o > 1; o >>= 1) {
#pragma unroll
          for (int k = 0; k < 4; k++) a[k] += __shfl_xor_sync(0xffffffffu, a[k], o);
        }
        const float sc = isv ? 0.5f : 1.f;
        if ((lane & 14) == 0)
          st_pkt(&p.s->uv[isv * 448 + bid * 4 + (lane & 1) * 2 + (lane >> 4)],
                 (__float_as_uint(a[0] * sc) & ~1u) | (tag & 1u), __float_as_uint(a[1] * sc), __float_as_uint(a[2] * sc),
                 __float_as_uint(a[3] * sc));
      }
#pragma unroll 1
      for (int i = lane; i < 56; i += 32) {
        uint32_t m[4];
        int spins = 0;
        do { ld_pkt(&p.s->uv[isv * 448 + j * 56 + i], m); } while (((m[0] ^ tag) & 1u) && ++spins < SPIN_LIMIT);
        const uint32_t ad = sb + SM_TAB + i * 32 + isv * 8;
        asm volatile("st.shared.v2.b32 [%0], {%1,%2};" ::"r"(ad), "r"(m[0]), "r"(m[1]) : "memory");
        asm volatile("st.shared.v2.b32 [%0], {%1,%2};" ::"r"(ad + 16), "r"(m[2]), "r"(m[3]) : "memory");
      }
      __syncwarp();
      if (lane == 0) mbar_arrive(bars + 72);

    } else {
      bar_sync(6, 352);
      if (lane < 8) l2_prefetch((const char*)p.wo + (size_t)bid * 32768 + lane * 4096, 4096);
      else if (lane < 12) l2_prefetch((const char*)p.w1 + (size_t)bid * 14336 + (lane - 8) * 3584, 3584);
      else if (lane < 16) l2_prefetch((const char*)p.w2 + (size_t)bid * 14336 + (lane - 12) * 3584, 3584);
    }
    if (warp > 8) {
      const int q = lane & 3, hw = warp - 9;
      float s0 = 0.f, s1 = 0.f, v0 = 0.f, v1 = 0.f;
      uint32_t ph = 0, buf = 0;
      auto item_issue = [&](int n, uint32_t bf) {
        if (lane == 0) {
          const int g = n & 31;
          const uint32_t bar = sb + SM_WBAR + 192 + (hw * 2 + bf) * 8;
          mbar_expect(bar, n < 32 ? 4096 + 192 + 512 : 4096 + 192);
          tma3d(sb + SM_PARK + (hw * 2 + bf) * 4096, &tmP, bar, 0, g, (rt * 8 + j) * 8);
          asm volatile("cp.async.bulk.shared::cluster.global.mbarrier::complete_tx::bytes [%0], [%1], 192, [%2];"
                       ::"r"(sb + SM_PARK + 6 * 4096 + (hw * 2 + bf) * 256), "l"(&p.s->mod2[g * 16]), "r"(bar) : "memory");
          if (n < 32) tma3d(sb + SM_PARK + SLOT + ((g & 7) ^ 4) * 4096 + (g >> 3) * 1024, &tmX, bar, 0, rt * 128 + j * 16, g);
        }
      };
      mbar_wait(sb + SM_SBAR, 0);
      item_issue(hw, 0);
#pragma unroll 1
      for (int n = hw; n < 32 + NITEM2; n += 3) {
        const int nn = n + 3, g = n & 31;
        const bool ex1 = n < 32, more = nn < 32 + NITEM2;
        const bool pre = more && mbar_test(sb + SM_SBAR + (nn >> 2) * 8, 0);
        if (pre) item_issue(nn, buf ^ 1);
        const uint32_t ls = sb + SM_PARK + (hw * 2 + buf) * 4096 + lane * 16;
        const uint32_t ms = sb + SM_PARK + 6 * 4096 + (hw * 2 + buf) * 256 + q * 16;
        const uint32_t xs = sb + SM_PARK + SLOT + ((g & 7) ^ 4) * 4096 + (g >> 3) * 1024;
        uint32_t m1[4], m2[4];
        float y[8];
#pragma unroll 1
        for (int spins = 0; spins < SPIN_LIMIT; spins++) {
          mbar_wait(sb + SM_WBAR + 192 + (hw * 2 + buf) * 8, (ph >> buf) & 1);
          ph ^= 1u << buf;
          lds128(ms + (ex1 ? 0 : 128), m1);
          lds128(ms + 64, m2);
          uint32_t bad = 0;
#pragma unroll
          for (int i = 0; i < 8; i++) {
            uint32_t r[4];
            lds128(ls + i * 512, r);
            bad |= r[0] ^ (uint32_t)ex1;
            r[0] |= 1u;
#pragma unroll
            for (int e = 0; e < 4; e++) {
              y[2 * e] = i ? y[2 * e] + bf_lo(r[e]) : bf_lo(r[e]);
              y[2 * e + 1] = i ? y[2 * e + 1] + bf_hi(r[e]) : bf_hi(r[e]);
            }
          }
          if (!__any_sync(0xffffffffu, (bad & 1u) || m1[2] != tag || m2[2] != tag)) break;
          item_issue(n, buf);
        }
        if (ex1) {
          uint32_t xr[4];
          asm volatile("ldmatrix.sync.aligned.m8n8.x4.shared.b16 {%0,%1,%2,%3}, [%4];"
                       : "=r"(xr[0]), "=r"(xr[1]), "=r"(xr[2]), "=r"(xr[3]) : "r"(xs + (lane & 15) * 32 + (lane >> 4) * 16) : "memory");
#pragma unroll
          for (int e = 0; e < 4; e++) {
            const float a = fmaf(bf_lo(m1[e >> 1]), y[2 * e], bf_lo(xr[e])), b = fmaf(bf_hi(m1[e >> 1]), y[2 * e + 1], bf_hi(xr[e]));
            y[2 * e] = a; y[2 * e + 1] = b;
            if (e & 1) { s1 += a + b; v1 = fmaf(a, a, fmaf(b, b, v1)); }
            else { s0 += a + b; v0 = fmaf(a, a, fmaf(b, b, v0)); }
          }
          st_pkt(p.s->G + ((rt * 8 + j) * 32 + g) * 32 + lane, pack_tag<0>(y[0] * bf_lo(m2[0]), y[1] * bf_hi(m2[0])),
                 pack_bf16(y[2] * bf_lo(m2[0]), y[3] * bf_hi(m2[0])), pack_bf16(y[4] * bf_lo(m2[1]), y[5] * bf_hi(m2[1])),
                 pack_bf16(y[6] * bf_lo(m2[1]), y[7] * bf_hi(m2[1])));
          sts128(xs + lane * 16, __float_as_uint(y[0]), __float_as_uint(y[1]), __float_as_uint(y[2]), __float_as_uint(y[3]));
          sts128(xs + 512 + lane * 16, __float_as_uint(y[4]), __float_as_uint(y[5]), __float_as_uint(y[6]), __float_as_uint(y[7]));
          if (nn >= 32) {
#pragma unroll
            for (int o = 1; o < 4; o <<= 1) {
              s0 += __shfl_xor_sync(0xffffffffu, s0, o);
              s1 += __shfl_xor_sync(0xffffffffu, s1, o);
              v0 += __shfl_xor_sync(0xffffffffu, v0, o);
              v1 += __shfl_xor_sync(0xffffffffu, v1, o);
            }
            if (hw && q == 0)
              sts128(sb + SM_RED + (hw - 1) * 128 + (lane >> 2) * 16, __float_as_uint(s0), __float_as_uint(v0),
                     __float_as_uint(s1), __float_as_uint(v1));
            bar_sync(8, 96);
            if (hw == 0) {
              lds128(sb + SM_RED + (lane >> 2) * 16, m1);
              lds128(sb + SM_RED + 128 + (lane >> 2) * 16, m2);
              const float a0 = (s0 + __uint_as_float(m1[0]) + __uint_as_float(m2[0])) * (1.f / 512.f);
              const float a1 = (s1 + __uint_as_float(m1[2]) + __uint_as_float(m2[2])) * (1.f / 512.f);
              const float b0 = (v0 + __uint_as_float(m1[1]) + __uint_as_float(m2[1])) * (1.f / 512.f);
              const float b1 = (v1 + __uint_as_float(m1[3]) + __uint_as_float(m2[3])) * (1.f / 512.f);
              const float r0 = 0.5f * rsqrtf(fmaxf(fmaf(-a0, a0, b0), 0.f) + 1e-5f);
              const float r1 = 0.5f * rsqrtf(fmaxf(fmaf(-a1, a1, b1), 0.f) + 1e-5f);
              if (q == 0)
                st_pkt(&p.s->stat[(rt * 8 + j) * 8 + (lane >> 2)], (__float_as_uint(r0) & ~1u) | (tag & 1u),
                       __float_as_uint(-a0 * r0), __float_as_uint(r1), __float_as_uint(-a1 * r1));
              if (lane == 0) mbar_arrive(bars + 88);
            }
          }
        } else {
          store_out(p.out, (uint32_t)(rt * 128 + 16 * j + (lane >> 2)) * 256 + g * 8 + q, xs + lane * 16, m1, y);
        }
        if (more && !pre) {
          mbar_wait(sb + SM_SBAR + (nn >> 2) * 8, 0);
          item_issue(nn, buf ^ 1);
        }
        buf ^= 1;
      }
    }
  } else {
    const int wg = warp >> 2;
    const int q = lane & 3, gq = lane >> 2;
    const Ring ring{(sb + SM_RING) >> 4, bars};
    const uint32_t xoff = (uint32_t)(rt * 128 + 16 * j + warp) * 256 + gq * 8 + q;
    const uint32_t ooff = ((uint32_t)(rt * 8 + j) * 32 + gq) * 32 + warp * 4 + q;
    const uint32_t wblk = sb + SM_PARK + warp * 4096, wprv = wblk + lane * 16;
    const uint32_t wbar = sb + SM_WBAR + warp * 24;
    const uint32_t goff = (uint32_t)(rt * 8 + warp) * 1024 + lane;

    {
      const uint32_t* xo = (const uint32_t*)p.x + xoff;
      uint32_t xr[4][4];
      CK_(d0);
#pragma unroll
      for (int c = 0; c < 4; c++) {
        xr[c][0] = ldg32(xo + c * 64);
        xr[c][1] = ldg32(xo + c * 64 + 8 * 256);
        xr[c][2] = ldg32(xo + c * 64 + 4);
        xr[c][3] = ldg32(xo + c * 64 + 4 + 8 * 256);
      }
      CK_(d1);
      fence_regs(xr);
      CK_(d2);
      float s0 = 0.f, s1 = 0.f, v0 = 0.f, v1 = 0.f;
#pragma unroll
      for (int c = 0; c < 4; c++) {
#pragma unroll
        for (int e = 0; e < 4; e++) {
          const float a = bf_lo(xr[c][e]), b = bf_hi(xr[c][e]);
          if (e & 1) { s1 += a + b; v1 = fmaf(a, a, fmaf(b, b, v1)); }
          else { s0 += a + b; v0 = fmaf(a, a, fmaf(b, b, v0)); }
        }
      }
#pragma unroll
      for (int o = 16; o > 0; o >>= 1) {
        s0 += __shfl_xor_sync(0xffffffffu, s0, o);
        s1 += __shfl_xor_sync(0xffffffffu, s1, o);
        v0 += __shfl_xor_sync(0xffffffffu, v0, o);
        v1 += __shfl_xor_sync(0xffffffffu, v1, o);
      }
      const float m0 = s0 * (1.f / 512.f), m1 = s1 * (1.f / 512.f);
      const float r0 = rsqrtf(fmaxf(fmaf(-m0, m0, v0 * (1.f / 512.f)), 0.f) + 1e-5f);
      const float r1 = rsqrtf(fmaxf(fmaf(-m1, m1, v1 * (1.f / 512.f)), 0.f) + 1e-5f);
#pragma unroll
      for (int c = 0; c < 4; c++) {
        st_pkt(p.s->G + ooff + c * 256,
               pack_tag<1>((bf_lo(xr[c][0]) - m0) * r0, (bf_hi(xr[c][0]) - m0) * r0),
               pack_bf16((bf_lo(xr[c][1]) - m1) * r1, (bf_hi(xr[c][1]) - m1) * r1),
               pack_bf16((bf_lo(xr[c][2]) - m0) * r0, (bf_hi(xr[c][2]) - m0) * r0),
               pack_bf16((bf_lo(xr[c][3]) - m1) * r1, (bf_hi(xr[c][3]) - m1) * r1));
      }
      CK_(d3);
      CKS(16, d0); CKS(17, d1); CKS(18, d2); CKS(19, d3);

    }
    asm volatile("setmaxnreg.inc.sync.aligned.u32 224;");
    uint32_t qf[8][4];
    {
      uint32_t h[32][4];
      float acc[64];
      const uint4* Gin = p.s->G + goff;
      bar_sync(7, 384);
      if (G_DELAY) spin_cycles(G_DELAY);
#pragma unroll
      for (int c = 0; c < 3; c++) warp_bulk_load(wblk + c * SLOT, Gin + c * 256, 4096, wbar + c * 8);
#pragma unroll
      for (int c = 0; c < 4; c++) {
        mbar_wait(wbar + (c % 3) * 8, c / 3);
#pragma unroll
        for (int i = 0; i < 8; i++) lds128(wprv + (c % 3) * SLOT + i * 512, h[c * 8 + i]);
        verify8_tag1<512>(Gin + c * 256, h + c * 8);
        if (c == 0) {
          warp_bulk_load(wblk, Gin + 768, 4096, wbar);
          TS(1);
          bar_sync(1, 384);
        }
#pragma unroll
        for (int i = 0; i < 8; i++) {
          uint32_t m[4];
          lds128(sb + SM_TAB + (uint32_t)((c * 8 + i) * 4 + q) * 16, m);
          uint32_t* hh = h[c * 8 + i];
          hh[0] = hfma2_bf16(hh[0], m[0], m[2]);
          hh[1] = hfma2_bf16(hh[1], m[0], m[2]);
          hh[2] = hfma2_bf16(hh[2], m[1], m[3]);
          hh[3] = hfma2_bf16(hh[3], m[1], m[3]);
        }
        fence_frags<8>(h + c * 8);
        const uint32_t b = ring.wait_full(c, 0);
        if (c > 0) { wg_wait<0>(); ring.release(c - 1); }
        if (c == 0) TS(2);
        wg_fence();
        static_for<0, 8>([&](auto K) { wgmma_rs_n128_tb1<LB_MN128 + K * 128, HI128>(acc, h[c * 8 + K], b, (c | K) != 0); });
        wg_commit();
      }
      bar_arrive(6, 352);
#pragma unroll 1
      for (int ps = 1; ps < 4; ps++) {
        wg_wait<0>();
        ring.release(3);
        fence_regs(acc);
#pragma unroll
        for (int i = 0; i < 8; i++) {
          uint32_t o[4];
          pack8(o, acc + 8 * i);
          sts128(wprv + (ps - 1) * SLOT + i * 512, o[0], o[1], o[2], o[3]);
        }
#pragma unroll
        for (int c = 0; c < 4; c++) {
          const uint32_t b = ring.wait_full(c, ps & 1);
          if (c > 0) { wg_wait<0>(); ring.release(c - 1); }
          wg_fence();
          static_for<0, 8>([&](auto K) { wgmma_rs_n128_tb1<LB_MN128 + K * 128, HI128>(acc, h[c * 8 + K], b, (c | K) != 0); });
          wg_commit();
        }
      }
      wg_wait<0>();
      ring.release(3);
      fence_regs(acc);
#pragma unroll
      for (int i = 0; i < 8; i++) pack8(qf[i], acc + 8 * i);
    }
    fence_regs(qf);
    TS(3);

    float S[64];
    {
      float O[64];
      uint32_t P[8][4];
      const float cs = 0.08838834764831845f * 1.4426950408889634f;
      const int TAU = 0x41800000;
      float m0, m1, l0, l1;

      auto float_block_max = [&]() {
        float b0 = fmaxf(S[0], S[1]), b1 = fmaxf(S[2], S[3]);
#pragma unroll
        for (int i = 1; i < 16; i++) {
          b0 = fmaxf(b0, fmaxf(S[4 * i], S[4 * i + 1]));
          b1 = fmaxf(b1, fmaxf(S[4 * i + 2], S[4 * i + 3]));
        }
        b0 = fmaxf(b0, __shfl_xor_sync(0xffffffffu, b0, 1)); b1 = fmaxf(b1, __shfl_xor_sync(0xffffffffu, b1, 1));
        b0 = fmaxf(b0, __shfl_xor_sync(0xffffffffu, b0, 2)); b1 = fmaxf(b1, __shfl_xor_sync(0xffffffffu, b1, 2));
        m0 = b0 * cs; m1 = b1 * cs;
      };
      auto first_block_max = [&]() {
        int a0 = max(__float_as_int(S[0]), __float_as_int(S[1]));
        int a1 = max(__float_as_int(S[2]), __float_as_int(S[3]));
#pragma unroll
        for (int i = 1; i < 16; i++) {
          a0 = __vimax3_s32(a0, __float_as_int(S[4 * i]), __float_as_int(S[4 * i + 1]));
          a1 = __vimax3_s32(a1, __float_as_int(S[4 * i + 2]), __float_as_int(S[4 * i + 3]));
        }
        a0 = max(a0, __shfl_xor_sync(0xffffffffu, a0, 1)); a1 = max(a1, __shfl_xor_sync(0xffffffffu, a1, 1));
        a0 = max(a0, __shfl_xor_sync(0xffffffffu, a0, 2)); a1 = max(a1, __shfl_xor_sync(0xffffffffu, a1, 2));
        m0 = __int_as_float(a0) * cs; m1 = __int_as_float(a1) * cs;
        if (__any_sync(0xffffffffu, (a0 | a1) < 0)) float_block_max();
      };
      auto scale_sub = [&]() {
#pragma unroll
        for (int i = 0; i < 16; i++) {
          S[4 * i] = fmaf(S[4 * i], cs, -m0); S[4 * i + 1] = fmaf(S[4 * i + 1], cs, -m0);
          S[4 * i + 2] = fmaf(S[4 * i + 2], cs, -m1); S[4 * i + 3] = fmaf(S[4 * i + 3], cs, -m1);
        }
      };
      auto exps = [&](int i0, int i1) {
#pragma unroll
        for (int i = i0; i < i1; i++) {
          S[4 * i] = ex2(S[4 * i]); S[4 * i + 1] = ex2(S[4 * i + 1]);
          S[4 * i + 2] = ex2(S[4 * i + 2]); S[4 * i + 3] = ex2(S[4 * i + 3]);
          l0 += S[4 * i]; l1 += S[4 * i + 2]; l0 += S[4 * i + 1]; l1 += S[4 * i + 3];
        }
      };
      {
        const uint32_t b = ring.wait_full(0, 0);
        wg_fence();
        static_for<0, 8>([&](auto K) { wgmma_rs_n128_tb0<LB_K128 + (K >> 2) * 1024 + (K & 3) * 2, HI128>(S, qf[K], b, K != 0); });
        wg_commit();
        wg_wait<0>();
        fence_regs(S);
        ring.release(0);
        float_block_max();
        scale_sub();
        l0 = 0.f; l1 = 0.f;
        exps(0, 16);
#pragma unroll
        for (int i = 0; i < 8; i++) pack8(P[i], S + 8 * i);
      }
      fence_regs(P);
      if (wg == 1) bar_arrive(2, 256);
#pragma unroll 1
      for (int n = 1; n < 16; n++) {
        const uint32_t tk = 2 * n - 1, tv = 2 * n;
        const bool newhead = (n & 3) == 0;
        const uint32_t bk = ring.wait_full(tk & 3, (tk >> 2) & 1);
        const uint32_t bv = ring.wait_full(tv & 3, (tv >> 2) & 1);
        bar_sync(2 + wg, 256);
        wg_fence();
        static_for<0, 8>([&](auto K) { wgmma_rs_n128_tb0<LB_K128 + (K >> 2) * 1024 + (K & 3) * 2, HI128>(S, qf[K], bk, K != 0); });
        wg_commit();
        static_for<0, 8>([&](auto K) { wgmma_rs_n128_tb1<LB_MN128 + K * 128, HI128>(O, P[K], bv, K != 0 || (n & 3) != 1); });
        wg_commit();
        bar_arrive(2 + (wg ^ 1), 256);
        wg_wait<1>();
        fence_regs(S);
        ring.release(tk & 3);
        if ((n & 3) == 3 && n != 15) {
          fence_regs(qf);
#pragma unroll
          for (int i = 0; i < 8; i++) lds128(wprv + (n >> 2) * SLOT + i * 512, qf[i]);
        }
        float f0 = 1.f, f1 = 1.f;
        bool resc = newhead;
        if (newhead) {
          l0 += __shfl_xor_sync(0xffffffffu, l0, 1); l1 += __shfl_xor_sync(0xffffffffu, l1, 1);
          l0 += __shfl_xor_sync(0xffffffffu, l0, 2); l1 += __shfl_xor_sync(0xffffffffu, l1, 2);
          f0 = rcp_hw(l0); f1 = rcp_hw(l1);
          l0 = 0.f; l1 = 0.f;
          first_block_max();
          scale_sub();
        } else {
          scale_sub();
          int a0 = __vimax3_s32(__float_as_int(S[0]), __float_as_int(S[1]), __float_as_int(S[1]));
          int a1 = __vimax3_s32(__float_as_int(S[2]), __float_as_int(S[3]), __float_as_int(S[3]));
#pragma unroll
          for (int i = 1; i < 16; i++) {
            a0 = __vimax3_s32(a0, __float_as_int(S[4 * i]), __float_as_int(S[4 * i + 1]));
            a1 = __vimax3_s32(a1, __float_as_int(S[4 * i + 2]), __float_as_int(S[4 * i + 3]));
          }
          if (__any_sync(0xffffffffu, max(a0, a1) > TAU)) {
            a0 = max(a0, 0); a1 = max(a1, 0);
            a0 = max(a0, __shfl_xor_sync(0xffffffffu, a0, 1)); a1 = max(a1, __shfl_xor_sync(0xffffffffu, a1, 1));
            a0 = max(a0, __shfl_xor_sync(0xffffffffu, a0, 2)); a1 = max(a1, __shfl_xor_sync(0xffffffffu, a1, 2));
            const float d0 = __int_as_float(a0), d1 = __int_as_float(a1);
#pragma unroll
            for (int i = 0; i < 16; i++) { S[4 * i] -= d0; S[4 * i + 1] -= d0; S[4 * i + 2] -= d1; S[4 * i + 3] -= d1; }
            m0 += d0; m1 += d1;
            f0 = ex2(-d0); f1 = ex2(-d1);
            l0 *= f0; l1 *= f1;
            resc = true;
          }
        }
        exps(0, 4);
        wg_wait<0>();
        fence_regs(O);
        fence_regs(P);
        ring.release(tv & 3);
        if (resc) {
#pragma unroll
          for (int i = 0; i < 16; i++) {
            O[4 * i] *= f0; O[4 * i + 1] *= f0; O[4 * i + 2] *= f1; O[4 * i + 3] *= f1;
          }
          if (newhead) {
#pragma unroll
            for (int i = 0; i < 8; i++) {
              uint32_t o[4];
              pack8(o, O + 8 * i);
              sts128(wprv + ((n >> 2) - 1) * SLOT + i * 512, o[0], o[1], o[2], o[3]);
            }
          }
        }
        exps(4, 16);
#pragma unroll
        for (int i = 0; i < 8; i++) pack8(P[i], S + 8 * i);
        fence_regs(P);
        fence_regs(O);
      }
      {
        const uint32_t bv = ring.wait_full(3, 1);
        if (wg == 0) bar_sync(2, 256);
        wg_fence();
        static_for<0, 8>([&](auto K) { wgmma_rs_n128_tb1<LB_MN128 + K * 128, HI128>(O, P[K], bv, 1); });
        wg_commit();
        l0 += __shfl_xor_sync(0xffffffffu, l0, 1); l1 += __shfl_xor_sync(0xffffffffu, l1, 1);
        l0 += __shfl_xor_sync(0xffffffffu, l0, 2); l1 += __shfl_xor_sync(0xffffffffu, l1, 2);
        const float f0 = rcp_hw(l0), f1 = rcp_hw(l1);
        wg_wait<0>();
        fence_regs(O);
        ring.release(3);
#pragma unroll
        for (int i = 0; i < 8; i++) {
          qf[i][0] = pack_bf16(O[8 * i] * f0, O[8 * i + 1] * f0); qf[i][1] = pack_bf16(O[8 * i + 2] * f1, O[8 * i + 3] * f1);
          qf[i][2] = pack_bf16(O[8 * i + 4] * f0, O[8 * i + 5] * f0); qf[i][3] = pack_bf16(O[8 * i + 6] * f1, O[8 * i + 7] * f1);
        }
      }
    }
    fence_regs(qf);
    TS(4);

    uint4* const Pout = p.s->P + ((size_t)(rt * 8 + warp) * 8 + j) * 1024 + lane;
    const uint32_t tag = *(volatile uint32_t*)(smem_raw + SM_BAR + 64);

    float acc2[32];
    uint32_t pk[4][4];
    auto pack_partial = [&](auto TAGC) {
      fence_regs(acc2);
#pragma unroll
      for (int i = 0; i < 4; i++) {
        pack8(pk[i], acc2 + 8 * i);
        pk[i][0] = pack_tag<TAGC>(acc2[8 * i], acc2[8 * i + 1]);
      }
      fence_regs(pk);
    };
    auto store_partial = [&](int step) {
#pragma unroll
      for (int i = 0; i < 4; i++) st_pkt(Pout + ((step & 7) * 4 + i) * 32, pk[i][0], pk[i][1], pk[i][2], pk[i][3]);
    };
    auto chunk_sent = [&](int step) { if (lane == 0) mbar_arrive(sb + SM_SBAR + step * 8); };
    const uint4* const Gin = p.s->G + goff;
    auto g_issue = [&](int u) { warp_bulk_load(wblk + 2 * SLOT + (u & 1) * 2048, Gin + u * 128, 2048, wbar + (u & 1) * 8); };

    uint32_t tl = 0, b = ring.wait_full(0, 0);
    auto next_tile = [&]() {
      const uint32_t cur = tl & 3;
      tl++;
      b = ring.wait_full(tl & 3, (tl >> 2) & 1);
      wg_wait<0>();
      TR(4);
      ring.release(cur);
    };
    {
      uint32_t o[24][4];
#pragma unroll
      for (int i = 0; i < 24; i++) lds128(wprv + (i >> 3) * SLOT + (i & 7) * 512, o[i]);
#pragma unroll 1
      for (int cc = 0; cc < 8; cc++) {
        wg_fence();
        static_for<0, 16>([&](auto K) { wgmma_rs_n64_tb1<K * 128, HI128>(acc2, o[K], b, K != 0); });
        wg_commit();
        if (cc > 0) store_partial(cc - 1);
        next_tile();
        wg_fence();
        static_for<0, 16>([&](auto K) { wgmma_rs_n64_tb1<K * 128, HI128>(acc2, K < 8 ? o[16 + (K & 7)] : qf[K & 7], b, 1); });
        wg_commit();
        if (cc > 0) chunk_sent(cc - 1);
        if (cc == 6) { g_issue(0); g_issue(1); }
        next_tile();
        pack_partial(IC<1>{});
      }
    }
    TS(5);

    uint32_t H[14][4];
    {
      float acc[112];
      const uint4* const statp = &p.s->stat[(rt * 8 + warp) * 8];
#pragma unroll 1
      for (int u = 0; u < 8; u++) {
        uint32_t fa[4][4];
        mbar_wait(wbar + (u & 1) * 8, ((u >> 1) + (u & 1)) & 1);
#pragma unroll
        for (int i = 0; i < 4; i++) lds128(wprv + 2 * SLOT + (u & 1) * 2048 + i * 512, fa[i]);
        verify4_tag0<512>(Gin + u * 128, fa);
        wg_fence();
        static_for<0, 4>([&](auto K) { wgmma_rs_n224_tb1<LB_W1 + K * 64, HI64>(acc, fa[K], b, (u | K) != 0); });
        wg_commit();
        if (u == 0) store_partial(7);
        if (u == 1) chunk_sent(7);
        if (u < 5) g_issue(u + 2);
        if (u == 7) warp_bulk_load(wblk + 2 * SLOT, statp, 128, wbar + 16);
        next_tile();
        if (u == 5) g_issue(7);
      }
      fence_regs(acc);
      TS(9);
      mbar_wait(bars + 72, 0);
      uint32_t xr[4];
      mbar_wait(wbar + 16, 1);
      lds128(wblk + 2 * SLOT + gq * 16, xr);
      {
        int spins = 0;
        while (((xr[0] ^ tag) & 1u) && ++spins < SPIN_LIMIT) ld_pkt(statp + gq, xr);
      }
      const float ra0 = __uint_as_float(xr[0]), rb0 = __uint_as_float(xr[1]), ra1 = __uint_as_float(xr[2]),
                  rb1 = __uint_as_float(xr[3]);
#pragma unroll
      for (int i = 0; i < 28; i++) {
        uint32_t m[4];
        lds128(sb + SM_TAB + (i * 4 + q) * 16, m);
        const float u0 = __uint_as_float(m[0]), u1 = __uint_as_float(m[1]), w0 = __uint_as_float(m[2]), w1 = __uint_as_float(m[3]);
        const float z0 = fmaf(acc[4 * i], ra0, fmaf(u0, rb0, w0)), z1 = fmaf(acc[4 * i + 1], ra0, fmaf(u1, rb0, w1));
        const float z2 = fmaf(acc[4 * i + 2], ra1, fmaf(u0, rb1, w0)), z3 = fmaf(acc[4 * i + 3], ra1, fmaf(u1, rb1, w1));
        H[i >> 1][(i & 1) * 2] = pack_bf16(fmaf(z0, tanh_hw(z0), z0), fmaf(z1, tanh_hw(z1), z1));
        H[i >> 1][(i & 1) * 2 + 1] = pack_bf16(fmaf(z2, tanh_hw(z2), z2), fmaf(z3, tanh_hw(z3), z3));
      }
    }
    fence_regs(H);
    TS(10);
    const int go = 24 + (warp ^ 4);
    uint32_t gb[4];
    ld_pkt(p.s->mod2 + go * 16 + 8 + q, gb);
#pragma unroll 1
    for (int cc = 0; cc < 8; cc++) {
      wg_fence();
      static_for<0, 14>([&](auto K) { wgmma_rs_n64_tb1<K * 128, HI128>(acc2, H[K], b, K != 0); });
      wg_commit();
      if (cc > 1) chunk_sent(8 + cc - 2);
      if (cc > 0) store_partial(cc - 1);
      if (cc < 7) next_tile();
      wg_wait<0>();
      pack_partial(IC<0>{});
    }
    store_partial(7);
    TS(11);
    {
      const uint4* const Pown = p.s->P + (size_t)(rt * 8 + j) * 8192 + go * 32 + lane;
      uint32_t r[8][4];
      float y[8];
      if (gb[2] != tag) ld_mod(p.s->mod2 + go * 16 + 8 + q, tag, gb);
      mbar_wait(bars + 88, 0);
      spin_cycles(wg ? FIN_DELAY1 : FIN_DELAY0);
      issue_pkts<0, 8>(Pown, 1024, r);
      verify8_tag0<16384>(Pown, r);
      TS(13);
#pragma unroll
      for (int e = 0; e < 4; e++) {
        y[2 * e] = bf_lo(r[0][e]); y[2 * e + 1] = bf_hi(r[0][e]);
#pragma unroll
        for (int s = 1; s < 8; s++) { y[2 * e] += bf_lo(r[s][e]); y[2 * e + 1] += bf_hi(r[s][e]); }
      }
      store_out(p.out, (uint32_t)(rt * 128 + 16 * j + gq) * 256 + go * 8 + q, wprv + SLOT + 3 * 1024, gb, y);
    }
    TS(12);
    if (bid == 0 && tid == 0) asm volatile("st.relaxed.gpu.global.u32 [%0], %1;" ::"l"(&p.s->epoch), "r"(tag) : "memory");
  }
}

typedef CUresult (*EncodeFn)(CUtensorMap*, CUtensorMapDataType, cuuint32_t, void*, const cuuint64_t*, const cuuint64_t*,
                             const cuuint32_t*, const cuuint32_t*, CUtensorMapInterleave, CUtensorMapSwizzle,
                             CUtensorMapL2promotion, CUtensorMapFloatOOBfill);

static void make_map(EncodeFn fn, CUtensorMap* tm, const void* ptr, int inner, int rows, int cols, int box_rows, int box_outer,
                     CUtensorMapSwizzle swz) {
  cuuint64_t gd[3] = {(cuuint64_t)inner, (cuuint64_t)rows, (cuuint64_t)(cols / inner)};
  cuuint64_t gs[2] = {(cuuint64_t)cols * 2, (cuuint64_t)inner * 2};
  cuuint32_t bx[3] = {(cuuint32_t)inner, (cuuint32_t)box_rows, (cuuint32_t)box_outer};
  cuuint32_t es[3] = {1, 1, 1};
  fn(tm, CU_TENSOR_MAP_DATA_TYPE_BFLOAT16, 3, const_cast<void*>(ptr), gd, gs, bx, es, CU_TENSOR_MAP_INTERLEAVE_NONE, swz,
     CU_TENSOR_MAP_L2_PROMOTION_L2_128B, CU_TENSOR_MAP_FLOAT_OOB_FILL_NONE);
}

extern "C" void kernel_launch(void* const* d_in, const int* in_sizes, int n_in, void* d_out, int out_size) {
  (void)in_sizes; (void)n_in; (void)out_size;
  void* fnp = nullptr;
  cudaDriverEntryPointQueryResult qr;
  cudaGetDriverEntryPoint("cuTensorMapEncodeTiled", &fnp, cudaEnableDefault, &qr);
  EncodeFn fn = (EncodeFn)fnp;
  CUtensorMap tmWq, tmK, tmV, tmWo, tmW1, tmW2, tmWm, tmP, tmX;
  make_map(fn, &tmWq, d_in[3], 64, 512, 4096, 128, 2, CU_TENSOR_MAP_SWIZZLE_128B);
  make_map(fn, &tmK, d_in[1], 64, 8 * SK, 128, 128, 2, CU_TENSOR_MAP_SWIZZLE_128B);
  make_map(fn, &tmV, d_in[2], 64, 8 * SK, 128, 128, 2, CU_TENSOR_MAP_SWIZZLE_128B);
  make_map(fn, &tmWo, d_in[4], 64, 4096, 512, 256, 1, CU_TENSOR_MAP_SWIZZLE_128B);
  make_map(fn, &tmW1, d_in[6], 32, 512, FF, 64, 7, CU_TENSOR_MAP_SWIZZLE_64B);
  make_map(fn, &tmW2, d_in[7], 64, FF, 512, 224, 1, CU_TENSOR_MAP_SWIZZLE_128B);
  make_map(fn, &tmWm, d_in[9], 8, 512, 3072, 256, 1, CU_TENSOR_MAP_SWIZZLE_NONE);
  make_map(fn, &tmX, d_in[0], 16, 2048, 512, 16, 1, CU_TENSOR_MAP_SWIZZLE_NONE);
  Params p;
  p.x = (const __nv_bfloat16*)d_in[0];
  p.c = (const __nv_bfloat16*)d_in[8];
  p.wmod = (const __nv_bfloat16*)d_in[9];
  p.wo = (const __nv_bfloat16*)d_in[4];
  p.w1 = (const __nv_bfloat16*)d_in[6];
  p.w2 = (const __nv_bfloat16*)d_in[7];
  p.out = (__nv_bfloat16*)d_out;
  cudaGetSymbolAddress((void**)&p.s, g_scratch);
  {
    cuuint64_t gd[3] = {256, 32, 1024};
    cuuint64_t gs[2] = {512, 16384};
    cuuint32_t bx[3] = {256, 1, 8};
    cuuint32_t es[3] = {1, 1, 1};
    fn(&tmP, CU_TENSOR_MAP_DATA_TYPE_BFLOAT16, 3, (void*)p.s->P, gd, gs, bx, es, CU_TENSOR_MAP_INTERLEAVE_NONE,
       CU_TENSOR_MAP_SWIZZLE_NONE, CU_TENSOR_MAP_L2_PROMOTION_NONE, CU_TENSOR_MAP_FLOAT_OOB_FILL_NONE);
  }
  cudaFuncSetAttribute(adaln_block_kernel, cudaFuncAttributeMaxDynamicSharedMemorySize, SM_TOTAL);
  adaln_block_kernel<<<128, 384, SM_TOTAL>>>(tmWq, tmK, tmV, tmWo, tmW1, tmW2, tmWm, tmP, tmX, p);
}
```

```cpp
#include <cuda_runtime.h>
#include <cuda_bf16.h>
#include <cuda.h>
#include <stdint.h>

template <int OFF, uint32_t HI>
__device__ __forceinline__ void wgmma_rs_n128_tb0(float (&d)[64], const uint32_t (&a)[4], uint32_t lo, int sd) {
  asm volatile("{\n.reg .pred p;\n.reg .b32 l;\n.reg .b64 db;\nsetp.ne.b32 p, %69, 0;\n"
    "add.u32 l, %68, %70;\nmov.b64 db, {l, %71};\n"
    "wgmma.mma_async.sync.aligned.m64n128k16.f32.bf16.bf16 "
    "{%0,%1,%2,%3,%4,%5,%6,%7,%8,%9,%10,%11,%12,%13,%14,%15,"
    "%16,%17,%18,%19,%20,%21,%22,%23,%24,%25,%26,%27,%28,%29,%30,%31,"
    "%32,%33,%34,%35,%36,%37,%38,%39,%40,%41,%42,%43,%44,%45,%46,%47,"
    "%48,%49,%50,%51,%52,%53,%54,%55,%56,%57,%58,%59,%60,%61,%62,%63}, "
    "{%64,%65,%66,%67}, db, p, 1, 1, 0;\n}\n"
    : "+f"(d[0]), "+f"(d[1]), "+f"(d[2]), "+f"(d[3]), "+f"(d[4]), "+f"(d[5]), "+f"(d[6]), "+f"(d[7]),
      "+f"(d[8]), "+f"(d[9]), "+f"(d[10]), "+f"(d[11]), "+f"(d[12]), "+f"(d[13]), "+f"(d[14]), "+f"(d[15]),
      "+f"(d[16]), "+f"(d[17]), "+f"(d[18]), "+f"(d[19]), "+f"(d[20]), "+f"(d[21]), "+f"(d[22]), "+f"(d[23]),
      "+f"(d[24]), "+f"(d[25]), "+f"(d[26]), "+f"(d[27]), "+f"(d[28]), "+f"(d[29]), "+f"(d[30]), "+f"(d[31]),
      "+f"(d[32]), "+f"(d[33]), "+f"(d[34]), "+f"(d[35]), "+f"(d[36]), "+f"(d[37]), "+f"(d[38]), "+f"(d[39]),
      "+f"(d[40]), "+f"(d[41]), "+f"(d[42]), "+f"(d[43]), "+f"(d[44]), "+f"(d[45]), "+f"(d[46]), "+f"(d[47]),
      "+f"(d[48]), "+f"(d[49]), "+f"(d[50]), "+f"(d[51]), "+f"(d[52]), "+f"(d[53]), "+f"(d[54]), "+f"(d[55]),
      "+f"(d[56]), "+f"(d[57]), "+f"(d[58]), "+f"(d[59]), "+f"(d[60]), "+f"(d[61]), "+f"(d[62]), "+f"(d[63])
    : "r"(a[0]), "r"(a[1]), "r"(a[2]), "r"(a[3]), "r"(lo), "r"(sd), "n"(OFF), "n"(HI));
}

template <int OFF, uint32_t HI>
__device__ __forceinline__ void wgmma_rs_n128_tb1(float (&d)[64], const uint32_t (&a)[4], uint32_t lo, int sd) {
  asm volatile("{\n.reg .pred p;\n.reg .b32 l;\n.reg .b64 db;\nsetp.ne.b32 p, %69, 0;\n"
    "add.u32 l, %68, %70;\nmov.b64 db, {l, %71};\n"
    "wgmma.mma_async.sync.aligned.m64n128k16.f32.bf16.bf16 "
    "{%0,%1,%2,%3,%4,%5,%6,%7,%8,%9,%10,%11,%12,%13,%14,%15,"
    "%16,%17,%18,%19,%20,%21,%22,%23,%24,%25,%26,%27,%28,%29,%30,%31,"
    "%32,%33,%34,%35,%36,%37,%38,%39,%40,%41,%42,%43,%44,%45,%46,%47,"
    "%48,%49,%50,%51,%52,%53,%54,%55,%56,%57,%58,%59,%60,%61,%62,%63}, "
    "{%64,%65,%66,%67}, db, p, 1, 1, 1;\n}\n"
    : "+f"(d[0]), "+f"(d[1]), "+f"(d[2]), "+f"(d[3]), "+f"(d[4]), "+f"(d[5]), "+f"(d[6]), "+f"(d[7]),
      "+f"(d[8]), "+f"(d[9]), "+f"(d[10]), "+f"(d[11]), "+f"(d[12]), "+f"(d[13]), "+f"(d[14]), "+f"(d[15]),
      "+f"(d[16]), "+f"(d[17]), "+f"(d[18]), "+f"(d[19]), "+f"(d[20]), "+f"(d[21]), "+f"(d[22]), "+f"(d[23]),
      "+f"(d[24]), "+f"(d[25]), "+f"(d[26]), "+f"(d[27]), "+f"(d[28]), "+f"(d[29]), "+f"(d[30]), "+f"(d[31]),
      "+f"(d[32]), "+f"(d[33]), "+f"(d[34]), "+f"(d[35]), "+f"(d[36]), "+f"(d[37]), "+f"(d[38]), "+f"(d[39]),
      "+f"(d[40]), "+f"(d[41]), "+f"(d[42]), "+f"(d[43]), "+f"(d[44]), "+f"(d[45]), "+f"(d[46]), "+f"(d[47]),
      "+f"(d[48]), "+f"(d[49]), "+f"(d[50]), "+f"(d[51]), "+f"(d[52]), "+f"(d[53]), "+f"(d[54]), "+f"(d[55]),
      "+f"(d[56]), "+f"(d[57]), "+f"(d[58]), "+f"(d[59]), "+f"(d[60]), "+f"(d[61]), "+f"(d[62]), "+f"(d[63])
    : "r"(a[0]), "r"(a[1]), "r"(a[2]), "r"(a[3]), "r"(lo), "r"(sd), "n"(OFF), "n"(HI));
}

template <int OFF, uint32_t HI>
__device__ __forceinline__ void wgmma_rs_n224_tb1(float (&d)[112], const uint32_t (&a)[4], uint32_t lo, int sd) {
  asm volatile("{\n.reg .pred p;\n.reg .b32 l;\n.reg .b64 db;\nsetp.ne.b32 p, %117, 0;\n"
    "add.u32 l, %116, %118;\nmov.b64 db, {l, %119};\n"
    "wgmma.mma_async.sync.aligned.m64n224k16.f32.bf16.bf16 "
    "{%0,%1,%2,%3,%4,%5,%6,%7,%8,%9,%10,%11,%12,%13,%14,%15,"
    "%16,%17,%18,%19,%20,%21,%22,%23,%24,%25,%26,%27,%28,%29,%30,%31,"
    "%32,%33,%34,%35,%36,%37,%38,%39,%40,%41,%42,%43,%44,%45,%46,%47,"
    "%48,%49,%50,%51,%52,%53,%54,%55,%56,%57,%58,%59,%60,%61,%62,%63,"
    "%64,%65,%66,%67,%68,%69,%70,%71,%72,%73,%74,%75,%76,%77,%78,%79,"
    "%80,%81,%82,%83,%84,%85,%86,%87,%88,%89,%90,%91,%92,%93,%94,%95,"
    "%96,%97,%98,%99,%100,%101,%102,%103,%104,%105,%106,%107,%108,%109,%110,%111}, "
    "{%112,%113,%114,%115}, db, p, 1, 1, 1;\n}\n"
    : "+f"(d[0]), "+f"(d[1]), "+f"(d[2]), "+f"(d[3]), "+f"(d[4]), "+f"(d[5]), "+f"(d[6]), "+f"(d[7]),
      "+f"(d[8]), "+f"(d[9]), "+f"(d[10]), "+f"(d[11]), "+f"(d[12]), "+f"(d[13]), "+f"(d[14]), "+f"(d[15]),
      "+f"(d[16]), "+f"(d[17]), "+f"(d[18]), "+f"(d[19]), "+f"(d[20]), "+f"(d[21]), "+f"(d[22]), "+f"(d[23]),
      "+f"(d[24]), "+f"(d[25]), "+f"(d[26]), "+f"(d[27]), "+f"(d[28]), "+f"(d[29]), "+f"(d[30]), "+f"(d[31]),
      "+f"(d[32]), "+f"(d[33]), "+f"(d[34]), "+f"(d[35]), "+f"(d[36]), "+f"(d[37]), "+f"(d[38]), "+f"(d[39]),
      "+f"(d[40]), "+f"(d[41]), "+f"(d[42]), "+f"(d[43]), "+f"(d[44]), "+f"(d[45]), "+f"(d[46]), "+f"(d[47]),
      "+f"(d[48]), "+f"(d[49]), "+f"(d[50]), "+f"(d[51]), "+f"(d[52]), "+f"(d[53]), "+f"(d[54]), "+f"(d[55]),
      "+f"(d[56]), "+f"(d[57]), "+f"(d[58]), "+f"(d[59]), "+f"(d[60]), "+f"(d[61]), "+f"(d[62]), "+f"(d[63]),
      "+f"(d[64]), "+f"(d[65]), "+f"(d[66]), "+f"(d[67]), "+f"(d[68]), "+f"(d[69]), "+f"(d[70]), "+f"(d[71]),
      "+f"(d[72]), "+f"(d[73]), "+f"(d[74]), "+f"(d[75]), "+f"(d[76]), "+f"(d[77]), "+f"(d[78]), "+f"(d[79]),
      "+f"(d[80]), "+f"(d[81]), "+f"(d[82]), "+f"(d[83]), "+f"(d[84]), "+f"(d[85]), "+f"(d[86]), "+f"(d[87]),
      "+f"(d[88]), "+f"(d[89]), "+f"(d[90]), "+f"(d[91]), "+f"(d[92]), "+f"(d[93]), "+f"(d[94]), "+f"(d[95]),
      "+f"(d[96]), "+f"(d[97]), "+f"(d[98]), "+f"(d[99]), "+f"(d[100]), "+f"(d[101]), "+f"(d[102]), "+f"(d[103]),
      "+f"(d[104]), "+f"(d[105]), "+f"(d[106]), "+f"(d[107]), "+f"(d[108]), "+f"(d[109]), "+f"(d[110]), "+f"(d[111])
    : "r"(a[0]), "r"(a[1]), "r"(a[2]), "r"(a[3]), "r"(lo), "r"(sd), "n"(OFF), "n"(HI));
}

template <int OFF, uint32_t HI>
__device__ __forceinline__ void wgmma_rs_n64_tb1(float (&d)[32], const uint32_t (&a)[4], uint32_t lo, int sd) {
  asm volatile("{\n.reg .pred p;\n.reg .b32 l;\n.reg .b64 db;\nsetp.ne.b32 p, %37, 0;\n"
    "add.u32 l, %36, %38;\nmov.b64 db, {l, %39};\n"
    "wgmma.mma_async.sync.aligned.m64n64k16.f32.bf16.bf16 "
    "{%0,%1,%2,%3,%4,%5,%6,%7,%8,%9,%10,%11,%12,%13,%14,%15,"
    "%16,%17,%18,%19,%20,%21,%22,%23,%24,%25,%26,%27,%28,%29,%30,%31}, "
    "{%32,%33,%34,%35}, db, p, 1, 1, 1;\n}\n"
    : "+f"(d[0]), "+f"(d[1]), "+f"(d[2]), "+f"(d[3]), "+f"(d[4]), "+f"(d[5]), "+f"(d[6]), "+f"(d[7]),
      "+f"(d[8]), "+f"(d[9]), "+f"(d[10]), "+f"(d[11]), "+f"(d[12]), "+f"(d[13]), "+f"(d[14]), "+f"(d[15]),
      "+f"(d[16]), "+f"(d[17]), "+f"(d[18]), "+f"(d[19]), "+f"(d[20]), "+f"(d[21]), "+f"(d[22]), "+f"(d[23]),
      "+f"(d[24]), "+f"(d[25]), "+f"(d[26]), "+f"(d[27]), "+f"(d[28]), "+f"(d[29]), "+f"(d[30]), "+f"(d[31])
    : "r"(a[0]), "r"(a[1]), "r"(a[2]), "r"(a[3]), "r"(lo), "r"(sd), "n"(OFF), "n"(HI));
}

template <int STR>
__device__ __forceinline__ void verify8_tag1(const uint4* p, uint32_t (*r)[4]) {
  asm volatile("{\n.reg .pred p, q;\n.reg .b32 a, n;\nmov.u32 n, 0;\n"
    "LAB_CHK:\n"
    "and.b32 a, %0, %4;\n"
    "and.b32 a, a, %8;\n"
    "and.b32 a, a, %12;\n"
    "and.b32 a, a, %16;\n"
    "and.b32 a, a, %20;\n"
    "and.b32 a, a, %24;\n"
    "and.b32 a, a, %28;\n"
    "and.b32 a, a, 1;\nsetp.eq.u32 p, a, 1;\nvote.sync.all.pred p, p, 0xffffffff;\n"
    "@p bra.uni LAB_OK;\n"
    "and.b32 a, %0, 1;\nsetp.ne.u32 q, a, 1;\n"
    "@q ld.relaxed.gpu.global.v4.b32 {%0,%1,%2,%3}, [%32+%33];\n"
    "and.b32 a, %4, 1;\nsetp.ne.u32 q, a, 1;\n"
    "@q ld.relaxed.gpu.global.v4.b32 {%4,%5,%6,%7}, [%32+%34];\n"
    "and.b32 a, %8, 1;\nsetp.ne.u32 q, a, 1;\n"
    "@q ld.relaxed.gpu.global.v4.b32 {%8,%9,%10,%11}, [%32+%35];\n"
    "and.b32 a, %12, 1;\nsetp.ne.u32 q, a, 1;\n"
    "@q ld.relaxed.gpu.global.v4.b32 {%12,%13,%14,%15}, [%32+%36];\n"
    "and.b32 a, %16, 1;\nsetp.ne.u32 q, a, 1;\n"
    "@q ld.relaxed.gpu.global.v4.b32 {%16,%17,%18,%19}, [%32+%37];\n"
    "and.b32 a, %20, 1;\nsetp.ne.u32 q, a, 1;\n"
    "@q ld.relaxed.gpu.global.v4.b32 {%20,%21,%22,%23}, [%32+%38];\n"
    "and.b32 a, %24, 1;\nsetp.ne.u32 q, a, 1;\n"
    "@q ld.relaxed.gpu.global.v4.b32 {%24,%25,%26,%27}, [%32+%39];\n"
    "and.b32 a, %28, 1;\nsetp.ne.u32 q, a, 1;\n"
    "@q ld.relaxed.gpu.global.v4.b32 {%28,%29,%30,%31}, [%32+%40];\n"
    "add.u32 n, n, 1;\nsetp.lt.u32 q, n, 262144;\n@q bra.uni LAB_CHK;\n"
    "LAB_OK:\n"
    "}\n"
    : "+r"(r[0][0]), "+r"(r[0][1]), "+r"(r[0][2]), "+r"(r[0][3]), "+r"(r[1][0]), "+r"(r[1][1]), "+r"(r[1][2]), "+r"(r[1][3]),
      "+r"(r[2][0]), "+r"(r[2][1]), "+r"(r[2][2]), "+r"(r[2][3]), "+r"(r[3][0]), "+r"(r[3][1]), "+r"(r[3][2]), "+r"(r[3][3]),
      "+r"(r[4][0]), "+r"(r[4][1]), "+r"(r[4][2]), "+r"(r[4][3]), "+r"(r[5][0]), "+r"(r[5][1]), "+r"(r[5][2]), "+r"(r[5][3]),
      "+r"(r[6][0]), "+r"(r[6][1]), "+r"(r[6][2]), "+r"(r[6][3]), "+r"(r[7][0]), "+r"(r[7][1]), "+r"(r[7][2]), "+r"(r[7][3])
    : "l"(p), "n"(0 * STR), "n"(1 * STR), "n"(2 * STR), "n"(3 * STR), "n"(4 * STR), "n"(5 * STR), "n"(6 * STR), "n"(7 * STR)
    : "memory");
}

template <int STR>
__device__ __forceinline__ void verify8_tag0(const uint4* p, uint32_t (*r)[4]) {
  asm volatile("{\n.reg .pred p, q;\n.reg .b32 a, n;\nmov.u32 n, 0;\n"
    "LAB_CHK:\n"
    "or.b32 a, %0, %4;\n"
    "or.b32 a, a, %8;\n"
    "or.b32 a, a, %12;\n"
    "or.b32 a, a, %16;\n"
    "or.b32 a, a, %20;\n"
    "or.b32 a, a, %24;\n"
    "or.b32 a, a, %28;\n"
    "and.b32 a, a, 1;\nsetp.eq.u32 p, a, 0;\nvote.sync.all.pred p, p, 0xffffffff;\n"
    "@p bra.uni LAB_OK;\n"
    "and.b32 a, %0, 1;\nsetp.ne.u32 q, a, 0;\n"
    "@q ld.relaxed.gpu.global.v4.b32 {%0,%1,%2,%3}, [%32+%33];\n"
    "and.b32 a, %4, 1;\nsetp.ne.u32 q, a, 0;\n"
    "@q ld.relaxed.gpu.global.v4.b32 {%4,%5,%6,%7}, [%32+%34];\n"
    "and.b32 a, %8, 1;\nsetp.ne.u32 q, a, 0;\n"
    "@q ld.relaxed.gpu.global.v4.b32 {%8,%9,%10,%11}, [%32+%35];\n"
    "and.b32 a, %12, 1;\nsetp.ne.u32 q, a, 0;\n"
    "@q ld.relaxed.gpu.global.v4.b32 {%12,%13,%14,%15}, [%32+%36];\n"
    "and.b32 a, %16, 1;\nsetp.ne.u32 q, a, 0;\n"
    "@q ld.relaxed.gpu.global.v4.b32 {%16,%17,%18,%19}, [%32+%37];\n"
    "and.b32 a, %20, 1;\nsetp.ne.u32 q, a, 0;\n"
    "@q ld.relaxed.gpu.global.v4.b32 {%20,%21,%22,%23}, [%32+%38];\n"
    "and.b32 a, %24, 1;\nsetp.ne.u32 q, a, 0;\n"
    "@q ld.relaxed.gpu.global.v4.b32 {%24,%25,%26,%27}, [%32+%39];\n"
    "and.b32 a, %28, 1;\nsetp.ne.u32 q, a, 0;\n"
    "@q ld.relaxed.gpu.global.v4.b32 {%28,%29,%30,%31}, [%32+%40];\n"
    "add.u32 n, n, 1;\nsetp.lt.u32 q, n, 262144;\n@q bra.uni LAB_CHK;\n"
    "LAB_OK:\n"
    "or.b32 %0, %0, 1;\n"
    "or.b32 %4, %4, 1;\n"
    "or.b32 %8, %8, 1;\n"
    "or.b32 %12, %12, 1;\n"
    "or.b32 %16, %16, 1;\n"
    "or.b32 %20, %20, 1;\n"
    "or.b32 %24, %24, 1;\n"
    "or.b32 %28, %28, 1;\n"
    "}\n"
    : "+r"(r[0][0]), "+r"(r[0][1]), "+r"(r[0][2]), "+r"(r[0][3]), "+r"(r[1][0]), "+r"(r[1][1]), "+r"(r[1][2]), "+r"(r[1][3]),
      "+r"(r[2][0]), "+r"(r[2][1]), "+r"(r[2][2]), "+r"(r[2][3]), "+r"(r[3][0]), "+r"(r[3][1]), "+r"(r[3][2]), "+r"(r[3][3]),
      "+r"(r[4][0]), "+r"(r[4][1]), "+r"(r[4][2]), "+r"(r[4][3]), "+r"(r[5][0]), "+r"(r[5][1]), "+r"(r[5][2]), "+r"(r[5][3]),
      "+r"(r[6][0]), "+r"(r[6][1]), "+r"(r[6][2]), "+r"(r[6][3]), "+r"(r[7][0]), "+r"(r[7][1]), "+r"(r[7][2]), "+r"(r[7][3])
    : "l"(p), "n"(0 * STR), "n"(1 * STR), "n"(2 * STR), "n"(3 * STR), "n"(4 * STR), "n"(5 * STR), "n"(6 * STR), "n"(7 * STR)
    : "memory");
}

template <int STR>
__device__ __forceinline__ void verify4_tag0(const uint4* p, uint32_t (*r)[4]) {
  asm volatile("{\n.reg .pred p, q;\n.reg .b32 a, n;\nmov.u32 n, 0;\n"
    "LAB_CHK:\n"
    "or.b32 a, %0, %4;\n"
    "or.b32 a, a, %8;\n"
    "or.b32 a, a, %12;\n"
    "and.b32 a, a, 1;\nsetp.eq.u32 p, a, 0;\nvote.sync.all.pred p, p, 0xffffffff;\n"
    "@p bra.uni LAB_OK;\n"
    "and.b32 a, %0, 1;\nsetp.ne.u32 q, a, 0;\n"
    "@q ld.relaxed.gpu.global.v4.b32 {%0,%1,%2,%3}, [%16+%17];\n"
    "and.b32 a, %4, 1;\nsetp.ne.u32 q, a, 0;\n"
    "@q ld.relaxed.gpu.global.v4.b32 {%4,%5,%6,%7}, [%16+%18];\n"
    "and.b32 a, %8, 1;\nsetp.ne.u32 q, a, 0;\n"
    "@q ld.relaxed.gpu.global.v4.b32 {%8,%9,%10,%11}, [%16+%19];\n"
    "and.b32 a, %12, 1;\nsetp.ne.u32 q, a, 0;\n"
    "@q ld.relaxed.gpu.global.v4.b32 {%12,%13,%14,%15}, [%16+%20];\n"
    "add.u32 n, n, 1;\nsetp.lt.u32 q, n, 262144;\n@q bra.uni LAB_CHK;\n"
    "LAB_OK:\n"
    "or.b32 %0, %0, 1;\n"
    "or.b32 %4, %4, 1;\n"
    "or.b32 %8, %8, 1;\n"
    "or.b32 %12, %12, 1;\n"
    "}\n"
    : "+r"(r[0][0]), "+r"(r[0][1]), "+r"(r[0][2]), "+r"(r[0][3]), "+r"(r[1][0]), "+r"(r[1][1]), "+r"(r[1][2]), "+r"(r[1][3]),
      "+r"(r[2][0]), "+r"(r[2][1]), "+r"(r[2][2]), "+r"(r[2][3]), "+r"(r[3][0]), "+r"(r[3][1]), "+r"(r[3][2]), "+r"(r[3][3])
    : "l"(p), "n"(0 * STR), "n"(1 * STR), "n"(2 * STR), "n"(3 * STR)
    : "memory");
}

#define SPIN_LIMIT (1 << 18)

__device__ __forceinline__ uint32_t smem_u32(const void* p) { return (uint32_t)__cvta_generic_to_shared(p); }
__device__ __forceinline__ void mbar_init(uint32_t a, uint32_t c) {
  asm volatile("mbarrier.init.shared::cta.b64 [%0], %1;" ::"r"(a), "r"(c) : "memory");
}
__device__ __forceinline__ void mbar_expect(uint32_t a, uint32_t b) {
  asm volatile("mbarrier.arrive.expect_tx.shared::cta.b64 _, [%0], %1;" ::"r"(a), "r"(b) : "memory");
}
__device__ __forceinline__ void mbar_arrive(uint32_t a) {
  asm volatile("mbarrier.arrive.shared::cta.b64 _, [%0];" ::"r"(a) : "memory");
}
__device__ __forceinline__ void mbar_wait(uint32_t a, uint32_t parity) {
  asm volatile(
      "{\n.reg .pred p;\n.reg .u32 n;\nmov.u32 n, 0;\n"
      "LAB_WAIT:\n"
      "mbarrier.try_wait.parity.shared::cta.b64 p, [%0], %1;\n"
      "@p bra LAB_DONE;\n"
      "add.u32 n, n, 1;\n"
      "setp.lt.u32 p, n, 262144;\n"
      "@p bra LAB_WAIT;\n"
      "LAB_DONE:\n}\n" ::"r"(a), "r"(parity) : "memory");
}
__device__ __forceinline__ bool mbar_test(uint32_t a, uint32_t parity) {
  uint32_t ok;
  asm volatile("{\n.reg .pred p;\nmbarrier.test_wait.parity.shared::cta.b64 p, [%1], %2;\nselp.u32 %0, 1, 0, p;\n}\n"
               : "=r"(ok) : "r"(a), "r"(parity) : "memory");
  return ok;
}
__device__ __forceinline__ void tma3d(uint32_t dst, const CUtensorMap* tm, uint32_t bar, int c0, int c1, int c2) {
  asm volatile(
      "cp.async.bulk.tensor.3d.shared::cluster.global.mbarrier::complete_tx::bytes [%0], [%1, {%3,%4,%5}], [%2];"
      ::"r"(dst), "l"(tm), "r"(bar), "r"(c0), "r"(c1), "r"(c2) : "memory");
}
__device__ __forceinline__ void wg_fence() { asm volatile("wgmma.fence.sync.aligned;" ::: "memory"); }
__device__ __forceinline__ void wg_commit() { asm volatile("wgmma.commit_group.sync.aligned;" ::: "memory"); }
template <int N> __device__ __forceinline__ void wg_wait() {
  asm volatile("wgmma.wait_group.sync.aligned %0;" ::"n"(N) : "memory");
}
template <int N> __device__ __forceinline__ void fence_regs(float (&d)[N]) {
#pragma unroll
  for (int i = 0; i < N; i++) asm volatile("" : "+f"(d[i])::"memory");
}
template <int N> __device__ __forceinline__ void fence_regs(uint32_t (&d)[N][4]) {
#pragma unroll
  for (int i = 0; i < N; i++) asm volatile("" : "+r"(d[i][0]), "+r"(d[i][1]), "+r"(d[i][2]), "+r"(d[i][3])::"memory");
}
template <int N> __device__ __forceinline__ void fence_frags(uint32_t (*d)[4]) {
#pragma unroll
  for (int i = 0; i < N; i++) asm volatile("" : "+r"(d[i][0]), "+r"(d[i][1]), "+r"(d[i][2]), "+r"(d[i][3])::"memory");
}
__device__ __forceinline__ void bar_sync(int id, int n) { asm volatile("bar.sync %0, %1;" ::"r"(id), "r"(n) : "memory"); }
__device__ __forceinline__ void bar_arrive(int id, int n) { asm volatile("bar.arrive %0, %1;" ::"r"(id), "r"(n) : "memory"); }

__device__ __forceinline__ uint32_t pack_bf16(float lo, float hi) {
  uint32_t r;
  asm("cvt.rn.bf16x2.f32 %0, %1, %2;" : "=r"(r) : "f"(hi), "f"(lo));
  return r;
}
__device__ __forceinline__ float bf_lo(uint32_t w) { return __uint_as_float(w << 16); }
__device__ __forceinline__ float bf_hi(uint32_t w) { return __uint_as_float(w & 0xFFFF0000u); }
__device__ __forceinline__ float round_bf16(float x) { return bf_lo(pack_bf16(x, 0.f)); }
__device__ __forceinline__ uint32_t hfma2_bf16(uint32_t a, uint32_t b, uint32_t c) {
  uint32_t r;
  asm("fma.rn.bf16x2 %0, %1, %2, %3;" : "=r"(r) : "r"(a), "r"(b), "r"(c));
  return r;
}
__device__ __forceinline__ float ex2(float x) {
  float r;
  asm("ex2.approx.ftz.f32 %0, %1;" : "=f"(r) : "f"(x));
  return r;
}
__device__ __forceinline__ float tanh_hw(float x) {
  float r;
  asm("tanh.approx.f32 %0, %1;" : "=f"(r) : "f"(x));
  return r;
}
template <int TAG> __device__ __forceinline__ uint32_t pack_tag(float lo, float hi) {
  uint32_t w = __byte_perm(__float_as_uint(lo), pack_bf16(lo, hi), 0x7632);
  return TAG ? (w | 1u) : (w & ~1u);
}
__device__ __forceinline__ void st_pkt(uint4* p, uint32_t a, uint32_t b, uint32_t c, uint32_t d) {
  asm volatile(
      "st.relaxed.gpu.global.v4.b32 [%0], {%1,%2,%3,%4};" ::"l"(p), "r"(a), "r"(b), "r"(c), "r"(d) : "memory");
}
__device__ __forceinline__ void ld_pkt(const uint4* p, uint32_t (&r)[4]) {
  asm volatile(
      "ld.relaxed.gpu.global.v4.b32 {%0,%1,%2,%3}, [%4];"
      : "=r"(r[0]), "=r"(r[1]), "=r"(r[2]), "=r"(r[3]) : "l"(p) : "memory");
}
__device__ __forceinline__ uint32_t ldg32(const void* p) {
  uint32_t r;
  asm volatile("ld.global.nc.b32 %0, [%1];" : "=r"(r) : "l"(p));
  return r;
}
__device__ __forceinline__ uint32_t ldg16(const void* p) {
  uint16_t r;
  asm volatile("ld.global.nc.b16 %0, [%1];" : "=h"(r) : "l"(p));
  return r;
}
__device__ __forceinline__ uint4 ldg128(const void* p) {
  uint4 r;
  asm volatile("ld.global.nc.v4.b32 {%0,%1,%2,%3}, [%4];" : "=r"(r.x), "=r"(r.y), "=r"(r.z), "=r"(r.w) : "l"(p));
  return r;
}
__device__ __forceinline__ void l2_prefetch(const void* p, uint32_t bytes) {
  asm volatile("cp.async.bulk.prefetch.L2.global [%0], %1;" ::"l"(p), "r"(bytes) : "memory");
}
__device__ __forceinline__ float rcp_hw(float x) {
  float r;
  asm("rcp.approx.ftz.f32 %0, %1;" : "=f"(r) : "f"(x));
  return r;
}
__device__ __forceinline__ void warp_bulk_load(uint32_t sdst, const void* gsrc, uint32_t bytes, uint32_t bar) {
  asm volatile(
      "{\n.reg .pred p;\nelect.sync _|p, 0xffffffff;\n"
      "@p mbarrier.arrive.expect_tx.shared::cta.b64 _, [%3], %2;\n"
      "@p cp.async.bulk.shared::cluster.global.mbarrier::complete_tx::bytes [%0], [%1], %2, [%3];\n}\n"
      ::"r"(sdst), "l"(gsrc), "r"(bytes), "r"(bar) : "memory");
}
__device__ __forceinline__ void warp_tma3d(uint32_t dst, const CUtensorMap* tm, uint32_t bar, uint32_t bytes, int c1, int c2) {
  asm volatile(
      "{\n.reg .pred p;\nelect.sync _|p, 0xffffffff;\n"
      "@p mbarrier.arrive.expect_tx.shared::cta.b64 _, [%2], %3;\n"
      "@p cp.async.bulk.tensor.3d.shared::cluster.global.mbarrier::complete_tx::bytes [%0], [%1, {%6,%4,%5}], [%2];\n}\n"
      ::"r"(dst), "l"(tm), "r"(bar), "r"(bytes), "r"(c1), "r"(c2), "r"(0) : "memory");
}
__device__ __forceinline__ void warp_arrive(uint32_t bar) {
  asm volatile("{\n.reg .pred p;\nelect.sync _|p, 0xffffffff;\n@p mbarrier.arrive.shared::cta.b64 _, [%0];\n}\n" ::"r"(bar) : "memory");
}
__device__ __forceinline__ uint32_t pack_trunc(float lo, float hi) {
  return __byte_perm(__float_as_uint(lo), __float_as_uint(hi), 0x7632);
}
__device__ __forceinline__ void add_partial(float (&y)[8], const uint32_t (&r)[4], uint32_t c0, bool first) {
#pragma unroll
  for (int e = 0; e < 4; e++) {
    const float lo = __uint_as_float(r[e] * 65536u + (e ? 0x8000u : c0)), hi = __uint_as_float(r[e]);
    y[2 * e] = first ? lo : y[2 * e] + lo;
    y[2 * e + 1] = first ? hi : y[2 * e + 1] + hi;
  }
}
__device__ __forceinline__ void spin_cycles(uint32_t n) {
  uint32_t t0, t;
  asm volatile("mov.u32 %0, %%clock;" : "=r"(t0));
  do { asm volatile("mov.u32 %0, %%clock;" : "=r"(t)); } while (t - t0 < n);
}
__device__ __forceinline__ void sts128(uint32_t a, uint32_t x, uint32_t y, uint32_t z, uint32_t w) {
  asm volatile("st.shared.v4.b32 [%0], {%1,%2,%3,%4};" ::"r"(a), "r"(x), "r"(y), "r"(z), "r"(w) : "memory");
}
__device__ __forceinline__ void lds128(uint32_t a, uint32_t (&r)[4]) {
  asm volatile("ld.shared.v4.b32 {%0,%1,%2,%3}, [%4];" : "=r"(r[0]), "=r"(r[1]), "=r"(r[2]), "=r"(r[3]) : "r"(a) : "memory");
}

__device__ __forceinline__ uint32_t lds32(uint32_t a) {
  uint32_t r;
  asm volatile("ld.shared.b32 %0, [%1];" : "=r"(r) : "r"(a) : "memory");
  return r;
}
__device__ __forceinline__ void store_out(__nv_bfloat16* out, uint32_t woff, uint32_t x2s, uint32_t gb0, uint32_t gb1,
                                          const float (&y)[8]) {
  const uint32_t gb[2] = {gb0, gb1};
  uint32_t xa[2][4];
  lds128(x2s, xa[0]);
  lds128(x2s + 512, xa[1]);
  uint32_t* const oo = (uint32_t*)out + woff;
#pragma unroll
  for (int e = 0; e < 4; e++)
    oo[(e >> 1) * 4 + (e & 1) * 8 * 256] =
        pack_bf16(fmaf(bf_lo(gb[e >> 1]), y[2 * e], __uint_as_float(xa[e >> 1][(e & 1) * 2])),
                  fmaf(bf_hi(gb[e >> 1]), y[2 * e + 1], __uint_as_float(xa[e >> 1][(e & 1) * 2 + 1])));
}

constexpr int SK = 2048, WIN = 512;
constexpr int FF = 1792, FSL = 224;
constexpr int NTILES = 80;
constexpr int NSLOT = 4;
constexpr uint32_t SLOT = 32768;
constexpr uint32_t SM_PARK = 0;
constexpr uint32_t SM_RING = 3 * SLOT;
constexpr uint32_t SM_TAB = 7 * SLOT;
constexpr uint32_t SM_RED = SM_TAB + 2048;
constexpr uint32_t SM_BAR = SM_RED + 256;
constexpr uint32_t SM_WBAR = SM_BAR + 128;
constexpr uint32_t SM_SBAR = SM_WBAR + 240;
constexpr uint32_t SM_TOTAL = SM_SBAR + 112;

struct Scratch {
  uint4 P[16 * 8 * 8 * 1024];
  uint4 G[16 * 8 * 32 * 32];
  uint4 mod1[8 * 256];
  uint4 mod2[512];
  uint4 uv[2 * 448];
  uint4 stat[16 * 8 * 8];
  uint32_t epoch;
};
__device__ Scratch g_scratch;

#define TS(i) do { } while (0)
#define TR(code)
#define CK_(v)
#define CKS(i, v)

struct Params {
  const __nv_bfloat16* x;
  const __nv_bfloat16* c;
  const __nv_bfloat16* wmod;
  const __nv_bfloat16* wo;
  const __nv_bfloat16* w1;
  const __nv_bfloat16* w2;
  __nv_bfloat16* out;
  Scratch* s;
};

constexpr uint32_t HI128 = (1024 >> 4) | (1u << 30);
constexpr uint32_t HI64 = (512 >> 4) | (2u << 30);
constexpr int LB_MN128 = (16384 >> 4) << 16;
constexpr int LB_K128 = 1 << 16;
constexpr int LB_W1 = (4096 >> 4) << 16;

template <int I> struct IC {
  __host__ __device__ constexpr operator int() const { return I; }
};
template <int I, int N, typename F> __device__ __forceinline__ void static_for(F&& f) {
  if constexpr (I < N) {
    f(IC<I>{});
    static_for<I + 1, N>(f);
  }
}

struct Ring {
  uint32_t base16, bars;
  __device__ __forceinline__ uint32_t wait_full(uint32_t slot, uint32_t parity) const {
    mbar_wait(bars + slot * 8, parity);
    return base16 + slot * (SLOT >> 4);
  }
  __device__ __forceinline__ void release(uint32_t slot) const {
    warp_arrive(bars + 32 + slot * 8);
  }
};

__device__ __forceinline__ float silu_c(uint32_t bits) {
  float x = bf_lo(bits);
  return round_bf16(x * rcp_hw(1.f + ex2(-1.4426950408889634f * x)));
}
__device__ __forceinline__ void pack8(uint32_t (&o)[4], const float* v) {
  o[0] = pack_bf16(v[0], v[1]); o[1] = pack_bf16(v[2], v[3]); o[2] = pack_bf16(v[4], v[5]); o[3] = pack_bf16(v[6], v[7]);
}

template <int TAG, int N>
__device__ __forceinline__ void issue_pkts(const uint4* p, int stride, uint32_t (*r)[4]) {
#pragma unroll
  for (int i = 0; i < N; i++) ld_pkt(p + i * stride, r[i]);
}
__device__ __forceinline__ void ld_mod(const uint4* p, uint32_t tag, uint32_t (&r)[4]) {
  int spins = 0;
  ld_pkt(p, r);
  while (r[2] != tag && ++spins < SPIN_LIMIT) ld_pkt(p, r);
}

#define EARLY_TILES 2
#define PF_WMOD 1
#define MOD1_DELAY 500
#define RED3_UNIT 3
#define JLO 2
#define NITEM2 24
#define FIN_DELAY0 800
#define FIN_DELAY1 0
#define G_DELAY 0

__global__ void __launch_bounds__(384, 1)
adaln_block_kernel(const __grid_constant__ CUtensorMap tmWq, const __grid_constant__ CUtensorMap tmK,
                   const __grid_constant__ CUtensorMap tmV, const __grid_constant__ CUtensorMap tmWo,
                   const __grid_constant__ CUtensorMap tmW1, const __grid_constant__ CUtensorMap tmW2,
                   const __grid_constant__ CUtensorMap tmWm, const __grid_constant__ CUtensorMap tmP,
                   const Params p) {
  extern __shared__ __align__(1024) uint8_t smem_raw[];
  const uint32_t sb = smem_u32(smem_raw);
  const int tid = threadIdx.x, lane = tid & 31;
  const int warp = __shfl_sync(0xffffffffu, tid >> 5, 0);
  const int bid = blockIdx.x;
  const int j = ((bid >> (4 + JLO)) << JLO) | (bid & ((1 << JLO) - 1)), rt = (bid >> JLO) & 15;
  const uint32_t bars = sb + SM_BAR;

  if (warp >= 8) {
    CK_(c0);
    asm volatile("setmaxnreg.dec.sync.aligned.u32 56;");
    CK_(c1);
    const int t = tid - 256;
    uint32_t tag;
    {
      uint32_t cb[4];
      if (t == 0) {
        mbar_init(bars + 80, 1);
        asm volatile("fence.mbarrier_init.release.cluster;" ::: "memory");
        mbar_expect(bars + 80, 8192);
        tma3d(sb + SM_RING + 3 * SLOT, &tmWm, bars + 80, 0, 0, bid);
        tma3d(sb + SM_RING + 3 * SLOT + 4096, &tmWm, bars + 80, 0, 256, bid);
        asm volatile("prefetch.tensormap [%0];" ::"l"(&tmWq) : "memory");
        for (int i = 0; i < NSLOT; i++) { mbar_init(bars + i * 8, 1); mbar_init(bars + 32 + i * 8, 8); }
        mbar_init(bars + 72, 2);
        mbar_init(bars + 88, 1);
        mbar_init(bars + 96, 8);
        for (int i = 0; i < 30; i++) mbar_init(sb + SM_WBAR + i * 8, 1);
        for (int i = 0; i < 14; i++) mbar_init(sb + SM_SBAR + i * 8, 8);
        asm volatile("fence.mbarrier_init.release.cluster;" ::: "memory");
      }
      __syncwarp();
      CK_(c2);
#pragma unroll
      for (int i = 0; i < 4; i++) cb[i] = ldg16(p.c + t + 128 * i);
      asm volatile("ld.relaxed.gpu.global.u32 %0, [%1];" : "=r"(tag) : "l"(&p.s->epoch) : "memory");
      bar_sync(5, 128);
      tag += 1;
      float a[8], sc[4];
#pragma unroll
      for (int i = 0; i < 4; i++) sc[i] = silu_c(cb[i]);
#pragma unroll
      for (int k = 0; k < 8; k++) a[k] = 0.f;
      mbar_wait(bars + 80, 0);
      CK_(c3);
#pragma unroll
      for (int i = 0; i < 4; i++) {
        uint32_t w[4];
        lds128(sb + SM_RING + 3 * SLOT + (t + 128 * i) * 16, w);
#pragma unroll
        for (int e = 0; e < 4; e++) {
          a[2 * e] = fmaf(sc[i], bf_lo(w[e]), a[2 * e]);
          a[2 * e + 1] = fmaf(sc[i], bf_hi(w[e]), a[2 * e + 1]);
        }
      }
      const bool h16 = lane & 16, h8 = lane & 8, h4 = lane & 4;
#pragma unroll
      for (int k = 0; k < 4; k++) {
        float send = h16 ? a[k] : a[k + 4], keep = h16 ? a[k + 4] : a[k];
        a[k] = keep + __shfl_xor_sync(0xffffffffu, send, 16);
      }
#pragma unroll
      for (int k = 0; k < 2; k++) {
        float send = h8 ? a[k] : a[k + 2], keep = h8 ? a[k + 2] : a[k];
        a[k] = keep + __shfl_xor_sync(0xffffffffu, send, 8);
      }
      {
        float send = h4 ? a[0] : a[1], keep = h4 ? a[1] : a[0];
        a[0] = keep + __shfl_xor_sync(0xffffffffu, send, 4);
      }
      a[0] += __shfl_xor_sync(0xffffffffu, a[0], 2);
      a[0] += __shfl_xor_sync(0xffffffffu, a[0], 1);
      float* red = (float*)(smem_raw + SM_RED);
      if ((lane & 3) == 0) red[(warp - 8) * 8 + (lane >> 2)] = a[0];
      if (t == 0) *(uint32_t*)(smem_raw + SM_BAR + 64) = tag;
      CK_(c4);
      bar_sync(5, 128);
      bar_arrive(7, 384);
      CK_(c5);
      if (warp == 8) {
#pragma unroll
        for (int i = 0; i < EARLY_TILES; i++) warp_tma3d(sb + SM_RING + i * SLOT, &tmWq, bars + i * 8, SLOT, i * 128, (j * 4 + 1) * 2);
      }
      if (warp == 9) {
        const int cl = lane & 7;
        float v = round_bf16(red[cl] + red[8 + cl] + red[16 + cl] + red[24 + cl]);
        if (bid >= 64) v = 1.f + v;
        float vn = __shfl_down_sync(0xffffffffu, v, 1);
        uint32_t wd = pack_bf16(v, vn);
        uint32_t w0 = __shfl_sync(0xffffffffu, wd, (lane & 1) * 4);
        uint32_t w1 = __shfl_sync(0xffffffffu, wd, (lane & 1) * 4 + 2);
        if (lane < 16) st_pkt(&p.s->mod1[(lane >> 1) * 256 + bid * 2 + (lane & 1)], w0, w1, tag, 0);
      }
      uint32_t r0[4], r1[4];
      const uint4* src = &p.s->mod1[j * 256 + t];
      CK_(c6);
      spin_cycles(MOD1_DELAY);
      CK_(c7);
      int spins = 0;
      do {
        ld_pkt(src, r0);
        ld_pkt(src + 128, r1);
      } while ((r0[2] != tag || r1[2] != tag) && ++spins < SPIN_LIMIT);
      const int g = t >> 2, pp = (t & 3) * 2;
      const uint32_t ad = sb + SM_TAB + (uint32_t)(g * 4 + (pp & 3)) * 16 + (pp >> 2) * 4;
      asm volatile("st.shared.b32 [%0], %1;" ::"r"(ad + 8), "r"(r0[0]) : "memory");
      asm volatile("st.shared.b32 [%0], %1;" ::"r"(ad + 24), "r"(r0[1]) : "memory");
      asm volatile("st.shared.b32 [%0], %1;" ::"r"(ad), "r"(r1[0]) : "memory");
      asm volatile("st.shared.b32 [%0], %1;" ::"r"(ad + 16), "r"(r1[1]) : "memory");
      bar_arrive(1, 384);
      CK_(c8);
      CKS(0, c0); CKS(1, c1); CKS(2, c2); CKS(3, c3); CKS(4, c4); CKS(5, c5); CKS(6, c6); CKS(7, c7); CKS(8, c8);
    }
    if (warp == 8) {
      {
        uint32_t s = EARLY_TILES & 3, ph = 1 ^ (EARLY_TILES >> 2);
#pragma unroll 1
        for (int tt = EARLY_TILES; tt < NTILES; tt++) {
          const CUtensorMap* tm;
          int c1, c2;
          uint32_t bytes = SLOT;
          if (tt < 16) {
            tm = &tmWq; c1 = (tt & 3) * 128; c2 = (j * 4 + (((tt >> 2) + 1) & 3)) * 2;
          } else if (tt < 48) {
            const int u = tt - 16;
            const bool isK = (u == 0) || ((u & 1) && u != 31);
            const int n = isK ? ((u + 1) >> 1) : (u == 31 ? 15 : (u >> 1) - 1);
            tm = isK ? &tmK : &tmV; c1 = j * SK + (SK - WIN) + (n & 3) * 128; c2 = 0;
          } else if (tt < 64) {
            const int u = tt - 48;
            tm = &tmWo; c1 = j * 512 + (u & 1) * 256; c2 = u >> 1;
          } else if (tt < 72) {
            tm = &tmW1; c1 = (tt - 64) * 64; c2 = j * 7; bytes = 28672;
          } else {
            tm = &tmW2; c1 = j * FSL; c2 = tt - 72; bytes = 28672;
          }
          mbar_wait(bars + 32 + s * 8, ph);
          warp_tma3d(sb + SM_RING + s * SLOT, tm, bars + s * 8, bytes, c1, c2);
          if (++s == 4) { s = 0; ph ^= 1; }
        }
      }
    } else if (warp >= 10) {
      const int t2 = tid - 320, hf = t2 & 1, r0 = t2 >> 1;
      bar_sync(6, 352);
      float a[8];
#pragma unroll
      for (int k = 0; k < 8; k++) a[k] = 0.f;
#pragma unroll 1
      for (int b = 0; b < 8; b++) {
        uint4 w[2];
        uint32_t cb[2];
#pragma unroll
        for (int i = 0; i < 2; i++) {
          w[i] = ldg128(p.wmod + (size_t)(r0 + 32 * (2 * b + i)) * 3072 + 1024 + bid * 16 + hf * 8);
          cb[i] = ldg16(p.c + r0 + 32 * (2 * b + i));
        }
#pragma unroll
        for (int i = 0; i < 2; i++) {
          const float s = silu_c(cb[i]);
          a[0] = fmaf(s, bf_lo(w[i].x), a[0]); a[1] = fmaf(s, bf_hi(w[i].x), a[1]);
          a[2] = fmaf(s, bf_lo(w[i].y), a[2]); a[3] = fmaf(s, bf_hi(w[i].y), a[3]);
          a[4] = fmaf(s, bf_lo(w[i].z), a[4]); a[5] = fmaf(s, bf_hi(w[i].z), a[5]);
          a[6] = fmaf(s, bf_lo(w[i].w), a[6]); a[7] = fmaf(s, bf_hi(w[i].w), a[7]);
        }
      }
      const bool h16 = lane & 16, h8 = lane & 8, h4 = lane & 4;
#pragma unroll
      for (int k = 0; k < 4; k++) {
        float send = h16 ? a[k] : a[k + 4], keep = h16 ? a[k + 4] : a[k];
        a[k] = keep + __shfl_xor_sync(0xffffffffu, send, 16);
      }
#pragma unroll
      for (int k = 0; k < 2; k++) {
        float send = h8 ? a[k] : a[k + 2], keep = h8 ? a[k + 2] : a[k];
        a[k] = keep + __shfl_xor_sync(0xffffffffu, send, 8);
      }
      {
        float send = h4 ? a[0] : a[1], keep = h4 ? a[1] : a[0];
        a[0] = keep + __shfl_xor_sync(0xffffffffu, send, 4);
      }
      a[0] += __shfl_xor_sync(0xffffffffu, a[0], 2);
      float* red = (float*)(smem_raw + SM_RED) + 32;
      if ((lane & 2) == 0) red[(warp - 10) * 16 + hf * 8 + (lane >> 2)] = a[0];
      bar_sync(4, 64);
      if (warp == 10) {
        const int cl = lane & 15;
        float v = round_bf16(red[cl] + red[16 + cl]);
        if ((bid >> 5) == 2) v = 1.f + v;
        float vn = __shfl_down_sync(0xffffffffu, v, 1);
        uint32_t wd = pack_bf16(v, vn);
        uint32_t w0 = __shfl_sync(0xffffffffu, wd, (lane & 3) * 2);
        uint32_t w1 = __shfl_sync(0xffffffffu, wd, (lane & 3) * 2 + 8);
        const int vec = (0x2130 >> ((bid >> 5) * 4)) & 3;
        if (lane < 4) st_pkt(&p.s->mod2[((bid & 31) * 4 + vec) * 4 + lane], w0, w1, tag, 0);
      }
      const int isv = warp - 10;
      if (bid < 112) {
        const int kk = lane >> 1;
        const uint4* mp = &p.s->mod2[(isv ? 3 : 1) * 4 + ((kk & 7) >> 1)];
#pragma unroll
        for (int k = 0; k < 8; k++) a[k] = 0.f;
#pragma unroll 1
        for (int g = 0; g < 32; g++) {
          const uint4 w = ldg128(p.w1 + (size_t)(g * 16 + kk) * FF + bid * 16 + (lane & 1) * 8);
          uint32_t m[4];
          ld_mod(mp + g * 16, tag, m);
          const uint32_t mw = (kk & 8) ? m[1] : m[0];
          const float s = (kk & 1) ? bf_hi(mw) : bf_lo(mw);
          a[0] = fmaf(s, bf_lo(w.x), a[0]); a[1] = fmaf(s, bf_hi(w.x), a[1]);
          a[2] = fmaf(s, bf_lo(w.y), a[2]); a[3] = fmaf(s, bf_hi(w.y), a[3]);
          a[4] = fmaf(s, bf_lo(w.z), a[4]); a[5] = fmaf(s, bf_hi(w.z), a[5]);
          a[6] = fmaf(s, bf_lo(w.w), a[6]); a[7] = fmaf(s, bf_hi(w.w), a[7]);
        }
#pragma unroll
        for (int k = 0; k < 4; k++) {
          float send = h16 ? a[k] : a[k + 4], keep = h16 ? a[k + 4] : a[k];
          a[k] = keep + __shfl_xor_sync(0xffffffffu, send, 16);
        }
#pragma unroll
        for (int o = 8; o > 1; o >>= 1) {
#pragma unroll
          for (int k = 0; k < 4; k++) a[k] += __shfl_xor_sync(0xffffffffu, a[k], o);
        }
        const float sc = isv ? 0.5f : 1.f;
        if ((lane & 14) == 0)
          st_pkt(&p.s->uv[isv * 448 + bid * 4 + (lane & 1) * 2 + (lane >> 4)],
                 (__float_as_uint(a[0] * sc) & ~1u) | (tag & 1u), __float_as_uint(a[1] * sc), __float_as_uint(a[2] * sc),
                 __float_as_uint(a[3] * sc));
      }
#pragma unroll 1
      for (int i = lane; i < 56; i += 32) {
        uint32_t m[4];
        int spins = 0;
        do { ld_pkt(&p.s->uv[isv * 448 + j * 56 + i], m); } while (((m[0] ^ tag) & 1u) && ++spins < SPIN_LIMIT);
        const uint32_t ad = sb + SM_TAB + i * 32 + isv * 8;
        asm volatile("st.shared.v2.b32 [%0], {%1,%2};" ::"r"(ad), "r"(m[0]), "r"(m[1]) : "memory");
        asm volatile("st.shared.v2.b32 [%0], {%1,%2};" ::"r"(ad + 16), "r"(m[2]), "r"(m[3]) : "memory");
      }
      __syncwarp();
      if (lane == 0) mbar_arrive(bars + 72);

    } else {
      bar_sync(6, 352);
      if (lane < 8) l2_prefetch((const char*)p.wo + (size_t)bid * 32768 + lane * 4096, 4096);
      else if (lane < 12) l2_prefetch((const char*)p.w1 + (size_t)bid * 14336 + (lane - 8) * 3584, 3584);
      else if (lane < 16) l2_prefetch((const char*)p.w2 + (size_t)bid * 14336 + (lane - 12) * 3584, 3584);
    }
    if (warp > 8) {
      const int q = lane & 3, hw = warp - 9;
      const uint32_t mtab = sb + SM_PARK + 6 * 4096;
      mbar_wait(bars + 96, 0);
#pragma unroll 1
      for (int i = tid - 288; i < 1024; i += 96) {
        const uint4 v = ldg128(p.x + (size_t)(rt * 128 + j * 16 + (i >> 6)) * 512 + (i & 63) * 8);
        sts128(sb + SM_PARK + SLOT + ((i & 63) >> 1) * 1024 + (i >> 6) * 32 + (i & 1) * 16, v.x, v.y, v.z, v.w);
      }
#pragma unroll 1
      for (int i = lane; i < 128; i += 32) {
        uint32_t m[4];
        ld_mod(&p.s->mod2[(i >> 2) * 16 + hw * 4 + q], tag, m);
        asm volatile("st.shared.v2.b32 [%0], {%1,%2};" ::"r"(hw < 2 ? mtab + i * 16 + hw * 8 : mtab + 2048 + i * 8), "r"(m[0]),
                     "r"(m[1]) : "memory");
      }
      bar_sync(8, 96);
      float s0 = 0.f, s1 = 0.f, v0 = 0.f, v1 = 0.f;
      uint32_t ph = 0, buf = 0;
      const uint32_t land = sb + SM_PARK + hw * 8192, lbar = sb + SM_WBAR + 192 + hw * 16;
      auto item_issue = [&](int n, uint32_t bf) { warp_tma3d(land + bf * 4096, &tmP, lbar + bf * 8, 4096, n & 31, (rt * 8 + j) * 8); };
      mbar_wait(sb + SM_SBAR, 0);
      item_issue(hw, 0);
#pragma unroll 1
      for (int n = hw; n < 32 + NITEM2; n += 3) {
        const int nn = n + 3, g = n & 31;
        const bool ex1 = n < 32, more = nn < 32 + NITEM2;
        const bool pre = more && __all_sync(0xffffffffu, mbar_test(sb + SM_SBAR + (nn >> 2) * 8, 0));
        if (pre) item_issue(nn, buf ^ 1);
        const uint32_t xs = sb + SM_PARK + SLOT + g * 1024;
        float y[8];
#pragma unroll 1
        for (int spins = 0; spins < SPIN_LIMIT; spins++) {
          mbar_wait(lbar + buf * 8, (ph >> buf) & 1);
          ph ^= 1u << buf;
          uint32_t all1 = 1, any1 = 0;
#pragma unroll
          for (int i = 0; i < 8; i++) {
            uint32_t r[4];
            lds128(land + buf * 4096 + i * 512 + lane * 16, r);
            all1 &= r[0]; any1 |= r[0];
            add_partial(y, r, ex1 ? 0u : 0x10000u, i == 0);
          }
          fence_regs(y);
          if (__all_sync(0xffffffffu, ((ex1 ? all1 : ~any1) & 1u) != 0)) break;
          item_issue(n, buf);
        }
        if (ex1) {
          uint32_t xr[4], m1[4];
          lds128(mtab + (g * 4 + q) * 16, m1);
          asm volatile("ldmatrix.sync.aligned.m8n8.x4.shared.b16 {%0,%1,%2,%3}, [%4];"
                       : "=r"(xr[0]), "=r"(xr[1]), "=r"(xr[2]), "=r"(xr[3]) : "r"(xs + (lane & 15) * 32 + (lane >> 4) * 16) : "memory");
#pragma unroll
          for (int e = 0; e < 4; e++) {
            const float a = fmaf(bf_lo(m1[e >> 1]), y[2 * e], bf_lo(xr[e])), b = fmaf(bf_hi(m1[e >> 1]), y[2 * e + 1], bf_hi(xr[e]));
            y[2 * e] = a; y[2 * e + 1] = b;
            if (e & 1) { s1 += a + b; v1 = fmaf(a, a, fmaf(b, b, v1)); }
            else { s0 += a + b; v0 = fmaf(a, a, fmaf(b, b, v0)); }
          }
          st_pkt(p.s->G + ((rt * 8 + j) * 32 + g) * 32 + lane, pack_tag<0>(y[0] * bf_lo(m1[2]), y[1] * bf_hi(m1[2])),
                 pack_bf16(y[2] * bf_lo(m1[2]), y[3] * bf_hi(m1[2])), pack_bf16(y[4] * bf_lo(m1[3]), y[5] * bf_hi(m1[3])),
                 pack_bf16(y[6] * bf_lo(m1[3]), y[7] * bf_hi(m1[3])));
          sts128(xs + lane * 16, __float_as_uint(y[0]), __float_as_uint(y[1]), __float_as_uint(y[2]), __float_as_uint(y[3]));
          sts128(xs + 512 + lane * 16, __float_as_uint(y[4]), __float_as_uint(y[5]), __float_as_uint(y[6]), __float_as_uint(y[7]));
          if (nn >= 32) {
#pragma unroll
            for (int o = 1; o < 4; o <<= 1) {
              s0 += __shfl_xor_sync(0xffffffffu, s0, o);
              s1 += __shfl_xor_sync(0xffffffffu, s1, o);
              v0 += __shfl_xor_sync(0xffffffffu, v0, o);
              v1 += __shfl_xor_sync(0xffffffffu, v1, o);
            }
            if (hw && q == 0)
              sts128(sb + SM_RED + (hw - 1) * 128 + (lane >> 2) * 16, __float_as_uint(s0), __float_as_uint(v0),
                     __float_as_uint(s1), __float_as_uint(v1));
            bar_sync(8, 96);
            if (hw == 0) {
              uint32_t m2[4];
              lds128(sb + SM_RED + (lane >> 2) * 16, m1);
              lds128(sb + SM_RED + 128 + (lane >> 2) * 16, m2);
              const float a0 = (s0 + __uint_as_float(m1[0]) + __uint_as_float(m2[0])) * (1.f / 512.f);
              const float a1 = (s1 + __uint_as_float(m1[2]) + __uint_as_float(m2[2])) * (1.f / 512.f);
              const float b0 = (v0 + __uint_as_float(m1[1]) + __uint_as_float(m2[1])) * (1.f / 512.f);
              const float b1 = (v1 + __uint_as_float(m1[3]) + __uint_as_float(m2[3])) * (1.f / 512.f);
              const float r0 = 0.5f * rsqrtf(fmaxf(fmaf(-a0, a0, b0), 0.f) + 1e-5f);
              const float r1 = 0.5f * rsqrtf(fmaxf(fmaf(-a1, a1, b1), 0.f) + 1e-5f);
              if (q == 0)
                st_pkt(&p.s->stat[(rt * 8 + j) * 8 + (lane >> 2)], (__float_as_uint(r0) & ~1u) | (tag & 1u),
                       __float_as_uint(-a0 * r0), __float_as_uint(r1), __float_as_uint(-a1 * r1));
              warp_arrive(bars + 88);
            }
          }
        } else {
          store_out(p.out, (uint32_t)(rt * 128 + 16 * j + (lane >> 2)) * 256 + g * 8 + q, xs + lane * 16,
                    lds32(mtab + 2048 + (g * 4 + q) * 8), lds32(mtab + 2052 + (g * 4 + q) * 8), y);
        }
        if (more && !pre) {
          mbar_wait(sb + SM_SBAR + (nn >> 2) * 8, 0);
          item_issue(nn, buf ^ 1);
        }
        buf ^= 1;
      }
    }
  } else {
    const int wg = warp >> 2;
    const int q = lane & 3, gq = lane >> 2;
    const Ring ring{(sb + SM_RING) >> 4, bars};
    const uint32_t xoff = (uint32_t)(rt * 128 + 16 * j + warp) * 256 + gq * 8 + q;
    const uint32_t ooff = ((uint32_t)(rt * 8 + j) * 32 + gq) * 32 + warp * 4 + q;
    const uint32_t wblk = sb + SM_PARK + warp * 4096, wprv = wblk + lane * 16;
    const uint32_t wbar = sb + SM_WBAR + warp * 24;
    const uint4* const Gw = p.s->G + (rt * 8 + warp) * 1024;

    {
      const uint32_t* xo = (const uint32_t*)p.x + xoff;
      uint32_t xr[4][4];
      CK_(d0);
#pragma unroll
      for (int c = 0; c < 4; c++) {
        xr[c][0] = ldg32(xo + c * 64);
        xr[c][1] = ldg32(xo + c * 64 + 8 * 256);
        xr[c][2] = ldg32(xo + c * 64 + 4);
        xr[c][3] = ldg32(xo + c * 64 + 4 + 8 * 256);
      }
      CK_(d1);
      fence_regs(xr);
      CK_(d2);
      float s0 = 0.f, s1 = 0.f, v0 = 0.f, v1 = 0.f;
#pragma unroll
      for (int c = 0; c < 4; c++) {
#pragma unroll
        for (int e = 0; e < 4; e++) {
          const float a = bf_lo(xr[c][e]), b = bf_hi(xr[c][e]);
          if (e & 1) { s1 += a + b; v1 = fmaf(a, a, fmaf(b, b, v1)); }
          else { s0 += a + b; v0 = fmaf(a, a, fmaf(b, b, v0)); }
        }
      }
#pragma unroll
      for (int o = 16; o > 0; o >>= 1) {
        s0 += __shfl_xor_sync(0xffffffffu, s0, o);
        s1 += __shfl_xor_sync(0xffffffffu, s1, o);
        v0 += __shfl_xor_sync(0xffffffffu, v0, o);
        v1 += __shfl_xor_sync(0xffffffffu, v1, o);
      }
      const float m0 = s0 * (1.f / 512.f), m1 = s1 * (1.f / 512.f);
      const float r0 = rsqrtf(fmaxf(fmaf(-m0, m0, v0 * (1.f / 512.f)), 0.f) + 1e-5f);
      const float r1 = rsqrtf(fmaxf(fmaf(-m1, m1, v1 * (1.f / 512.f)), 0.f) + 1e-5f);
#pragma unroll
      for (int c = 0; c < 4; c++) {
        st_pkt(p.s->G + ooff + c * 256,
               pack_tag<1>((bf_lo(xr[c][0]) - m0) * r0, (bf_hi(xr[c][0]) - m0) * r0),
               pack_bf16((bf_lo(xr[c][1]) - m1) * r1, (bf_hi(xr[c][1]) - m1) * r1),
               pack_bf16((bf_lo(xr[c][2]) - m0) * r0, (bf_hi(xr[c][2]) - m0) * r0),
               pack_bf16((bf_lo(xr[c][3]) - m1) * r1, (bf_hi(xr[c][3]) - m1) * r1));
      }
      CK_(d3);
      CKS(16, d0); CKS(17, d1); CKS(18, d2); CKS(19, d3);

    }
    asm volatile("setmaxnreg.inc.sync.aligned.u32 224;");
    uint32_t qf[8][4];
    {
      uint32_t h[32][4];
      float acc[64];
      const uint4* Gin = Gw + lane;
      bar_sync(7, 384);
      if (G_DELAY) spin_cycles(G_DELAY);
#pragma unroll
      for (int c = 0; c < 3; c++) warp_bulk_load(wblk + c * SLOT, Gw + c * 256, 4096, wbar + c * 8);
#pragma unroll
      for (int c = 0; c < 4; c++) {
        mbar_wait(wbar + (c % 3) * 8, c / 3);
#pragma unroll
        for (int i = 0; i < 8; i++) lds128(wprv + (c % 3) * SLOT + i * 512, h[c * 8 + i]);
        verify8_tag1<512>(Gin + c * 256, h + c * 8);
        if (c == 0) {
          warp_bulk_load(wblk, Gw + 768, 4096, wbar);
          TS(1);
          bar_sync(1, 384);
        }
#pragma unroll
        for (int i = 0; i < 8; i++) {
          uint32_t m[4];
          lds128(sb + SM_TAB + (uint32_t)((c * 8 + i) * 4 + q) * 16, m);
          uint32_t* hh = h[c * 8 + i];
          hh[0] = hfma2_bf16(hh[0], m[0], m[2]);
          hh[1] = hfma2_bf16(hh[1], m[0], m[2]);
          hh[2] = hfma2_bf16(hh[2], m[1], m[3]);
          hh[3] = hfma2_bf16(hh[3], m[1], m[3]);
        }
        fence_frags<8>(h + c * 8);
        const uint32_t b = ring.wait_full(c, 0);
        if (c > 0) { wg_wait<0>(); ring.release(c - 1); }
        if (c == 0) TS(2);
        wg_fence();
        static_for<0, 8>([&](auto K) { wgmma_rs_n128_tb1<LB_MN128 + K * 128, HI128>(acc, h[c * 8 + K], b, (c | K) != 0); });
        wg_commit();
      }
      bar_arrive(6, 352);
#pragma unroll 1
      for (int ps = 1; ps < 4; ps++) {
        wg_wait<0>();
        ring.release(3);
        fence_regs(acc);
#pragma unroll
        for (int i = 0; i < 8; i++) {
          uint32_t o[4];
          pack8(o, acc + 8 * i);
          sts128(wprv + (ps - 1) * SLOT + i * 512, o[0], o[1], o[2], o[3]);
        }
#pragma unroll
        for (int c = 0; c < 4; c++) {
          const uint32_t b = ring.wait_full(c, ps & 1);
          if (c > 0) { wg_wait<0>(); ring.release(c - 1); }
          wg_fence();
          static_for<0, 8>([&](auto K) { wgmma_rs_n128_tb1<LB_MN128 + K * 128, HI128>(acc, h[c * 8 + K], b, (c | K) != 0); });
          wg_commit();
        }
      }
      wg_wait<0>();
      ring.release(3);
      fence_regs(acc);
#pragma unroll
      for (int i = 0; i < 8; i++) pack8(qf[i], acc + 8 * i);
    }
    fence_regs(qf);
    TS(3);

    float S[64];
    {
      float O[64];
      uint32_t P[8][4];
      const float cs = 0.08838834764831845f * 1.4426950408889634f;
      const int TAU = 0x41800000;
      float m0, m1, l0, l1;

      auto float_block_max = [&]() {
        float b0 = fmaxf(S[0], S[1]), b1 = fmaxf(S[2], S[3]);
#pragma unroll
        for (int i = 1; i < 16; i++) {
          b0 = fmaxf(b0, fmaxf(S[4 * i], S[4 * i + 1]));
          b1 = fmaxf(b1, fmaxf(S[4 * i + 2], S[4 * i + 3]));
        }
        b0 = fmaxf(b0, __shfl_xor_sync(0xffffffffu, b0, 1)); b1 = fmaxf(b1, __shfl_xor_sync(0xffffffffu, b1, 1));
        b0 = fmaxf(b0, __shfl_xor_sync(0xffffffffu, b0, 2)); b1 = fmaxf(b1, __shfl_xor_sync(0xffffffffu, b1, 2));
        m0 = b0 * cs; m1 = b1 * cs;
      };
      auto first_block_max = [&]() {
        int a0 = max(__float_as_int(S[0]), __float_as_int(S[1]));
        int a1 = max(__float_as_int(S[2]), __float_as_int(S[3]));
#pragma unroll
        for (int i = 1; i < 16; i++) {
          a0 = __vimax3_s32(a0, __float_as_int(S[4 * i]), __float_as_int(S[4 * i + 1]));
          a1 = __vimax3_s32(a1, __float_as_int(S[4 * i + 2]), __float_as_int(S[4 * i + 3]));
        }
        a0 = max(a0, __shfl_xor_sync(0xffffffffu, a0, 1)); a1 = max(a1, __shfl_xor_sync(0xffffffffu, a1, 1));
        a0 = max(a0, __shfl_xor_sync(0xffffffffu, a0, 2)); a1 = max(a1, __shfl_xor_sync(0xffffffffu, a1, 2));
        m0 = __int_as_float(a0) * cs; m1 = __int_as_float(a1) * cs;
        if (__any_sync(0xffffffffu, (a0 | a1) < 0)) float_block_max();
      };
      auto scale_sub = [&]() {
#pragma unroll
        for (int i = 0; i < 16; i++) {
          S[4 * i] = fmaf(S[4 * i], cs, -m0); S[4 * i + 1] = fmaf(S[4 * i + 1], cs, -m0);
          S[4 * i + 2] = fmaf(S[4 * i + 2], cs, -m1); S[4 * i + 3] = fmaf(S[4 * i + 3], cs, -m1);
        }
      };
      auto exps = [&](int i0, int i1) {
#pragma unroll
        for (int i = i0; i < i1; i++) {
          S[4 * i] = ex2(S[4 * i]); S[4 * i + 1] = ex2(S[4 * i + 1]);
          S[4 * i + 2] = ex2(S[4 * i + 2]); S[4 * i + 3] = ex2(S[4 * i + 3]);
          l0 += S[4 * i]; l1 += S[4 * i + 2]; l0 += S[4 * i + 1]; l1 += S[4 * i + 3];
        }
      };
      {
        const uint32_t b = ring.wait_full(0, 0);
        wg_fence();
        static_for<0, 8>([&](auto K) { wgmma_rs_n128_tb0<LB_K128 + (K >> 2) * 1024 + (K & 3) * 2, HI128>(S, qf[K], b, K != 0); });
        wg_commit();
        wg_wait<0>();
        fence_regs(S);
        ring.release(0);
        float_block_max();
        scale_sub();
        l0 = 0.f; l1 = 0.f;
        exps(0, 16);
#pragma unroll
        for (int i = 0; i < 8; i++) pack8(P[i], S + 8 * i);
      }
      fence_regs(P);
      if (wg == 1) bar_arrive(2, 256);
#pragma unroll 1
      for (int n = 1; n < 16; n++) {
        const uint32_t tk = 2 * n - 1, tv = 2 * n;
        const bool newhead = (n & 3) == 0;
        const uint32_t bk = ring.wait_full(tk & 3, (tk >> 2) & 1);
        const uint32_t bv = ring.wait_full(tv & 3, (tv >> 2) & 1);
        bar_sync(2 + wg, 256);
        wg_fence();
        static_for<0, 8>([&](auto K) { wgmma_rs_n128_tb0<LB_K128 + (K >> 2) * 1024 + (K & 3) * 2, HI128>(S, qf[K], bk, K != 0); });
        wg_commit();
        static_for<0, 8>([&](auto K) { wgmma_rs_n128_tb1<LB_MN128 + K * 128, HI128>(O, P[K], bv, K != 0 || (n & 3) != 1); });
        wg_commit();
        bar_arrive(2 + (wg ^ 1), 256);
        wg_wait<1>();
        fence_regs(S);
        ring.release(tk & 3);
        if ((n & 3) == 3 && n != 15) {
          fence_regs(qf);
#pragma unroll
          for (int i = 0; i < 8; i++) lds128(wprv + (n >> 2) * SLOT + i * 512, qf[i]);
        }
        float f0 = 1.f, f1 = 1.f;
        bool resc = newhead;
        if (newhead) {
          l0 += __shfl_xor_sync(0xffffffffu, l0, 1); l1 += __shfl_xor_sync(0xffffffffu, l1, 1);
          l0 += __shfl_xor_sync(0xffffffffu, l0, 2); l1 += __shfl_xor_sync(0xffffffffu, l1, 2);
          f0 = rcp_hw(l0); f1 = rcp_hw(l1);
          l0 = 0.f; l1 = 0.f;
          first_block_max();
          scale_sub();
        } else {
          scale_sub();
          int a0 = __vimax3_s32(__float_as_int(S[0]), __float_as_int(S[1]), __float_as_int(S[1]));
          int a1 = __vimax3_s32(__float_as_int(S[2]), __float_as_int(S[3]), __float_as_int(S[3]));
#pragma unroll
          for (int i = 1; i < 16; i++) {
            a0 = __vimax3_s32(a0, __float_as_int(S[4 * i]), __float_as_int(S[4 * i + 1]));
            a1 = __vimax3_s32(a1, __float_as_int(S[4 * i + 2]), __float_as_int(S[4 * i + 3]));
          }
          if (__any_sync(0xffffffffu, max(a0, a1) > TAU)) {
            a0 = max(a0, 0); a1 = max(a1, 0);
            a0 = max(a0, __shfl_xor_sync(0xffffffffu, a0, 1)); a1 = max(a1, __shfl_xor_sync(0xffffffffu, a1, 1));
            a0 = max(a0, __shfl_xor_sync(0xffffffffu, a0, 2)); a1 = max(a1, __shfl_xor_sync(0xffffffffu, a1, 2));
            const float d0 = __int_as_float(a0), d1 = __int_as_float(a1);
#pragma unroll
            for (int i = 0; i < 16; i++) { S[4 * i] -= d0; S[4 * i + 1] -= d0; S[4 * i + 2] -= d1; S[4 * i + 3] -= d1; }
            m0 += d0; m1 += d1;
            f0 = ex2(-d0); f1 = ex2(-d1);
            l0 *= f0; l1 *= f1;
            resc = true;
          }
        }
        exps(0, 4);
        wg_wait<0>();
        fence_regs(O);
        fence_regs(P);
        ring.release(tv & 3);
        if (resc) {
#pragma unroll
          for (int i = 0; i < 16; i++) {
            O[4 * i] *= f0; O[4 * i + 1] *= f0; O[4 * i + 2] *= f1; O[4 * i + 3] *= f1;
          }
          if (newhead) {
#pragma unroll
            for (int i = 0; i < 8; i++) {
              uint32_t o[4];
              pack8(o, O + 8 * i);
              sts128(wprv + ((n >> 2) - 1) * SLOT + i * 512, o[0], o[1], o[2], o[3]);
            }
          }
        }
        exps(4, 16);
#pragma unroll
        for (int i = 0; i < 8; i++) pack8(P[i], S + 8 * i);
        fence_regs(P);
        fence_regs(O);
      }
      {
        const uint32_t bv = ring.wait_full(3, 1);
        if (wg == 0) bar_sync(2, 256);
        wg_fence();
        static_for<0, 8>([&](auto K) { wgmma_rs_n128_tb1<LB_MN128 + K * 128, HI128>(O, P[K], bv, 1); });
        wg_commit();
        l0 += __shfl_xor_sync(0xffffffffu, l0, 1); l1 += __shfl_xor_sync(0xffffffffu, l1, 1);
        l0 += __shfl_xor_sync(0xffffffffu, l0, 2); l1 += __shfl_xor_sync(0xffffffffu, l1, 2);
        const float f0 = rcp_hw(l0), f1 = rcp_hw(l1);
        wg_wait<0>();
        fence_regs(O);
        ring.release(3);
#pragma unroll
        for (int i = 0; i < 8; i++) {
          qf[i][0] = pack_bf16(O[8 * i] * f0, O[8 * i + 1] * f0); qf[i][1] = pack_bf16(O[8 * i + 2] * f1, O[8 * i + 3] * f1);
          qf[i][2] = pack_bf16(O[8 * i + 4] * f0, O[8 * i + 5] * f0); qf[i][3] = pack_bf16(O[8 * i + 6] * f1, O[8 * i + 7] * f1);
        }
      }
    }
    fence_regs(qf);
    TS(4);

    uint4* const Pout = p.s->P + ((size_t)(rt * 8 + warp) * 8 + j) * 1024 + lane;
    const uint32_t tag = *(volatile uint32_t*)(smem_raw + SM_BAR + 64);

    float acc2[32];
    uint32_t pk[4][4];
    auto pack_partial = [&](auto TAGC) {
      fence_regs(acc2);
#pragma unroll
      for (int i = 0; i < 4; i++) {
#pragma unroll
        for (int e = 0; e < 4; e++) pk[i][e] = pack_trunc(acc2[8 * i + 2 * e], acc2[8 * i + 2 * e + 1]);
        pk[i][0] = TAGC ? (pk[i][0] | 1u) : (pk[i][0] & ~1u);
      }
      fence_regs(pk);
    };
    auto store_partial = [&](int step) {
#pragma unroll
      for (int i = 0; i < 4; i++) st_pkt(Pout + ((step & 7) * 4 + i) * 32, pk[i][0], pk[i][1], pk[i][2], pk[i][3]);
    };
    auto chunk_sent = [&](int step) { warp_arrive(sb + SM_SBAR + step * 8); };
    const uint4* const Gin = Gw + lane;
    auto g_issue = [&](int u) { warp_bulk_load(wblk + 2 * SLOT + (u & 1) * 2048, Gw + u * 128, 2048, wbar + (u & 1) * 8); };

    uint32_t tl = 0, b = ring.wait_full(0, 0);
    auto next_tile = [&]() {
      const uint32_t cur = tl & 3;
      tl++;
      b = ring.wait_full(tl & 3, (tl >> 2) & 1);
      wg_wait<0>();
      TR(4);
      ring.release(cur);
    };
    {
      uint32_t o[24][4];
#pragma unroll
      for (int i = 0; i < 24; i++) lds128(wprv + (i >> 3) * SLOT + (i & 7) * 512, o[i]);
#pragma unroll 1
      for (int cc = 0; cc < 8; cc++) {
        wg_fence();
        static_for<0, 16>([&](auto K) { wgmma_rs_n64_tb1<K * 128, HI128>(acc2, o[K], b, K != 0); });
        wg_commit();
        if (cc > 0) store_partial(cc - 1);
        next_tile();
        wg_fence();
        static_for<0, 16>([&](auto K) { wgmma_rs_n64_tb1<K * 128, HI128>(acc2, K < 8 ? o[16 + (K & 7)] : qf[K & 7], b, 1); });
        wg_commit();
        warp_arrive(cc > 0 ? sb + SM_SBAR + (cc - 1) * 8 : bars + 96);
        if (cc == 6) { g_issue(0); g_issue(1); }
        next_tile();
        pack_partial(IC<1>{});
      }
    }
    TS(5);

    uint32_t H[14][4];
    {
      float acc[112];
      const uint4* const statp = &p.s->stat[(rt * 8 + warp) * 8];
#pragma unroll 1
      for (int u = 0; u < 8; u++) {
        uint32_t fa[4][4];
        mbar_wait(wbar + (u & 1) * 8, ((u >> 1) + (u & 1)) & 1);
#pragma unroll
        for (int i = 0; i < 4; i++) lds128(wprv + 2 * SLOT + (u & 1) * 2048 + i * 512, fa[i]);
        verify4_tag0<512>(Gin + u * 128, fa);
        wg_fence();
        static_for<0, 4>([&](auto K) { wgmma_rs_n224_tb1<LB_W1 + K * 64, HI64>(acc, fa[K], b, (u | K) != 0); });
        wg_commit();
        if (u == 0) store_partial(7);
        if (u == 1) chunk_sent(7);
        if (u < 5) g_issue(u + 2);
        if (u == 7) warp_bulk_load(wblk + 2 * SLOT, statp, 128, wbar + 16);
        next_tile();
        if (u == 5) g_issue(7);
      }
      fence_regs(acc);
      TS(9);
      mbar_wait(bars + 72, 0);
      uint32_t xr[4];
      mbar_wait(wbar + 16, 1);
      lds128(wblk + 2 * SLOT + gq * 16, xr);
      {
        int spins = 0;
        while (((xr[0] ^ tag) & 1u) && ++spins < SPIN_LIMIT) ld_pkt(statp + gq, xr);
      }
      const float ra0 = __uint_as_float(xr[0]), rb0 = __uint_as_float(xr[1]), ra1 = __uint_as_float(xr[2]),
                  rb1 = __uint_as_float(xr[3]);
#pragma unroll
      for (int i = 0; i < 28; i++) {
        uint32_t m[4];
        lds128(sb + SM_TAB + (i * 4 + q) * 16, m);
        const float u0 = __uint_as_float(m[0]), u1 = __uint_as_float(m[1]), w0 = __uint_as_float(m[2]), w1 = __uint_as_float(m[3]);
        const float z0 = fmaf(acc[4 * i], ra0, fmaf(u0, rb0, w0)), z1 = fmaf(acc[4 * i + 1], ra0, fmaf(u1, rb0, w1));
        const float z2 = fmaf(acc[4 * i + 2], ra1, fmaf(u0, rb1, w0)), z3 = fmaf(acc[4 * i + 3], ra1, fmaf(u1, rb1, w1));
        H[i >> 1][(i & 1) * 2] = pack_bf16(fmaf(z0, tanh_hw(z0), z0), fmaf(z1, tanh_hw(z1), z1));
        H[i >> 1][(i & 1) * 2 + 1] = pack_bf16(fmaf(z2, tanh_hw(z2), z2), fmaf(z3, tanh_hw(z3), z3));
      }
    }
    fence_regs(H);
    TS(10);
    const int go = 24 + (warp ^ 4);
#pragma unroll 1
    for (int cc = 0; cc < 8; cc++) {
      wg_fence();
      static_for<0, 14>([&](auto K) { wgmma_rs_n64_tb1<K * 128, HI128>(acc2, H[K], b, K != 0); });
      wg_commit();
      if (cc > 1) chunk_sent(8 + cc - 2);
      if (cc > 0) store_partial(cc - 1);
      if (cc < 7) next_tile();
      wg_wait<0>();
      pack_partial(IC<0>{});
    }
    store_partial(7);
    TS(11);
    {
      const uint4* const Pown = p.s->P + (size_t)(rt * 8 + j) * 8192 + go * 32 + lane;
      uint32_t r[8][4];
      float y[8];
      mbar_wait(bars + 88, 0);
      spin_cycles(wg ? FIN_DELAY1 : FIN_DELAY0);
      issue_pkts<0, 8>(Pown, 1024, r);
      verify8_tag0<16384>(Pown, r);
      TS(13);
#pragma unroll
      for (int s = 0; s < 8; s++) add_partial(y, r[s], 0u, s == 0);
      const uint32_t gt = sb + SM_PARK + 6 * 4096 + 2048 + (go * 4 + q) * 8;
      store_out(p.out, (uint32_t)(rt * 128 + 16 * j + gq) * 256 + go * 8 + q, sb + SM_PARK + SLOT + go * 1024 + lane * 16,
                lds32(gt), lds32(gt + 4), y);
    }
    TS(12);
    if (bid == 0 && tid == 0) asm volatile("st.relaxed.gpu.global.u32 [%0], %1;" ::"l"(&p.s->epoch), "r"(tag) : "memory");
  }
}

typedef CUresult (*EncodeFn)(CUtensorMap*, CUtensorMapDataType, cuuint32_t, void*, const cuuint64_t*, const cuuint64_t*,
                             const cuuint32_t*, const cuuint32_t*, CUtensorMapInterleave, CUtensorMapSwizzle,
                             CUtensorMapL2promotion, CUtensorMapFloatOOBfill);

static void make_map(EncodeFn fn, CUtensorMap* tm, const void* ptr, int inner, int rows, int cols, int box_rows, int box_outer,
                     CUtensorMapSwizzle swz) {
  cuuint64_t gd[3] = {(cuuint64_t)inner, (cuuint64_t)rows, (cuuint64_t)(cols / inner)};
  cuuint64_t gs[2] = {(cuuint64_t)cols * 2, (cuuint64_t)inner * 2};
  cuuint32_t bx[3] = {(cuuint32_t)inner, (cuuint32_t)box_rows, (cuuint32_t)box_outer};
  cuuint32_t es[3] = {1, 1, 1};
  fn(tm, CU_TENSOR_MAP_DATA_TYPE_BFLOAT16, 3, const_cast<void*>(ptr), gd, gs, bx, es, CU_TENSOR_MAP_INTERLEAVE_NONE, swz,
     CU_TENSOR_MAP_L2_PROMOTION_L2_128B, CU_TENSOR_MAP_FLOAT_OOB_FILL_NONE);
}

extern "C" void kernel_launch(void* const* d_in, const int* in_sizes, int n_in, void* d_out, int out_size) {
  (void)in_sizes; (void)n_in; (void)out_size;
  void* fnp = nullptr;
  cudaDriverEntryPointQueryResult qr;
  cudaGetDriverEntryPoint("cuTensorMapEncodeTiled", &fnp, cudaEnableDefault, &qr);
  EncodeFn fn = (EncodeFn)fnp;
  CUtensorMap tmWq, tmK, tmV, tmWo, tmW1, tmW2, tmWm, tmP;
  make_map(fn, &tmWq, d_in[3], 64, 512, 4096, 128, 2, CU_TENSOR_MAP_SWIZZLE_128B);
  make_map(fn, &tmK, d_in[1], 64, 8 * SK, 128, 128, 2, CU_TENSOR_MAP_SWIZZLE_128B);
  make_map(fn, &tmV, d_in[2], 64, 8 * SK, 128, 128, 2, CU_TENSOR_MAP_SWIZZLE_128B);
  make_map(fn, &tmWo, d_in[4], 64, 4096, 512, 256, 1, CU_TENSOR_MAP_SWIZZLE_128B);
  make_map(fn, &tmW1, d_in[6], 32, 512, FF, 64, 7, CU_TENSOR_MAP_SWIZZLE_64B);
  make_map(fn, &tmW2, d_in[7], 64, FF, 512, 224, 1, CU_TENSOR_MAP_SWIZZLE_128B);
  make_map(fn, &tmWm, d_in[9], 8, 512, 3072, 256, 1, CU_TENSOR_MAP_SWIZZLE_NONE);
  Params p;
  p.x = (const __nv_bfloat16*)d_in[0];
  p.c = (const __nv_bfloat16*)d_in[8];
  p.wmod = (const __nv_bfloat16*)d_in[9];
  p.wo = (const __nv_bfloat16*)d_in[4];
  p.w1 = (const __nv_bfloat16*)d_in[6];
  p.w2 = (const __nv_bfloat16*)d_in[7];
  p.out = (__nv_bfloat16*)d_out;
  cudaGetSymbolAddress((void**)&p.s, g_scratch);
  {
    cuuint64_t gd[3] = {256, 32, 1024};
    cuuint64_t gs[2] = {512, 16384};
    cuuint32_t bx[3] = {256, 1, 8};
    cuuint32_t es[3] = {1, 1, 1};
    fn(&tmP, CU_TENSOR_MAP_DATA_TYPE_BFLOAT16, 3, (void*)p.s->P, gd, gs, bx, es, CU_TENSOR_MAP_INTERLEAVE_NONE,
       CU_TENSOR_MAP_SWIZZLE_NONE, CU_TENSOR_MAP_L2_PROMOTION_NONE, CU_TENSOR_MAP_FLOAT_OOB_FILL_NONE);
  }
  cudaFuncSetAttribute(adaln_block_kernel, cudaFuncAttributeMaxDynamicSharedMemorySize, SM_TOTAL);
  adaln_block_kernel<<<128, 384, SM_TOTAL>>>(tmWq, tmK, tmV, tmWo, tmW1, tmW2, tmWm, tmP, p);
}
```

```cpp
#include <cuda_runtime.h>
#include <cuda_bf16.h>
#include <cuda.h>
#include <stdint.h>

template <int OFF, uint32_t HI>
__device__ __forceinline__ void wgmma_rs_n128_tb0(float (&d)[64], const uint32_t (&a)[4], uint32_t lo, int sd) {
  asm volatile("{\n.reg .pred p;\n.reg .b32 l;\n.reg .b64 db;\nsetp.ne.b32 p, %69, 0;\n"
    "add.u32 l, %68, %70;\nmov.b64 db, {l, %71};\n"
    "wgmma.mma_async.sync.aligned.m64n128k16.f32.bf16.bf16 "
    "{%0,%1,%2,%3,%4,%5,%6,%7,%8,%9,%10,%11,%12,%13,%14,%15,"
    "%16,%17,%18,%19,%20,%21,%22,%23,%24,%25,%26,%27,%28,%29,%30,%31,"
    "%32,%33,%34,%35,%36,%37,%38,%39,%40,%41,%42,%43,%44,%45,%46,%47,"
    "%48,%49,%50,%51,%52,%53,%54,%55,%56,%57,%58,%59,%60,%61,%62,%63}, "
    "{%64,%65,%66,%67}, db, p, 1, 1, 0;\n}\n"
    : "+f"(d[0]), "+f"(d[1]), "+f"(d[2]), "+f"(d[3]), "+f"(d[4]), "+f"(d[5]), "+f"(d[6]), "+f"(d[7]),
      "+f"(d[8]), "+f"(d[9]), "+f"(d[10]), "+f"(d[11]), "+f"(d[12]), "+f"(d[13]), "+f"(d[14]), "+f"(d[15]),
      "+f"(d[16]), "+f"(d[17]), "+f"(d[18]), "+f"(d[19]), "+f"(d[20]), "+f"(d[21]), "+f"(d[22]), "+f"(d[23]),
      "+f"(d[24]), "+f"(d[25]), "+f"(d[26]), "+f"(d[27]), "+f"(d[28]), "+f"(d[29]), "+f"(d[30]), "+f"(d[31]),
      "+f"(d[32]), "+f"(d[33]), "+f"(d[34]), "+f"(d[35]), "+f"(d[36]), "+f"(d[37]), "+f"(d[38]), "+f"(d[39]),
      "+f"(d[40]), "+f"(d[41]), "+f"(d[42]), "+f"(d[43]), "+f"(d[44]), "+f"(d[45]), "+f"(d[46]), "+f"(d[47]),
      "+f"(d[48]), "+f"(d[49]), "+f"(d[50]), "+f"(d[51]), "+f"(d[52]), "+f"(d[53]), "+f"(d[54]), "+f"(d[55]),
      "+f"(d[56]), "+f"(d[57]), "+f"(d[58]), "+f"(d[59]), "+f"(d[60]), "+f"(d[61]), "+f"(d[62]), "+f"(d[63])
    : "r"(a[0]), "r"(a[1]), "r"(a[2]), "r"(a[3]), "r"(lo), "r"(sd), "n"(OFF), "n"(HI));
}

template <int OFF, uint32_t HI>
__device__ __forceinline__ void wgmma_rs_n128_tb1(float (&d)[64], const uint32_t (&a)[4], uint32_t lo, int sd) {
  asm volatile("{\n.reg .pred p;\n.reg .b32 l;\n.reg .b64 db;\nsetp.ne.b32 p, %69, 0;\n"
    "add.u32 l, %68, %70;\nmov.b64 db, {l, %71};\n"
    "wgmma.mma_async.sync.aligned.m64n128k16.f32.bf16.bf16 "
    "{%0,%1,%2,%3,%4,%5,%6,%7,%8,%9,%10,%11,%12,%13,%14,%15,"
    "%16,%17,%18,%19,%20,%21,%22,%23,%24,%25,%26,%27,%28,%29,%30,%31,"
    "%32,%33,%34,%35,%36,%37,%38,%39,%40,%41,%42,%43,%44,%45,%46,%47,"
    "%48,%49,%50,%51,%52,%53,%54,%55,%56,%57,%58,%59,%60,%61,%62,%63}, "
    "{%64,%65,%66,%67}, db, p, 1, 1, 1;\n}\n"
    : "+f"(d[0]), "+f"(d[1]), "+f"(d[2]), "+f"(d[3]), "+f"(d[4]), "+f"(d[5]), "+f"(d[6]), "+f"(d[7]),
      "+f"(d[8]), "+f"(d[9]), "+f"(d[10]), "+f"(d[11]), "+f"(d[12]), "+f"(d[13]), "+f"(d[14]), "+f"(d[15]),
      "+f"(d[16]), "+f"(d[17]), "+f"(d[18]), "+f"(d[19]), "+f"(d[20]), "+f"(d[21]), "+f"(d[22]), "+f"(d[23]),
      "+f"(d[24]), "+f"(d[25]), "+f"(d[26]), "+f"(d[27]), "+f"(d[28]), "+f"(d[29]), "+f"(d[30]), "+f"(d[31]),
      "+f"(d[32]), "+f"(d[33]), "+f"(d[34]), "+f"(d[35]), "+f"(d[36]), "+f"(d[37]), "+f"(d[38]), "+f"(d[39]),
      "+f"(d[40]), "+f"(d[41]), "+f"(d[42]), "+f"(d[43]), "+f"(d[44]), "+f"(d[45]), "+f"(d[46]), "+f"(d[47]),
      "+f"(d[48]), "+f"(d[49]), "+f"(d[50]), "+f"(d[51]), "+f"(d[52]), "+f"(d[53]), "+f"(d[54]), "+f"(d[55]),
      "+f"(d[56]), "+f"(d[57]), "+f"(d[58]), "+f"(d[59]), "+f"(d[60]), "+f"(d[61]), "+f"(d[62]), "+f"(d[63])
    : "r"(a[0]), "r"(a[1]), "r"(a[2]), "r"(a[3]), "r"(lo), "r"(sd), "n"(OFF), "n"(HI));
}

template <int OFF, uint32_t HI>
__device__ __forceinline__ void wgmma_rs_n96_tb1(float (&d)[48], const uint32_t (&a)[4], uint32_t lo, int sd) {
  asm volatile("{\n.reg .pred p;\n.reg .b32 l;\n.reg .b64 db;\nsetp.ne.b32 p, %53, 0;\n"
    "add.u32 l, %52, %54;\nmov.b64 db, {l, %55};\n"
    "wgmma.mma_async.sync.aligned.m64n96k16.f32.bf16.bf16 "
    "{%0,%1,%2,%3,%4,%5,%6,%7,%8,%9,%10,%11,%12,%13,%14,%15,"
    "%16,%17,%18,%19,%20,%21,%22,%23,%24,%25,%26,%27,%28,%29,%30,%31,"
    "%32,%33,%34,%35,%36,%37,%38,%39,%40,%41,%42,%43,%44,%45,%46,%47}, "
    "{%48,%49,%50,%51}, db, p, 1, 1, 1;\n}\n"
    : "+f"(d[0]), "+f"(d[1]), "+f"(d[2]), "+f"(d[3]), "+f"(d[4]), "+f"(d[5]), "+f"(d[6]), "+f"(d[7]),
      "+f"(d[8]), "+f"(d[9]), "+f"(d[10]), "+f"(d[11]), "+f"(d[12]), "+f"(d[13]), "+f"(d[14]), "+f"(d[15]),
      "+f"(d[16]), "+f"(d[17]), "+f"(d[18]), "+f"(d[19]), "+f"(d[20]), "+f"(d[21]), "+f"(d[22]), "+f"(d[23]),
      "+f"(d[24]), "+f"(d[25]), "+f"(d[26]), "+f"(d[27]), "+f"(d[28]), "+f"(d[29]), "+f"(d[30]), "+f"(d[31]),
      "+f"(d[32]), "+f"(d[33]), "+f"(d[34]), "+f"(d[35]), "+f"(d[36]), "+f"(d[37]), "+f"(d[38]), "+f"(d[39]),
      "+f"(d[40]), "+f"(d[41]), "+f"(d[42]), "+f"(d[43]), "+f"(d[44]), "+f"(d[45]), "+f"(d[46]), "+f"(d[47])
    : "r"(a[0]), "r"(a[1]), "r"(a[2]), "r"(a[3]), "r"(lo), "r"(sd), "n"(OFF), "n"(HI));
}

template <int OFF, uint32_t HI>
__device__ __forceinline__ void wgmma_rs_n64_tb1(float (&d)[32], const uint32_t (&a)[4], uint32_t lo, int sd) {
  asm volatile("{\n.reg .pred p;\n.reg .b32 l;\n.reg .b64 db;\nsetp.ne.b32 p, %37, 0;\n"
    "add.u32 l, %36, %38;\nmov.b64 db, {l, %39};\n"
    "wgmma.mma_async.sync.aligned.m64n64k16.f32.bf16.bf16 "
    "{%0,%1,%2,%3,%4,%5,%6,%7,%8,%9,%10,%11,%12,%13,%14,%15,"
    "%16,%17,%18,%19,%20,%21,%22,%23,%24,%25,%26,%27,%28,%29,%30,%31}, "
    "{%32,%33,%34,%35}, db, p, 1, 1, 1;\n}\n"
    : "+f"(d[0]), "+f"(d[1]), "+f"(d[2]), "+f"(d[3]), "+f"(d[4]), "+f"(d[5]), "+f"(d[6]), "+f"(d[7]),
      "+f"(d[8]), "+f"(d[9]), "+f"(d[10]), "+f"(d[11]), "+f"(d[12]), "+f"(d[13]), "+f"(d[14]), "+f"(d[15]),
      "+f"(d[16]), "+f"(d[17]), "+f"(d[18]), "+f"(d[19]), "+f"(d[20]), "+f"(d[21]), "+f"(d[22]), "+f"(d[23]),
      "+f"(d[24]), "+f"(d[25]), "+f"(d[26]), "+f"(d[27]), "+f"(d[28]), "+f"(d[29]), "+f"(d[30]), "+f"(d[31])
    : "r"(a[0]), "r"(a[1]), "r"(a[2]), "r"(a[3]), "r"(lo), "r"(sd), "n"(OFF), "n"(HI));
}

template <int STR>
__device__ __forceinline__ void verify8_tag1(const uint4* p, uint32_t (*r)[4]) {
  asm volatile("{\n.reg .pred p, q;\n.reg .b32 a, n;\nmov.u32 n, 0;\n"
    "LAB_CHK:\n"
    "and.b32 a, %0, %4;\n"
    "and.b32 a, a, %8;\n"
    "and.b32 a, a, %12;\n"
    "and.b32 a, a, %16;\n"
    "and.b32 a, a, %20;\n"
    "and.b32 a, a, %24;\n"
    "and.b32 a, a, %28;\n"
    "and.b32 a, a, 1;\nsetp.eq.u32 p, a, 1;\nvote.sync.all.pred p, p, 0xffffffff;\n"
    "@p bra.uni LAB_OK;\n"
    "and.b32 a, %0, 1;\nsetp.ne.u32 q, a, 1;\n"
    "@q ld.relaxed.gpu.global.v4.b32 {%0,%1,%2,%3}, [%32+%33];\n"
    "and.b32 a, %4, 1;\nsetp.ne.u32 q, a, 1;\n"
    "@q ld.relaxed.gpu.global.v4.b32 {%4,%5,%6,%7}, [%32+%34];\n"
    "and.b32 a, %8, 1;\nsetp.ne.u32 q, a, 1;\n"
    "@q ld.relaxed.gpu.global.v4.b32 {%8,%9,%10,%11}, [%32+%35];\n"
    "and.b32 a, %12, 1;\nsetp.ne.u32 q, a, 1;\n"
    "@q ld.relaxed.gpu.global.v4.b32 {%12,%13,%14,%15}, [%32+%36];\n"
    "and.b32 a, %16, 1;\nsetp.ne.u32 q, a, 1;\n"
    "@q ld.relaxed.gpu.global.v4.b32 {%16,%17,%18,%19}, [%32+%37];\n"
    "and.b32 a, %20, 1;\nsetp.ne.u32 q, a, 1;\n"
    "@q ld.relaxed.gpu.global.v4.b32 {%20,%21,%22,%23}, [%32+%38];\n"
    "and.b32 a, %24, 1;\nsetp.ne.u32 q, a, 1;\n"
    "@q ld.relaxed.gpu.global.v4.b32 {%24,%25,%26,%27}, [%32+%39];\n"
    "and.b32 a, %28, 1;\nsetp.ne.u32 q, a, 1;\n"
    "@q ld.relaxed.gpu.global.v4.b32 {%28,%29,%30,%31}, [%32+%40];\n"
    "add.u32 n, n, 1;\nsetp.lt.u32 q, n, 262144;\n@q bra.uni LAB_CHK;\n"
    "LAB_OK:\n"
    "}\n"
    : "+r"(r[0][0]), "+r"(r[0][1]), "+r"(r[0][2]), "+r"(r[0][3]), "+r"(r[1][0]), "+r"(r[1][1]), "+r"(r[1][2]), "+r"(r[1][3]),
      "+r"(r[2][0]), "+r"(r[2][1]), "+r"(r[2][2]), "+r"(r[2][3]), "+r"(r[3][0]), "+r"(r[3][1]), "+r"(r[3][2]), "+r"(r[3][3]),
      "+r"(r[4][0]), "+r"(r[4][1]), "+r"(r[4][2]), "+r"(r[4][3]), "+r"(r[5][0]), "+r"(r[5][1]), "+r"(r[5][2]), "+r"(r[5][3]),
      "+r"(r[6][0]), "+r"(r[6][1]), "+r"(r[6][2]), "+r"(r[6][3]), "+r"(r[7][0]), "+r"(r[7][1]), "+r"(r[7][2]), "+r"(r[7][3])
    : "l"(p), "n"(0 * STR), "n"(1 * STR), "n"(2 * STR), "n"(3 * STR), "n"(4 * STR), "n"(5 * STR), "n"(6 * STR), "n"(7 * STR)
    : "memory");
}

template <int STR>
__device__ __forceinline__ void verify8_tag0(const uint4* p, uint32_t (*r)[4]) {
  asm volatile("{\n.reg .pred p, q;\n.reg .b32 a, n;\nmov.u32 n, 0;\n"
    "LAB_CHK:\n"
    "or.b32 a, %0, %4;\n"
    "or.b32 a, a, %8;\n"
    "or.b32 a, a, %12;\n"
    "or.b32 a, a, %16;\n"
    "or.b32 a, a, %20;\n"
    "or.b32 a, a, %24;\n"
    "or.b32 a, a, %28;\n"
    "and.b32 a, a, 1;\nsetp.eq.u32 p, a, 0;\nvote.sync.all.pred p, p, 0xffffffff;\n"
    "@p bra.uni LAB_OK;\n"
    "and.b32 a, %0, 1;\nsetp.ne.u32 q, a, 0;\n"
    "@q ld.relaxed.gpu.global.v4.b32 {%0,%1,%2,%3}, [%32+%33];\n"
    "and.b32 a, %4, 1;\nsetp.ne.u32 q, a, 0;\n"
    "@q ld.relaxed.gpu.global.v4.b32 {%4,%5,%6,%7}, [%32+%34];\n"
    "and.b32 a, %8, 1;\nsetp.ne.u32 q, a, 0;\n"
    "@q ld.relaxed.gpu.global.v4.b32 {%8,%9,%10,%11}, [%32+%35];\n"
    "and.b32 a, %12, 1;\nsetp.ne.u32 q, a, 0;\n"
    "@q ld.relaxed.gpu.global.v4.b32 {%12,%13,%14,%15}, [%32+%36];\n"
    "and.b32 a, %16, 1;\nsetp.ne.u32 q, a, 0;\n"
    "@q ld.relaxed.gpu.global.v4.b32 {%16,%17,%18,%19}, [%32+%37];\n"
    "and.b32 a, %20, 1;\nsetp.ne.u32 q, a, 0;\n"
    "@q ld.relaxed.gpu.global.v4.b32 {%20,%21,%22,%23}, [%32+%38];\n"
    "and.b32 a, %24, 1;\nsetp.ne.u32 q, a, 0;\n"
    "@q ld.relaxed.gpu.global.v4.b32 {%24,%25,%26,%27}, [%32+%39];\n"
    "and.b32 a, %28, 1;\nsetp.ne.u32 q, a, 0;\n"
    "@q ld.relaxed.gpu.global.v4.b32 {%28,%29,%30,%31}, [%32+%40];\n"
    "add.u32 n, n, 1;\nsetp.lt.u32 q, n, 262144;\n@q bra.uni LAB_CHK;\n"
    "LAB_OK:\n"
    "or.b32 %0, %0, 1;\n"
    "or.b32 %4, %4, 1;\n"
    "or.b32 %8, %8, 1;\n"
    "or.b32 %12, %12, 1;\n"
    "or.b32 %16, %16, 1;\n"
    "or.b32 %20, %20, 1;\n"
    "or.b32 %24, %24, 1;\n"
    "or.b32 %28, %28, 1;\n"
    "}\n"
    : "+r"(r[0][0]), "+r"(r[0][1]), "+r"(r[0][2]), "+r"(r[0][3]), "+r"(r[1][0]), "+r"(r[1][1]), "+r"(r[1][2]), "+r"(r[1][3]),
      "+r"(r[2][0]), "+r"(r[2][1]), "+r"(r[2][2]), "+r"(r[2][3]), "+r"(r[3][0]), "+r"(r[3][1]), "+r"(r[3][2]), "+r"(r[3][3]),
      "+r"(r[4][0]), "+r"(r[4][1]), "+r"(r[4][2]), "+r"(r[4][3]), "+r"(r[5][0]), "+r"(r[5][1]), "+r"(r[5][2]), "+r"(r[5][3]),
      "+r"(r[6][0]), "+r"(r[6][1]), "+r"(r[6][2]), "+r"(r[6][3]), "+r"(r[7][0]), "+r"(r[7][1]), "+r"(r[7][2]), "+r"(r[7][3])
    : "l"(p), "n"(0 * STR), "n"(1 * STR), "n"(2 * STR), "n"(3 * STR), "n"(4 * STR), "n"(5 * STR), "n"(6 * STR), "n"(7 * STR)
    : "memory");
}

template <int STR>
__device__ __forceinline__ void verify4_tag0(const uint4* p, uint32_t (*r)[4]) {
  asm volatile("{\n.reg .pred p, q;\n.reg .b32 a, n;\nmov.u32 n, 0;\n"
    "LAB_CHK:\n"
    "or.b32 a, %0, %4;\n"
    "or.b32 a, a, %8;\n"
    "or.b32 a, a, %12;\n"
    "and.b32 a, a, 1;\nsetp.eq.u32 p, a, 0;\nvote.sync.all.pred p, p, 0xffffffff;\n"
    "@p bra.uni LAB_OK;\n"
    "and.b32 a, %0, 1;\nsetp.ne.u32 q, a, 0;\n"
    "@q ld.relaxed.gpu.global.v4.b32 {%0,%1,%2,%3}, [%16+%17];\n"
    "and.b32 a, %4, 1;\nsetp.ne.u32 q, a, 0;\n"
    "@q ld.relaxed.gpu.global.v4.b32 {%4,%5,%6,%7}, [%16+%18];\n"
    "and.b32 a, %8, 1;\nsetp.ne.u32 q, a, 0;\n"
    "@q ld.relaxed.gpu.global.v4.b32 {%8,%9,%10,%11}, [%16+%19];\n"
    "and.b32 a, %12, 1;\nsetp.ne.u32 q, a, 0;\n"
    "@q ld.relaxed.gpu.global.v4.b32 {%12,%13,%14,%15}, [%16+%20];\n"
    "add.u32 n, n, 1;\nsetp.lt.u32 q, n, 262144;\n@q bra.uni LAB_CHK;\n"
    "LAB_OK:\n"
    "or.b32 %0, %0, 1;\n"
    "or.b32 %4, %4, 1;\n"
    "or.b32 %8, %8, 1;\n"
    "or.b32 %12, %12, 1;\n"
    "}\n"
    : "+r"(r[0][0]), "+r"(r[0][1]), "+r"(r[0][2]), "+r"(r[0][3]), "+r"(r[1][0]), "+r"(r[1][1]), "+r"(r[1][2]), "+r"(r[1][3]),
      "+r"(r[2][0]), "+r"(r[2][1]), "+r"(r[2][2]), "+r"(r[2][3]), "+r"(r[3][0]), "+r"(r[3][1]), "+r"(r[3][2]), "+r"(r[3][3])
    : "l"(p), "n"(0 * STR), "n"(1 * STR), "n"(2 * STR), "n"(3 * STR)
    : "memory");
}

#define SPIN_LIMIT (1 << 18)

__device__ __forceinline__ uint32_t smem_u32(const void* p) { return (uint32_t)__cvta_generic_to_shared(p); }
__device__ __forceinline__ void mbar_init(uint32_t a, uint32_t c) {
  asm volatile("mbarrier.init.shared::cta.b64 [%0], %1;" ::"r"(a), "r"(c) : "memory");
}
__device__ __forceinline__ void mbar_expect(uint32_t a, uint32_t b) {
  asm volatile("mbarrier.arrive.expect_tx.shared::cta.b64 _, [%0], %1;" ::"r"(a), "r"(b) : "memory");
}
__device__ __forceinline__ void mbar_arrive(uint32_t a) {
  asm volatile("mbarrier.arrive.shared::cta.b64 _, [%0];" ::"r"(a) : "memory");
}
__device__ __forceinline__ void mbar_wait(uint32_t a, uint32_t parity) {
  asm volatile(
      "{\n.reg .pred p;\n.reg .u32 n;\nmov.u32 n, 0;\n"
      "LAB_WAIT:\n"
      "mbarrier.try_wait.parity.shared::cta.b64 p, [%0], %1;\n"
      "@p bra LAB_DONE;\n"
      "add.u32 n, n, 1;\n"
      "setp.lt.u32 p, n, 262144;\n"
      "@p bra LAB_WAIT;\n"
      "LAB_DONE:\n}\n" ::"r"(a), "r"(parity) : "memory");
}
__device__ __forceinline__ void mbar_wait_long(uint32_t a, uint32_t parity) {
  asm volatile(
      "{\n.reg .pred p;\n.reg .u32 n;\nmov.u32 n, 0;\n"
      "LAB_WAIT:\n"
      "mbarrier.try_wait.parity.shared::cta.b64 p, [%0], %1, 20000;\n"
      "@p bra LAB_DONE;\n"
      "add.u32 n, n, 1;\n"
      "setp.lt.u32 p, n, 4096;\n"
      "@p bra LAB_WAIT;\n"
      "LAB_DONE:\n}\n" ::"r"(a), "r"(parity) : "memory");
}
__device__ __forceinline__ bool mbar_test(uint32_t a, uint32_t parity) {
  uint32_t ok;
  asm volatile("{\n.reg .pred p;\nmbarrier.test_wait.parity.shared::cta.b64 p, [%1], %2;\nselp.u32 %0, 1, 0, p;\n}\n"
               : "=r"(ok) : "r"(a), "r"(parity) : "memory");
  return ok;
}
__device__ __forceinline__ void tma3d(uint32_t dst, const CUtensorMap* tm, uint32_t bar, int c0, int c1, int c2) {
  asm volatile(
      "cp.async.bulk.tensor.3d.shared::cluster.global.mbarrier::complete_tx::bytes [%0], [%1, {%3,%4,%5}], [%2];"
      ::"r"(dst), "l"(tm), "r"(bar), "r"(c0), "r"(c1), "r"(c2) : "memory");
}
__device__ __forceinline__ void wg_fence() { asm volatile("wgmma.fence.sync.aligned;" ::: "memory"); }
__device__ __forceinline__ void wg_commit() { asm volatile("wgmma.commit_group.sync.aligned;" ::: "memory"); }
template <int N> __device__ __forceinline__ void wg_wait() {
  asm volatile("wgmma.wait_group.sync.aligned %0;" ::"n"(N) : "memory");
}
template <int N> __device__ __forceinline__ void fence_regs(float (&d)[N]) {
#pragma unroll
  for (int i = 0; i < N; i++) asm volatile("" : "+f"(d[i])::"memory");
}
template <int N> __device__ __forceinline__ void fence_regs(uint32_t (&d)[N][4]) {
#pragma unroll
  for (int i = 0; i < N; i++) asm volatile("" : "+r"(d[i][0]), "+r"(d[i][1]), "+r"(d[i][2]), "+r"(d[i][3])::"memory");
}
template <int N> __device__ __forceinline__ void fence_frags(uint32_t (*d)[4]) {
#pragma unroll
  for (int i = 0; i < N; i++) asm volatile("" : "+r"(d[i][0]), "+r"(d[i][1]), "+r"(d[i][2]), "+r"(d[i][3])::"memory");
}
__device__ __forceinline__ void bar_sync(int id, int n) { asm volatile("bar.sync %0, %1;" ::"r"(id), "r"(n) : "memory"); }
__device__ __forceinline__ void bar_arrive(int id, int n) { asm volatile("bar.arrive %0, %1;" ::"r"(id), "r"(n) : "memory"); }

__device__ __forceinline__ uint32_t pack_bf16(float lo, float hi) {
  uint32_t r;
  asm("cvt.rn.bf16x2.f32 %0, %1, %2;" : "=r"(r) : "f"(hi), "f"(lo));
  return r;
}
__device__ __forceinline__ float bf_lo(uint32_t w) { return __uint_as_float(w << 16); }
__device__ __forceinline__ float bf_hi(uint32_t w) { return __uint_as_float(w & 0xFFFF0000u); }
__device__ __forceinline__ float round_bf16(float x) { return bf_lo(pack_bf16(x, 0.f)); }
__device__ __forceinline__ uint32_t hfma2_bf16(uint32_t a, uint32_t b, uint32_t c) {
  uint32_t r;
  asm("fma.rn.bf16x2 %0, %1, %2, %3;" : "=r"(r) : "r"(a), "r"(b), "r"(c));
  return r;
}
__device__ __forceinline__ float ex2(float x) {
  float r;
  asm("ex2.approx.ftz.f32 %0, %1;" : "=f"(r) : "f"(x));
  return r;
}
__device__ __forceinline__ float tanh_hw(float x) {
  float r;
  asm("tanh.approx.f32 %0, %1;" : "=f"(r) : "f"(x));
  return r;
}
template <int TAG> __device__ __forceinline__ uint32_t pack_tag(float lo, float hi) {
  uint32_t w = __byte_perm(__float_as_uint(lo), pack_bf16(lo, hi), 0x7632);
  return TAG ? (w | 1u) : (w & ~1u);
}
__device__ __forceinline__ void st_pkt(uint4* p, uint32_t a, uint32_t b, uint32_t c, uint32_t d) {
  asm volatile(
      "st.relaxed.gpu.global.v4.b32 [%0], {%1,%2,%3,%4};" ::"l"(p), "r"(a), "r"(b), "r"(c), "r"(d) : "memory");
}
__device__ __forceinline__ void ld_pkt(const uint4* p, uint32_t (&r)[4]) {
  asm volatile(
      "ld.relaxed.gpu.global.v4.b32 {%0,%1,%2,%3}, [%4];"
      : "=r"(r[0]), "=r"(r[1]), "=r"(r[2]), "=r"(r[3]) : "l"(p) : "memory");
}
__device__ __forceinline__ uint32_t ldg32(const void* p) {
  uint32_t r;
  asm volatile("ld.global.nc.b32 %0, [%1];" : "=r"(r) : "l"(p));
  return r;
}
__device__ __forceinline__ uint32_t ldg16(const void* p) {
  uint16_t r;
  asm volatile("ld.global.nc.b16 %0, [%1];" : "=h"(r) : "l"(p));
  return r;
}
__device__ __forceinline__ uint4 ldg128(const void* p) {
  uint4 r;
  asm volatile("ld.global.nc.v4.b32 {%0,%1,%2,%3}, [%4];" : "=r"(r.x), "=r"(r.y), "=r"(r.z), "=r"(r.w) : "l"(p));
  return r;
}
__device__ __forceinline__ void l2_prefetch(const void* p, uint32_t bytes) {
  asm volatile("cp.async.bulk.prefetch.L2.global [%0], %1;" ::"l"(p), "r"(bytes) : "memory");
}
__device__ __forceinline__ float rcp_hw(float x) {
  float r;
  asm("rcp.approx.ftz.f32 %0, %1;" : "=f"(r) : "f"(x));
  return r;
}
__device__ __forceinline__ void warp_bulk_load(uint32_t sdst, const void* gsrc, uint32_t bytes, uint32_t bar) {
  asm volatile(
      "{\n.reg .pred p;\nelect.sync _|p, 0xffffffff;\n"
      "@p mbarrier.arrive.expect_tx.shared::cta.b64 _, [%3], %2;\n"
      "@p cp.async.bulk.shared::cluster.global.mbarrier::complete_tx::bytes [%0], [%1], %2, [%3];\n}\n"
      ::"r"(sdst), "l"(gsrc), "r"(bytes), "r"(bar) : "memory");
}
__device__ __forceinline__ void warp_tma3d(uint32_t dst, const CUtensorMap* tm, uint32_t bar, uint32_t bytes, int c1, int c2) {
  asm volatile(
      "{\n.reg .pred p;\nelect.sync _|p, 0xffffffff;\n"
      "@p mbarrier.arrive.expect_tx.shared::cta.b64 _, [%2], %3;\n"
      "@p cp.async.bulk.tensor.3d.shared::cluster.global.mbarrier::complete_tx::bytes [%0], [%1, {%6,%4,%5}], [%2];\n}\n"
      ::"r"(dst), "l"(tm), "r"(bar), "r"(bytes), "r"(c1), "r"(c2), "r"(0) : "memory");
}
__device__ __forceinline__ void warp_arrive(uint32_t bar) {
  asm volatile("{\n.reg .pred p;\nelect.sync _|p, 0xffffffff;\n@p mbarrier.arrive.shared::cta.b64 _, [%0];\n}\n" ::"r"(bar) : "memory");
}
__device__ __forceinline__ uint32_t pack_trunc(float lo, float hi) {
  return __byte_perm(__float_as_uint(lo), __float_as_uint(hi), 0x7632);
}
__device__ __forceinline__ void add_partial(float (&y)[8], const uint32_t (&r)[4], uint32_t c0, bool first) {
#pragma unroll
  for (int e = 0; e < 4; e++) {
    const float lo = __uint_as_float(r[e] * 65536u + (e ? 0x8000u : c0)), hi = __uint_as_float(r[e]);
    y[2 * e] = first ? lo : y[2 * e] + lo;
    y[2 * e + 1] = first ? hi : y[2 * e + 1] + hi;
  }
}
__device__ __forceinline__ void spin_cycles(uint32_t n) {
  uint32_t t0, t;
  asm volatile("mov.u32 %0, %%clock;" : "=r"(t0));
  do { asm volatile("mov.u32 %0, %%clock;" : "=r"(t)); } while (t - t0 < n);
}
__device__ __forceinline__ void sts128(uint32_t a, uint32_t x, uint32_t y, uint32_t z, uint32_t w) {
  asm volatile("st.shared.v4.b32 [%0], {%1,%2,%3,%4};" ::"r"(a), "r"(x), "r"(y), "r"(z), "r"(w) : "memory");
}
__device__ __forceinline__ void lds128(uint32_t a, uint32_t (&r)[4]) {
  asm volatile("ld.shared.v4.b32 {%0,%1,%2,%3}, [%4];" : "=r"(r[0]), "=r"(r[1]), "=r"(r[2]), "=r"(r[3]) : "r"(a) : "memory");
}

__device__ __forceinline__ uint32_t lds32(uint32_t a) {
  uint32_t r;
  asm volatile("ld.shared.b32 %0, [%1];" : "=r"(r) : "r"(a) : "memory");
  return r;
}
__device__ __forceinline__ void store_out(__nv_bfloat16* out, uint32_t woff, uint32_t x2s, uint32_t gb0, uint32_t gb1,
                                          const float (&y)[8]) {
  const uint32_t gb[2] = {gb0, gb1};
  uint32_t xa[2][4];
  lds128(x2s, xa[0]);
  lds128(x2s + 512, xa[1]);
  uint32_t* const oo = (uint32_t*)out + woff;
#pragma unroll
  for (int e = 0; e < 4; e++)
    oo[(e >> 1) * 4 + (e & 1) * 8 * 256] =
        pack_bf16(fmaf(bf_lo(gb[e >> 1]), y[2 * e], __uint_as_float(xa[e >> 1][(e & 1) * 2])),
                  fmaf(bf_hi(gb[e >> 1]), y[2 * e + 1], __uint_as_float(xa[e >> 1][(e & 1) * 2 + 1])));
}

constexpr int SK = 2048, WIN = 512;
constexpr int FF = 1792, FSL = 224;
constexpr int NTILES = 80;
constexpr int NSLOT = 4;
constexpr uint32_t SLOT = 32768;
constexpr uint32_t SM_PARK = 0;
constexpr uint32_t SM_RING = 3 * SLOT;
constexpr uint32_t SM_TAB = 7 * SLOT;
constexpr uint32_t SM_RED = SM_TAB + 2048;
constexpr uint32_t SM_BAR = SM_RED + 256;
constexpr uint32_t SM_WBAR = SM_BAR + 128;
constexpr uint32_t SM_SBAR = SM_WBAR + 256;
constexpr uint32_t BAR_SLAB = 64, BAR_UV = 72, BAR_X2 = 80, BAR_TAG = 88;
constexpr uint32_t SM_TOTAL = SM_SBAR + 112;

struct Scratch {
  uint4 P[16 * 8 * 8 * 1024];
  uint4 G[16 * 8 * 32 * 32];
  uint4 mod1[8 * 256];
  uint4 mod2[512];
  uint4 uv[2 * 448];
  uint4 stat[16 * 8 * 8];
  uint32_t epoch;
};
__device__ Scratch g_scratch;

#define TS(i) do { } while (0)
#define TR(code)
#define CK_(v)
#define CKS(i, v)

struct Params {
  const __nv_bfloat16* x;
  const __nv_bfloat16* c;
  const __nv_bfloat16* wmod;
  const __nv_bfloat16* wo;
  const __nv_bfloat16* w1;
  const __nv_bfloat16* w2;
  __nv_bfloat16* out;
  Scratch* s;
};

constexpr uint32_t HI128 = (1024 >> 4) | (1u << 30);
constexpr uint32_t HI64 = (512 >> 4) | (2u << 30);
constexpr int LB_MN128 = (16384 >> 4) << 16;
constexpr int LB_K128 = 1 << 16;
constexpr int LB_W1 = (4096 >> 4) << 16;

template <int I> struct IC {
  __host__ __device__ constexpr operator int() const { return I; }
};
template <int I, int N, typename F> __device__ __forceinline__ void static_for(F&& f) {
  if constexpr (I < N) {
    f(IC<I>{});
    static_for<I + 1, N>(f);
  }
}

struct Ring {
  uint32_t base16, bars;
  __device__ __forceinline__ uint32_t wait_full(uint32_t slot, uint32_t parity) const {
    mbar_wait(bars + slot * 8, parity);
    return base16 + slot * (SLOT >> 4);
  }
  __device__ __forceinline__ void release(uint32_t slot) const {
    warp_arrive(bars + 32 + slot * 8);
  }
};

__device__ __forceinline__ float silu_c(uint32_t bits) {
  float x = bf_lo(bits);
  return round_bf16(x * rcp_hw(1.f + ex2(-1.4426950408889634f * x)));
}
__device__ __forceinline__ void pack8(uint32_t (&o)[4], const float* v) {
  o[0] = pack_bf16(v[0], v[1]); o[1] = pack_bf16(v[2], v[3]); o[2] = pack_bf16(v[4], v[5]); o[3] = pack_bf16(v[6], v[7]);
}

template <int TAG, int N>
__device__ __forceinline__ void issue_pkts(const uint4* p, int stride, uint32_t (*r)[4]) {
#pragma unroll
  for (int i = 0; i < N; i++) ld_pkt(p + i * stride, r[i]);
}
__device__ __forceinline__ void ld_mod(const uint4* p, uint32_t tag, uint32_t (&r)[4]) {
  int spins = 0;
  ld_pkt(p, r);
  while (r[2] != tag && ++spins < SPIN_LIMIT) ld_pkt(p, r);
}

#define EARLY_TILES 2
#define PF_WMOD 1
#define MOD1_DELAY 500
#define RED3_UNIT 3
#define JLO 2
#define NITEM2 24
#define FIN_DELAY0 800
#define FIN_DELAY1 0
#define G_DELAY 300

__device__ __forceinline__ float reduce8(float (&a)[8], int lane) {
  const bool h16 = lane & 16, h8 = lane & 8, h4 = lane & 4;
#pragma unroll
  for (int k = 0; k < 4; k++) a[k] = (h16 ? a[k + 4] : a[k]) + __shfl_xor_sync(0xffffffffu, h16 ? a[k] : a[k + 4], 16);
#pragma unroll
  for (int k = 0; k < 2; k++) a[k] = (h8 ? a[k + 2] : a[k]) + __shfl_xor_sync(0xffffffffu, h8 ? a[k] : a[k + 2], 8);
  const float r = (h4 ? a[1] : a[0]) + __shfl_xor_sync(0xffffffffu, h4 ? a[0] : a[1], 4);
  return r + __shfl_xor_sync(0xffffffffu, r, 2);
}
__device__ __forceinline__ void fma8(float (&a)[8], float s, uint32_t w0, uint32_t w1, uint32_t w2, uint32_t w3) {
  a[0] = fmaf(s, bf_lo(w0), a[0]); a[1] = fmaf(s, bf_hi(w0), a[1]);
  a[2] = fmaf(s, bf_lo(w1), a[2]); a[3] = fmaf(s, bf_hi(w1), a[3]);
  a[4] = fmaf(s, bf_lo(w2), a[4]); a[5] = fmaf(s, bf_hi(w2), a[5]);
  a[6] = fmaf(s, bf_lo(w3), a[6]); a[7] = fmaf(s, bf_hi(w3), a[7]);
}

enum { NB_TAB = 1, NB_WG0 = 2, NB_WG1 = 3, NB_HELP = 4, NB_INIT = 5, NB_PASS0 = 6, NB_GATHER = 7, NB_PARK = 8, NB_PROD = 9 };

__global__ void __launch_bounds__(512, 1)
adaln_block_kernel(const __grid_constant__ CUtensorMap tmWq, const __grid_constant__ CUtensorMap tmK,
                   const __grid_constant__ CUtensorMap tmV, const __grid_constant__ CUtensorMap tmWo,
                   const __grid_constant__ CUtensorMap tmW1, const __grid_constant__ CUtensorMap tmW2,
                   const __grid_constant__ CUtensorMap tmWm, const __grid_constant__ CUtensorMap tmP,
                   const Params p) {
  extern __shared__ __align__(1024) uint8_t smem_raw[];
  const uint32_t sb = smem_u32(smem_raw);
  const int tid = threadIdx.x, lane = tid & 31;
  const int warp = __shfl_sync(0xffffffffu, tid >> 5, 0);
  const int bid = blockIdx.x;
  const int j = ((bid >> (4 + JLO)) << JLO) | (bid & ((1 << JLO) - 1)), rt = (bid >> JLO) & 15;
  const uint32_t bars = sb + SM_BAR;

  if (warp >= 12) {
    asm volatile("setmaxnreg.dec.sync.aligned.u32 24;");
    if (warp == 12) {
      if (lane < 11) mbar_init(bars + lane * 8, lane >= 4 && lane < 8 ? 8 : lane == 9 ? 2 : 1);
      mbar_init(sb + SM_WBAR + lane * 8, 1);
      if (lane < 14) mbar_init(sb + SM_SBAR + lane * 8, 8);
      asm volatile("fence.mbarrier_init.release.cluster;" ::: "memory");
      __syncwarp();
      warp_tma3d(sb + SM_RING + 3 * SLOT, &tmWm, bars + BAR_SLAB, 8192, 0, bid);
      if (lane == 0) {
        tma3d(sb + SM_RING + 3 * SLOT + 4096, &tmWm, bars + BAR_SLAB, 0, 256, bid);
        asm volatile("prefetch.tensormap [%0];" ::"l"(&tmWq) : "memory");
      }
      bar_arrive(NB_INIT, 160);
      mbar_wait_long(bars + BAR_SLAB, 0);
      uint32_t s = 0, ph = 1;
#pragma unroll 1
      for (int tt = 0; tt < NTILES; tt++) {
        const CUtensorMap* tm;
        int c1, c2;
        uint32_t bytes = SLOT;
        if (tt < 16) {
          tm = &tmWq; c1 = (tt & 3) * 128; c2 = (j * 4 + (((tt >> 2) + 1) & 3)) * 2;
        } else if (tt < 48) {
          const int u = tt - 16;
          const bool isK = (u == 0) || ((u & 1) && u != 31);
          const int n = isK ? ((u + 1) >> 1) : (u == 31 ? 15 : (u >> 1) - 1);
          tm = isK ? &tmK : &tmV; c1 = j * SK + (SK - WIN) + (n & 3) * 128; c2 = 0;
        } else if (tt < 64) {
          const int u = tt - 48;
          tm = &tmWo; c1 = j * 512 + (u & 1) * 256; c2 = u >> 1;
        } else if (tt < 72) {
          tm = &tmW1; c1 = (tt - 64) * 64; c2 = j * 7; bytes = 28672;
        } else {
          tm = &tmW2; c1 = j * FSL; c2 = tt - 72; bytes = 28672;
        }
        if (tt == EARLY_TILES) bar_sync(NB_PROD, 160);
        mbar_wait_long(bars + 32 + s * 8, ph);
        warp_tma3d(sb + SM_RING + s * SLOT, tm, bars + s * 8, bytes, c1, c2);
        if (++s == 4) { s = 0; ph ^= 1; }
      }
    }
  } else if (warp >= 8) {
    CK_(c0);
    asm volatile("setmaxnreg.dec.sync.aligned.u32 40;");
    const int t = tid - 256, hw = warp - 8, q = lane & 3;
    float* const red = (float*)(smem_raw + SM_RED);
    uint32_t tag;
    float a[8];
    {
      uint32_t cb[4];
#pragma unroll
      for (int i = 0; i < 4; i++) cb[i] = ldg16(p.c + t + 128 * i);
      asm volatile("ld.relaxed.gpu.global.u32 %0, [%1];" : "=r"(tag) : "l"(&p.s->epoch) : "memory");
      bar_sync(NB_INIT, 160);
      CK_(c2);
      tag += 1;
      float sc[4];
#pragma unroll
      for (int i = 0; i < 4; i++) sc[i] = silu_c(cb[i]);
#pragma unroll
      for (int k = 0; k < 8; k++) a[k] = 0.f;
      if (t == 0) *(uint32_t*)(smem_raw + SM_BAR + BAR_TAG) = tag;
      mbar_wait(bars + BAR_SLAB, 0);
      CK_(c3);
      bar_arrive(NB_GATHER, 384);
#pragma unroll
      for (int i = 0; i < 4; i++) {
        uint32_t w[4];
        lds128(sb + SM_RING + 3 * SLOT + (t + 128 * i) * 16, w);
        fma8(a, sc[i], w[0], w[1], w[2], w[3]);
      }
      float r = reduce8(a, lane);
      r += __shfl_xor_sync(0xffffffffu, r, 1);
      if (q == 0) red[hw * 8 + (lane >> 2)] = r;
      CK_(c4);
      bar_sync(NB_HELP, 128);
      CK_(c5);
      if (hw == 0) {
        const int cl = lane & 7;
        float v = round_bf16(red[cl] + red[8 + cl] + red[16 + cl] + red[24 + cl]);
        if (bid >= 64) v = 1.f + v;
        float vn = __shfl_down_sync(0xffffffffu, v, 1);
        uint32_t wd = pack_bf16(v, vn);
        uint32_t w0 = __shfl_sync(0xffffffffu, wd, (lane & 1) * 4);
        uint32_t w1 = __shfl_sync(0xffffffffu, wd, (lane & 1) * 4 + 2);
        if (lane < 16) st_pkt(&p.s->mod1[(lane >> 1) * 256 + bid * 2 + (lane & 1)], w0, w1, tag, 0);
      }
      uint32_t r0[4], r1[4];
      const uint4* src = &p.s->mod1[j * 256 + t];
      CK_(c6);
      spin_cycles(MOD1_DELAY);
      CK_(c7);
      int spins = 0;
      do {
        ld_pkt(src, r0);
        ld_pkt(src + 128, r1);
      } while ((r0[2] != tag || r1[2] != tag) && ++spins < SPIN_LIMIT);
      const int g = t >> 2, pp = q * 2;
      const uint32_t ad = sb + SM_TAB + (uint32_t)(g * 4 + (pp & 3)) * 16 + (pp >> 2) * 4;
      asm volatile("st.shared.b32 [%0], %1;" ::"r"(ad + 8), "r"(r0[0]) : "memory");
      asm volatile("st.shared.b32 [%0], %1;" ::"r"(ad + 24), "r"(r0[1]) : "memory");
      asm volatile("st.shared.b32 [%0], %1;" ::"r"(ad), "r"(r1[0]) : "memory");
      asm volatile("st.shared.b32 [%0], %1;" ::"r"(ad + 16), "r"(r1[1]) : "memory");
      bar_arrive(NB_TAB, 384);
      bar_arrive(NB_PROD, 160);
      CK_(c8);
      CKS(0, c0); CKS(2, c2); CKS(3, c3); CKS(4, c4); CKS(5, c5); CKS(6, c6); CKS(7, c7); CKS(8, c8);
    }
    bar_sync(NB_PASS0, 384);
    if (t < 8) l2_prefetch((const char*)p.wo + (size_t)bid * 32768 + t * 4096, 4096);
    else if (t < 12) l2_prefetch((const char*)p.w1 + (size_t)bid * 14336 + (t - 8) * 3584, 3584);
    else if (t < 16) l2_prefetch((const char*)p.w2 + (size_t)bid * 14336 + (t - 12) * 3584, 3584);
    {
#pragma unroll
      for (int k = 0; k < 8; k++) a[k] = 0.f;
#pragma unroll 1
      for (int b = 0; b < 8; b++) {
        const int row = b * 64 + (t >> 1);
        const uint4 w = ldg128(p.wmod + (size_t)row * 3072 + 1024 + bid * 16 + (t & 1) * 8);
        fma8(a, silu_c(ldg16(p.c + row)), w.x, w.y, w.z, w.w);
      }
      const float r = reduce8(a, lane);
      if ((lane & 2) == 0) red[hw * 16 + (lane & 1) * 8 + (lane >> 2)] = r;
      bar_sync(NB_HELP, 128);
      if (hw == 0) {
        const int cl = lane & 15;
        float v = round_bf16(red[cl] + red[16 + cl] + red[32 + cl] + red[48 + cl]);
        if ((bid >> 5) == 2) v = 1.f + v;
        float vn = __shfl_down_sync(0xffffffffu, v, 1);
        uint32_t wd = pack_bf16(v, vn);
        uint32_t w0 = __shfl_sync(0xffffffffu, wd, q * 2);
        uint32_t w1 = __shfl_sync(0xffffffffu, wd, q * 2 + 8);
        const int vec = (0x2130 >> ((bid >> 5) * 4)) & 3;
        if (lane < 4) st_pkt(&p.s->mod2[((bid & 31) * 4 + vec) * 4 + lane], w0, w1, tag, 0);
      }
    }
    if (hw >= 2) {
      const int isv = hw - 2;
      if (bid < 112) {
        const int kk = lane >> 1;
        const uint4* mp = &p.s->mod2[(isv ? 3 : 1) * 4 + ((kk & 7) >> 1)];
#pragma unroll
        for (int k = 0; k < 8; k++) a[k] = 0.f;
#pragma unroll 1
        for (int g = 0; g < 32; g++) {
          const uint4 w = ldg128(p.w1 + (size_t)(g * 16 + kk) * FF + bid * 16 + (lane & 1) * 8);
          uint32_t m[4];
          ld_mod(mp + g * 16, tag, m);
          const uint32_t mw = (kk & 8) ? m[1] : m[0];
          fma8(a, (kk & 1) ? bf_hi(mw) : bf_lo(mw), w.x, w.y, w.z, w.w);
        }
        const float r = reduce8(a, lane) * (isv ? 0.5f : 1.f);
        const float r1 = __shfl_down_sync(0xffffffffu, r, 4), r2 = __shfl_down_sync(0xffffffffu, r, 8),
                    r3 = __shfl_down_sync(0xffffffffu, r, 12);
        if ((lane & 14) == 0)
          st_pkt(&p.s->uv[isv * 448 + bid * 4 + (lane & 1) * 2 + (lane >> 4)], (__float_as_uint(r) & ~1u) | (tag & 1u),
                 __float_as_uint(r1), __float_as_uint(r2), __float_as_uint(r3));
      }
#pragma unroll 1
      for (int i = lane; i < 56; i += 32) {
        uint32_t m[4];
        int spins = 0;
        do { ld_pkt(&p.s->uv[isv * 448 + j * 56 + i], m); } while (((m[0] ^ tag) & 1u) && ++spins < SPIN_LIMIT);
        const uint32_t ad = sb + SM_TAB + i * 32 + isv * 8;
        asm volatile("st.shared.v2.b32 [%0], {%1,%2};" ::"r"(ad), "r"(m[0]), "r"(m[1]) : "memory");
        asm volatile("st.shared.v2.b32 [%0], {%1,%2};" ::"r"(ad + 16), "r"(m[2]), "r"(m[3]) : "memory");
      }
      __syncwarp();
      warp_arrive(bars + BAR_UV);
    }
    {
      uint32_t mga[4], mg2[4], mgb[4];
      const uint4* mp = &p.s->mod2[((lane >> 2) * 4 + hw) * 16 + q];
      ld_mod(mp, tag, mga);
      ld_mod(mp + 4, tag, mg2);
      ld_mod(mp + 8, tag, mgb);
      if (lane >= 24) asm volatile("st.shared.v2.b32 [%0], {%1,%2};" ::"r"(sb + SM_TAB + 1792 + ((((lane >> 2) & 1) * 4 + hw) * 4 + q) * 8),
                                   "r"(mgb[0]), "r"(mgb[1]) : "memory");
      const __nv_bfloat16* xp = p.x + (size_t)(rt * 128 + j * 16 + (lane >> 1)) * 512 + hw * 16 + (lane & 1) * 8;
      const uint32_t x2s = sb + SM_PARK + SLOT + hw * 1024 + lane * 16;
      uint4 xv[4];
#pragma unroll
      for (int i = 0; i < 4; i++) xv[i] = ldg128(xp + i * 64);
      bar_sync(NB_PARK, 384);
#pragma unroll
      for (int i = 0; i < 4; i++) sts128(x2s + i * 4096, xv[i].x, xv[i].y, xv[i].z, xv[i].w);
#pragma unroll
      for (int i = 0; i < 4; i++) xv[i] = ldg128(xp + (4 + i) * 64);
#pragma unroll
      for (int i = 0; i < 4; i++) sts128(x2s + (4 + i) * 4096, xv[i].x, xv[i].y, xv[i].z, xv[i].w);
      __syncwarp();
      float s0 = 0.f, s1 = 0.f, v0 = 0.f, v1 = 0.f;
      uint32_t ph = 0;
      const uint32_t land = sb + SM_PARK + hw * 8192, lbar = sb + SM_WBAR + 192 + hw * 16;
      auto item_issue = [&](int n) { warp_tma3d(land + (n & 1) * 4096, &tmP, lbar + (n & 1) * 8, 4096, (n & 7) * 4 + hw, (rt * 8 + j) * 8); };
      mbar_wait_long(sb + SM_SBAR, 0);
      item_issue(0);
#pragma unroll 1
      for (int n = 0; n < 14; n++) {
        const int cc = n & 7;
        const bool ex1 = n < 8;
        const bool pre = n < 13 && __all_sync(0xffffffffu, mbar_test(sb + SM_SBAR + (n + 1) * 8, 0));
        if (pre) item_issue(n + 1);
        float y[8];
#pragma unroll 1
        for (int spins = 0; spins < SPIN_LIMIT; spins++) {
          mbar_wait(lbar + (n & 1) * 8, (ph >> (n & 1)) & 1);
          ph ^= 1u << (n & 1);
          uint32_t bad = 0;
#pragma unroll
          for (int hf = 0; hf < 2; hf++) {
            uint32_t r[4][4];
#pragma unroll
            for (int i = 0; i < 4; i++) lds128(land + (n & 1) * 4096 + (hf * 4 + i) * 512 + lane * 16, r[i]);
            bad |= ex1 ? ~(r[0][0] & r[1][0] & r[2][0] & r[3][0]) : (r[0][0] | r[1][0] | r[2][0] | r[3][0]);
#pragma unroll
            for (int i = 0; i < 4; i++) add_partial(y, r[i], ex1 ? 0u : 0x10000u, (hf | i) == 0);
            fence_regs(y);
          }
          if (__all_sync(0xffffffffu, (bad & 1u) == 0)) break;
          item_issue(n);
        }
        const int src = cc * 4 + q;
        const uint32_t ma = __shfl_sync(0xffffffffu, ex1 ? mga[0] : mgb[0], src), mb = __shfl_sync(0xffffffffu, ex1 ? mga[1] : mgb[1], src);
        if (ex1) {
          uint32_t xr[4];
          asm volatile("ldmatrix.sync.aligned.m8n8.x4.shared.b16 {%0,%1,%2,%3}, [%4];"
                       : "=r"(xr[0]), "=r"(xr[1]), "=r"(xr[2]), "=r"(xr[3])
                       : "r"(sb + SM_PARK + SLOT + hw * 1024 + cc * 4096 + (lane & 15) * 32 + (lane >> 4) * 16) : "memory");
          const uint32_t mc = __shfl_sync(0xffffffffu, mg2[0], src), md = __shfl_sync(0xffffffffu, mg2[1], src);
#pragma unroll
          for (int e = 0; e < 4; e++) {
            const uint32_t m = e < 2 ? ma : mb;
            const float u = fmaf(bf_lo(m), y[2 * e], bf_lo(xr[e])), v = fmaf(bf_hi(m), y[2 * e + 1], bf_hi(xr[e]));
            y[2 * e] = u; y[2 * e + 1] = v;
            if (e & 1) { s1 += u + v; v1 = fmaf(u, u, fmaf(v, v, v1)); }
            else { s0 += u + v; v0 = fmaf(u, u, fmaf(v, v, v0)); }
          }
          st_pkt(p.s->G + ((rt * 8 + j) * 32 + cc * 4 + hw) * 32 + lane, pack_tag<0>(y[0] * bf_lo(mc), y[1] * bf_hi(mc)),
                 pack_bf16(y[2] * bf_lo(mc), y[3] * bf_hi(mc)), pack_bf16(y[4] * bf_lo(md), y[5] * bf_hi(md)),
                 pack_bf16(y[6] * bf_lo(md), y[7] * bf_hi(md)));
          sts128(x2s + cc * 4096, __float_as_uint(y[0]), __float_as_uint(y[1]), __float_as_uint(y[2]), __float_as_uint(y[3]));
          sts128(x2s + cc * 4096 + 512, __float_as_uint(y[4]), __float_as_uint(y[5]), __float_as_uint(y[6]), __float_as_uint(y[7]));
          if (n == 7) {
            const bool o1 = lane & 1, o2 = lane & 2;
            float c0 = (o1 ? v0 : s0) + __shfl_xor_sync(0xffffffffu, o1 ? s0 : v0, 1);
            float c1 = (o1 ? v1 : s1) + __shfl_xor_sync(0xffffffffu, o1 ? s1 : v1, 1);
            c0 = (o2 ? c1 : c0) + __shfl_xor_sync(0xffffffffu, o2 ? c0 : c1, 2);
            *(float*)(smem_raw + SM_PARK + hw * 8192 + lane * 4) = c0;
            bar_sync(NB_HELP, 128);
            if (hw == 0) {
              const float* ps = (const float*)(smem_raw + SM_PARK) + lane;
              const float m = (c0 + ps[2048] + ps[4096] + ps[6144]) * (1.f / 512.f);
              const float mean = __shfl_sync(0xffffffffu, m, lane & ~1), sq = __shfl_sync(0xffffffffu, m, lane | 1);
              const float rs = 0.5f * rsqrtf(fmaxf(fmaf(-mean, mean, sq), 0.f) + 1e-5f), mr = -mean * rs;
              const float rs1 = __shfl_down_sync(0xffffffffu, rs, 2), mr1 = __shfl_down_sync(0xffffffffu, mr, 2);
              if (q == 0)
                st_pkt(&p.s->stat[(rt * 8 + j) * 8 + (lane >> 2)], (__float_as_uint(rs) & ~1u) | (tag & 1u), __float_as_uint(mr),
                       __float_as_uint(rs1), __float_as_uint(mr1));
              warp_arrive(bars + BAR_X2);
            }
          }
        } else {
          store_out(p.out, (uint32_t)(rt * 128 + 16 * j + (lane >> 2)) * 256 + (cc * 4 + hw) * 8 + q, x2s + cc * 4096, ma, mb, y);
        }
        if (n < 13 && !pre) {
          mbar_wait_long(sb + SM_SBAR + (n + 1) * 8, 0);
          item_issue(n + 1);
        }
      }
    }
  } else {
    const int wg = warp >> 2;
    const int q = lane & 3, gq = lane >> 2;
    const Ring ring{(sb + SM_RING) >> 4, bars};
    const uint32_t xoff = (uint32_t)(rt * 128 + 16 * j + warp) * 256 + gq * 8 + q;
    const uint32_t ooff = ((uint32_t)(rt * 8 + j) * 32 + gq) * 32 + warp * 4 + q;
    const uint32_t wblk = sb + SM_PARK + warp * 4096, wprv = wblk + lane * 16;
    const uint32_t wbar = sb + SM_WBAR + warp * 24;
    const uint4* const Gw = p.s->G + (rt * 8 + warp) * 1024;

    {
      const uint32_t* xo = (const uint32_t*)p.x + xoff;
      uint32_t xr[4][4];
      CK_(d0);
#pragma unroll
      for (int c = 0; c < 4; c++) {
        xr[c][0] = ldg32(xo + c * 64);
        xr[c][1] = ldg32(xo + c * 64 + 8 * 256);
        xr[c][2] = ldg32(xo + c * 64 + 4);
        xr[c][3] = ldg32(xo + c * 64 + 4 + 8 * 256);
      }
      CK_(d1);
      fence_regs(xr);
      CK_(d2);
      float s0 = 0.f, s1 = 0.f, v0 = 0.f, v1 = 0.f;
#pragma unroll
      for (int c = 0; c < 4; c++) {
#pragma unroll
        for (int e = 0; e < 4; e++) {
          const float a = bf_lo(xr[c][e]), b = bf_hi(xr[c][e]);
          if (e & 1) { s1 += a + b; v1 = fmaf(a, a, fmaf(b, b, v1)); }
          else { s0 += a + b; v0 = fmaf(a, a, fmaf(b, b, v0)); }
        }
      }
#pragma unroll
      for (int o = 16; o > 0; o >>= 1) {
        s0 += __shfl_xor_sync(0xffffffffu, s0, o);
        s1 += __shfl_xor_sync(0xffffffffu, s1, o);
        v0 += __shfl_xor_sync(0xffffffffu, v0, o);
        v1 += __shfl_xor_sync(0xffffffffu, v1, o);
      }
      const float m0 = s0 * (1.f / 512.f), m1 = s1 * (1.f / 512.f);
      const float r0 = rsqrtf(fmaxf(fmaf(-m0, m0, v0 * (1.f / 512.f)), 0.f) + 1e-5f);
      const float r1 = rsqrtf(fmaxf(fmaf(-m1, m1, v1 * (1.f / 512.f)), 0.f) + 1e-5f);
#pragma unroll
      for (int c = 0; c < 4; c++) {
        st_pkt(p.s->G + ooff + c * 256,
               pack_tag<1>((bf_lo(xr[c][0]) - m0) * r0, (bf_hi(xr[c][0]) - m0) * r0),
               pack_bf16((bf_lo(xr[c][1]) - m1) * r1, (bf_hi(xr[c][1]) - m1) * r1),
               pack_bf16((bf_lo(xr[c][2]) - m0) * r0, (bf_hi(xr[c][2]) - m0) * r0),
               pack_bf16((bf_lo(xr[c][3]) - m1) * r1, (bf_hi(xr[c][3]) - m1) * r1));
      }
      CK_(d3);
      CKS(16, d0); CKS(17, d1); CKS(18, d2); CKS(19, d3);

    }
    asm volatile("setmaxnreg.inc.sync.aligned.u32 224;");
    uint32_t qf[8][4];
    {
      uint32_t h[32][4];
      float acc[64];
      const uint4* Gin = Gw + lane;
      bar_sync(NB_GATHER, 384);
      if (G_DELAY) spin_cycles(G_DELAY);
#pragma unroll
      for (int c = 0; c < 3; c++) warp_bulk_load(wblk + c * SLOT, Gw + c * 256, 4096, wbar + c * 8);
#pragma unroll
      for (int c = 0; c < 4; c++) {
        mbar_wait(wbar + (c % 3) * 8, c / 3);
#pragma unroll
        for (int i = 0; i < 8; i++) lds128(wprv + (c % 3) * SLOT + i * 512, h[c * 8 + i]);
        verify8_tag1<512>(Gin + c * 256, h + c * 8);
        if (c == 0) {
          warp_bulk_load(wblk, Gw + 768, 4096, wbar);
          TS(1);
          bar_sync(NB_TAB, 384);
        }
#pragma unroll
        for (int i = 0; i < 8; i++) {
          uint32_t m[4];
          lds128(sb + SM_TAB + (uint32_t)((c * 8 + i) * 4 + q) * 16, m);
          uint32_t* hh = h[c * 8 + i];
          hh[0] = hfma2_bf16(hh[0], m[0], m[2]);
          hh[1] = hfma2_bf16(hh[1], m[0], m[2]);
          hh[2] = hfma2_bf16(hh[2], m[1], m[3]);
          hh[3] = hfma2_bf16(hh[3], m[1], m[3]);
        }
        fence_frags<8>(h + c * 8);
        const uint32_t b = ring.wait_full(c, 0);
        if (c > 0) { wg_wait<0>(); ring.release(c - 1); }
        if (c == 0) TS(2);
        wg_fence();
        static_for<0, 8>([&](auto K) { wgmma_rs_n128_tb1<LB_MN128 + K * 128, HI128>(acc, h[c * 8 + K], b, (c | K) != 0); });
        wg_commit();
      }
      bar_arrive(NB_PASS0, 384);
#pragma unroll 1
      for (int ps = 1; ps < 4; ps++) {
        wg_wait<0>();
        ring.release(3);
        fence_regs(acc);
#pragma unroll
        for (int i = 0; i < 8; i++) {
          uint32_t o[4];
          pack8(o, acc + 8 * i);
          sts128(wprv + (ps - 1) * SLOT + i * 512, o[0], o[1], o[2], o[3]);
        }
#pragma unroll
        for (int c = 0; c < 4; c++) {
          const uint32_t b = ring.wait_full(c, ps & 1);
          if (c > 0) { wg_wait<0>(); ring.release(c - 1); }
          wg_fence();
          static_for<0, 8>([&](auto K) { wgmma_rs_n128_tb1<LB_MN128 + K * 128, HI128>(acc, h[c * 8 + K], b, (c | K) != 0); });
          wg_commit();
        }
      }
      wg_wait<0>();
      ring.release(3);
      fence_regs(acc);
#pragma unroll
      for (int i = 0; i < 8; i++) pack8(qf[i], acc + 8 * i);
    }
    fence_regs(qf);
    TS(3);

    float S[64];
    {
      float O[64];
      uint32_t P[8][4];
      const float cs = 0.08838834764831845f * 1.4426950408889634f;
      const int TAU = 0x41800000;
      float m0, m1, l0, l1;

      auto float_block_max = [&]() {
        float b0 = fmaxf(S[0], S[1]), b1 = fmaxf(S[2], S[3]);
#pragma unroll
        for (int i = 1; i < 16; i++) {
          b0 = fmaxf(b0, fmaxf(S[4 * i], S[4 * i + 1]));
          b1 = fmaxf(b1, fmaxf(S[4 * i + 2], S[4 * i + 3]));
        }
        b0 = fmaxf(b0, __shfl_xor_sync(0xffffffffu, b0, 1)); b1 = fmaxf(b1, __shfl_xor_sync(0xffffffffu, b1, 1));
        b0 = fmaxf(b0, __shfl_xor_sync(0xffffffffu, b0, 2)); b1 = fmaxf(b1, __shfl_xor_sync(0xffffffffu, b1, 2));
        m0 = b0 * cs; m1 = b1 * cs;
      };
      auto first_block_max = [&]() {
        int a0 = max(__float_as_int(S[0]), __float_as_int(S[1]));
        int a1 = max(__float_as_int(S[2]), __float_as_int(S[3]));
#pragma unroll
        for (int i = 1; i < 16; i++) {
          a0 = __vimax3_s32(a0, __float_as_int(S[4 * i]), __float_as_int(S[4 * i + 1]));
          a1 = __vimax3_s32(a1, __float_as_int(S[4 * i + 2]), __float_as_int(S[4 * i + 3]));
        }
        a0 = max(a0, __shfl_xor_sync(0xffffffffu, a0, 1)); a1 = max(a1, __shfl_xor_sync(0xffffffffu, a1, 1));
        a0 = max(a0, __shfl_xor_sync(0xffffffffu, a0, 2)); a1 = max(a1, __shfl_xor_sync(0xffffffffu, a1, 2));
        m0 = __int_as_float(a0) * cs; m1 = __int_as_float(a1) * cs;
        if (__any_sync(0xffffffffu, (a0 | a1) < 0)) float_block_max();
      };
      auto scale_sub = [&]() {
#pragma unroll
        for (int i = 0; i < 16; i++) {
          S[4 * i] = fmaf(S[4 * i], cs, -m0); S[4 * i + 1] = fmaf(S[4 * i + 1], cs, -m0);
          S[4 * i + 2] = fmaf(S[4 * i + 2], cs, -m1); S[4 * i + 3] = fmaf(S[4 * i + 3], cs, -m1);
        }
      };
      auto exps = [&](int i0, int i1) {
#pragma unroll
        for (int i = i0; i < i1; i++) {
          S[4 * i] = ex2(S[4 * i]); S[4 * i + 1] = ex2(S[4 * i + 1]);
          S[4 * i + 2] = ex2(S[4 * i + 2]); S[4 * i + 3] = ex2(S[4 * i + 3]);
          l0 += S[4 * i]; l1 += S[4 * i + 2]; l0 += S[4 * i + 1]; l1 += S[4 * i + 3];
        }
      };
      {
        const uint32_t b = ring.wait_full(0, 0);
        wg_fence();
        static_for<0, 8>([&](auto K) { wgmma_rs_n128_tb0<LB_K128 + (K >> 2) * 1024 + (K & 3) * 2, HI128>(S, qf[K], b, K != 0); });
        wg_commit();
        wg_wait<0>();
        fence_regs(S);
        ring.release(0);
        float_block_max();
        scale_sub();
        l0 = 0.f; l1 = 0.f;
        exps(0, 16);
#pragma unroll
        for (int i = 0; i < 8; i++) pack8(P[i], S + 8 * i);
      }
      fence_regs(P);
      if (wg == 1) bar_arrive(2, 256);
#pragma unroll 1
      for (int n = 1; n < 16; n++) {
        const uint32_t tk = 2 * n - 1, tv = 2 * n;
        const bool newhead = (n & 3) == 0;
        const uint32_t bk = ring.wait_full(tk & 3, (tk >> 2) & 1);
        const uint32_t bv = ring.wait_full(tv & 3, (tv >> 2) & 1);
        bar_sync(2 + wg, 256);
        wg_fence();
        static_for<0, 8>([&](auto K) { wgmma_rs_n128_tb0<LB_K128 + (K >> 2) * 1024 + (K & 3) * 2, HI128>(S, qf[K], bk, K != 0); });
        wg_commit();
        static_for<0, 8>([&](auto K) { wgmma_rs_n128_tb1<LB_MN128 + K * 128, HI128>(O, P[K], bv, K != 0 || (n & 3) != 1); });
        wg_commit();
        bar_arrive(2 + (wg ^ 1), 256);
        wg_wait<1>();
        fence_regs(S);
        ring.release(tk & 3);
        if ((n & 3) == 3 && n != 15) {
          fence_regs(qf);
#pragma unroll
          for (int i = 0; i < 8; i++) lds128(wprv + (n >> 2) * SLOT + i * 512, qf[i]);
        }
        float f0 = 1.f, f1 = 1.f;
        bool resc = newhead;
        if (newhead) {
          l0 += __shfl_xor_sync(0xffffffffu, l0, 1); l1 += __shfl_xor_sync(0xffffffffu, l1, 1);
          l0 += __shfl_xor_sync(0xffffffffu, l0, 2); l1 += __shfl_xor_sync(0xffffffffu, l1, 2);
          f0 = rcp_hw(l0); f1 = rcp_hw(l1);
          l0 = 0.f; l1 = 0.f;
          first_block_max();
          scale_sub();
        } else {
          scale_sub();
          int a0 = __vimax3_s32(__float_as_int(S[0]), __float_as_int(S[1]), __float_as_int(S[1]));
          int a1 = __vimax3_s32(__float_as_int(S[2]), __float_as_int(S[3]), __float_as_int(S[3]));
#pragma unroll
          for (int i = 1; i < 16; i++) {
            a0 = __vimax3_s32(a0, __float_as_int(S[4 * i]), __float_as_int(S[4 * i + 1]));
            a1 = __vimax3_s32(a1, __float_as_int(S[4 * i + 2]), __float_as_int(S[4 * i + 3]));
          }
          if (__any_sync(0xffffffffu, max(a0, a1) > TAU)) {
            a0 = max(a0, 0); a1 = max(a1, 0);
            a0 = max(a0, __shfl_xor_sync(0xffffffffu, a0, 1)); a1 = max(a1, __shfl_xor_sync(0xffffffffu, a1, 1));
            a0 = max(a0, __shfl_xor_sync(0xffffffffu, a0, 2)); a1 = max(a1, __shfl_xor_sync(0xffffffffu, a1, 2));
            const float d0 = __int_as_float(a0), d1 = __int_as_float(a1);
#pragma unroll
            for (int i = 0; i < 16; i++) { S[4 * i] -= d0; S[4 * i + 1] -= d0; S[4 * i + 2] -= d1; S[4 * i + 3] -= d1; }
            m0 += d0; m1 += d1;
            f0 = ex2(-d0); f1 = ex2(-d1);
            l0 *= f0; l1 *= f1;
            resc = true;
          }
        }
        exps(0, 4);
        wg_wait<0>();
        fence_regs(O);
        fence_regs(P);
        ring.release(tv & 3);
        if (resc) {
#pragma unroll
          for (int i = 0; i < 16; i++) {
            O[4 * i] *= f0; O[4 * i + 1] *= f0; O[4 * i + 2] *= f1; O[4 * i + 3] *= f1;
          }
          if (newhead) {
#pragma unroll
            for (int i = 0; i < 8; i++) {
              uint32_t o[4];
              pack8(o, O + 8 * i);
              sts128(wprv + ((n >> 2) - 1) * SLOT + i * 512, o[0], o[1], o[2], o[3]);
            }
          }
        }
        exps(4, 16);
#pragma unroll
        for (int i = 0; i < 8; i++) pack8(P[i], S + 8 * i);
        fence_regs(P);
        fence_regs(O);
      }
      {
        const uint32_t bv = ring.wait_full(3, 1);
        if (wg == 0) bar_sync(2, 256);
        wg_fence();
        static_for<0, 8>([&](auto K) { wgmma_rs_n128_tb1<LB_MN128 + K * 128, HI128>(O, P[K], bv, 1); });
        wg_commit();
        l0 += __shfl_xor_sync(0xffffffffu, l0, 1); l1 += __shfl_xor_sync(0xffffffffu, l1, 1);
        l0 += __shfl_xor_sync(0xffffffffu, l0, 2); l1 += __shfl_xor_sync(0xffffffffu, l1, 2);
        const float f0 = rcp_hw(l0), f1 = rcp_hw(l1);
        wg_wait<0>();
        fence_regs(O);
        ring.release(3);
#pragma unroll
        for (int i = 0; i < 8; i++) {
          qf[i][0] = pack_bf16(O[8 * i] * f0, O[8 * i + 1] * f0); qf[i][1] = pack_bf16(O[8 * i + 2] * f1, O[8 * i + 3] * f1);
          qf[i][2] = pack_bf16(O[8 * i + 4] * f0, O[8 * i + 5] * f0); qf[i][3] = pack_bf16(O[8 * i + 6] * f1, O[8 * i + 7] * f1);
        }
      }
    }
    fence_regs(qf);
    TS(4);

    uint4* const Pout = p.s->P + ((size_t)(rt * 8 + warp) * 8 + j) * 1024 + lane;
    const uint32_t tag = *(volatile uint32_t*)(smem_raw + SM_BAR + BAR_TAG);

    float acc2[32];
    uint32_t pk[4][4];
    auto pack_partial = [&](auto TAGC) {
      fence_regs(acc2);
#pragma unroll
      for (int i = 0; i < 4; i++) {
#pragma unroll
        for (int e = 0; e < 4; e++) pk[i][e] = pack_trunc(acc2[8 * i + 2 * e], acc2[8 * i + 2 * e + 1]);
        pk[i][0] = TAGC ? (pk[i][0] | 1u) : (pk[i][0] & ~1u);
      }
      fence_regs(pk);
    };
    auto store_partial = [&](int step) {
#pragma unroll
      for (int i = 0; i < 4; i++) st_pkt(Pout + ((step & 7) * 4 + i) * 32, pk[i][0], pk[i][1], pk[i][2], pk[i][3]);
    };
    auto chunk_sent = [&](int step) { warp_arrive(sb + SM_SBAR + step * 8); };
    const uint4* const Gin = Gw + lane;
    auto g_issue = [&](int u) { warp_bulk_load(wblk + 2 * SLOT + (u & 1) * 2048, Gw + u * 128, 2048, wbar + (u & 1) * 8); };

    uint32_t tl = 0, b = ring.wait_full(0, 0);
    auto next_tile = [&]() {
      const uint32_t cur = tl & 3;
      tl++;
      b = ring.wait_full(tl & 3, (tl >> 2) & 1);
      wg_wait<0>();
      TR(4);
      ring.release(cur);
    };
    {
      uint32_t o[24][4];
#pragma unroll
      for (int i = 0; i < 24; i++) lds128(wprv + (i >> 3) * SLOT + (i & 7) * 512, o[i]);
#pragma unroll 1
      for (int cc = 0; cc < 8; cc++) {
        wg_fence();
        static_for<0, 16>([&](auto K) { wgmma_rs_n64_tb1<K * 128, HI128>(acc2, o[K], b, K != 0); });
        wg_commit();
        if (cc > 0) store_partial(cc - 1);
        next_tile();
        wg_fence();
        static_for<0, 16>([&](auto K) { wgmma_rs_n64_tb1<K * 128, HI128>(acc2, K < 8 ? o[16 + (K & 7)] : qf[K & 7], b, 1); });
        wg_commit();
        if (cc > 0) chunk_sent(cc - 1);
        else bar_arrive(NB_PARK, 384);
        if (cc == 6) { g_issue(0); g_issue(1); }
        next_tile();
        pack_partial(IC<1>{});
      }
    }
    TS(5);

    uint32_t H[14][4];
    {
      float acca[64], accb[48];
      const uint4* const statp = &p.s->stat[(rt * 8 + warp) * 8];
#pragma unroll 1
      for (int u = 0; u < 8; u++) {
        uint32_t fa[4][4];
        mbar_wait(wbar + (u & 1) * 8, ((u >> 1) + (u & 1)) & 1);
#pragma unroll
        for (int i = 0; i < 4; i++) lds128(wprv + 2 * SLOT + (u & 1) * 2048 + i * 512, fa[i]);
        verify4_tag0<512>(Gin + u * 128, fa);
        wg_fence();
        static_for<0, 4>([&](auto K) { wgmma_rs_n128_tb1<LB_W1 + K * 64, HI64>(acca, fa[K], b, (u | K) != 0); });
        static_for<0, 4>([&](auto K) { wgmma_rs_n96_tb1<LB_W1 + 1024 + K * 64, HI64>(accb, fa[K], b, (u | K) != 0); });
        wg_commit();
        if (u == 0) store_partial(7);
        if (u == 1) chunk_sent(7);
        if (u < 5) g_issue(u + 2);
        if (u == 7) warp_bulk_load(wblk + 2 * SLOT, statp, 128, wbar + 16);
        next_tile();
        if (u == 5) g_issue(7);
      }
      fence_regs(acca);
      fence_regs(accb);
      TS(9);
      mbar_wait(bars + BAR_UV, 0);
      uint32_t xr[4];
      mbar_wait(wbar + 16, 1);
      lds128(wblk + 2 * SLOT + gq * 16, xr);
      {
        int spins = 0;
        while (((xr[0] ^ tag) & 1u) && ++spins < SPIN_LIMIT) ld_pkt(statp + gq, xr);
      }
      const float ra0 = __uint_as_float(xr[0]), rb0 = __uint_as_float(xr[1]), ra1 = __uint_as_float(xr[2]),
                  rb1 = __uint_as_float(xr[3]);
#pragma unroll
      for (int i = 0; i < 28; i++) {
        uint32_t m[4];
        lds128(sb + SM_TAB + (i * 4 + q) * 16, m);
        const float u0 = __uint_as_float(m[0]), u1 = __uint_as_float(m[1]), w0 = __uint_as_float(m[2]), w1 = __uint_as_float(m[3]);
        const float* acc = i < 16 ? acca + 4 * i : accb + 4 * (i - 16);
        const float z0 = fmaf(acc[0], ra0, fmaf(u0, rb0, w0)), z1 = fmaf(acc[1], ra0, fmaf(u1, rb0, w1));
        const float z2 = fmaf(acc[2], ra1, fmaf(u0, rb1, w0)), z3 = fmaf(acc[3], ra1, fmaf(u1, rb1, w1));
        H[i >> 1][(i & 1) * 2] = pack_bf16(fmaf(z0, tanh_hw(z0), z0), fmaf(z1, tanh_hw(z1), z1));
        H[i >> 1][(i & 1) * 2 + 1] = pack_bf16(fmaf(z2, tanh_hw(z2), z2), fmaf(z3, tanh_hw(z3), z3));
      }
    }
    fence_regs(H);
    TS(10);
    const int go = 24 + (warp ^ 4);
#pragma unroll 1
    for (int cc = 0; cc < 8; cc++) {
      wg_fence();
      static_for<0, 14>([&](auto K) { wgmma_rs_n64_tb1<K * 128, HI128>(acc2, H[K], b, K != 0); });
      wg_commit();
      if (cc > 1) chunk_sent(8 + cc - 2);
      if (cc > 0) store_partial(cc - 1);
      if (cc < 7) next_tile();
      wg_wait<0>();
      pack_partial(IC<0>{});
    }
    store_partial(7);
    TS(11);
    {
      const uint4* const Pown = p.s->P + (size_t)(rt * 8 + j) * 8192 + go * 32 + lane;
      uint32_t r[8][4];
      float y[8];
      mbar_wait(bars + BAR_X2, 0);
      spin_cycles(wg ? FIN_DELAY1 : FIN_DELAY0);
      issue_pkts<0, 8>(Pown, 1024, r);
      verify8_tag0<16384>(Pown, r);
      TS(13);
#pragma unroll
      for (int s = 0; s < 8; s++) add_partial(y, r[s], 0u, s == 0);
      const uint32_t gt = sb + SM_TAB + 1792 + ((go - 24) * 4 + q) * 8;
      store_out(p.out, (uint32_t)(rt * 128 + 16 * j + gq) * 256 + go * 8 + q, sb + SM_PARK + SLOT + go * 1024 + lane * 16,
                lds32(gt), lds32(gt + 4), y);
    }
    TS(12);
    if (bid == 0 && tid == 0) asm volatile("st.relaxed.gpu.global.u32 [%0], %1;" ::"l"(&p.s->epoch), "r"(tag) : "memory");
  }
}

typedef CUresult (*EncodeFn)(CUtensorMap*, CUtensorMapDataType, cuuint32_t, void*, const cuuint64_t*, const cuuint64_t*,
                             const cuuint32_t*, const cuuint32_t*, CUtensorMapInterleave, CUtensorMapSwizzle,
                             CUtensorMapL2promotion, CUtensorMapFloatOOBfill);

static void make_map(EncodeFn fn, CUtensorMap* tm, const void* ptr, int inner, int rows, int cols, int box_rows, int box_outer,
                     CUtensorMapSwizzle swz) {
  cuuint64_t gd[3] = {(cuuint64_t)inner, (cuuint64_t)rows, (cuuint64_t)(cols / inner)};
  cuuint64_t gs[2] = {(cuuint64_t)cols * 2, (cuuint64_t)inner * 2};
  cuuint32_t bx[3] = {(cuuint32_t)inner, (cuuint32_t)box_rows, (cuuint32_t)box_outer};
  cuuint32_t es[3] = {1, 1, 1};
  fn(tm, CU_TENSOR_MAP_DATA_TYPE_BFLOAT16, 3, const_cast<void*>(ptr), gd, gs, bx, es, CU_TENSOR_MAP_INTERLEAVE_NONE, swz,
     CU_TENSOR_MAP_L2_PROMOTION_L2_128B, CU_TENSOR_MAP_FLOAT_OOB_FILL_NONE);
}

extern "C" void kernel_launch(void* const* d_in, const int* in_sizes, int n_in, void* d_out, int out_size) {
  (void)in_sizes; (void)n_in; (void)out_size;
  void* fnp = nullptr;
  cudaDriverEntryPointQueryResult qr;
  cudaGetDriverEntryPoint("cuTensorMapEncodeTiled", &fnp, cudaEnableDefault, &qr);
  EncodeFn fn = (EncodeFn)fnp;
  CUtensorMap tmWq, tmK, tmV, tmWo, tmW1, tmW2, tmWm, tmP;
  make_map(fn, &tmWq, d_in[3], 64, 512, 4096, 128, 2, CU_TENSOR_MAP_SWIZZLE_128B);
  make_map(fn, &tmK, d_in[1], 64, 8 * SK, 128, 128, 2, CU_TENSOR_MAP_SWIZZLE_128B);
  make_map(fn, &tmV, d_in[2], 64, 8 * SK, 128, 128, 2, CU_TENSOR_MAP_SWIZZLE_128B);
  make_map(fn, &tmWo, d_in[4], 64, 4096, 512, 256, 1, CU_TENSOR_MAP_SWIZZLE_128B);
  make_map(fn, &tmW1, d_in[6], 32, 512, FF, 64, 7, CU_TENSOR_MAP_SWIZZLE_64B);
  make_map(fn, &tmW2, d_in[7], 64, FF, 512, 224, 1, CU_TENSOR_MAP_SWIZZLE_128B);
  make_map(fn, &tmWm, d_in[9], 8, 512, 3072, 256, 1, CU_TENSOR_MAP_SWIZZLE_NONE);
  Params p;
  p.x = (const __nv_bfloat16*)d_in[0];
  p.c = (const __nv_bfloat16*)d_in[8];
  p.wmod = (const __nv_bfloat16*)d_in[9];
  p.wo = (const __nv_bfloat16*)d_in[4];
  p.w1 = (const __nv_bfloat16*)d_in[6];
  p.w2 = (const __nv_bfloat16*)d_in[7];
  p.out = (__nv_bfloat16*)d_out;
  cudaGetSymbolAddress((void**)&p.s, g_scratch);
  {
    cuuint64_t gd[3] = {256, 32, 1024};
    cuuint64_t gs[2] = {512, 16384};
    cuuint32_t bx[3] = {256, 1, 8};
    cuuint32_t es[3] = {1, 1, 1};
    fn(&tmP, CU_TENSOR_MAP_DATA_TYPE_BFLOAT16, 3, (void*)p.s->P, gd, gs, bx, es, CU_TENSOR_MAP_INTERLEAVE_NONE,
       CU_TENSOR_MAP_SWIZZLE_NONE, CU_TENSOR_MAP_L2_PROMOTION_NONE, CU_TENSOR_MAP_FLOAT_OOB_FILL_NONE);
  }
  cudaFuncSetAttribute(adaln_block_kernel, cudaFuncAttributeMaxDynamicSharedMemorySize, SM_TOTAL);
  adaln_block_kernel<<<128, 512, SM_TOTAL>>>(tmWq, tmK, tmV, tmWo, tmW1, tmW2, tmWm, tmP, p);
}
```

```cpp
#include <cuda_runtime.h>
#include <cuda_bf16.h>
#include <cuda.h>
#include <stdint.h>

template <int OFF, uint32_t HI>
__device__ __forceinline__ void wgmma_rs_n128_tb0(float (&d)[64], const uint32_t (&a)[4], uint32_t lo, int sd) {
  asm volatile("{\n.reg .pred p;\n.reg .b32 l;\n.reg .b64 db;\nsetp.ne.b32 p, %69, 0;\n"
    "add.u32 l, %68, %70;\nmov.b64 db, {l, %71};\n"
    "wgmma.mma_async.sync.aligned.m64n128k16.f32.bf16.bf16 "
    "{%0,%1,%2,%3,%4,%5,%6,%7,%8,%9,%10,%11,%12,%13,%14,%15,"
    "%16,%17,%18,%19,%20,%21,%22,%23,%24,%25,%26,%27,%28,%29,%30,%31,"
    "%32,%33,%34,%35,%36,%37,%38,%39,%40,%41,%42,%43,%44,%45,%46,%47,"
    "%48,%49,%50,%51,%52,%53,%54,%55,%56,%57,%58,%59,%60,%61,%62,%63}, "
    "{%64,%65,%66,%67}, db, p, 1, 1, 0;\n}\n"
    : "+f"(d[0]), "+f"(d[1]), "+f"(d[2]), "+f"(d[3]), "+f"(d[4]), "+f"(d[5]), "+f"(d[6]), "+f"(d[7]),
      "+f"(d[8]), "+f"(d[9]), "+f"(d[10]), "+f"(d[11]), "+f"(d[12]), "+f"(d[13]), "+f"(d[14]), "+f"(d[15]),
      "+f"(d[16]), "+f"(d[17]), "+f"(d[18]), "+f"(d[19]), "+f"(d[20]), "+f"(d[21]), "+f"(d[22]), "+f"(d[23]),
      "+f"(d[24]), "+f"(d[25]), "+f"(d[26]), "+f"(d[27]), "+f"(d[28]), "+f"(d[29]), "+f"(d[30]), "+f"(d[31]),
      "+f"(d[32]), "+f"(d[33]), "+f"(d[34]), "+f"(d[35]), "+f"(d[36]), "+f"(d[37]), "+f"(d[38]), "+f"(d[39]),
      "+f"(d[40]), "+f"(d[41]), "+f"(d[42]), "+f"(d[43]), "+f"(d[44]), "+f"(d[45]), "+f"(d[46]), "+f"(d[47]),
      "+f"(d[48]), "+f"(d[49]), "+f"(d[50]), "+f"(d[51]), "+f"(d[52]), "+f"(d[53]), "+f"(d[54]), "+f"(d[55]),
      "+f"(d[56]), "+f"(d[57]), "+f"(d[58]), "+f"(d[59]), "+f"(d[60]), "+f"(d[61]), "+f"(d[62]), "+f"(d[63])
    : "r"(a[0]), "r"(a[1]), "r"(a[2]), "r"(a[3]), "r"(lo), "r"(sd), "n"(OFF), "n"(HI));
}

template <int OFF, uint32_t HI>
__device__ __forceinline__ void wgmma_rs_n128_tb1(float (&d)[64], const uint32_t (&a)[4], uint32_t lo, int sd) {
  asm volatile("{\n.reg .pred p;\n.reg .b32 l;\n.reg .b64 db;\nsetp.ne.b32 p, %69, 0;\n"
    "add.u32 l, %68, %70;\nmov.b64 db, {l, %71};\n"
    "wgmma.mma_async.sync.aligned.m64n128k16.f32.bf16.bf16 "
    "{%0,%1,%2,%3,%4,%5,%6,%7,%8,%9,%10,%11,%12,%13,%14,%15,"
    "%16,%17,%18,%19,%20,%21,%22,%23,%24,%25,%26,%27,%28,%29,%30,%31,"
    "%32,%33,%34,%35,%36,%37,%38,%39,%40,%41,%42,%43,%44,%45,%46,%47,"
    "%48,%49,%50,%51,%52,%53,%54,%55,%56,%57,%58,%59,%60,%61,%62,%63}, "
    "{%64,%65,%66,%67}, db, p, 1, 1, 1;\n}\n"
    : "+f"(d[0]), "+f"(d[1]), "+f"(d[2]), "+f"(d[3]), "+f"(d[4]), "+f"(d[5]), "+f"(d[6]), "+f"(d[7]),
      "+f"(d[8]), "+f"(d[9]), "+f"(d[10]), "+f"(d[11]), "+f"(d[12]), "+f"(d[13]), "+f"(d[14]), "+f"(d[15]),
      "+f"(d[16]), "+f"(d[17]), "+f"(d[18]), "+f"(d[19]), "+f"(d[20]), "+f"(d[21]), "+f"(d[22]), "+f"(d[23]),
      "+f"(d[24]), "+f"(d[25]), "+f"(d[26]), "+f"(d[27]), "+f"(d[28]), "+f"(d[29]), "+f"(d[30]), "+f"(d[31]),
      "+f"(d[32]), "+f"(d[33]), "+f"(d[34]), "+f"(d[35]), "+f"(d[36]), "+f"(d[37]), "+f"(d[38]), "+f"(d[39]),
      "+f"(d[40]), "+f"(d[41]), "+f"(d[42]), "+f"(d[43]), "+f"(d[44]), "+f"(d[45]), "+f"(d[46]), "+f"(d[47]),
      "+f"(d[48]), "+f"(d[49]), "+f"(d[50]), "+f"(d[51]), "+f"(d[52]), "+f"(d[53]), "+f"(d[54]), "+f"(d[55]),
      "+f"(d[56]), "+f"(d[57]), "+f"(d[58]), "+f"(d[59]), "+f"(d[60]), "+f"(d[61]), "+f"(d[62]), "+f"(d[63])
    : "r"(a[0]), "r"(a[1]), "r"(a[2]), "r"(a[3]), "r"(lo), "r"(sd), "n"(OFF), "n"(HI));
}

template <int OFF, uint32_t HI>
__device__ __forceinline__ void wgmma_rs_n96_tb1(float (&d)[48], const uint32_t (&a)[4], uint32_t lo, int sd) {
  asm volatile("{\n.reg .pred p;\n.reg .b32 l;\n.reg .b64 db;\nsetp.ne.b32 p, %53, 0;\n"
    "add.u32 l, %52, %54;\nmov.b64 db, {l, %55};\n"
    "wgmma.mma_async.sync.aligned.m64n96k16.f32.bf16.bf16 "
    "{%0,%1,%2,%3,%4,%5,%6,%7,%8,%9,%10,%11,%12,%13,%14,%15,"
    "%16,%17,%18,%19,%20,%21,%22,%23,%24,%25,%26,%27,%28,%29,%30,%31,"
    "%32,%33,%34,%35,%36,%37,%38,%39,%40,%41,%42,%43,%44,%45,%46,%47}, "
    "{%48,%49,%50,%51}, db, p, 1, 1, 1;\n}\n"
    : "+f"(d[0]), "+f"(d[1]), "+f"(d[2]), "+f"(d[3]), "+f"(d[4]), "+f"(d[5]), "+f"(d[6]), "+f"(d[7]),
      "+f"(d[8]), "+f"(d[9]), "+f"(d[10]), "+f"(d[11]), "+f"(d[12]), "+f"(d[13]), "+f"(d[14]), "+f"(d[15]),
      "+f"(d[16]), "+f"(d[17]), "+f"(d[18]), "+f"(d[19]), "+f"(d[20]), "+f"(d[21]), "+f"(d[22]), "+f"(d[23]),
      "+f"(d[24]), "+f"(d[25]), "+f"(d[26]), "+f"(d[27]), "+f"(d[28]), "+f"(d[29]), "+f"(d[30]), "+f"(d[31]),
      "+f"(d[32]), "+f"(d[33]), "+f"(d[34]), "+f"(d[35]), "+f"(d[36]), "+f"(d[37]), "+f"(d[38]), "+f"(d[39]),
      "+f"(d[40]), "+f"(d[41]), "+f"(d[42]), "+f"(d[43]), "+f"(d[44]), "+f"(d[45]), "+f"(d[46]), "+f"(d[47])
    : "r"(a[0]), "r"(a[1]), "r"(a[2]), "r"(a[3]), "r"(lo), "r"(sd), "n"(OFF), "n"(HI));
}

template <int OFF, uint32_t HI>
__device__ __forceinline__ void wgmma_rs_n64_tb1(float (&d)[32], const uint32_t (&a)[4], uint32_t lo, int sd) {
  asm volatile("{\n.reg .pred p;\n.reg .b32 l;\n.reg .b64 db;\nsetp.ne.b32 p, %37, 0;\n"
    "add.u32 l, %36, %38;\nmov.b64 db, {l, %39};\n"
    "wgmma.mma_async.sync.aligned.m64n64k16.f32.bf16.bf16 "
    "{%0,%1,%2,%3,%4,%5,%6,%7,%8,%9,%10,%11,%12,%13,%14,%15,"
    "%16,%17,%18,%19,%20,%21,%22,%23,%24,%25,%26,%27,%28,%29,%30,%31}, "
    "{%32,%33,%34,%35}, db, p, 1, 1, 1;\n}\n"
    : "+f"(d[0]), "+f"(d[1]), "+f"(d[2]), "+f"(d[3]), "+f"(d[4]), "+f"(d[5]), "+f"(d[6]), "+f"(d[7]),
      "+f"(d[8]), "+f"(d[9]), "+f"(d[10]), "+f"(d[11]), "+f"(d[12]), "+f"(d[13]), "+f"(d[14]), "+f"(d[15]),
      "+f"(d[16]), "+f"(d[17]), "+f"(d[18]), "+f"(d[19]), "+f"(d[20]), "+f"(d[21]), "+f"(d[22]), "+f"(d[23]),
      "+f"(d[24]), "+f"(d[25]), "+f"(d[26]), "+f"(d[27]), "+f"(d[28]), "+f"(d[29]), "+f"(d[30]), "+f"(d[31])
    : "r"(a[0]), "r"(a[1]), "r"(a[2]), "r"(a[3]), "r"(lo), "r"(sd), "n"(OFF), "n"(HI));
}

template <int STR>
__device__ __forceinline__ void verify8_tag1(const uint4* p, uint32_t (*r)[4]) {
  asm volatile("{\n.reg .pred p, q;\n.reg .b32 a, n;\nmov.u32 n, 0;\n"
    "LAB_CHK:\n"
    "and.b32 a, %0, %4;\n"
    "and.b32 a, a, %8;\n"
    "and.b32 a, a, %12;\n"
    "and.b32 a, a, %16;\n"
    "and.b32 a, a, %20;\n"
    "and.b32 a, a, %24;\n"
    "and.b32 a, a, %28;\n"
    "and.b32 a, a, 1;\nsetp.eq.u32 p, a, 1;\nvote.sync.all.pred p, p, 0xffffffff;\n"
    "@p bra.uni LAB_OK;\n"
    "and.b32 a, %0, 1;\nsetp.ne.u32 q, a, 1;\n"
    "@q ld.relaxed.gpu.global.v4.b32 {%0,%1,%2,%3}, [%32+%33];\n"
    "and.b32 a, %4, 1;\nsetp.ne.u32 q, a, 1;\n"
    "@q ld.relaxed.gpu.global.v4.b32 {%4,%5,%6,%7}, [%32+%34];\n"
    "and.b32 a, %8, 1;\nsetp.ne.u32 q, a, 1;\n"
    "@q ld.relaxed.gpu.global.v4.b32 {%8,%9,%10,%11}, [%32+%35];\n"
    "and.b32 a, %12, 1;\nsetp.ne.u32 q, a, 1;\n"
    "@q ld.relaxed.gpu.global.v4.b32 {%12,%13,%14,%15}, [%32+%36];\n"
    "and.b32 a, %16, 1;\nsetp.ne.u32 q, a, 1;\n"
    "@q ld.relaxed.gpu.global.v4.b32 {%16,%17,%18,%19}, [%32+%37];\n"
    "and.b32 a, %20, 1;\nsetp.ne.u32 q, a, 1;\n"
    "@q ld.relaxed.gpu.global.v4.b32 {%20,%21,%22,%23}, [%32+%38];\n"
    "and.b32 a, %24, 1;\nsetp.ne.u32 q, a, 1;\n"
    "@q ld.relaxed.gpu.global.v4.b32 {%24,%25,%26,%27}, [%32+%39];\n"
    "and.b32 a, %28, 1;\nsetp.ne.u32 q, a, 1;\n"
    "@q ld.relaxed.gpu.global.v4.b32 {%28,%29,%30,%31}, [%32+%40];\n"
    "add.u32 n, n, 1;\nsetp.lt.u32 q, n, 262144;\n@q bra.uni LAB_CHK;\n"
    "LAB_OK:\n"
    "}\n"
    : "+r"(r[0][0]), "+r"(r[0][1]), "+r"(r[0][2]), "+r"(r[0][3]), "+r"(r[1][0]), "+r"(r[1][1]), "+r"(r[1][2]), "+r"(r[1][3]),
      "+r"(r[2][0]), "+r"(r[2][1]), "+r"(r[2][2]), "+r"(r[2][3]), "+r"(r[3][0]), "+r"(r[3][1]), "+r"(r[3][2]), "+r"(r[3][3]),
      "+r"(r[4][0]), "+r"(r[4][1]), "+r"(r[4][2]), "+r"(r[4][3]), "+r"(r[5][0]), "+r"(r[5][1]), "+r"(r[5][2]), "+r"(r[5][3]),
      "+r"(r[6][0]), "+r"(r[6][1]), "+r"(r[6][2]), "+r"(r[6][3]), "+r"(r[7][0]), "+r"(r[7][1]), "+r"(r[7][2]), "+r"(r[7][3])
    : "l"(p), "n"(0 * STR), "n"(1 * STR), "n"(2 * STR), "n"(3 * STR), "n"(4 * STR), "n"(5 * STR), "n"(6 * STR), "n"(7 * STR)
    : "memory");
}

template <int STR>
__device__ __forceinline__ void verify8_rt(const uint4* p, uint32_t (*r)[4], uint32_t tag) {
  asm volatile("{\n.reg .pred p, q;\n.reg .b32 a, b, n;\nmov.u32 n, 0;\n"
    "LAB_CHK:\n"
    "lop3.b32 a, %0, %4, %41, 0x7e;\n"
    "lop3.b32 b, %8, %12, %41, 0x7e;\nor.b32 a, a, b;\n"
    "lop3.b32 b, %16, %20, %41, 0x7e;\nor.b32 a, a, b;\n"
    "lop3.b32 b, %24, %28, %41, 0x7e;\nor.b32 a, a, b;\n"
    "and.b32 a, a, 1;\nsetp.eq.u32 p, a, 0;\nvote.sync.all.pred p, p, 0xffffffff;\n"
    "@p bra.uni LAB_OK;\n"
    "and.b32 a, %0, 1;\nsetp.ne.u32 q, a, %41;\n"
    "@q ld.relaxed.gpu.global.v4.b32 {%0,%1,%2,%3}, [%32+%33];\n"
    "and.b32 a, %4, 1;\nsetp.ne.u32 q, a, %41;\n"
    "@q ld.relaxed.gpu.global.v4.b32 {%4,%5,%6,%7}, [%32+%34];\n"
    "and.b32 a, %8, 1;\nsetp.ne.u32 q, a, %41;\n"
    "@q ld.relaxed.gpu.global.v4.b32 {%8,%9,%10,%11}, [%32+%35];\n"
    "and.b32 a, %12, 1;\nsetp.ne.u32 q, a, %41;\n"
    "@q ld.relaxed.gpu.global.v4.b32 {%12,%13,%14,%15}, [%32+%36];\n"
    "and.b32 a, %16, 1;\nsetp.ne.u32 q, a, %41;\n"
    "@q ld.relaxed.gpu.global.v4.b32 {%16,%17,%18,%19}, [%32+%37];\n"
    "and.b32 a, %20, 1;\nsetp.ne.u32 q, a, %41;\n"
    "@q ld.relaxed.gpu.global.v4.b32 {%20,%21,%22,%23}, [%32+%38];\n"
    "and.b32 a, %24, 1;\nsetp.ne.u32 q, a, %41;\n"
    "@q ld.relaxed.gpu.global.v4.b32 {%24,%25,%26,%27}, [%32+%39];\n"
    "and.b32 a, %28, 1;\nsetp.ne.u32 q, a, %41;\n"
    "@q ld.relaxed.gpu.global.v4.b32 {%28,%29,%30,%31}, [%32+%40];\n"
    "add.u32 n, n, 1;\nsetp.lt.u32 q, n, 262144;\n@q bra.uni LAB_CHK;\n"
    "LAB_OK:\n}\n"
    : "+r"(r[0][0]), "+r"(r[0][1]), "+r"(r[0][2]), "+r"(r[0][3]), "+r"(r[1][0]), "+r"(r[1][1]), "+r"(r[1][2]), "+r"(r[1][3]),
      "+r"(r[2][0]), "+r"(r[2][1]), "+r"(r[2][2]), "+r"(r[2][3]), "+r"(r[3][0]), "+r"(r[3][1]), "+r"(r[3][2]), "+r"(r[3][3]),
      "+r"(r[4][0]), "+r"(r[4][1]), "+r"(r[4][2]), "+r"(r[4][3]), "+r"(r[5][0]), "+r"(r[5][1]), "+r"(r[5][2]), "+r"(r[5][3]),
      "+r"(r[6][0]), "+r"(r[6][1]), "+r"(r[6][2]), "+r"(r[6][3]), "+r"(r[7][0]), "+r"(r[7][1]), "+r"(r[7][2]), "+r"(r[7][3])
    : "l"(p), "n"(0 * STR), "n"(1 * STR), "n"(2 * STR), "n"(3 * STR), "n"(4 * STR), "n"(5 * STR), "n"(6 * STR), "n"(7 * STR), "r"(tag)
    : "memory");
}

template <int STR>
__device__ __forceinline__ void verify4_tag0(const uint4* p, uint32_t (*r)[4]) {
  asm volatile("{\n.reg .pred p, q;\n.reg .b32 a, n;\nmov.u32 n, 0;\n"
    "LAB_CHK:\n"
    "or.b32 a, %0, %4;\n"
    "or.b32 a, a, %8;\n"
    "or.b32 a, a, %12;\n"
    "and.b32 a, a, 1;\nsetp.eq.u32 p, a, 0;\nvote.sync.all.pred p, p, 0xffffffff;\n"
    "@p bra.uni LAB_OK;\n"
    "and.b32 a, %0, 1;\nsetp.ne.u32 q, a, 0;\n"
    "@q ld.relaxed.gpu.global.v4.b32 {%0,%1,%2,%3}, [%16+%17];\n"
    "and.b32 a, %4, 1;\nsetp.ne.u32 q, a, 0;\n"
    "@q ld.relaxed.gpu.global.v4.b32 {%4,%5,%6,%7}, [%16+%18];\n"
    "and.b32 a, %8, 1;\nsetp.ne.u32 q, a, 0;\n"
    "@q ld.relaxed.gpu.global.v4.b32 {%8,%9,%10,%11}, [%16+%19];\n"
    "and.b32 a, %12, 1;\nsetp.ne.u32 q, a, 0;\n"
    "@q ld.relaxed.gpu.global.v4.b32 {%12,%13,%14,%15}, [%16+%20];\n"
    "add.u32 n, n, 1;\nsetp.lt.u32 q, n, 262144;\n@q bra.uni LAB_CHK;\n"
    "LAB_OK:\n"
    "or.b32 %0, %0, 1;\n"
    "or.b32 %4, %4, 1;\n"
    "or.b32 %8, %8, 1;\n"
    "or.b32 %12, %12, 1;\n"
    "}\n"
    : "+r"(r[0][0]), "+r"(r[0][1]), "+r"(r[0][2]), "+r"(r[0][3]), "+r"(r[1][0]), "+r"(r[1][1]), "+r"(r[1][2]), "+r"(r[1][3]),
      "+r"(r[2][0]), "+r"(r[2][1]), "+r"(r[2][2]), "+r"(r[2][3]), "+r"(r[3][0]), "+r"(r[3][1]), "+r"(r[3][2]), "+r"(r[3][3])
    : "l"(p), "n"(0 * STR), "n"(1 * STR), "n"(2 * STR), "n"(3 * STR)
    : "memory");
}

#define SPIN_LIMIT (1 << 18)

__device__ __forceinline__ uint32_t smem_u32(const void* p) { return (uint32_t)__cvta_generic_to_shared(p); }
__device__ __forceinline__ void mbar_init(uint32_t a, uint32_t c) {
  asm volatile("mbarrier.init.shared::cta.b64 [%0], %1;" ::"r"(a), "r"(c) : "memory");
}
__device__ __forceinline__ void mbar_expect(uint32_t a, uint32_t b) {
  asm volatile("mbarrier.arrive.expect_tx.shared::cta.b64 _, [%0], %1;" ::"r"(a), "r"(b) : "memory");
}
__device__ __forceinline__ void mbar_arrive(uint32_t a) {
  asm volatile("mbarrier.arrive.shared::cta.b64 _, [%0];" ::"r"(a) : "memory");
}
__device__ __forceinline__ void mbar_wait(uint32_t a, uint32_t parity) {
  asm volatile(
      "{\n.reg .pred p;\n.reg .u32 n;\nmov.u32 n, 0;\n"
      "LAB_WAIT:\n"
      "mbarrier.try_wait.parity.shared::cta.b64 p, [%0], %1;\n"
      "@p bra LAB_DONE;\n"
      "add.u32 n, n, 1;\n"
      "setp.lt.u32 p, n, 262144;\n"
      "@p bra LAB_WAIT;\n"
      "LAB_DONE:\n}\n" ::"r"(a), "r"(parity) : "memory");
}
__device__ __forceinline__ bool mbar_test(uint32_t a, uint32_t parity) {
  uint32_t ok;
  asm volatile("{\n.reg .pred p;\nmbarrier.test_wait.parity.shared::cta.b64 p, [%1], %2;\nselp.u32 %0, 1, 0, p;\n}\n"
               : "=r"(ok) : "r"(a), "r"(parity) : "memory");
  return ok;
}
__device__ __forceinline__ void tma3d(uint32_t dst, const CUtensorMap* tm, uint32_t bar, int c0, int c1, int c2) {
  asm volatile(
      "cp.async.bulk.tensor.3d.shared::cluster.global.mbarrier::complete_tx::bytes [%0], [%1, {%3,%4,%5}], [%2];"
      ::"r"(dst), "l"(tm), "r"(bar), "r"(c0), "r"(c1), "r"(c2) : "memory");
}
__device__ __forceinline__ void wg_fence() { asm volatile("wgmma.fence.sync.aligned;" ::: "memory"); }
__device__ __forceinline__ void wg_commit() { asm volatile("wgmma.commit_group.sync.aligned;" ::: "memory"); }
template <int N> __device__ __forceinline__ void wg_wait() {
  asm volatile("wgmma.wait_group.sync.aligned %0;" ::"n"(N) : "memory");
}
template <int N> __device__ __forceinline__ void fence_regs(float (&d)[N]) {
#pragma unroll
  for (int i = 0; i < N; i++) asm volatile("" : "+f"(d[i])::"memory");
}
template <int N> __device__ __forceinline__ void fence_regs(uint32_t (&d)[N][4]) {
#pragma unroll
  for (int i = 0; i < N; i++) asm volatile("" : "+r"(d[i][0]), "+r"(d[i][1]), "+r"(d[i][2]), "+r"(d[i][3])::"memory");
}
template <int N> __device__ __forceinline__ void fence_frags(uint32_t (*d)[4]) {
#pragma unroll
  for (int i = 0; i < N; i++) asm volatile("" : "+r"(d[i][0]), "+r"(d[i][1]), "+r"(d[i][2]), "+r"(d[i][3])::"memory");
}
__device__ __forceinline__ void bar_sync(int id, int n) { asm volatile("bar.sync %0, %1;" ::"r"(id), "r"(n) : "memory"); }
__device__ __forceinline__ void bar_arrive(int id, int n) { asm volatile("bar.arrive %0, %1;" ::"r"(id), "r"(n) : "memory"); }

__device__ __forceinline__ uint32_t pack_bf16(float lo, float hi) {
  uint32_t r;
  asm("cvt.rn.bf16x2.f32 %0, %1, %2;" : "=r"(r) : "f"(hi), "f"(lo));
  return r;
}
__device__ __forceinline__ float bf_lo(uint32_t w) { return __uint_as_float(w << 16); }
__device__ __forceinline__ float bf_hi(uint32_t w) { return __uint_as_float(w & 0xFFFF0000u); }
__device__ __forceinline__ float round_bf16(float x) { return bf_lo(pack_bf16(x, 0.f)); }
__device__ __forceinline__ uint32_t hfma2_bf16(uint32_t a, uint32_t b, uint32_t c) {
  uint32_t r;
  asm("fma.rn.bf16x2 %0, %1, %2, %3;" : "=r"(r) : "r"(a), "r"(b), "r"(c));
  return r;
}
__device__ __forceinline__ float ex2(float x) {
  float r;
  asm("ex2.approx.ftz.f32 %0, %1;" : "=f"(r) : "f"(x));
  return r;
}
__device__ __forceinline__ float tanh_hw(float x) {
  float r;
  asm("tanh.approx.f32 %0, %1;" : "=f"(r) : "f"(x));
  return r;
}
template <int TAG> __device__ __forceinline__ uint32_t pack_tag(float lo, float hi) {
  uint32_t w = __byte_perm(__float_as_uint(lo), pack_bf16(lo, hi), 0x7632);
  return TAG ? (w | 1u) : (w & ~1u);
}
__device__ __forceinline__ void st_pkt(uint4* p, uint32_t a, uint32_t b, uint32_t c, uint32_t d) {
  asm volatile(
      "st.relaxed.gpu.global.v4.b32 [%0], {%1,%2,%3,%4};" ::"l"(p), "r"(a), "r"(b), "r"(c), "r"(d) : "memory");
}
__device__ __forceinline__ void ld_pkt(const uint4* p, uint32_t (&r)[4]) {
  asm volatile(
      "ld.relaxed.gpu.global.v4.b32 {%0,%1,%2,%3}, [%4];"
      : "=r"(r[0]), "=r"(r[1]), "=r"(r[2]), "=r"(r[3]) : "l"(p) : "memory");
}
__device__ __forceinline__ uint32_t ldg32(const void* p) {
  uint32_t r;
  asm volatile("ld.global.nc.b32 %0, [%1];" : "=r"(r) : "l"(p));
  return r;
}
__device__ __forceinline__ uint32_t ldg16(const void* p) {
  uint16_t r;
  asm volatile("ld.global.nc.b16 %0, [%1];" : "=h"(r) : "l"(p));
  return r;
}
__device__ __forceinline__ uint4 ldg128(const void* p) {
  uint4 r;
  asm volatile("ld.global.nc.v4.b32 {%0,%1,%2,%3}, [%4];" : "=r"(r.x), "=r"(r.y), "=r"(r.z), "=r"(r.w) : "l"(p));
  return r;
}
__device__ __forceinline__ void l2_prefetch(const void* p, uint32_t bytes) {
  asm volatile("cp.async.bulk.prefetch.L2.global [%0], %1;" ::"l"(p), "r"(bytes) : "memory");
}
__device__ __forceinline__ float rcp_hw(float x) {
  float r;
  asm("rcp.approx.ftz.f32 %0, %1;" : "=f"(r) : "f"(x));
  return r;
}
__device__ __forceinline__ void warp_bulk_load(uint32_t sdst, const void* gsrc, uint32_t bytes, uint32_t bar) {
  asm volatile(
      "{\n.reg .pred p;\nelect.sync _|p, 0xffffffff;\n"
      "@p mbarrier.arrive.expect_tx.shared::cta.b64 _, [%3], %2;\n"
      "@p cp.async.bulk.shared::cluster.global.mbarrier::complete_tx::bytes [%0], [%1], %2, [%3];\n}\n"
      ::"r"(sdst), "l"(gsrc), "r"(bytes), "r"(bar) : "memory");
}
__device__ __forceinline__ void warp_tma3d(uint32_t dst, const CUtensorMap* tm, uint32_t bar, uint32_t bytes, int c1, int c2) {
  asm volatile(
      "{\n.reg .pred p;\nelect.sync _|p, 0xffffffff;\n"
      "@p mbarrier.arrive.expect_tx.shared::cta.b64 _, [%2], %3;\n"
      "@p cp.async.bulk.tensor.3d.shared::cluster.global.mbarrier::complete_tx::bytes [%0], [%1, {%6,%4,%5}], [%2];\n}\n"
      ::"r"(dst), "l"(tm), "r"(bar), "r"(bytes), "r"(c1), "r"(c2), "r"(0) : "memory");
}
__device__ __forceinline__ bool elect_one() {
  uint32_t r;
  asm volatile("{\n.reg .pred p;\nelect.sync _|p, 0xffffffff;\nselp.u32 %0, 1, 0, p;\n}\n" : "=r"(r));
  return r;
}
__device__ __forceinline__ void warp_arrive(uint32_t bar) {
  asm volatile("{\n.reg .pred p;\nelect.sync _|p, 0xffffffff;\n@p mbarrier.arrive.shared::cta.b64 _, [%0];\n}\n" ::"r"(bar) : "memory");
}
__device__ __forceinline__ uint32_t pack_trunc(float lo, float hi) {
  return __byte_perm(__float_as_uint(lo), __float_as_uint(hi), 0x7632);
}
__device__ __forceinline__ void add_partial(float (&y)[8], const uint32_t (&r)[4], uint32_t c0, bool first) {
#pragma unroll
  for (int e = 0; e < 4; e++) {
    const float lo = __uint_as_float(r[e] * 65536u + (e ? 0x8000u : c0)), hi = __uint_as_float(r[e]);
    y[2 * e] = first ? lo : y[2 * e] + lo;
    y[2 * e + 1] = first ? hi : y[2 * e + 1] + hi;
  }
}
__device__ __forceinline__ void spin_cycles(uint32_t n) {
  uint32_t t0, t;
  asm volatile("mov.u32 %0, %%clock;" : "=r"(t0));
  do { asm volatile("mov.u32 %0, %%clock;" : "=r"(t)); } while (t - t0 < n);
}
__device__ __forceinline__ void sts128(uint32_t a, uint32_t x, uint32_t y, uint32_t z, uint32_t w) {
  asm volatile("st.shared.v4.b32 [%0], {%1,%2,%3,%4};" ::"r"(a), "r"(x), "r"(y), "r"(z), "r"(w) : "memory");
}
__device__ __forceinline__ void lds128(uint32_t a, uint32_t (&r)[4]) {
  asm volatile("ld.shared.v4.b32 {%0,%1,%2,%3}, [%4];" : "=r"(r[0]), "=r"(r[1]), "=r"(r[2]), "=r"(r[3]) : "r"(a) : "memory");
}

__device__ __forceinline__ uint32_t lds32(uint32_t a) {
  uint32_t r;
  asm volatile("ld.shared.b32 %0, [%1];" : "=r"(r) : "r"(a) : "memory");
  return r;
}
__device__ __forceinline__ void store_out(__nv_bfloat16* out, uint32_t woff, uint32_t x2s, uint32_t gb0, uint32_t gb1,
                                          const float (&y)[8]) {
  const uint32_t gb[2] = {gb0, gb1};
  uint32_t xa[2][4];
  lds128(x2s, xa[0]);
  lds128(x2s + 2048, xa[1]);
  uint32_t* const oo = (uint32_t*)out + woff;
#pragma unroll
  for (int e = 0; e < 4; e++)
    oo[(e >> 1) * 4 + (e & 1) * 8 * 256] =
        pack_bf16(fmaf(bf_lo(gb[e >> 1]), y[2 * e], __uint_as_float(xa[e >> 1][(e & 1) * 2])),
                  fmaf(bf_hi(gb[e >> 1]), y[2 * e + 1], __uint_as_float(xa[e >> 1][(e & 1) * 2 + 1])));
}

constexpr int SK = 2048, WIN = 512;
constexpr int FF = 1792, FSL = 224;
constexpr int NTILES = 80;
constexpr int NSLOT = 4;
constexpr uint32_t SLOT = 32768;
constexpr uint32_t SM_PARK = 0;
constexpr uint32_t SM_RING = 3 * SLOT;
constexpr uint32_t SM_TAB = 7 * SLOT;
constexpr uint32_t SM_RED = SM_TAB + 2048;
constexpr uint32_t SM_BAR = SM_RED + 256;
constexpr uint32_t SM_WBAR = SM_BAR + 128;
constexpr uint32_t SM_SBAR = SM_WBAR + 256;
constexpr uint32_t BAR_SLAB = 64, BAR_UV = 72, BAR_X2 = 80, BAR_TAG = 88;
constexpr uint32_t SM_TOTAL = SM_SBAR + 112;

struct Scratch {
  uint4 P[16 * 8 * 8 * 1024];
  uint4 G[16 * 8 * 32 * 32];
  uint4 mod1[8 * 256];
  uint4 mod2[512];
  uint4 uv[2 * 448];
  uint4 stat[16 * 8 * 8];
  uint32_t epoch;
};
__device__ Scratch g_scratch;

#define TS(i) do { } while (0)
#define TR(code)
#define CK_(v)
#define CKS(i, v)

struct Params {
  const __nv_bfloat16* x;
  const __nv_bfloat16* c;
  const __nv_bfloat16* wmod;
  const __nv_bfloat16* wo;
  const __nv_bfloat16* w1;
  const __nv_bfloat16* w2;
  __nv_bfloat16* out;
  Scratch* s;
};

constexpr uint32_t HI128 = (1024 >> 4) | (1u << 30);
constexpr uint32_t HI64 = (512 >> 4) | (2u << 30);
constexpr int LB_MN128 = (16384 >> 4) << 16;
constexpr int LB_K128 = 1 << 16;
constexpr int LB_W1 = (4096 >> 4) << 16;

template <int I> struct IC {
  __host__ __device__ constexpr operator int() const { return I; }
};
template <int I, int N, typename F> __device__ __forceinline__ void static_for(F&& f) {
  if constexpr (I < N) {
    f(IC<I>{});
    static_for<I + 1, N>(f);
  }
}

struct Ring {
  uint32_t base16, bars;
  __device__ __forceinline__ uint32_t wait_full(uint32_t slot, uint32_t parity) const {
    mbar_wait(bars + slot * 8, parity);
    return base16 + slot * (SLOT >> 4);
  }
  __device__ __forceinline__ void release(uint32_t slot) const {
    warp_arrive(bars + 32 + slot * 8);
  }
};

__device__ __forceinline__ float silu_c(uint32_t bits) {
  float x = bf_lo(bits);
  return round_bf16(x * rcp_hw(1.f + ex2(-1.4426950408889634f * x)));
}
__device__ __forceinline__ void pack8(uint32_t (&o)[4], const float* v) {
  o[0] = pack_bf16(v[0], v[1]); o[1] = pack_bf16(v[2], v[3]); o[2] = pack_bf16(v[4], v[5]); o[3] = pack_bf16(v[6], v[7]);
}

template <int TAG, int N>
__device__ __forceinline__ void issue_pkts(const uint4* p, int stride, uint32_t (*r)[4]) {
#pragma unroll
  for (int i = 0; i < N; i++) ld_pkt(p + i * stride, r[i]);
}
__device__ __forceinline__ void ld_mod(const uint4* p, uint32_t tag, uint32_t (&r)[4]) {
  int spins = 0;
  ld_pkt(p, r);
  while (r[2] != tag && ++spins < SPIN_LIMIT) ld_pkt(p, r);
}

#define EARLY_TILES 2
#define PF_WMOD 1
#define MOD1_DELAY 500
#define RED3_UNIT 3
#define JLO 2
#define NITEM2 24
#define FIN_DELAY0 800
#define FIN_DELAY1 0
#define G_DELAY 300

__device__ __forceinline__ float reduce8(float (&a)[8], int lane) {
  const bool h16 = lane & 16, h8 = lane & 8, h4 = lane & 4;
#pragma unroll
  for (int k = 0; k < 4; k++) a[k] = (h16 ? a[k + 4] : a[k]) + __shfl_xor_sync(0xffffffffu, h16 ? a[k] : a[k + 4], 16);
#pragma unroll
  for (int k = 0; k < 2; k++) a[k] = (h8 ? a[k + 2] : a[k]) + __shfl_xor_sync(0xffffffffu, h8 ? a[k] : a[k + 2], 8);
  const float r = (h4 ? a[1] : a[0]) + __shfl_xor_sync(0xffffffffu, h4 ? a[0] : a[1], 4);
  return r + __shfl_xor_sync(0xffffffffu, r, 2);
}
__device__ __forceinline__ void fma8(float (&a)[8], float s, uint32_t w0, uint32_t w1, uint32_t w2, uint32_t w3) {
  a[0] = fmaf(s, bf_lo(w0), a[0]); a[1] = fmaf(s, bf_hi(w0), a[1]);
  a[2] = fmaf(s, bf_lo(w1), a[2]); a[3] = fmaf(s, bf_hi(w1), a[3]);
  a[4] = fmaf(s, bf_lo(w2), a[4]); a[5] = fmaf(s, bf_hi(w2), a[5]);
  a[6] = fmaf(s, bf_lo(w3), a[6]); a[7] = fmaf(s, bf_hi(w3), a[7]);
}

enum { NB_TAB = 1, NB_WG0 = 2, NB_WG1 = 3, NB_HELP = 4, NB_INIT = 5, NB_PASS0 = 6, NB_GATHER = 7, NB_PARK = 8, NB_PROD = 9 };

__global__ void __launch_bounds__(512, 1)
adaln_block_kernel(const __grid_constant__ CUtensorMap tmWq, const __grid_constant__ CUtensorMap tmK,
                   const __grid_constant__ CUtensorMap tmV, const __grid_constant__ CUtensorMap tmWo,
                   const __grid_constant__ CUtensorMap tmW1, const __grid_constant__ CUtensorMap tmW2,
                   const __grid_constant__ CUtensorMap tmWm, const __grid_constant__ CUtensorMap tmP,
                   const __grid_constant__ CUtensorMap tmX, const Params p) {
  extern __shared__ __align__(1024) uint8_t smem_raw[];
  const uint32_t sb = smem_u32(smem_raw);
  const int tid = threadIdx.x, lane = tid & 31;
  const int warp = __shfl_sync(0xffffffffu, tid >> 5, 0);
  const int bid = blockIdx.x;
  const int j = ((bid >> (4 + JLO)) << JLO) | (bid & ((1 << JLO) - 1)), rt = (bid >> JLO) & 15;
  const uint32_t bars = sb + SM_BAR;

  if (warp >= 12) {
    asm volatile("setmaxnreg.dec.sync.aligned.u32 24;");
    if (warp == 13) {
      if (elect_one()) {
#pragma unroll
        for (int i = 0; i < 28; i++) mbar_init(sb + SM_WBAR + i * 8, i < 26 ? 1 : 4);
#pragma unroll
        for (int i = 0; i < 14; i++) mbar_init(sb + SM_SBAR + i * 8, 8);
        asm volatile("fence.mbarrier_init.release.cluster;" ::: "memory");
      }
      __syncwarp();
      bar_arrive(NB_INIT, 192);
#pragma unroll 1
      for (int n = 0; n < 14; n++) {
        const uint32_t lb = sb + SM_WBAR + 192 + (n & 1) * 8;
        mbar_wait(sb + SM_SBAR + n * 8, 0);
        mbar_wait(lb + 16, ((n >> 1) & 1) ^ 1);
        warp_tma3d(sb + SM_PARK + (n & 1) * 16384, &tmP, lb, n < 8 ? 16384 + 2048 : 16384, (n & 7) * 4, (rt * 8 + j) * 8);
        if (n < 8 && elect_one()) tma3d(sb + SM_PARK + SLOT + n * 4096, &tmX, lb, 0, rt * 128 + j * 16, n * 4);
      }
    } else if (warp == 14) {
      if (elect_one()) {
        asm volatile("prefetch.tensormap [%0];" ::"l"(&tmWq) : "memory");
        asm volatile("prefetch.tensormap [%0];" ::"l"(&tmK) : "memory");
        asm volatile("prefetch.tensormap [%0];" ::"l"(&tmV) : "memory");
        asm volatile("prefetch.tensormap [%0];" ::"l"(&tmWo) : "memory");
        asm volatile("prefetch.tensormap [%0];" ::"l"(&tmP) : "memory");
        asm volatile("prefetch.tensormap [%0];" ::"l"(&tmX) : "memory");
        asm volatile("prefetch.tensormap [%0];" ::"l"(&tmW1) : "memory");
        asm volatile("prefetch.tensormap [%0];" ::"l"(&tmW2) : "memory");
      }
    } else if (warp == 12) {
      if (elect_one()) {
        mbar_init(bars + BAR_SLAB, 1);
        asm volatile("fence.mbarrier_init.release.cluster;" ::: "memory");
        mbar_expect(bars + BAR_SLAB, 8192);
        tma3d(sb + SM_RING + 3 * SLOT, &tmWm, bars + BAR_SLAB, 0, 0, bid);
        tma3d(sb + SM_RING + 3 * SLOT + 4096, &tmWm, bars + BAR_SLAB, 0, 256, bid);
#pragma unroll
        for (int i = 0; i < 4; i++) { mbar_init(bars + i * 8, 1); mbar_init(bars + 32 + i * 8, 8); }
        mbar_init(bars + BAR_UV, 2);
        mbar_init(bars + BAR_X2, 1);
        asm volatile("fence.mbarrier_init.release.cluster;" ::: "memory");
      }
      __syncwarp();
      bar_arrive(NB_INIT, 192);
      mbar_wait(bars + BAR_SLAB, 0);
      uint32_t s = 0, ph = 1;
#pragma unroll 1
      for (int tt = 0; tt < NTILES; tt++) {
        const CUtensorMap* tm;
        int c1, c2;
        uint32_t bytes = SLOT;
        if (tt < 16) {
          tm = &tmWq; c1 = (tt & 3) * 128; c2 = (j * 4 + (((tt >> 2) + 1) & 3)) * 2;
        } else if (tt < 48) {
          const int u = tt - 16;
          const bool isK = (u == 0) || ((u & 1) && u != 31);
          const int n = isK ? ((u + 1) >> 1) : (u == 31 ? 15 : (u >> 1) - 1);
          tm = isK ? &tmK : &tmV; c1 = j * SK + (SK - WIN) + (n & 3) * 128; c2 = 0;
        } else if (tt < 64) {
          const int u = tt - 48;
          tm = &tmWo; c1 = j * 512 + (u & 1) * 256; c2 = u >> 1;
        } else if (tt < 72) {
          tm = &tmW1; c1 = (tt - 64) * 64; c2 = j * 7; bytes = 28672;
        } else {
          tm = &tmW2; c1 = j * FSL; c2 = tt - 72; bytes = 28672;
        }
        if (tt == EARLY_TILES) bar_sync(NB_PROD, 160);
        mbar_wait(bars + 32 + s * 8, ph);
        warp_tma3d(sb + SM_RING + s * SLOT, tm, bars + s * 8, bytes, c1, c2);
        if (++s == 4) { s = 0; ph ^= 1; }
      }
    }
  } else if (warp >= 8) {
    CK_(c0);
    asm volatile("setmaxnreg.dec.sync.aligned.u32 40;");
    const int t = tid - 256, hw = warp - 8, q = lane & 3;
    float* const red = (float*)(smem_raw + SM_RED);
    uint32_t tag;
    float a[8];
    {
      uint32_t cb[4];
#pragma unroll
      for (int i = 0; i < 4; i++) cb[i] = ldg16(p.c + t + 128 * i);
      asm volatile("ld.relaxed.gpu.global.u32 %0, [%1];" : "=r"(tag) : "l"(&p.s->epoch) : "memory");
      bar_sync(NB_INIT, 192);
      CK_(c2);
      tag += 1;
      float sc[4];
#pragma unroll
      for (int i = 0; i < 4; i++) sc[i] = silu_c(cb[i]);
#pragma unroll
      for (int k = 0; k < 8; k++) a[k] = 0.f;
      if (t == 0) *(uint32_t*)(smem_raw + SM_BAR + BAR_TAG) = tag;
      mbar_wait(bars + BAR_SLAB, 0);
      CK_(c3);
      bar_arrive(NB_GATHER, 384);
#pragma unroll
      for (int i = 0; i < 4; i++) {
        uint32_t w[4];
        lds128(sb + SM_RING + 3 * SLOT + (t + 128 * i) * 16, w);
        fma8(a, sc[i], w[0], w[1], w[2], w[3]);
      }
      float r = reduce8(a, lane);
      r += __shfl_xor_sync(0xffffffffu, r, 1);
      if (q == 0) red[hw * 8 + (lane >> 2)] = r;
      CK_(c4);
      bar_sync(NB_HELP, 128);
      CK_(c5);
      if (hw == 0) {
        const int cl = lane & 7;
        float v = round_bf16(red[cl] + red[8 + cl] + red[16 + cl] + red[24 + cl]);
        if (bid >= 64) v = 1.f + v;
        float vn = __shfl_down_sync(0xffffffffu, v, 1);
        uint32_t wd = pack_bf16(v, vn);
        uint32_t w0 = __shfl_sync(0xffffffffu, wd, (lane & 1) * 4);
        uint32_t w1 = __shfl_sync(0xffffffffu, wd, (lane & 1) * 4 + 2);
        if (lane < 16) st_pkt(&p.s->mod1[(lane >> 1) * 256 + bid * 2 + (lane & 1)], w0, w1, tag, 0);
      }
      uint32_t r0[4], r1[4];
      const uint4* src = &p.s->mod1[j * 256 + t];
      CK_(c6);
      spin_cycles(MOD1_DELAY);
      CK_(c7);
      int spins = 0;
      do {
        ld_pkt(src, r0);
        ld_pkt(src + 128, r1);
      } while ((r0[2] != tag || r1[2] != tag) && ++spins < SPIN_LIMIT);
      const int g = t >> 2, pp = q * 2;
      const uint32_t ad = sb + SM_TAB + (uint32_t)(g * 4 + (pp & 3)) * 16 + (pp >> 2) * 4;
      asm volatile("st.shared.b32 [%0], %1;" ::"r"(ad + 8), "r"(r0[0]) : "memory");
      asm volatile("st.shared.b32 [%0], %1;" ::"r"(ad + 24), "r"(r0[1]) : "memory");
      asm volatile("st.shared.b32 [%0], %1;" ::"r"(ad), "r"(r1[0]) : "memory");
      asm volatile("st.shared.b32 [%0], %1;" ::"r"(ad + 16), "r"(r1[1]) : "memory");
      bar_arrive(NB_TAB, 384);
      bar_arrive(NB_PROD, 160);
      CK_(c8);
      CKS(0, c0); CKS(2, c2); CKS(3, c3); CKS(4, c4); CKS(5, c5); CKS(6, c6); CKS(7, c7); CKS(8, c8);
    }
    bar_sync(NB_PASS0, 384);
    if (t < 8) l2_prefetch((const char*)p.wo + (size_t)bid * 32768 + t * 4096, 4096);
    else if (t < 12) l2_prefetch((const char*)p.w1 + (size_t)bid * 14336 + (t - 8) * 3584, 3584);
    else if (t < 16) l2_prefetch((const char*)p.w2 + (size_t)bid * 14336 + (t - 12) * 3584, 3584);
    {
#pragma unroll
      for (int k = 0; k < 8; k++) a[k] = 0.f;
#pragma unroll 1
      for (int b = 0; b < 8; b++) {
        const int row = b * 64 + (t >> 1);
        const uint4 w = ldg128(p.wmod + (size_t)row * 3072 + 1024 + bid * 16 + (t & 1) * 8);
        fma8(a, silu_c(ldg16(p.c + row)), w.x, w.y, w.z, w.w);
      }
      const float r = reduce8(a, lane);
      if ((lane & 2) == 0) red[hw * 16 + (lane & 1) * 8 + (lane >> 2)] = r;
      bar_sync(NB_HELP, 128);
      if (hw == 0) {
        const int cl = lane & 15;
        float v = round_bf16(red[cl] + red[16 + cl] + red[32 + cl] + red[48 + cl]);
        if ((bid >> 5) == 2) v = 1.f + v;
        float vn = __shfl_down_sync(0xffffffffu, v, 1);
        uint32_t wd = pack_bf16(v, vn);
        uint32_t w0 = __shfl_sync(0xffffffffu, wd, q * 2);
        uint32_t w1 = __shfl_sync(0xffffffffu, wd, q * 2 + 8);
        const int vec = (0x2130 >> ((bid >> 5) * 4)) & 3;
        if (lane < 4) st_pkt(&p.s->mod2[((bid & 31) * 4 + vec) * 4 + lane], w0, w1, tag, 0);
      }
    }
    if (hw >= 2) {
      const int isv = hw - 2;
      if (bid < 112) {
        const int kk = lane >> 1;
        const uint4* mp = &p.s->mod2[(isv ? 3 : 1) * 4 + ((kk & 7) >> 1)];
#pragma unroll
        for (int k = 0; k < 8; k++) a[k] = 0.f;
#pragma unroll 1
        for (int g = 0; g < 32; g++) {
          const uint4 w = ldg128(p.w1 + (size_t)(g * 16 + kk) * FF + bid * 16 + (lane & 1) * 8);
          uint32_t m[4];
          ld_mod(mp + g * 16, tag, m);
          const uint32_t mw = (kk & 8) ? m[1] : m[0];
          fma8(a, (kk & 1) ? bf_hi(mw) : bf_lo(mw), w.x, w.y, w.z, w.w);
        }
        const float r = reduce8(a, lane) * (isv ? 0.5f : 1.f);
        const float r1 = __shfl_down_sync(0xffffffffu, r, 4), r2 = __shfl_down_sync(0xffffffffu, r, 8),
                    r3 = __shfl_down_sync(0xffffffffu, r, 12);
        if ((lane & 14) == 0)
          st_pkt(&p.s->uv[isv * 448 + bid * 4 + (lane & 1) * 2 + (lane >> 4)], (__float_as_uint(r) & ~1u) | (tag & 1u),
                 __float_as_uint(r1), __float_as_uint(r2), __float_as_uint(r3));
      }
#pragma unroll 1
      for (int i = lane; i < 56; i += 32) {
        uint32_t m[4];
        int spins = 0;
        do { ld_pkt(&p.s->uv[isv * 448 + j * 56 + i], m); } while (((m[0] ^ tag) & 1u) && ++spins < SPIN_LIMIT);
        const uint32_t ad = sb + SM_TAB + i * 32 + isv * 8;
        asm volatile("st.shared.v2.b32 [%0], {%1,%2};" ::"r"(ad), "r"(m[0]), "r"(m[1]) : "memory");
        asm volatile("st.shared.v2.b32 [%0], {%1,%2};" ::"r"(ad + 16), "r"(m[2]), "r"(m[3]) : "memory");
      }
      __syncwarp();
      warp_arrive(bars + BAR_UV);
    }
    {
      uint32_t mga[4], mg2[4], mgb[4];
      const uint4* mp = &p.s->mod2[((lane >> 2) * 4 + hw) * 16 + q];
      ld_mod(mp, tag, mga);
      ld_mod(mp + 4, tag, mg2);
      ld_mod(mp + 8, tag, mgb);
      if (lane >= 24) asm volatile("st.shared.v2.b32 [%0], {%1,%2};" ::"r"(sb + SM_TAB + 1792 + ((((lane >> 2) & 1) * 4 + hw) * 4 + q) * 8),
                                   "r"(mgb[0]), "r"(mgb[1]) : "memory");
      const uint32_t x2s = sb + SM_PARK + SLOT + hw * 512 + lane * 16;
      const uint4* const Pown = p.s->P + (size_t)(rt * 8 + j) * 8192 + hw * 32 + lane;
      float s0 = 0.f, s1 = 0.f, v0 = 0.f, v1 = 0.f;
      bar_sync(NB_PARK, 384);
      asm volatile("setmaxnreg.inc.sync.aligned.u32 88;");
#pragma unroll 1
      for (int n = 0; n < 14; n++) {
        const int cc = n & 7;
        const bool ex1 = n < 8;
        const uint32_t lb = sb + SM_WBAR + 192 + (n & 1) * 8;
        uint32_t r[8][4];
        float y[8];
        mbar_wait(lb, (n >> 1) & 1);
#pragma unroll
        for (int i = 0; i < 8; i++) lds128(sb + SM_PARK + (n & 1) * 16384 + i * 2048 + hw * 512 + lane * 16, r[i]);
        verify8_rt<16384>(Pown + cc * 128, r, ex1);
        warp_arrive(lb + 16);
#pragma unroll
        for (int i = 0; i < 8; i++) add_partial(y, r[i], ex1 ? 0u : 0x10000u, i == 0);
        const int src = cc * 4 + q;
        const uint32_t ma = __shfl_sync(0xffffffffu, ex1 ? mga[0] : mgb[0], src), mb = __shfl_sync(0xffffffffu, ex1 ? mga[1] : mgb[1], src);
        if (ex1) {
          uint32_t xr[4];
          asm volatile("ldmatrix.sync.aligned.m8n8.x4.shared.b16 {%0,%1,%2,%3}, [%4];"
                       : "=r"(xr[0]), "=r"(xr[1]), "=r"(xr[2]), "=r"(xr[3])
                       : "r"(sb + SM_PARK + SLOT + hw * 512 + cc * 4096 + (lane & 15) * 32 + (lane >> 4) * 16) : "memory");
          const uint32_t mc = __shfl_sync(0xffffffffu, mg2[0], src), md = __shfl_sync(0xffffffffu, mg2[1], src);
#pragma unroll
          for (int e = 0; e < 4; e++) {
            const uint32_t m = e < 2 ? ma : mb;
            const float u = fmaf(bf_lo(m), y[2 * e], bf_lo(xr[e])), v = fmaf(bf_hi(m), y[2 * e + 1], bf_hi(xr[e]));
            y[2 * e] = u; y[2 * e + 1] = v;
            if (e & 1) { s1 += u + v; v1 = fmaf(u, u, fmaf(v, v, v1)); }
            else { s0 += u + v; v0 = fmaf(u, u, fmaf(v, v, v0)); }
          }
          st_pkt(p.s->G + ((rt * 8 + j) * 32 + cc * 4 + hw) * 32 + lane, pack_tag<0>(y[0] * bf_lo(mc), y[1] * bf_hi(mc)),
                 pack_bf16(y[2] * bf_lo(mc), y[3] * bf_hi(mc)), pack_bf16(y[4] * bf_lo(md), y[5] * bf_hi(md)),
                 pack_bf16(y[6] * bf_lo(md), y[7] * bf_hi(md)));
          sts128(x2s + cc * 4096, __float_as_uint(y[0]), __float_as_uint(y[1]), __float_as_uint(y[2]), __float_as_uint(y[3]));
          sts128(x2s + cc * 4096 + 2048, __float_as_uint(y[4]), __float_as_uint(y[5]), __float_as_uint(y[6]), __float_as_uint(y[7]));
          if (n == 7) {
            const bool o1 = lane & 1, o2 = lane & 2;
            float c0 = (o1 ? v0 : s0) + __shfl_xor_sync(0xffffffffu, o1 ? s0 : v0, 1);
            float c1 = (o1 ? v1 : s1) + __shfl_xor_sync(0xffffffffu, o1 ? s1 : v1, 1);
            c0 = (o2 ? c1 : c0) + __shfl_xor_sync(0xffffffffu, o2 ? c0 : c1, 2);
            *(float*)(smem_raw + SM_PARK + 16384 + hw * 512 + lane * 4) = c0;
            bar_sync(NB_HELP, 128);
            if (hw == 0) {
              const float* ps = (const float*)(smem_raw + SM_PARK + 16384) + lane;
              const float m = (c0 + ps[128] + ps[256] + ps[384]) * (1.f / 512.f);
              const float mean = __shfl_sync(0xffffffffu, m, lane & ~1), sq = __shfl_sync(0xffffffffu, m, lane | 1);
              const float rs = 0.5f * rsqrtf(fmaxf(fmaf(-mean, mean, sq), 0.f) + 1e-5f), mr = -mean * rs;
              const float rs1 = __shfl_down_sync(0xffffffffu, rs, 2), mr1 = __shfl_down_sync(0xffffffffu, mr, 2);
              if (q == 0)
                st_pkt(&p.s->stat[(rt * 8 + j) * 8 + (lane >> 2)], (__float_as_uint(rs) & ~1u) | (tag & 1u), __float_as_uint(mr),
                       __float_as_uint(rs1), __float_as_uint(mr1));
              warp_arrive(bars + BAR_X2);
            }
          }
        } else {
          store_out(p.out, (uint32_t)(rt * 128 + 16 * j + (lane >> 2)) * 256 + (cc * 4 + hw) * 8 + q, x2s + cc * 4096, ma, mb, y);
        }
      }
    }
  } else {
    const int wg = warp >> 2;
    const int q = lane & 3, gq = lane >> 2;
    const Ring ring{(sb + SM_RING) >> 4, bars};
    const uint32_t xoff = (uint32_t)(rt * 128 + 16 * j + warp) * 256 + gq * 8 + q;
    const uint32_t ooff = ((uint32_t)(rt * 8 + j) * 32 + gq) * 32 + warp * 4 + q;
    const uint32_t wblk = sb + SM_PARK + warp * 4096, wprv = wblk + lane * 16;
    const uint32_t wbar = sb + SM_WBAR + warp * 24;
    const uint4* const Gw = p.s->G + (rt * 8 + warp) * 1024;

    {
      const uint32_t* xo = (const uint32_t*)p.x + xoff;
      uint32_t xr[4][4];
      CK_(d0);
#pragma unroll
      for (int c = 0; c < 4; c++) {
        xr[c][0] = ldg32(xo + c * 64);
        xr[c][1] = ldg32(xo + c * 64 + 8 * 256);
        xr[c][2] = ldg32(xo + c * 64 + 4);
        xr[c][3] = ldg32(xo + c * 64 + 4 + 8 * 256);
      }
      CK_(d1);
      fence_regs(xr);
      CK_(d2);
      float s0 = 0.f, s1 = 0.f, v0 = 0.f, v1 = 0.f;
#pragma unroll
      for (int c = 0; c < 4; c++) {
#pragma unroll
        for (int e = 0; e < 4; e++) {
          const float a = bf_lo(xr[c][e]), b = bf_hi(xr[c][e]);
          if (e & 1) { s1 += a + b; v1 = fmaf(a, a, fmaf(b, b, v1)); }
          else { s0 += a + b; v0 = fmaf(a, a, fmaf(b, b, v0)); }
        }
      }
#pragma unroll
      for (int o = 16; o > 0; o >>= 1) {
        s0 += __shfl_xor_sync(0xffffffffu, s0, o);
        s1 += __shfl_xor_sync(0xffffffffu, s1, o);
        v0 += __shfl_xor_sync(0xffffffffu, v0, o);
        v1 += __shfl_xor_sync(0xffffffffu, v1, o);
      }
      const float m0 = s0 * (1.f / 512.f), m1 = s1 * (1.f / 512.f);
      const float r0 = rsqrtf(fmaxf(fmaf(-m0, m0, v0 * (1.f / 512.f)), 0.f) + 1e-5f);
      const float r1 = rsqrtf(fmaxf(fmaf(-m1, m1, v1 * (1.f / 512.f)), 0.f) + 1e-5f);
#pragma unroll
      for (int c = 0; c < 4; c++) {
        st_pkt(p.s->G + ooff + c * 256,
               pack_tag<1>((bf_lo(xr[c][0]) - m0) * r0, (bf_hi(xr[c][0]) - m0) * r0),
               pack_bf16((bf_lo(xr[c][1]) - m1) * r1, (bf_hi(xr[c][1]) - m1) * r1),
               pack_bf16((bf_lo(xr[c][2]) - m0) * r0, (bf_hi(xr[c][2]) - m0) * r0),
               pack_bf16((bf_lo(xr[c][3]) - m1) * r1, (bf_hi(xr[c][3]) - m1) * r1));
      }
      CK_(d3);
      CKS(16, d0); CKS(17, d1); CKS(18, d2); CKS(19, d3);

    }
    asm volatile("setmaxnreg.inc.sync.aligned.u32 224;");
    uint32_t qf[8][4];
    {
      uint32_t h[32][4];
      float acc[64];
      const uint4* Gin = Gw + lane;
      bar_sync(NB_GATHER, 384);
      if (G_DELAY) spin_cycles(G_DELAY);
#pragma unroll
      for (int c = 0; c < 3; c++) warp_bulk_load(wblk + c * SLOT, Gw + c * 256, 4096, wbar + c * 8);
#pragma unroll
      for (int c = 0; c < 4; c++) {
        mbar_wait(wbar + (c % 3) * 8, c / 3);
#pragma unroll
        for (int i = 0; i < 8; i++) lds128(wprv + (c % 3) * SLOT + i * 512, h[c * 8 + i]);
        verify8_tag1<512>(Gin + c * 256, h + c * 8);
        if (c == 0) {
          warp_bulk_load(wblk, Gw + 768, 4096, wbar);
          TS(1);
          bar_sync(NB_TAB, 384);
        }
#pragma unroll
        for (int i = 0; i < 8; i++) {
          uint32_t m[4];
          lds128(sb + SM_TAB + (uint32_t)((c * 8 + i) * 4 + q) * 16, m);
          uint32_t* hh = h[c * 8 + i];
          hh[0] = hfma2_bf16(hh[0], m[0], m[2]);
          hh[1] = hfma2_bf16(hh[1], m[0], m[2]);
          hh[2] = hfma2_bf16(hh[2], m[1], m[3]);
          hh[3] = hfma2_bf16(hh[3], m[1], m[3]);
        }
        fence_frags<8>(h + c * 8);
        const uint32_t b = ring.wait_full(c, 0);
        if (c > 0) { wg_wait<0>(); ring.release(c - 1); }
        if (c == 0) TS(2);
        wg_fence();
        static_for<0, 8>([&](auto K) { wgmma_rs_n128_tb1<LB_MN128 + K * 128, HI128>(acc, h[c * 8 + K], b, (c | K) != 0); });
        wg_commit();
      }
      bar_arrive(NB_PASS0, 384);
#pragma unroll 1
      for (int ps = 1; ps < 4; ps++) {
        wg_wait<0>();
        ring.release(3);
        fence_regs(acc);
#pragma unroll
        for (int i = 0; i < 8; i++) {
          uint32_t o[4];
          pack8(o, acc + 8 * i);
          sts128(wprv + (ps - 1) * SLOT + i * 512, o[0], o[1], o[2], o[3]);
        }
#pragma unroll
        for (int c = 0; c < 4; c++) {
          const uint32_t b = ring.wait_full(c, ps & 1);
          if (c > 0) { wg_wait<0>(); ring.release(c - 1); }
          wg_fence();
          static_for<0, 8>([&](auto K) { wgmma_rs_n128_tb1<LB_MN128 + K * 128, HI128>(acc, h[c * 8 + K], b, (c | K) != 0); });
          wg_commit();
        }
      }
      wg_wait<0>();
      ring.release(3);
      fence_regs(acc);
#pragma unroll
      for (int i = 0; i < 8; i++) pack8(qf[i], acc + 8 * i);
    }
    fence_regs(qf);
    TS(3);

    float S[64];
    {
      float O[64];
      uint32_t P[8][4];
      const float cs = 0.08838834764831845f * 1.4426950408889634f;
      const int TAU = 0x41800000;
      float m0, m1, l0, l1;

      auto float_block_max = [&]() {
        float b0 = fmaxf(S[0], S[1]), b1 = fmaxf(S[2], S[3]);
#pragma unroll
        for (int i = 1; i < 16; i++) {
          b0 = fmaxf(b0, fmaxf(S[4 * i], S[4 * i + 1]));
          b1 = fmaxf(b1, fmaxf(S[4 * i + 2], S[4 * i + 3]));
        }
        b0 = fmaxf(b0, __shfl_xor_sync(0xffffffffu, b0, 1)); b1 = fmaxf(b1, __shfl_xor_sync(0xffffffffu, b1, 1));
        b0 = fmaxf(b0, __shfl_xor_sync(0xffffffffu, b0, 2)); b1 = fmaxf(b1, __shfl_xor_sync(0xffffffffu, b1, 2));
        m0 = b0 * cs; m1 = b1 * cs;
      };
      auto first_block_max = [&]() {
        int a0 = max(__float_as_int(S[0]), __float_as_int(S[1]));
        int a1 = max(__float_as_int(S[2]), __float_as_int(S[3]));
#pragma unroll
        for (int i = 1; i < 16; i++) {
          a0 = __vimax3_s32(a0, __float_as_int(S[4 * i]), __float_as_int(S[4 * i + 1]));
          a1 = __vimax3_s32(a1, __float_as_int(S[4 * i + 2]), __float_as_int(S[4 * i + 3]));
        }
        a0 = max(a0, __shfl_xor_sync(0xffffffffu, a0, 1)); a1 = max(a1, __shfl_xor_sync(0xffffffffu, a1, 1));
        a0 = max(a0, __shfl_xor_sync(0xffffffffu, a0, 2)); a1 = max(a1, __shfl_xor_sync(0xffffffffu, a1, 2));
        m0 = __int_as_float(a0) * cs; m1 = __int_as_float(a1) * cs;
        if (__any_sync(0xffffffffu, (a0 | a1) < 0)) float_block_max();
      };
      auto scale_sub = [&]() {
#pragma unroll
        for (int i = 0; i < 16; i++) {
          S[4 * i] = fmaf(S[4 * i], cs, -m0); S[4 * i + 1] = fmaf(S[4 * i + 1], cs, -m0);
          S[4 * i + 2] = fmaf(S[4 * i + 2], cs, -m1); S[4 * i + 3] = fmaf(S[4 * i + 3], cs, -m1);
        }
      };
      auto exps = [&](int i0, int i1) {
#pragma unroll
        for (int i = i0; i < i1; i++) {
          S[4 * i] = ex2(S[4 * i]); S[4 * i + 1] = ex2(S[4 * i + 1]);
          S[4 * i + 2] = ex2(S[4 * i + 2]); S[4 * i + 3] = ex2(S[4 * i + 3]);
          l0 += S[4 * i]; l1 += S[4 * i + 2]; l0 += S[4 * i + 1]; l1 += S[4 * i + 3];
        }
      };
      {
        const uint32_t b = ring.wait_full(0, 0);
        wg_fence();
        static_for<0, 8>([&](auto K) { wgmma_rs_n128_tb0<LB_K128 + (K >> 2) * 1024 + (K & 3) * 2, HI128>(S, qf[K], b, K != 0); });
        wg_commit();
        wg_wait<0>();
        fence_regs(S);
        ring.release(0);
        float_block_max();
        scale_sub();
        l0 = 0.f; l1 = 0.f;
        exps(0, 16);
#pragma unroll
        for (int i = 0; i < 8; i++) pack8(P[i], S + 8 * i);
      }
      fence_regs(P);
      if (wg == 1) bar_arrive(2, 256);
#pragma unroll 1
      for (int n = 1; n < 16; n++) {
        const uint32_t tk = 2 * n - 1, tv = 2 * n;
        const bool newhead = (n & 3) == 0;
        const uint32_t bk = ring.wait_full(tk & 3, (tk >> 2) & 1);
        const uint32_t bv = ring.wait_full(tv & 3, (tv >> 2) & 1);
        bar_sync(2 + wg, 256);
        wg_fence();
        static_for<0, 8>([&](auto K) { wgmma_rs_n128_tb0<LB_K128 + (K >> 2) * 1024 + (K & 3) * 2, HI128>(S, qf[K], bk, K != 0); });
        wg_commit();
        static_for<0, 8>([&](auto K) { wgmma_rs_n128_tb1<LB_MN128 + K * 128, HI128>(O, P[K], bv, K != 0 || (n & 3) != 1); });
        wg_commit();
        bar_arrive(2 + (wg ^ 1), 256);
        wg_wait<1>();
        fence_regs(S);
        ring.release(tk & 3);
        if ((n & 3) == 3 && n != 15) {
          fence_regs(qf);
#pragma unroll
          for (int i = 0; i < 8; i++) lds128(wprv + (n >> 2) * SLOT + i * 512, qf[i]);
        }
        float f0 = 1.f, f1 = 1.f;
        bool resc = newhead;
        if (newhead) {
          l0 += __shfl_xor_sync(0xffffffffu, l0, 1); l1 += __shfl_xor_sync(0xffffffffu, l1, 1);
          l0 += __shfl_xor_sync(0xffffffffu, l0, 2); l1 += __shfl_xor_sync(0xffffffffu, l1, 2);
          f0 = rcp_hw(l0); f1 = rcp_hw(l1);
          l0 = 0.f; l1 = 0.f;
          first_block_max();
          scale_sub();
        } else {
          scale_sub();
          int a0 = __vimax3_s32(__float_as_int(S[0]), __float_as_int(S[1]), __float_as_int(S[1]));
          int a1 = __vimax3_s32(__float_as_int(S[2]), __float_as_int(S[3]), __float_as_int(S[3]));
#pragma unroll
          for (int i = 1; i < 16; i++) {
            a0 = __vimax3_s32(a0, __float_as_int(S[4 * i]), __float_as_int(S[4 * i + 1]));
            a1 = __vimax3_s32(a1, __float_as_int(S[4 * i + 2]), __float_as_int(S[4 * i + 3]));
          }
          if (__any_sync(0xffffffffu, max(a0, a1) > TAU)) {
            a0 = max(a0, 0); a1 = max(a1, 0);
            a0 = max(a0, __shfl_xor_sync(0xffffffffu, a0, 1)); a1 = max(a1, __shfl_xor_sync(0xffffffffu, a1, 1));
            a0 = max(a0, __shfl_xor_sync(0xffffffffu, a0, 2)); a1 = max(a1, __shfl_xor_sync(0xffffffffu, a1, 2));
            const float d0 = __int_as_float(a0), d1 = __int_as_float(a1);
#pragma unroll
            for (int i = 0; i < 16; i++) { S[4 * i] -= d0; S[4 * i + 1] -= d0; S[4 * i + 2] -= d1; S[4 * i + 3] -= d1; }
            m0 += d0; m1 += d1;
            f0 = ex2(-d0); f1 = ex2(-d1);
            l0 *= f0; l1 *= f1;
            resc = true;
          }
        }
        exps(0, 4);
        wg_wait<0>();
        fence_regs(O);
        fence_regs(P);
        ring.release(tv & 3);
        if (resc) {
#pragma unroll
          for (int i = 0; i < 16; i++) {
            O[4 * i] *= f0; O[4 * i + 1] *= f0; O[4 * i + 2] *= f1; O[4 * i + 3] *= f1;
          }
          if (newhead) {
#pragma unroll
            for (int i = 0; i < 8; i++) {
              uint32_t o[4];
              pack8(o, O + 8 * i);
              sts128(wprv + ((n >> 2) - 1) * SLOT + i * 512, o[0], o[1], o[2], o[3]);
            }
          }
        }
        exps(4, 16);
#pragma unroll
        for (int i = 0; i < 8; i++) pack8(P[i], S + 8 * i);
        fence_regs(P);
        fence_regs(O);
      }
      {
        const uint32_t bv = ring.wait_full(3, 1);
        if (wg == 0) bar_sync(2, 256);
        wg_fence();
        static_for<0, 8>([&](auto K) { wgmma_rs_n128_tb1<LB_MN128 + K * 128, HI128>(O, P[K], bv, 1); });
        wg_commit();
        l0 += __shfl_xor_sync(0xffffffffu, l0, 1); l1 += __shfl_xor_sync(0xffffffffu, l1, 1);
        l0 += __shfl_xor_sync(0xffffffffu, l0, 2); l1 += __shfl_xor_sync(0xffffffffu, l1, 2);
        const float f0 = rcp_hw(l0), f1 = rcp_hw(l1);
        wg_wait<0>();
        fence_regs(O);
        ring.release(3);
#pragma unroll
        for (int i = 0; i < 8; i++) {
          qf[i][0] = pack_bf16(O[8 * i] * f0, O[8 * i + 1] * f0); qf[i][1] = pack_bf16(O[8 * i + 2] * f1, O[8 * i + 3] * f1);
          qf[i][2] = pack_bf16(O[8 * i + 4] * f0, O[8 * i + 5] * f0); qf[i][3] = pack_bf16(O[8 * i + 6] * f1, O[8 * i + 7] * f1);
        }
      }
    }
    fence_regs(qf);
    TS(4);
    asm volatile("setmaxnreg.dec.sync.aligned.u32 200;");
    bar_arrive(NB_PARK, 384);

    uint4* const Pout = p.s->P + ((size_t)(rt * 8 + warp) * 8 + j) * 1024 + lane;
    const uint32_t tag = *(volatile uint32_t*)(smem_raw + SM_BAR + BAR_TAG);

    float acc2[32];
    uint32_t pk[4][4];
    auto pack_partial = [&](auto TAGC) {
      fence_regs(acc2);
#pragma unroll
      for (int i = 0; i < 4; i++) {
#pragma unroll
        for (int e = 0; e < 4; e++) pk[i][e] = pack_trunc(acc2[8 * i + 2 * e], acc2[8 * i + 2 * e + 1]);
        pk[i][0] = TAGC ? (pk[i][0] | 1u) : (pk[i][0] & ~1u);
      }
      fence_regs(pk);
    };
    auto store_partial = [&](int step) {
#pragma unroll
      for (int i = 0; i < 4; i++) st_pkt(Pout + ((step & 7) * 4 + i) * 32, pk[i][0], pk[i][1], pk[i][2], pk[i][3]);
    };
    auto chunk_sent = [&](int step) { warp_arrive(sb + SM_SBAR + step * 8); };
    const uint4* const Gin = Gw + lane;
    auto g_issue = [&](int u) { warp_bulk_load(wblk + 2 * SLOT + (u & 1) * 2048, Gw + u * 128, 2048, wbar + (u & 1) * 8); };

    uint32_t tl = 0, b = ring.wait_full(0, 0);
    auto next_tile = [&]() {
      const uint32_t cur = tl & 3;
      tl++;
      b = ring.wait_full(tl & 3, (tl >> 2) & 1);
      wg_wait<0>();
      TR(4);
      ring.release(cur);
    };
    {
      uint32_t o[24][4];
#pragma unroll
      for (int i = 0; i < 24; i++) lds128(wprv + (i >> 3) * SLOT + (i & 7) * 512, o[i]);
#pragma unroll 1
      for (int cc = 0; cc < 8; cc++) {
        wg_fence();
        static_for<0, 16>([&](auto K) { wgmma_rs_n64_tb1<K * 128, HI128>(acc2, o[K], b, K != 0); });
        wg_commit();
        if (cc > 0) store_partial(cc - 1);
        next_tile();
        wg_fence();
        static_for<0, 16>([&](auto K) { wgmma_rs_n64_tb1<K * 128, HI128>(acc2, K < 8 ? o[16 + (K & 7)] : qf[K & 7], b, 1); });
        wg_commit();
        if (cc > 0) chunk_sent(cc - 1);
        if (cc == 6) { g_issue(0); g_issue(1); }
        next_tile();
        pack_partial(IC<1>{});
      }
    }
    TS(5);

    uint32_t H[14][4];
    {
      float acca[64], accb[48];
      const uint4* const statp = &p.s->stat[(rt * 8 + warp) * 8];
#pragma unroll 1
      for (int u = 0; u < 8; u++) {
        uint32_t fa[4][4];
        mbar_wait(wbar + (u & 1) * 8, ((u >> 1) + (u & 1)) & 1);
#pragma unroll
        for (int i = 0; i < 4; i++) lds128(wprv + 2 * SLOT + (u & 1) * 2048 + i * 512, fa[i]);
        verify4_tag0<512>(Gin + u * 128, fa);
        wg_fence();
        static_for<0, 4>([&](auto K) { wgmma_rs_n128_tb1<LB_W1 + K * 64, HI64>(acca, fa[K], b, (u | K) != 0); });
        static_for<0, 4>([&](auto K) { wgmma_rs_n96_tb1<LB_W1 + 1024 + K * 64, HI64>(accb, fa[K], b, (u | K) != 0); });
        wg_commit();
        if (u == 0) store_partial(7);
        if (u == 1) chunk_sent(7);
        if (u < 5) g_issue(u + 2);
        if (u == 7) warp_bulk_load(wblk + 2 * SLOT, statp, 128, wbar + 16);
        next_tile();
        if (u == 5) g_issue(7);
      }
      fence_regs(acca);
      fence_regs(accb);
      TS(9);
      mbar_wait(bars + BAR_UV, 0);
      uint32_t xr[4];
      mbar_wait(wbar + 16, 1);
      lds128(wblk + 2 * SLOT + gq * 16, xr);
      {
        int spins = 0;
        while (((xr[0] ^ tag) & 1u) && ++spins < SPIN_LIMIT) ld_pkt(statp + gq, xr);
      }
      const float ra0 = __uint_as_float(xr[0]), rb0 = __uint_as_float(xr[1]), ra1 = __uint_as_float(xr[2]),
                  rb1 = __uint_as_float(xr[3]);
#pragma unroll
      for (int i = 0; i < 28; i++) {
        uint32_t m[4];
        lds128(sb + SM_TAB + (i * 4 + q) * 16, m);
        const float u0 = __uint_as_float(m[0]), u1 = __uint_as_float(m[1]), w0 = __uint_as_float(m[2]), w1 = __uint_as_float(m[3]);
        const float* acc = i < 16 ? acca + 4 * i : accb + 4 * (i - 16);
        const float z0 = fmaf(acc[0], ra0, fmaf(u0, rb0, w0)), z1 = fmaf(acc[1], ra0, fmaf(u1, rb0, w1));
        const float z2 = fmaf(acc[2], ra1, fmaf(u0, rb1, w0)), z3 = fmaf(acc[3], ra1, fmaf(u1, rb1, w1));
        H[i >> 1][(i & 1) * 2] = pack_bf16(fmaf(z0, tanh_hw(z0), z0), fmaf(z1, tanh_hw(z1), z1));
        H[i >> 1][(i & 1) * 2 + 1] = pack_bf16(fmaf(z2, tanh_hw(z2), z2), fmaf(z3, tanh_hw(z3), z3));
      }
    }
    fence_regs(H);
    TS(10);
    const int go = 24 + (warp ^ 4);
#pragma unroll 1
    for (int cc = 0; cc < 8; cc++) {
      wg_fence();
      static_for<0, 14>([&](auto K) { wgmma_rs_n64_tb1<K * 128, HI128>(acc2, H[K], b, K != 0); });
      wg_commit();
      if (cc > 1) chunk_sent(8 + cc - 2);
      if (cc > 0) store_partial(cc - 1);
      if (cc < 7) next_tile();
      wg_wait<0>();
      pack_partial(IC<0>{});
    }
    store_partial(7);
    TS(11);
    {
      const uint4* const Pown = p.s->P + (size_t)(rt * 8 + j) * 8192 + go * 32 + lane;
      uint32_t r[8][4];
      float y[8];
      mbar_wait(bars + BAR_X2, 0);
      spin_cycles(wg ? FIN_DELAY1 : FIN_DELAY0);
      issue_pkts<0, 8>(Pown, 1024, r);
      verify8_rt<16384>(Pown, r, 0);
      TS(13);
#pragma unroll
      for (int s = 0; s < 8; s++) add_partial(y, r[s], 0x10000u, s == 0);
      const uint32_t gt = sb + SM_TAB + 1792 + ((go - 24) * 4 + q) * 8;
      store_out(p.out, (uint32_t)(rt * 128 + 16 * j + gq) * 256 + go * 8 + q, sb + SM_PARK + SLOT + (go >> 2) * 4096 + (go & 3) * 512 + lane * 16,
                lds32(gt), lds32(gt + 4), y);
    }
    TS(12);
    if (bid == 0 && tid == 0) asm volatile("st.relaxed.gpu.global.u32 [%0], %1;" ::"l"(&p.s->epoch), "r"(tag) : "memory");
  }
}

typedef CUresult (*EncodeFn)(CUtensorMap*, CUtensorMapDataType, cuuint32_t, void*, const cuuint64_t*, const cuuint64_t*,
                             const cuuint32_t*, const cuuint32_t*, CUtensorMapInterleave, CUtensorMapSwizzle,
                             CUtensorMapL2promotion, CUtensorMapFloatOOBfill);

static void make_map(EncodeFn fn, CUtensorMap* tm, const void* ptr, int inner, int rows, int cols, int box_rows, int box_outer,
                     CUtensorMapSwizzle swz) {
  cuuint64_t gd[3] = {(cuuint64_t)inner, (cuuint64_t)rows, (cuuint64_t)(cols / inner)};
  cuuint64_t gs[2] = {(cuuint64_t)cols * 2, (cuuint64_t)inner * 2};
  cuuint32_t bx[3] = {(cuuint32_t)inner, (cuuint32_t)box_rows, (cuuint32_t)box_outer};
  cuuint32_t es[3] = {1, 1, 1};
  fn(tm, CU_TENSOR_MAP_DATA_TYPE_BFLOAT16, 3, const_cast<void*>(ptr), gd, gs, bx, es, CU_TENSOR_MAP_INTERLEAVE_NONE, swz,
     CU_TENSOR_MAP_L2_PROMOTION_L2_128B, CU_TENSOR_MAP_FLOAT_OOB_FILL_NONE);
}

extern "C" void kernel_launch(void* const* d_in, const int* in_sizes, int n_in, void* d_out, int out_size) {
  (void)in_sizes; (void)n_in; (void)out_size;
  void* fnp = nullptr;
  cudaDriverEntryPointQueryResult qr;
  cudaGetDriverEntryPoint("cuTensorMapEncodeTiled", &fnp, cudaEnableDefault, &qr);
  EncodeFn fn = (EncodeFn)fnp;
  CUtensorMap tmWq, tmK, tmV, tmWo, tmW1, tmW2, tmWm, tmP, tmX;
  make_map(fn, &tmWq, d_in[3], 64, 512, 4096, 128, 2, CU_TENSOR_MAP_SWIZZLE_128B);
  make_map(fn, &tmK, d_in[1], 64, 8 * SK, 128, 128, 2, CU_TENSOR_MAP_SWIZZLE_128B);
  make_map(fn, &tmV, d_in[2], 64, 8 * SK, 128, 128, 2, CU_TENSOR_MAP_SWIZZLE_128B);
  make_map(fn, &tmWo, d_in[4], 64, 4096, 512, 256, 1, CU_TENSOR_MAP_SWIZZLE_128B);
  make_map(fn, &tmW1, d_in[6], 32, 512, FF, 64, 7, CU_TENSOR_MAP_SWIZZLE_64B);
  make_map(fn, &tmW2, d_in[7], 64, FF, 512, 224, 1, CU_TENSOR_MAP_SWIZZLE_128B);
  make_map(fn, &tmWm, d_in[9], 8, 512, 3072, 256, 1, CU_TENSOR_MAP_SWIZZLE_NONE);
  make_map(fn, &tmX, d_in[0], 16, 2048, 512, 16, 4, CU_TENSOR_MAP_SWIZZLE_NONE);
  Params p;
  p.x = (const __nv_bfloat16*)d_in[0];
  p.c = (const __nv_bfloat16*)d_in[8];
  p.wmod = (const __nv_bfloat16*)d_in[9];
  p.wo = (const __nv_bfloat16*)d_in[4];
  p.w1 = (const __nv_bfloat16*)d_in[6];
  p.w2 = (const __nv_bfloat16*)d_in[7];
  p.out = (__nv_bfloat16*)d_out;
  cudaGetSymbolAddress((void**)&p.s, g_scratch);
  {
    cuuint64_t gd[3] = {256, 32, 1024};
    cuuint64_t gs[2] = {512, 16384};
    cuuint32_t bx[3] = {256, 4, 8};
    cuuint32_t es[3] = {1, 1, 1};
    fn(&tmP, CU_TENSOR_MAP_DATA_TYPE_BFLOAT16, 3, (void*)p.s->P, gd, gs, bx, es, CU_TENSOR_MAP_INTERLEAVE_NONE,
       CU_TENSOR_MAP_SWIZZLE_NONE, CU_TENSOR_MAP_L2_PROMOTION_NONE, CU_TENSOR_MAP_FLOAT_OOB_FILL_NONE);
  }
  cudaFuncSetAttribute(adaln_block_kernel, cudaFuncAttributeMaxDynamicSharedMemorySize, SM_TOTAL);
  adaln_block_kernel<<<128, 512, SM_TOTAL>>>(tmWq, tmK, tmV, tmWo, tmW1, tmW2, tmWm, tmP, tmX, p);
}
```

```cpp
#include <cuda_runtime.h>
#include <cuda_bf16.h>
#include <cuda.h>
#include <stdint.h>

template <int OFF, uint32_t HI>
__device__ __forceinline__ void wgmma_rs_n128_tb0(float (&d)[64], const uint32_t (&a)[4], uint32_t lo, int sd) {
  asm volatile("{\n.reg .pred p;\n.reg .b32 l;\n.reg .b64 db;\nsetp.ne.b32 p, %69, 0;\n"
    "add.u32 l, %68, %70;\nmov.b64 db, {l, %71};\n"
    "wgmma.mma_async.sync.aligned.m64n128k16.f32.bf16.bf16 "
    "{%0,%1,%2,%3,%4,%5,%6,%7,%8,%9,%10,%11,%12,%13,%14,%15,"
    "%16,%17,%18,%19,%20,%21,%22,%23,%24,%25,%26,%27,%28,%29,%30,%31,"
    "%32,%33,%34,%35,%36,%37,%38,%39,%40,%41,%42,%43,%44,%45,%46,%47,"
    "%48,%49,%50,%51,%52,%53,%54,%55,%56,%57,%58,%59,%60,%61,%62,%63}, "
    "{%64,%65,%66,%67}, db, p, 1, 1, 0;\n}\n"
    : "+f"(d[0]), "+f"(d[1]), "+f"(d[2]), "+f"(d[3]), "+f"(d[4]), "+f"(d[5]), "+f"(d[6]), "+f"(d[7]),
      "+f"(d[8]), "+f"(d[9]), "+f"(d[10]), "+f"(d[11]), "+f"(d[12]), "+f"(d[13]), "+f"(d[14]), "+f"(d[15]),
      "+f"(d[16]), "+f"(d[17]), "+f"(d[18]), "+f"(d[19]), "+f"(d[20]), "+f"(d[21]), "+f"(d[22]), "+f"(d[23]),
      "+f"(d[24]), "+f"(d[25]), "+f"(d[26]), "+f"(d[27]), "+f"(d[28]), "+f"(d[29]), "+f"(d[30]), "+f"(d[31]),
      "+f"(d[32]), "+f"(d[33]), "+f"(d[34]), "+f"(d[35]), "+f"(d[36]), "+f"(d[37]), "+f"(d[38]), "+f"(d[39]),
      "+f"(d[40]), "+f"(d[41]), "+f"(d[42]), "+f"(d[43]), "+f"(d[44]), "+f"(d[45]), "+f"(d[46]), "+f"(d[47]),
      "+f"(d[48]), "+f"(d[49]), "+f"(d[50]), "+f"(d[51]), "+f"(d[52]), "+f"(d[53]), "+f"(d[54]), "+f"(d[55]),
      "+f"(d[56]), "+f"(d[57]), "+f"(d[58]), "+f"(d[59]), "+f"(d[60]), "+f"(d[61]), "+f"(d[62]), "+f"(d[63])
    : "r"(a[0]), "r"(a[1]), "r"(a[2]), "r"(a[3]), "r"(lo), "r"(sd), "n"(OFF), "n"(HI));
}

template <int OFF, uint32_t HI>
__device__ __forceinline__ void wgmma_rs_n128_tb1(float (&d)[64], const uint32_t (&a)[4], uint32_t lo, int sd) {
  asm volatile("{\n.reg .pred p;\n.reg .b32 l;\n.reg .b64 db;\nsetp.ne.b32 p, %69, 0;\n"
    "add.u32 l, %68, %70;\nmov.b64 db, {l, %71};\n"
    "wgmma.mma_async.sync.aligned.m64n128k16.f32.bf16.bf16 "
    "{%0,%1,%2,%3,%4,%5,%6,%7,%8,%9,%10,%11,%12,%13,%14,%15,"
    "%16,%17,%18,%19,%20,%21,%22,%23,%24,%25,%26,%27,%28,%29,%30,%31,"
    "%32,%33,%34,%35,%36,%37,%38,%39,%40,%41,%42,%43,%44,%45,%46,%47,"
    "%48,%49,%50,%51,%52,%53,%54,%55,%56,%57,%58,%59,%60,%61,%62,%63}, "
    "{%64,%65,%66,%67}, db, p, 1, 1, 1;\n}\n"
    : "+f"(d[0]), "+f"(d[1]), "+f"(d[2]), "+f"(d[3]), "+f"(d[4]), "+f"(d[5]), "+f"(d[6]), "+f"(d[7]),
      "+f"(d[8]), "+f"(d[9]), "+f"(d[10]), "+f"(d[11]), "+f"(d[12]), "+f"(d[13]), "+f"(d[14]), "+f"(d[15]),
      "+f"(d[16]), "+f"(d[17]), "+f"(d[18]), "+f"(d[19]), "+f"(d[20]), "+f"(d[21]), "+f"(d[22]), "+f"(d[23]),
      "+f"(d[24]), "+f"(d[25]), "+f"(d[26]), "+f"(d[27]), "+f"(d[28]), "+f"(d[29]), "+f"(d[30]), "+f"(d[31]),
      "+f"(d[32]), "+f"(d[33]), "+f"(d[34]), "+f"(d[35]), "+f"(d[36]), "+f"(d[37]), "+f"(d[38]), "+f"(d[39]),
      "+f"(d[40]), "+f"(d[41]), "+f"(d[42]), "+f"(d[43]), "+f"(d[44]), "+f"(d[45]), "+f"(d[46]), "+f"(d[47]),
      "+f"(d[48]), "+f"(d[49]), "+f"(d[50]), "+f"(d[51]), "+f"(d[52]), "+f"(d[53]), "+f"(d[54]), "+f"(d[55]),
      "+f"(d[56]), "+f"(d[57]), "+f"(d[58]), "+f"(d[59]), "+f"(d[60]), "+f"(d[61]), "+f"(d[62]), "+f"(d[63])
    : "r"(a[0]), "r"(a[1]), "r"(a[2]), "r"(a[3]), "r"(lo), "r"(sd), "n"(OFF), "n"(HI));
}

template <int OFF, uint32_t HI>
__device__ __forceinline__ void wgmma_rs_n192_tb1(float (&d)[96], const uint32_t (&a)[4], uint32_t lo, int sd) {
  asm volatile("{\n.reg .pred p;\n.reg .b32 l;\n.reg .b64 db;\nsetp.ne.b32 p, %101, 0;\n"
    "add.u32 l, %100, %102;\nmov.b64 db, {l, %103};\n"
    "wgmma.mma_async.sync.aligned.m64n192k16.f32.bf16.bf16 "
    "{%0,%1,%2,%3,%4,%5,%6,%7,%8,%9,%10,%11,%12,%13,%14,%15,"
    "%16,%17,%18,%19,%20,%21,%22,%23,%24,%25,%26,%27,%28,%29,%30,%31,"
    "%32,%33,%34,%35,%36,%37,%38,%39,%40,%41,%42,%43,%44,%45,%46,%47,"
    "%48,%49,%50,%51,%52,%53,%54,%55,%56,%57,%58,%59,%60,%61,%62,%63,"
    "%64,%65,%66,%67,%68,%69,%70,%71,%72,%73,%74,%75,%76,%77,%78,%79,"
    "%80,%81,%82,%83,%84,%85,%86,%87,%88,%89,%90,%91,%92,%93,%94,%95}, "
    "{%96,%97,%98,%99}, db, p, 1, 1, 1;\n}\n"
    : "+f"(d[0]), "+f"(d[1]), "+f"(d[2]), "+f"(d[3]), "+f"(d[4]), "+f"(d[5]), "+f"(d[6]), "+f"(d[7]),
      "+f"(d[8]), "+f"(d[9]), "+f"(d[10]), "+f"(d[11]), "+f"(d[12]), "+f"(d[13]), "+f"(d[14]), "+f"(d[15]),
      "+f"(d[16]), "+f"(d[17]), "+f"(d[18]), "+f"(d[19]), "+f"(d[20]), "+f"(d[21]), "+f"(d[22]), "+f"(d[23]),
      "+f"(d[24]), "+f"(d[25]), "+f"(d[26]), "+f"(d[27]), "+f"(d[28]), "+f"(d[29]), "+f"(d[30]), "+f"(d[31]),
      "+f"(d[32]), "+f"(d[33]), "+f"(d[34]), "+f"(d[35]), "+f"(d[36]), "+f"(d[37]), "+f"(d[38]), "+f"(d[39]),
      "+f"(d[40]), "+f"(d[41]), "+f"(d[42]), "+f"(d[43]), "+f"(d[44]), "+f"(d[45]), "+f"(d[46]), "+f"(d[47]),
      "+f"(d[48]), "+f"(d[49]), "+f"(d[50]), "+f"(d[51]), "+f"(d[52]), "+f"(d[53]), "+f"(d[54]), "+f"(d[55]),
      "+f"(d[56]), "+f"(d[57]), "+f"(d[58]), "+f"(d[59]), "+f"(d[60]), "+f"(d[61]), "+f"(d[62]), "+f"(d[63]),
      "+f"(d[64]), "+f"(d[65]), "+f"(d[66]), "+f"(d[67]), "+f"(d[68]), "+f"(d[69]), "+f"(d[70]), "+f"(d[71]),
      "+f"(d[72]), "+f"(d[73]), "+f"(d[74]), "+f"(d[75]), "+f"(d[76]), "+f"(d[77]), "+f"(d[78]), "+f"(d[79]),
      "+f"(d[80]), "+f"(d[81]), "+f"(d[82]), "+f"(d[83]), "+f"(d[84]), "+f"(d[85]), "+f"(d[86]), "+f"(d[87]),
      "+f"(d[88]), "+f"(d[89]), "+f"(d[90]), "+f"(d[91]), "+f"(d[92]), "+f"(d[93]), "+f"(d[94]), "+f"(d[95])
    : "r"(a[0]), "r"(a[1]), "r"(a[2]), "r"(a[3]), "r"(lo), "r"(sd), "n"(OFF), "n"(HI));
}

template <int OFF, uint32_t HI>
__device__ __forceinline__ void wgmma_rs_n32_tb1(float (&d)[16], const uint32_t (&a)[4], uint32_t lo, int sd) {
  asm volatile("{\n.reg .pred p;\n.reg .b32 l;\n.reg .b64 db;\nsetp.ne.b32 p, %21, 0;\n"
    "add.u32 l, %20, %22;\nmov.b64 db, {l, %23};\n"
    "wgmma.mma_async.sync.aligned.m64n32k16.f32.bf16.bf16 "
    "{%0,%1,%2,%3,%4,%5,%6,%7,%8,%9,%10,%11,%12,%13,%14,%15}, "
    "{%16,%17,%18,%19}, db, p, 1, 1, 1;\n}\n"
    : "+f"(d[0]), "+f"(d[1]), "+f"(d[2]), "+f"(d[3]), "+f"(d[4]), "+f"(d[5]), "+f"(d[6]), "+f"(d[7]),
      "+f"(d[8]), "+f"(d[9]), "+f"(d[10]), "+f"(d[11]), "+f"(d[12]), "+f"(d[13]), "+f"(d[14]), "+f"(d[15])
    : "r"(a[0]), "r"(a[1]), "r"(a[2]), "r"(a[3]), "r"(lo), "r"(sd), "n"(OFF), "n"(HI));
}

template <int OFF, uint32_t HI>
__device__ __forceinline__ void wgmma_rs_n64_tb1(float (&d)[32], const uint32_t (&a)[4], uint32_t lo, int sd) {
  asm volatile("{\n.reg .pred p;\n.reg .b32 l;\n.reg .b64 db;\nsetp.ne.b32 p, %37, 0;\n"
    "add.u32 l, %36, %38;\nmov.b64 db, {l, %39};\n"
    "wgmma.mma_async.sync.aligned.m64n64k16.f32.bf16.bf16 "
    "{%0,%1,%2,%3,%4,%5,%6,%7,%8,%9,%10,%11,%12,%13,%14,%15,"
    "%16,%17,%18,%19,%20,%21,%22,%23,%24,%25,%26,%27,%28,%29,%30,%31}, "
    "{%32,%33,%34,%35}, db, p, 1, 1, 1;\n}\n"
    : "+f"(d[0]), "+f"(d[1]), "+f"(d[2]), "+f"(d[3]), "+f"(d[4]), "+f"(d[5]), "+f"(d[6]), "+f"(d[7]),
      "+f"(d[8]), "+f"(d[9]), "+f"(d[10]), "+f"(d[11]), "+f"(d[12]), "+f"(d[13]), "+f"(d[14]), "+f"(d[15]),
      "+f"(d[16]), "+f"(d[17]), "+f"(d[18]), "+f"(d[19]), "+f"(d[20]), "+f"(d[21]), "+f"(d[22]), "+f"(d[23]),
      "+f"(d[24]), "+f"(d[25]), "+f"(d[26]), "+f"(d[27]), "+f"(d[28]), "+f"(d[29]), "+f"(d[30]), "+f"(d[31])
    : "r"(a[0]), "r"(a[1]), "r"(a[2]), "r"(a[3]), "r"(lo), "r"(sd), "n"(OFF), "n"(HI));
}

template <int STR>
__device__ __forceinline__ void verify8_tag1(const uint4* p, uint32_t (*r)[4]) {
  asm volatile("{\n.reg .pred p, q;\n.reg .b32 a, n;\nmov.u32 n, 0;\n"
    "LAB_CHK:\n"
    "and.b32 a, %0, %4;\n"
    "and.b32 a, a, %8;\n"
    "and.b32 a, a, %12;\n"
    "and.b32 a, a, %16;\n"
    "and.b32 a, a, %20;\n"
    "and.b32 a, a, %24;\n"
    "and.b32 a, a, %28;\n"
    "and.b32 a, a, 1;\nsetp.eq.u32 p, a, 1;\nvote.sync.all.pred p, p, 0xffffffff;\n"
    "@p bra.uni LAB_OK;\n"
    "and.b32 a, %0, 1;\nsetp.ne.u32 q, a, 1;\n"
    "@q ld.relaxed.gpu.global.v4.b32 {%0,%1,%2,%3}, [%32+%33];\n"
    "and.b32 a, %4, 1;\nsetp.ne.u32 q, a, 1;\n"
    "@q ld.relaxed.gpu.global.v4.b32 {%4,%5,%6,%7}, [%32+%34];\n"
    "and.b32 a, %8, 1;\nsetp.ne.u32 q, a, 1;\n"
    "@q ld.relaxed.gpu.global.v4.b32 {%8,%9,%10,%11}, [%32+%35];\n"
    "and.b32 a, %12, 1;\nsetp.ne.u32 q, a, 1;\n"
    "@q ld.relaxed.gpu.global.v4.b32 {%12,%13,%14,%15}, [%32+%36];\n"
    "and.b32 a, %16, 1;\nsetp.ne.u32 q, a, 1;\n"
    "@q ld.relaxed.gpu.global.v4.b32 {%16,%17,%18,%19}, [%32+%37];\n"
    "and.b32 a, %20, 1;\nsetp.ne.u32 q, a, 1;\n"
    "@q ld.relaxed.gpu.global.v4.b32 {%20,%21,%22,%23}, [%32+%38];\n"
    "and.b32 a, %24, 1;\nsetp.ne.u32 q, a, 1;\n"
    "@q ld.relaxed.gpu.global.v4.b32 {%24,%25,%26,%27}, [%32+%39];\n"
    "and.b32 a, %28, 1;\nsetp.ne.u32 q, a, 1;\n"
    "@q ld.relaxed.gpu.global.v4.b32 {%28,%29,%30,%31}, [%32+%40];\n"
    "add.u32 n, n, 1;\nsetp.lt.u32 q, n, 262144;\n@q bra.uni LAB_CHK;\n"
    "LAB_OK:\n"
    "}\n"
    : "+r"(r[0][0]), "+r"(r[0][1]), "+r"(r[0][2]), "+r"(r[0][3]), "+r"(r[1][0]), "+r"(r[1][1]), "+r"(r[1][2]), "+r"(r[1][3]),
      "+r"(r[2][0]), "+r"(r[2][1]), "+r"(r[2][2]), "+r"(r[2][3]), "+r"(r[3][0]), "+r"(r[3][1]), "+r"(r[3][2]), "+r"(r[3][3]),
      "+r"(r[4][0]), "+r"(r[4][1]), "+r"(r[4][2]), "+r"(r[4][3]), "+r"(r[5][0]), "+r"(r[5][1]), "+r"(r[5][2]), "+r"(r[5][3]),
      "+r"(r[6][0]), "+r"(r[6][1]), "+r"(r[6][2]), "+r"(r[6][3]), "+r"(r[7][0]), "+r"(r[7][1]), "+r"(r[7][2]), "+r"(r[7][3])
    : "l"(p), "n"(0 * STR), "n"(1 * STR), "n"(2 * STR), "n"(3 * STR), "n"(4 * STR), "n"(5 * STR), "n"(6 * STR), "n"(7 * STR)
    : "memory");
}

template <int STR>
__device__ __forceinline__ void verify8_rt(const uint4* p, uint32_t (*r)[4], uint32_t tag) {
  asm volatile("{\n.reg .pred p, q;\n.reg .b32 a, b, n;\nmov.u32 n, 0;\n"
    "LAB_CHK:\n"
    "lop3.b32 a, %0, %4, %41, 0x7e;\n"
    "lop3.b32 b, %8, %12, %41, 0x7e;\nor.b32 a, a, b;\n"
    "lop3.b32 b, %16, %20, %41, 0x7e;\nor.b32 a, a, b;\n"
    "lop3.b32 b, %24, %28, %41, 0x7e;\nor.b32 a, a, b;\n"
    "and.b32 a, a, 1;\nsetp.eq.u32 p, a, 0;\nvote.sync.all.pred p, p, 0xffffffff;\n"
    "@p bra.uni LAB_OK;\n"
    "and.b32 a, %0, 1;\nsetp.ne.u32 q, a, %41;\n"
    "@q ld.relaxed.gpu.global.v4.b32 {%0,%1,%2,%3}, [%32+%33];\n"
    "and.b32 a, %4, 1;\nsetp.ne.u32 q, a, %41;\n"
    "@q ld.relaxed.gpu.global.v4.b32 {%4,%5,%6,%7}, [%32+%34];\n"
    "and.b32 a, %8, 1;\nsetp.ne.u32 q, a, %41;\n"
    "@q ld.relaxed.gpu.global.v4.b32 {%8,%9,%10,%11}, [%32+%35];\n"
    "and.b32 a, %12, 1;\nsetp.ne.u32 q, a, %41;\n"
    "@q ld.relaxed.gpu.global.v4.b32 {%12,%13,%14,%15}, [%32+%36];\n"
    "and.b32 a, %16, 1;\nsetp.ne.u32 q, a, %41;\n"
    "@q ld.relaxed.gpu.global.v4.b32 {%16,%17,%18,%19}, [%32+%37];\n"
    "and.b32 a, %20, 1;\nsetp.ne.u32 q, a, %41;\n"
    "@q ld.relaxed.gpu.global.v4.b32 {%20,%21,%22,%23}, [%32+%38];\n"
    "and.b32 a, %24, 1;\nsetp.ne.u32 q, a, %41;\n"
    "@q ld.relaxed.gpu.global.v4.b32 {%24,%25,%26,%27}, [%32+%39];\n"
    "and.b32 a, %28, 1;\nsetp.ne.u32 q, a, %41;\n"
    "@q ld.relaxed.gpu.global.v4.b32 {%28,%29,%30,%31}, [%32+%40];\n"
    "add.u32 n, n, 1;\nsetp.lt.u32 q, n, 262144;\n@q bra.uni LAB_CHK;\n"
    "LAB_OK:\n}\n"
    : "+r"(r[0][0]), "+r"(r[0][1]), "+r"(r[0][2]), "+r"(r[0][3]), "+r"(r[1][0]), "+r"(r[1][1]), "+r"(r[1][2]), "+r"(r[1][3]),
      "+r"(r[2][0]), "+r"(r[2][1]), "+r"(r[2][2]), "+r"(r[2][3]), "+r"(r[3][0]), "+r"(r[3][1]), "+r"(r[3][2]), "+r"(r[3][3]),
      "+r"(r[4][0]), "+r"(r[4][1]), "+r"(r[4][2]), "+r"(r[4][3]), "+r"(r[5][0]), "+r"(r[5][1]), "+r"(r[5][2]), "+r"(r[5][3]),
      "+r"(r[6][0]), "+r"(r[6][1]), "+r"(r[6][2]), "+r"(r[6][3]), "+r"(r[7][0]), "+r"(r[7][1]), "+r"(r[7][2]), "+r"(r[7][3])
    : "l"(p), "n"(0 * STR), "n"(1 * STR), "n"(2 * STR), "n"(3 * STR), "n"(4 * STR), "n"(5 * STR), "n"(6 * STR), "n"(7 * STR), "r"(tag)
    : "memory");
}

template <int STR>
__device__ __forceinline__ void verify4_tag0(const uint4* p, uint32_t (*r)[4]) {
  asm volatile("{\n.reg .pred p, q;\n.reg .b32 a, n;\nmov.u32 n, 0;\n"
    "LAB_CHK:\n"
    "or.b32 a, %0, %4;\n"
    "or.b32 a, a, %8;\n"
    "or.b32 a, a, %12;\n"
    "and.b32 a, a, 1;\nsetp.eq.u32 p, a, 0;\nvote.sync.all.pred p, p, 0xffffffff;\n"
    "@p bra.uni LAB_OK;\n"
    "and.b32 a, %0, 1;\nsetp.ne.u32 q, a, 0;\n"
    "@q ld.relaxed.gpu.global.v4.b32 {%0,%1,%2,%3}, [%16+%17];\n"
    "and.b32 a, %4, 1;\nsetp.ne.u32 q, a, 0;\n"
    "@q ld.relaxed.gpu.global.v4.b32 {%4,%5,%6,%7}, [%16+%18];\n"
    "and.b32 a, %8, 1;\nsetp.ne.u32 q, a, 0;\n"
    "@q ld.relaxed.gpu.global.v4.b32 {%8,%9,%10,%11}, [%16+%19];\n"
    "and.b32 a, %12, 1;\nsetp.ne.u32 q, a, 0;\n"
    "@q ld.relaxed.gpu.global.v4.b32 {%12,%13,%14,%15}, [%16+%20];\n"
    "add.u32 n, n, 1;\nsetp.lt.u32 q, n, 262144;\n@q bra.uni LAB_CHK;\n"
    "LAB_OK:\n"
    "or.b32 %0, %0, 1;\n"
    "or.b32 %4, %4, 1;\n"
    "or.b32 %8, %8, 1;\n"
    "or.b32 %12, %12, 1;\n"
    "}\n"
    : "+r"(r[0][0]), "+r"(r[0][1]), "+r"(r[0][2]), "+r"(r[0][3]), "+r"(r[1][0]), "+r"(r[1][1]), "+r"(r[1][2]), "+r"(r[1][3]),
      "+r"(r[2][0]), "+r"(r[2][1]), "+r"(r[2][2]), "+r"(r[2][3]), "+r"(r[3][0]), "+r"(r[3][1]), "+r"(r[3][2]), "+r"(r[3][3])
    : "l"(p), "n"(0 * STR), "n"(1 * STR), "n"(2 * STR), "n"(3 * STR)
    : "memory");
}

#define SPIN_LIMIT (1 << 18)

__device__ __forceinline__ uint32_t smem_u32(const void* p) { return (uint32_t)__cvta_generic_to_shared(p); }
__device__ __forceinline__ void mbar_init(uint32_t a, uint32_t c) {
  asm volatile("mbarrier.init.shared::cta.b64 [%0], %1;" ::"r"(a), "r"(c) : "memory");
}
__device__ __forceinline__ void mbar_expect(uint32_t a, uint32_t b) {
  asm volatile("mbarrier.arrive.expect_tx.shared::cta.b64 _, [%0], %1;" ::"r"(a), "r"(b) : "memory");
}
__device__ __forceinline__ void mbar_arrive(uint32_t a) {
  asm volatile("mbarrier.arrive.shared::cta.b64 _, [%0];" ::"r"(a) : "memory");
}
__device__ __forceinline__ void mbar_wait(uint32_t a, uint32_t parity) {
  asm volatile(
      "{\n.reg .pred p;\n.reg .u32 n;\nmov.u32 n, 0;\n"
      "LAB_WAIT:\n"
      "mbarrier.try_wait.parity.shared::cta.b64 p, [%0], %1;\n"
      "@p bra LAB_DONE;\n"
      "add.u32 n, n, 1;\n"
      "setp.lt.u32 p, n, 262144;\n"
      "@p bra LAB_WAIT;\n"
      "LAB_DONE:\n}\n" ::"r"(a), "r"(parity) : "memory");
}
__device__ __forceinline__ bool mbar_test(uint32_t a, uint32_t parity) {
  uint32_t ok;
  asm volatile("{\n.reg .pred p;\nmbarrier.test_wait.parity.shared::cta.b64 p, [%1], %2;\nselp.u32 %0, 1, 0, p;\n}\n"
               : "=r"(ok) : "r"(a), "r"(parity) : "memory");
  return ok;
}
__device__ __forceinline__ void tma3d(uint32_t dst, const CUtensorMap* tm, uint32_t bar, int c0, int c1, int c2) {
  asm volatile(
      "cp.async.bulk.tensor.3d.shared::cluster.global.mbarrier::complete_tx::bytes [%0], [%1, {%3,%4,%5}], [%2];"
      ::"r"(dst), "l"(tm), "r"(bar), "r"(c0), "r"(c1), "r"(c2) : "memory");
}
__device__ __forceinline__ void wg_fence() { asm volatile("wgmma.fence.sync.aligned;" ::: "memory"); }
__device__ __forceinline__ void wg_commit() { asm volatile("wgmma.commit_group.sync.aligned;" ::: "memory"); }
template <int N> __device__ __forceinline__ void wg_wait() {
  asm volatile("wgmma.wait_group.sync.aligned %0;" ::"n"(N) : "memory");
}
template <int N> __device__ __forceinline__ void fence_regs(float (&d)[N]) {
#pragma unroll
  for (int i = 0; i < N; i++) asm volatile("" : "+f"(d[i])::"memory");
}
template <int N> __device__ __forceinline__ void fence_regs(uint32_t (&d)[N][4]) {
#pragma unroll
  for (int i = 0; i < N; i++) asm volatile("" : "+r"(d[i][0]), "+r"(d[i][1]), "+r"(d[i][2]), "+r"(d[i][3])::"memory");
}
template <int N> __device__ __forceinline__ void fence_frags(uint32_t (*d)[4]) {
#pragma unroll
  for (int i = 0; i < N; i++) asm volatile("" : "+r"(d[i][0]), "+r"(d[i][1]), "+r"(d[i][2]), "+r"(d[i][3])::"memory");
}
__device__ __forceinline__ void bar_sync(int id, int n) { asm volatile("bar.sync %0, %1;" ::"r"(id), "r"(n) : "memory"); }
__device__ __forceinline__ void bar_arrive(int id, int n) { asm volatile("bar.arrive %0, %1;" ::"r"(id), "r"(n) : "memory"); }

__device__ __forceinline__ uint32_t pack_bf16(float lo, float hi) {
  uint32_t r;
  asm("cvt.rn.bf16x2.f32 %0, %1, %2;" : "=r"(r) : "f"(hi), "f"(lo));
  return r;
}
__device__ __forceinline__ float bf_lo(uint32_t w) { return __uint_as_float(w << 16); }
__device__ __forceinline__ float bf_hi(uint32_t w) { return __uint_as_float(w & 0xFFFF0000u); }
__device__ __forceinline__ float round_bf16(float x) { return bf_lo(pack_bf16(x, 0.f)); }
__device__ __forceinline__ uint32_t hfma2_bf16(uint32_t a, uint32_t b, uint32_t c) {
  uint32_t r;
  asm("fma.rn.bf16x2 %0, %1, %2, %3;" : "=r"(r) : "r"(a), "r"(b), "r"(c));
  return r;
}
__device__ __forceinline__ float ex2(float x) {
  float r;
  asm("ex2.approx.ftz.f32 %0, %1;" : "=f"(r) : "f"(x));
  return r;
}
__device__ __forceinline__ float tanh_hw(float x) {
  float r;
  asm("tanh.approx.f32 %0, %1;" : "=f"(r) : "f"(x));
  return r;
}
template <int TAG> __device__ __forceinline__ uint32_t pack_tag(float lo, float hi) {
  uint32_t w = __byte_perm(__float_as_uint(lo), pack_bf16(lo, hi), 0x7632);
  return TAG ? (w | 1u) : (w & ~1u);
}
__device__ __forceinline__ void st_pkt(uint4* p, uint32_t a, uint32_t b, uint32_t c, uint32_t d) {
  asm volatile(
      "st.relaxed.gpu.global.v4.b32 [%0], {%1,%2,%3,%4};" ::"l"(p), "r"(a), "r"(b), "r"(c), "r"(d) : "memory");
}
__device__ __forceinline__ void ld_pkt(const uint4* p, uint32_t (&r)[4]) {
  asm volatile(
      "ld.relaxed.gpu.global.v4.b32 {%0,%1,%2,%3}, [%4];"
      : "=r"(r[0]), "=r"(r[1]), "=r"(r[2]), "=r"(r[3]) : "l"(p) : "memory");
}
__device__ __forceinline__ uint32_t ldg32(const void* p) {
  uint32_t r;
  asm volatile("ld.global.nc.b32 %0, [%1];" : "=r"(r) : "l"(p));
  return r;
}
__device__ __forceinline__ uint32_t ldg16(const void* p) {
  uint16_t r;
  asm volatile("ld.global.nc.b16 %0, [%1];" : "=h"(r) : "l"(p));
  return r;
}
__device__ __forceinline__ uint4 ldg128(const void* p) {
  uint4 r;
  asm volatile("ld.global.nc.v4.b32 {%0,%1,%2,%3}, [%4];" : "=r"(r.x), "=r"(r.y), "=r"(r.z), "=r"(r.w) : "l"(p));
  return r;
}
__device__ __forceinline__ void l2_prefetch(const void* p, uint32_t bytes) {
  asm volatile("cp.async.bulk.prefetch.L2.global [%0], %1;" ::"l"(p), "r"(bytes) : "memory");
}
__device__ __forceinline__ float rcp_hw(float x) {
  float r;
  asm("rcp.approx.ftz.f32 %0, %1;" : "=f"(r) : "f"(x));
  return r;
}
__device__ __forceinline__ void warp_bulk_load(uint32_t sdst, const void* gsrc, uint32_t bytes, uint32_t bar) {
  asm volatile(
      "{\n.reg .pred p;\nelect.sync _|p, 0xffffffff;\n"
      "@p mbarrier.arrive.expect_tx.shared::cta.b64 _, [%3], %2;\n"
      "@p cp.async.bulk.shared::cluster.global.mbarrier::complete_tx::bytes [%0], [%1], %2, [%3];\n}\n"
      ::"r"(sdst), "l"(gsrc), "r"(bytes), "r"(bar) : "memory");
}
__device__ __forceinline__ void warp_tma3d(uint32_t dst, const CUtensorMap* tm, uint32_t bar, uint32_t bytes, int c1, int c2) {
  asm volatile(
      "{\n.reg .pred p;\nelect.sync _|p, 0xffffffff;\n"
      "@p mbarrier.arrive.expect_tx.shared::cta.b64 _, [%2], %3;\n"
      "@p cp.async.bulk.tensor.3d.shared::cluster.global.mbarrier::complete_tx::bytes [%0], [%1, {%6,%4,%5}], [%2];\n}\n"
      ::"r"(dst), "l"(tm), "r"(bar), "r"(bytes), "r"(c1), "r"(c2), "r"(0) : "memory");
}
__device__ __forceinline__ bool elect_one() {
  uint32_t r;
  asm volatile("{\n.reg .pred p;\nelect.sync _|p, 0xffffffff;\nselp.u32 %0, 1, 0, p;\n}\n" : "=r"(r));
  return r;
}
__device__ __forceinline__ void warp_arrive(uint32_t bar) {
  asm volatile("{\n.reg .pred p;\nelect.sync _|p, 0xffffffff;\n@p mbarrier.arrive.shared::cta.b64 _, [%0];\n}\n" ::"r"(bar) : "memory");
}
__device__ __forceinline__ uint32_t pack_trunc(float lo, float hi) {
  return __byte_perm(__float_as_uint(lo), __float_as_uint(hi), 0x7632);
}
__device__ __forceinline__ void add_partial(float (&y)[8], const uint32_t (&r)[4], uint32_t c0, bool first) {
#pragma unroll
  for (int e = 0; e < 4; e++) {
    const float lo = __uint_as_float(r[e] * 65536u + (e ? 0x8000u : c0)), hi = __uint_as_float(r[e]);
    y[2 * e] = first ? lo : y[2 * e] + lo;
    y[2 * e + 1] = first ? hi : y[2 * e + 1] + hi;
  }
}
__device__ __forceinline__ void spin_cycles(uint32_t n) {
  uint32_t t0, t;
  asm volatile("mov.u32 %0, %%clock;" : "=r"(t0));
  do { asm volatile("mov.u32 %0, %%clock;" : "=r"(t)); } while (t - t0 < n);
}
__device__ __forceinline__ void sts128(uint32_t a, uint32_t x, uint32_t y, uint32_t z, uint32_t w) {
  asm volatile("st.shared.v4.b32 [%0], {%1,%2,%3,%4};" ::"r"(a), "r"(x), "r"(y), "r"(z), "r"(w) : "memory");
}
__device__ __forceinline__ void lds128(uint32_t a, uint32_t (&r)[4]) {
  asm volatile("ld.shared.v4.b32 {%0,%1,%2,%3}, [%4];" : "=r"(r[0]), "=r"(r[1]), "=r"(r[2]), "=r"(r[3]) : "r"(a) : "memory");
}

__device__ __forceinline__ uint32_t lds32(uint32_t a) {
  uint32_t r;
  asm volatile("ld.shared.b32 %0, [%1];" : "=r"(r) : "r"(a) : "memory");
  return r;
}
__device__ __forceinline__ void store_out(__nv_bfloat16* out, uint32_t woff, uint32_t x2s, uint32_t gb0, uint32_t gb1,
                                          const float (&y)[8]) {
  const uint32_t gb[2] = {gb0, gb1};
  uint32_t xa[2][4];
  lds128(x2s, xa[0]);
  lds128(x2s + 2048, xa[1]);
  uint32_t* const oo = (uint32_t*)out + woff;
#pragma unroll
  for (int e = 0; e < 4; e++)
    oo[(e >> 1) * 4 + (e & 1) * 8 * 256] =
        pack_bf16(fmaf(bf_lo(gb[e >> 1]), y[2 * e], __uint_as_float(xa[e >> 1][(e & 1) * 2])),
                  fmaf(bf_hi(gb[e >> 1]), y[2 * e + 1], __uint_as_float(xa[e >> 1][(e & 1) * 2 + 1])));
}

constexpr int SK = 2048, WIN = 512;
constexpr int FF = 1792, FSL = 224;
constexpr int NTILES = 80;
constexpr int NSLOT = 4;
constexpr uint32_t SLOT = 32768;
constexpr uint32_t SM_PARK = 0;
constexpr uint32_t SM_RING = 3 * SLOT;
constexpr uint32_t SM_TAB = 7 * SLOT;
constexpr uint32_t SM_RED = SM_TAB + 2048;
constexpr uint32_t SM_BAR = SM_RED + 256;
constexpr uint32_t SM_WBAR = SM_BAR + 128;
constexpr uint32_t SM_SBAR = SM_WBAR + 256;
constexpr uint32_t BAR_SLAB = 64, BAR_UV = 72, BAR_X2 = 80, BAR_TAG = 88;
constexpr uint32_t SM_TOTAL = SM_SBAR + 112;

struct Scratch {
  uint4 P[16 * 8 * 8 * 1024];
  uint4 G[16 * 8 * 32 * 32];
  uint4 mod1[8 * 256];
  uint4 mod2[512];
  uint4 uv[2 * 448];
  uint4 stat[16 * 8 * 8];
  uint32_t epoch;
};
__device__ Scratch g_scratch;

#define TS(i) do { } while (0)
#define TR(code)
#define CK_(v)
#define CKS(i, v)

struct Params {
  const __nv_bfloat16* x;
  const __nv_bfloat16* c;
  const __nv_bfloat16* wmod;
  const __nv_bfloat16* wo;
  const __nv_bfloat16* w1;
  const __nv_bfloat16* w2;
  __nv_bfloat16* out;
  Scratch* s;
};

constexpr uint32_t HI128 = (1024 >> 4) | (1u << 30);
constexpr int LB_MN128 = (16384 >> 4) << 16;
constexpr int LB_K128 = 1 << 16;
constexpr int LB_W1 = (8192 >> 4) << 16;

template <int I> struct IC {
  __host__ __device__ constexpr operator int() const { return I; }
};
template <int I, int N, typename F> __device__ __forceinline__ void static_for(F&& f) {
  if constexpr (I < N) {
    f(IC<I>{});
    static_for<I + 1, N>(f);
  }
}

struct Ring {
  uint32_t base16, bars;
  __device__ __forceinline__ uint32_t wait_full(uint32_t slot, uint32_t parity) const {
    mbar_wait(bars + slot * 8, parity);
    return base16 + slot * (SLOT >> 4);
  }
  __device__ __forceinline__ void release(uint32_t slot) const {
    warp_arrive(bars + 32 + slot * 8);
  }
};

__device__ __forceinline__ float silu_c(uint32_t bits) {
  float x = bf_lo(bits);
  return round_bf16(x * rcp_hw(1.f + ex2(-1.4426950408889634f * x)));
}
__device__ __forceinline__ void pack8(uint32_t (&o)[4], const float* v) {
  o[0] = pack_bf16(v[0], v[1]); o[1] = pack_bf16(v[2], v[3]); o[2] = pack_bf16(v[4], v[5]); o[3] = pack_bf16(v[6], v[7]);
}

template <int TAG, int N>
__device__ __forceinline__ void issue_pkts(const uint4* p, int stride, uint32_t (*r)[4]) {
#pragma unroll
  for (int i = 0; i < N; i++) ld_pkt(p + i * stride, r[i]);
}
__device__ __forceinline__ void ld_mod(const uint4* p, uint32_t tag, uint32_t (&r)[4]) {
  int spins = 0;
  ld_pkt(p, r);
  while (r[2] != tag && ++spins < SPIN_LIMIT) ld_pkt(p, r);
}

#define EARLY_TILES 2
#define PF_WMOD 1
#define MOD1_DELAY 500
#define RED3_UNIT 3
#define JLO 2
#define NITEM2 24
#define FIN_DELAY0 800
#define FIN_DELAY1 0
#define G_DELAY 300

__device__ __forceinline__ float reduce8(float (&a)[8], int lane) {
  const bool h16 = lane & 16, h8 = lane & 8, h4 = lane & 4;
#pragma unroll
  for (int k = 0; k < 4; k++) a[k] = (h16 ? a[k + 4] : a[k]) + __shfl_xor_sync(0xffffffffu, h16 ? a[k] : a[k + 4], 16);
#pragma unroll
  for (int k = 0; k < 2; k++) a[k] = (h8 ? a[k + 2] : a[k]) + __shfl_xor_sync(0xffffffffu, h8 ? a[k] : a[k + 2], 8);
  const float r = (h4 ? a[1] : a[0]) + __shfl_xor_sync(0xffffffffu, h4 ? a[0] : a[1], 4);
  return r + __shfl_xor_sync(0xffffffffu, r, 2);
}
__device__ __forceinline__ void fma8(float (&a)[8], float s, uint32_t w0, uint32_t w1, uint32_t w2, uint32_t w3) {
  a[0] = fmaf(s, bf_lo(w0), a[0]); a[1] = fmaf(s, bf_hi(w0), a[1]);
  a[2] = fmaf(s, bf_lo(w1), a[2]); a[3] = fmaf(s, bf_hi(w1), a[3]);
  a[4] = fmaf(s, bf_lo(w2), a[4]); a[5] = fmaf(s, bf_hi(w2), a[5]);
  a[6] = fmaf(s, bf_lo(w3), a[6]); a[7] = fmaf(s, bf_hi(w3), a[7]);
}

enum { NB_TAB = 1, NB_WG0 = 2, NB_WG1 = 3, NB_HELP = 4, NB_INIT = 5, NB_PASS0 = 6, NB_GATHER = 7, NB_PARK = 8, NB_PROD = 9 };

__global__ void __launch_bounds__(512, 1)
adaln_block_kernel(const __grid_constant__ CUtensorMap tmWq, const __grid_constant__ CUtensorMap tmK,
                   const __grid_constant__ CUtensorMap tmV, const __grid_constant__ CUtensorMap tmWo,
                   const __grid_constant__ CUtensorMap tmW1, const __grid_constant__ CUtensorMap tmW2,
                   const __grid_constant__ CUtensorMap tmWm, const __grid_constant__ CUtensorMap tmP,
                   const __grid_constant__ CUtensorMap tmX, const Params p) {
  extern __shared__ __align__(1024) uint8_t smem_raw[];
  const uint32_t sb = smem_u32(smem_raw);
  const int tid = threadIdx.x, lane = tid & 31;
  const int warp = __shfl_sync(0xffffffffu, tid >> 5, 0);
  const int bid = blockIdx.x;
  const int j = ((bid >> (4 + JLO)) << JLO) | (bid & ((1 << JLO) - 1)), rt = (bid >> JLO) & 15;
  const uint32_t bars = sb + SM_BAR;

  if (warp >= 12) {
    asm volatile("setmaxnreg.dec.sync.aligned.u32 24;");
    if (warp == 13) {
      if (elect_one()) {
#pragma unroll
        for (int i = 0; i < 28; i++) mbar_init(sb + SM_WBAR + i * 8, i < 26 ? 1 : 4);
#pragma unroll
        for (int i = 0; i < 14; i++) mbar_init(sb + SM_SBAR + i * 8, 8);
        asm volatile("fence.mbarrier_init.release.cluster;" ::: "memory");
      }
      __syncwarp();
      bar_arrive(NB_INIT, 192);
#pragma unroll 1
      for (int n = 0; n < 14; n++) {
        const uint32_t lb = sb + SM_WBAR + 192 + (n & 1) * 8;
        mbar_wait(sb + SM_SBAR + n * 8, 0);
        mbar_wait(lb + 16, ((n >> 1) & 1) ^ 1);
        warp_tma3d(sb + SM_PARK + (n & 1) * 16384, &tmP, lb, n < 8 ? 16384 + 2048 : 16384, (n & 7) * 4, (rt * 8 + j) * 8);
        if (n < 8 && elect_one()) tma3d(sb + SM_PARK + SLOT + n * 4096, &tmX, lb, 0, rt * 128 + j * 16, n * 4);
      }
    } else if (warp == 14) {
      if (elect_one()) {
        asm volatile("prefetch.tensormap [%0];" ::"l"(&tmWq) : "memory");
        asm volatile("prefetch.tensormap [%0];" ::"l"(&tmK) : "memory");
        asm volatile("prefetch.tensormap [%0];" ::"l"(&tmV) : "memory");
        asm volatile("prefetch.tensormap [%0];" ::"l"(&tmWo) : "memory");
        asm volatile("prefetch.tensormap [%0];" ::"l"(&tmP) : "memory");
        asm volatile("prefetch.tensormap [%0];" ::"l"(&tmX) : "memory");
        asm volatile("prefetch.tensormap [%0];" ::"l"(&tmW1) : "memory");
        asm volatile("prefetch.tensormap [%0];" ::"l"(&tmW2) : "memory");
      }
    } else if (warp == 12) {
      if (elect_one()) {
        mbar_init(bars + BAR_SLAB, 1);
        asm volatile("fence.mbarrier_init.release.cluster;" ::: "memory");
        mbar_expect(bars + BAR_SLAB, 8192);
        tma3d(sb + SM_RING + 3 * SLOT, &tmWm, bars + BAR_SLAB, 0, 0, bid);
        tma3d(sb + SM_RING + 3 * SLOT + 4096, &tmWm, bars + BAR_SLAB, 0, 256, bid);
#pragma unroll
        for (int i = 0; i < 4; i++) { mbar_init(bars + i * 8, 1); mbar_init(bars + 32 + i * 8, 8); }
        mbar_init(bars + BAR_UV, 4);
        mbar_init(bars + BAR_X2, 1);
        asm volatile("fence.mbarrier_init.release.cluster;" ::: "memory");
      }
      __syncwarp();
      bar_arrive(NB_INIT, 192);
      mbar_wait(bars + BAR_SLAB, 0);
      uint32_t s = 0, ph = 1;
#pragma unroll 1
      for (int tt = 0; tt < NTILES; tt++) {
        const CUtensorMap* tm;
        int c1, c2;
        uint32_t bytes = SLOT;
        if (tt < 16) {
          tm = &tmWq; c1 = (tt & 3) * 128; c2 = (j * 4 + (((tt >> 2) + 1) & 3)) * 2;
        } else if (tt < 48) {
          const int u = tt - 16;
          const bool isK = (u == 0) || ((u & 1) && u != 31);
          const int n = isK ? ((u + 1) >> 1) : (u == 31 ? 15 : (u >> 1) - 1);
          tm = isK ? &tmK : &tmV; c1 = j * SK + (SK - WIN) + (n & 3) * 128; c2 = 0;
        } else if (tt < 64) {
          const int u = tt - 48;
          tm = &tmWo; c1 = j * 512 + (u & 1) * 256; c2 = u >> 1;
        } else if (tt < 72) {
          tm = &tmW1; c1 = (tt - 64) * 64; c2 = (j * 7) >> 1;
        } else {
          tm = &tmW2; c1 = j * FSL; c2 = tt - 72; bytes = 28672;
        }
        if (tt == EARLY_TILES) bar_sync(NB_PROD, 160);
        mbar_wait(bars + 32 + s * 8, ph);
        warp_tma3d(sb + SM_RING + s * SLOT, tm, bars + s * 8, bytes, c1, c2);
        if (++s == 4) { s = 0; ph ^= 1; }
      }
    }
  } else if (warp >= 8) {
    CK_(c0);
    asm volatile("setmaxnreg.dec.sync.aligned.u32 40;");
    const int t = tid - 256, hw = warp - 8, q = lane & 3;
    float* const red = (float*)(smem_raw + SM_RED);
    uint32_t tag;
    float a[8];
    {
      uint32_t cb[4];
#pragma unroll
      for (int i = 0; i < 4; i++) cb[i] = ldg16(p.c + t + 128 * i);
      asm volatile("ld.relaxed.gpu.global.u32 %0, [%1];" : "=r"(tag) : "l"(&p.s->epoch) : "memory");
      bar_sync(NB_INIT, 192);
      CK_(c2);
      tag += 1;
      float sc[4];
#pragma unroll
      for (int i = 0; i < 4; i++) sc[i] = silu_c(cb[i]);
#pragma unroll
      for (int k = 0; k < 8; k++) a[k] = 0.f;
      if (t == 0) *(uint32_t*)(smem_raw + SM_BAR + BAR_TAG) = tag;
      mbar_wait(bars + BAR_SLAB, 0);
      CK_(c3);
      bar_arrive(NB_GATHER, 384);
#pragma unroll
      for (int i = 0; i < 4; i++) {
        uint32_t w[4];
        lds128(sb + SM_RING + 3 * SLOT + (t + 128 * i) * 16, w);
        fma8(a, sc[i], w[0], w[1], w[2], w[3]);
      }
      float r = reduce8(a, lane);
      r += __shfl_xor_sync(0xffffffffu, r, 1);
      if (q == 0) red[hw * 8 + (lane >> 2)] = r;
      CK_(c4);
      bar_sync(NB_HELP, 128);
      CK_(c5);
      if (hw == 0) {
        const int cl = lane & 7;
        float v = round_bf16(red[cl] + red[8 + cl] + red[16 + cl] + red[24 + cl]);
        if (bid >= 64) v = 1.f + v;
        float vn = __shfl_down_sync(0xffffffffu, v, 1);
        uint32_t wd = pack_bf16(v, vn);
        uint32_t w0 = __shfl_sync(0xffffffffu, wd, (lane & 1) * 4);
        uint32_t w1 = __shfl_sync(0xffffffffu, wd, (lane & 1) * 4 + 2);
        if (lane < 16) st_pkt(&p.s->mod1[(lane >> 1) * 256 + bid * 2 + (lane & 1)], w0, w1, tag, 0);
      }
      uint32_t r0[4], r1[4];
      const uint4* src = &p.s->mod1[j * 256 + t];
      CK_(c6);
      spin_cycles(MOD1_DELAY);
      CK_(c7);
      int spins = 0;
      do {
        ld_pkt(src, r0);
        ld_pkt(src + 128, r1);
      } while ((r0[2] != tag || r1[2] != tag) && ++spins < SPIN_LIMIT);
      const int g = t >> 2, pp = q * 2;
      const uint32_t ad = sb + SM_TAB + (uint32_t)(g * 4 + (pp & 3)) * 16 + (pp >> 2) * 4;
      asm volatile("st.shared.b32 [%0], %1;" ::"r"(ad + 8), "r"(r0[0]) : "memory");
      asm volatile("st.shared.b32 [%0], %1;" ::"r"(ad + 24), "r"(r0[1]) : "memory");
      asm volatile("st.shared.b32 [%0], %1;" ::"r"(ad), "r"(r1[0]) : "memory");
      asm volatile("st.shared.b32 [%0], %1;" ::"r"(ad + 16), "r"(r1[1]) : "memory");
      bar_arrive(NB_TAB, 384);
      bar_arrive(NB_PROD, 160);
      CK_(c8);
      CKS(0, c0); CKS(2, c2); CKS(3, c3); CKS(4, c4); CKS(5, c5); CKS(6, c6); CKS(7, c7); CKS(8, c8);
    }
    bar_sync(NB_PASS0, 384);
    if (t < 8) l2_prefetch((const char*)p.wo + (size_t)bid * 32768 + t * 4096, 4096);
    else if (t < 12) l2_prefetch((const char*)p.w1 + (size_t)bid * 14336 + (t - 8) * 3584, 3584);
    else if (t < 16) l2_prefetch((const char*)p.w2 + (size_t)bid * 14336 + (t - 12) * 3584, 3584);
    {
#pragma unroll
      for (int k = 0; k < 8; k++) a[k] = 0.f;
#pragma unroll 1
      for (int b = 0; b < 4; b++) {
        const int row = b * 128 + (t >> 1);
        const __nv_bfloat16* wp = p.wmod + (size_t)row * 3072 + 1024 + bid * 16 + (t & 1) * 8;
        const uint4 w0 = ldg128(wp), w1 = ldg128(wp + 64 * 3072);
        const uint32_t c0 = ldg16(p.c + row), c1 = ldg16(p.c + row + 64);
        fma8(a, silu_c(c0), w0.x, w0.y, w0.z, w0.w);
        fma8(a, silu_c(c1), w1.x, w1.y, w1.z, w1.w);
      }
      const float r = reduce8(a, lane);
      if ((lane & 2) == 0) red[hw * 16 + (lane & 1) * 8 + (lane >> 2)] = r;
      bar_sync(NB_HELP, 128);
      if (hw == 0) {
        const int cl = lane & 15;
        float v = round_bf16(red[cl] + red[16 + cl] + red[32 + cl] + red[48 + cl]);
        if ((bid >> 5) == 2) v = 1.f + v;
        float vn = __shfl_down_sync(0xffffffffu, v, 1);
        uint32_t wd = pack_bf16(v, vn);
        uint32_t w0 = __shfl_sync(0xffffffffu, wd, q * 2);
        uint32_t w1 = __shfl_sync(0xffffffffu, wd, q * 2 + 8);
        const int vec = (0x2130 >> ((bid >> 5) * 4)) & 3;
        if (lane < 4) st_pkt(&p.s->mod2[((bid & 31) * 4 + vec) * 4 + lane], w0, w1, tag, 0);
      }
    }
    {
      const int isv = hw & 1, kh = hw >> 1;
      if (bid < 112) {
        const int kk = lane >> 1;
        uint32_t m0[4], m1[4];
        const uint4* mp = &p.s->mod2[(kh * 16 + (lane >> 2)) * 16 + (isv ? 12 : 4) + q];
        ld_mod(mp, tag, m0);
        ld_mod(mp + 128, tag, m1);
#pragma unroll
        for (int k = 0; k < 8; k++) a[k] = 0.f;
#pragma unroll 1
        for (int g0 = 0; g0 < 16; g0 += 2) {
          uint4 w[2];
#pragma unroll
          for (int i = 0; i < 2; i++) w[i] = ldg128(p.w1 + (size_t)((kh * 16 + g0 + i) * 16 + kk) * FF + bid * 16 + (lane & 1) * 8);
#pragma unroll
          for (int i = 0; i < 2; i++) {
            const int sl = ((g0 + i) & 7) * 4 + ((kk & 7) >> 1);
            const uint32_t wa = __shfl_sync(0xffffffffu, g0 < 8 ? m0[0] : m1[0], sl), wb = __shfl_sync(0xffffffffu, g0 < 8 ? m0[1] : m1[1], sl);
            const uint32_t mw = (kk & 8) ? wb : wa;
            fma8(a, (kk & 1) ? bf_hi(mw) : bf_lo(mw), w[i].x, w[i].y, w[i].z, w[i].w);
          }
        }
        float r = reduce8(a, lane);
        bar_sync(NB_HELP, 128);
        if (kh) red[isv * 32 + lane] = r;
        bar_sync(NB_HELP, 128);
        if (!kh) {
          r = (r + red[isv * 32 + lane]) * (isv ? 0.5f : 1.f);
          const float r1 = __shfl_down_sync(0xffffffffu, r, 4), r2 = __shfl_down_sync(0xffffffffu, r, 8),
                      r3 = __shfl_down_sync(0xffffffffu, r, 12);
          if ((lane & 14) == 0)
            st_pkt(&p.s->uv[isv * 448 + bid * 4 + (lane & 1) * 2 + (lane >> 4)], (__float_as_uint(r) & ~1u) | (tag & 1u),
                   __float_as_uint(r1), __float_as_uint(r2), __float_as_uint(r3));
        }
      }
      const int i = kh * 32 + lane;
      if (i < 56) {
        uint32_t m[4];
        int spins = 0;
        while (true) {
          ld_pkt(&p.s->uv[isv * 448 + j * 56 + i], m);
          if (!((m[0] ^ tag) & 1u) || ++spins >= SPIN_LIMIT) break;
          __nanosleep(200);
        }
        const int ip = (j & 1) ? (i < 8 ? i + 48 : i - 8) : i;
        const uint32_t ad = sb + SM_TAB + ip * 32 + isv * 8;
        asm volatile("st.shared.v2.b32 [%0], {%1,%2};" ::"r"(ad), "r"(m[0]), "r"(m[1]) : "memory");
        asm volatile("st.shared.v2.b32 [%0], {%1,%2};" ::"r"(ad + 16), "r"(m[2]), "r"(m[3]) : "memory");
      }
      __syncwarp();
      warp_arrive(bars + BAR_UV);
      TS(9);
    }
    {
      uint32_t mga[4], mg2[4], mgb[4];
      const uint4* mp = &p.s->mod2[((lane >> 2) * 4 + hw) * 16 + q];
      ld_mod(mp, tag, mga);
      ld_mod(mp + 4, tag, mg2);
      ld_mod(mp + 8, tag, mgb);
      if (lane >= 24) asm volatile("st.shared.v2.b32 [%0], {%1,%2};" ::"r"(sb + SM_TAB + 1792 + ((((lane >> 2) & 1) * 4 + hw) * 4 + q) * 8),
                                   "r"(mgb[0]), "r"(mgb[1]) : "memory");
      const uint32_t x2s = sb + SM_PARK + SLOT + hw * 512 + lane * 16;
      const uint4* const Pown = p.s->P + (size_t)(rt * 8 + j) * 8192 + hw * 32 + lane;
      float s0 = 0.f, s1 = 0.f, v0 = 0.f, v1 = 0.f;
      bar_sync(NB_PARK, 384);
      asm volatile("setmaxnreg.inc.sync.aligned.u32 88;");
#pragma unroll 1
      for (int n = 0; n < 14; n++) {
        const int cc = n & 7;
        const bool ex1 = n < 8;
        const uint32_t lb = sb + SM_WBAR + 192 + (n & 1) * 8;
        uint32_t r[8][4];
        float y[8];
        mbar_wait(lb, (n >> 1) & 1);
#pragma unroll
        for (int i = 0; i < 8; i++) lds128(sb + SM_PARK + (n & 1) * 16384 + i * 2048 + hw * 512 + lane * 16, r[i]);
        verify8_rt<16384>(Pown + cc * 128, r, ex1);
        warp_arrive(lb + 16);
#pragma unroll
        for (int i = 0; i < 8; i++) add_partial(y, r[i], ex1 ? 0u : 0x10000u, i == 0);
        const int src = cc * 4 + q;
        const uint32_t ma = __shfl_sync(0xffffffffu, ex1 ? mga[0] : mgb[0], src), mb = __shfl_sync(0xffffffffu, ex1 ? mga[1] : mgb[1], src);
        if (ex1) {
          uint32_t xr[4];
          asm volatile("ldmatrix.sync.aligned.m8n8.x4.shared.b16 {%0,%1,%2,%3}, [%4];"
                       : "=r"(xr[0]), "=r"(xr[1]), "=r"(xr[2]), "=r"(xr[3])
                       : "r"(sb + SM_PARK + SLOT + hw * 512 + cc * 4096 + (lane & 15) * 32 + (lane >> 4) * 16) : "memory");
          const uint32_t mc = __shfl_sync(0xffffffffu, mg2[0], src), md = __shfl_sync(0xffffffffu, mg2[1], src);
#pragma unroll
          for (int e = 0; e < 4; e++) {
            const uint32_t m = e < 2 ? ma : mb;
            const float u = fmaf(bf_lo(m), y[2 * e], bf_lo(xr[e])), v = fmaf(bf_hi(m), y[2 * e + 1], bf_hi(xr[e]));
            y[2 * e] = u; y[2 * e + 1] = v;
            if (e & 1) { s1 += u + v; v1 = fmaf(u, u, fmaf(v, v, v1)); }
            else { s0 += u + v; v0 = fmaf(u, u, fmaf(v, v, v0)); }
          }
          st_pkt(p.s->G + ((rt * 8 + j) * 32 + cc * 4 + hw) * 32 + lane, pack_tag<0>(y[0] * bf_lo(mc), y[1] * bf_hi(mc)),
                 pack_bf16(y[2] * bf_lo(mc), y[3] * bf_hi(mc)), pack_bf16(y[4] * bf_lo(md), y[5] * bf_hi(md)),
                 pack_bf16(y[6] * bf_lo(md), y[7] * bf_hi(md)));
          sts128(x2s + cc * 4096, __float_as_uint(y[0]), __float_as_uint(y[1]), __float_as_uint(y[2]), __float_as_uint(y[3]));
          sts128(x2s + cc * 4096 + 2048, __float_as_uint(y[4]), __float_as_uint(y[5]), __float_as_uint(y[6]), __float_as_uint(y[7]));
          if (n == 7) {
            const bool o1 = lane & 1, o2 = lane & 2;
            float c0 = (o1 ? v0 : s0) + __shfl_xor_sync(0xffffffffu, o1 ? s0 : v0, 1);
            float c1 = (o1 ? v1 : s1) + __shfl_xor_sync(0xffffffffu, o1 ? s1 : v1, 1);
            c0 = (o2 ? c1 : c0) + __shfl_xor_sync(0xffffffffu, o2 ? c0 : c1, 2);
            *(float*)(smem_raw + SM_PARK + 16384 + hw * 512 + lane * 4) = c0;
            bar_sync(NB_HELP, 128);
            if (hw == 0) {
              const float* ps = (const float*)(smem_raw + SM_PARK + 16384) + lane;
              const float m = (c0 + ps[128] + ps[256] + ps[384]) * (1.f / 512.f);
              const float mean = __shfl_sync(0xffffffffu, m, lane & ~1), sq = __shfl_sync(0xffffffffu, m, lane | 1);
              const float rs = 0.5f * rsqrtf(fmaxf(fmaf(-mean, mean, sq), 0.f) + 1e-5f), mr = -mean * rs;
              const float rs1 = __shfl_down_sync(0xffffffffu, rs, 2), mr1 = __shfl_down_sync(0xffffffffu, mr, 2);
              if (q == 0)
                st_pkt(&p.s->stat[(rt * 8 + j) * 8 + (lane >> 2)], (__float_as_uint(rs) & ~1u) | (tag & 1u), __float_as_uint(mr),
                       __float_as_uint(rs1), __float_as_uint(mr1));
              warp_arrive(bars + BAR_X2);
            }
          }
        } else {
          store_out(p.out, (uint32_t)(rt * 128 + 16 * j + (lane >> 2)) * 256 + (cc * 4 + hw) * 8 + q, x2s + cc * 4096, ma, mb, y);
        }
      }
    }
  } else {
    const int wg = warp >> 2;
    const int q = lane & 3, gq = lane >> 2;
    const Ring ring{(sb + SM_RING) >> 4, bars};
    const uint32_t xoff = (uint32_t)(rt * 128 + 16 * j + warp) * 256 + gq * 8 + q;
    const uint32_t ooff = ((uint32_t)(rt * 8 + j) * 32 + gq) * 32 + warp * 4 + q;
    const uint32_t wblk = sb + SM_PARK + warp * 4096, wprv = wblk + lane * 16;
    const uint32_t wbar = sb + SM_WBAR + warp * 24;
    const uint4* const Gw = p.s->G + (rt * 8 + warp) * 1024;

    {
      const uint32_t* xo = (const uint32_t*)p.x + xoff;
      uint32_t xr[4][4];
      CK_(d0);
#pragma unroll
      for (int c = 0; c < 4; c++) {
        xr[c][0] = ldg32(xo + c * 64);
        xr[c][1] = ldg32(xo + c * 64 + 8 * 256);
        xr[c][2] = ldg32(xo + c * 64 + 4);
        xr[c][3] = ldg32(xo + c * 64 + 4 + 8 * 256);
      }
      CK_(d1);
      fence_regs(xr);
      CK_(d2);
      float s0 = 0.f, s1 = 0.f, v0 = 0.f, v1 = 0.f;
#pragma unroll
      for (int c = 0; c < 4; c++) {
#pragma unroll
        for (int e = 0; e < 4; e++) {
          const float a = bf_lo(xr[c][e]), b = bf_hi(xr[c][e]);
          if (e & 1) { s1 += a + b; v1 = fmaf(a, a, fmaf(b, b, v1)); }
          else { s0 += a + b; v0 = fmaf(a, a, fmaf(b, b, v0)); }
        }
      }
#pragma unroll
      for (int o = 16; o > 0; o >>= 1) {
        s0 += __shfl_xor_sync(0xffffffffu, s0, o);
        s1 += __shfl_xor_sync(0xffffffffu, s1, o);
        v0 += __shfl_xor_sync(0xffffffffu, v0, o);
        v1 += __shfl_xor_sync(0xffffffffu, v1, o);
      }
      const float m0 = s0 * (1.f / 512.f), m1 = s1 * (1.f / 512.f);
      const float r0 = rsqrtf(fmaxf(fmaf(-m0, m0, v0 * (1.f / 512.f)), 0.f) + 1e-5f);
      const float r1 = rsqrtf(fmaxf(fmaf(-m1, m1, v1 * (1.f / 512.f)), 0.f) + 1e-5f);
#pragma unroll
      for (int c = 0; c < 4; c++) {
        st_pkt(p.s->G + ooff + c * 256,
               pack_tag<1>((bf_lo(xr[c][0]) - m0) * r0, (bf_hi(xr[c][0]) - m0) * r0),
               pack_bf16((bf_lo(xr[c][1]) - m1) * r1, (bf_hi(xr[c][1]) - m1) * r1),
               pack_bf16((bf_lo(xr[c][2]) - m0) * r0, (bf_hi(xr[c][2]) - m0) * r0),
               pack_bf16((bf_lo(xr[c][3]) - m1) * r1, (bf_hi(xr[c][3]) - m1) * r1));
      }
      CK_(d3);
      CKS(16, d0); CKS(17, d1); CKS(18, d2); CKS(19, d3);

    }
    asm volatile("setmaxnreg.inc.sync.aligned.u32 224;");
    uint32_t qf[8][4];
    {
      uint32_t h[32][4];
      float acc[64];
      const uint4* Gin = Gw + lane;
      bar_sync(NB_GATHER, 384);
      if (G_DELAY) spin_cycles(G_DELAY);
#pragma unroll
      for (int c = 0; c < 3; c++) warp_bulk_load(wblk + c * SLOT, Gw + c * 256, 4096, wbar + c * 8);
#pragma unroll
      for (int c = 0; c < 4; c++) {
        mbar_wait(wbar + (c % 3) * 8, c / 3);
#pragma unroll
        for (int i = 0; i < 8; i++) lds128(wprv + (c % 3) * SLOT + i * 512, h[c * 8 + i]);
        verify8_tag1<512>(Gin + c * 256, h + c * 8);
        if (c == 0) {
          warp_bulk_load(wblk, Gw + 768, 4096, wbar);
          TS(1);
          bar_sync(NB_TAB, 384);
        }
#pragma unroll
        for (int i = 0; i < 8; i++) {
          uint32_t m[4];
          lds128(sb + SM_TAB + (uint32_t)((c * 8 + i) * 4 + q) * 16, m);
          uint32_t* hh = h[c * 8 + i];
          hh[0] = hfma2_bf16(hh[0], m[0], m[2]);
          hh[1] = hfma2_bf16(hh[1], m[0], m[2]);
          hh[2] = hfma2_bf16(hh[2], m[1], m[3]);
          hh[3] = hfma2_bf16(hh[3], m[1], m[3]);
        }
        fence_frags<8>(h + c * 8);
        const uint32_t b = ring.wait_full(c, 0);
        if (c > 0) { wg_wait<0>(); ring.release(c - 1); }
        if (c == 0) TS(2);
        wg_fence();
        static_for<0, 8>([&](auto K) { wgmma_rs_n128_tb1<LB_MN128 + K * 128, HI128>(acc, h[c * 8 + K], b, (c | K) != 0); });
        wg_commit();
      }
      bar_arrive(NB_PASS0, 384);
#pragma unroll 1
      for (int ps = 1; ps < 4; ps++) {
        wg_wait<0>();
        ring.release(3);
        fence_regs(acc);
#pragma unroll
        for (int i = 0; i < 8; i++) {
          uint32_t o[4];
          pack8(o, acc + 8 * i);
          sts128(wprv + (ps - 1) * SLOT + i * 512, o[0], o[1], o[2], o[3]);
        }
#pragma unroll
        for (int c = 0; c < 4; c++) {
          const uint32_t b = ring.wait_full(c, ps & 1);
          if (c > 0) { wg_wait<0>(); ring.release(c - 1); }
          wg_fence();
          static_for<0, 8>([&](auto K) { wgmma_rs_n128_tb1<LB_MN128 + K * 128, HI128>(acc, h[c * 8 + K], b, (c | K) != 0); });
          wg_commit();
        }
      }
      wg_wait<0>();
      ring.release(3);
      fence_regs(acc);
#pragma unroll
      for (int i = 0; i < 8; i++) pack8(qf[i], acc + 8 * i);
    }
    fence_regs(qf);
    TS(3);

    float S[64];
    {
      float O[64];
      uint32_t P[8][4];
      const float cs = 0.08838834764831845f * 1.4426950408889634f;
      const int TAU = 0x41800000;
      float m0, m1, l0, l1;

      auto float_block_max = [&]() {
        float b0 = fmaxf(S[0], S[1]), b1 = fmaxf(S[2], S[3]);
#pragma unroll
        for (int i = 1; i < 16; i++) {
          b0 = fmaxf(b0, fmaxf(S[4 * i], S[4 * i + 1]));
          b1 = fmaxf(b1, fmaxf(S[4 * i + 2], S[4 * i + 3]));
        }
        b0 = fmaxf(b0, __shfl_xor_sync(0xffffffffu, b0, 1)); b1 = fmaxf(b1, __shfl_xor_sync(0xffffffffu, b1, 1));
        b0 = fmaxf(b0, __shfl_xor_sync(0xffffffffu, b0, 2)); b1 = fmaxf(b1, __shfl_xor_sync(0xffffffffu, b1, 2));
        m0 = b0 * cs; m1 = b1 * cs;
      };
      auto first_block_max = [&]() {
        int a0 = max(__float_as_int(S[0]), __float_as_int(S[1]));
        int a1 = max(__float_as_int(S[2]), __float_as_int(S[3]));
#pragma unroll
        for (int i = 1; i < 16; i++) {
          a0 = __vimax3_s32(a0, __float_as_int(S[4 * i]), __float_as_int(S[4 * i + 1]));
          a1 = __vimax3_s32(a1, __float_as_int(S[4 * i + 2]), __float_as_int(S[4 * i + 3]));
        }
        a0 = max(a0, __shfl_xor_sync(0xffffffffu, a0, 1)); a1 = max(a1, __shfl_xor_sync(0xffffffffu, a1, 1));
        a0 = max(a0, __shfl_xor_sync(0xffffffffu, a0, 2)); a1 = max(a1, __shfl_xor_sync(0xffffffffu, a1, 2));
        m0 = __int_as_float(a0) * cs; m1 = __int_as_float(a1) * cs;
        if (__any_sync(0xffffffffu, (a0 | a1) < 0)) float_block_max();
      };
      auto scale_sub = [&]() {
#pragma unroll
        for (int i = 0; i < 16; i++) {
          S[4 * i] = fmaf(S[4 * i], cs, -m0); S[4 * i + 1] = fmaf(S[4 * i + 1], cs, -m0);
          S[4 * i + 2] = fmaf(S[4 * i + 2], cs, -m1); S[4 * i + 3] = fmaf(S[4 * i + 3], cs, -m1);
        }
      };
      auto exps = [&](int i0, int i1) {
#pragma unroll
        for (int i = i0; i < i1; i++) {
          S[4 * i] = ex2(S[4 * i]); S[4 * i + 1] = ex2(S[4 * i + 1]);
          S[4 * i + 2] = ex2(S[4 * i + 2]); S[4 * i + 3] = ex2(S[4 * i + 3]);
          l0 += S[4 * i]; l1 += S[4 * i + 2]; l0 += S[4 * i + 1]; l1 += S[4 * i + 3];
        }
      };
      {
        const uint32_t b = ring.wait_full(0, 0);
        wg_fence();
        static_for<0, 8>([&](auto K) { wgmma_rs_n128_tb0<LB_K128 + (K >> 2) * 1024 + (K & 3) * 2, HI128>(S, qf[K], b, K != 0); });
        wg_commit();
        wg_wait<0>();
        fence_regs(S);
        ring.release(0);
        float_block_max();
        scale_sub();
        l0 = 0.f; l1 = 0.f;
        exps(0, 16);
#pragma unroll
        for (int i = 0; i < 8; i++) pack8(P[i], S + 8 * i);
      }
      fence_regs(P);
      if (wg == 1) bar_arrive(2, 256);
#pragma unroll 1
      for (int n = 1; n < 16; n++) {
        const uint32_t tk = 2 * n - 1, tv = 2 * n;
        const bool newhead = (n & 3) == 0;
        const uint32_t bk = ring.wait_full(tk & 3, (tk >> 2) & 1);
        const uint32_t bv = ring.wait_full(tv & 3, (tv >> 2) & 1);
        bar_sync(2 + wg, 256);
        wg_fence();
        static_for<0, 8>([&](auto K) { wgmma_rs_n128_tb0<LB_K128 + (K >> 2) * 1024 + (K & 3) * 2, HI128>(S, qf[K], bk, K != 0); });
        wg_commit();
        static_for<0, 8>([&](auto K) { wgmma_rs_n128_tb1<LB_MN128 + K * 128, HI128>(O, P[K], bv, K != 0 || (n & 3) != 1); });
        wg_commit();
        bar_arrive(2 + (wg ^ 1), 256);
        wg_wait<1>();
        fence_regs(S);
        ring.release(tk & 3);
        if ((n & 3) == 3 && n != 15) {
          fence_regs(qf);
#pragma unroll
          for (int i = 0; i < 8; i++) lds128(wprv + (n >> 2) * SLOT + i * 512, qf[i]);
        }
        float f0 = 1.f, f1 = 1.f;
        bool resc = newhead;
        if (newhead) {
          l0 += __shfl_xor_sync(0xffffffffu, l0, 1); l1 += __shfl_xor_sync(0xffffffffu, l1, 1);
          l0 += __shfl_xor_sync(0xffffffffu, l0, 2); l1 += __shfl_xor_sync(0xffffffffu, l1, 2);
          f0 = rcp_hw(l0); f1 = rcp_hw(l1);
          l0 = 0.f; l1 = 0.f;
          first_block_max();
          scale_sub();
        } else {
          scale_sub();
          int a0 = __vimax3_s32(__float_as_int(S[0]), __float_as_int(S[1]), __float_as_int(S[1]));
          int a1 = __vimax3_s32(__float_as_int(S[2]), __float_as_int(S[3]), __float_as_int(S[3]));
#pragma unroll
          for (int i = 1; i < 16; i++) {
            a0 = __vimax3_s32(a0, __float_as_int(S[4 * i]), __float_as_int(S[4 * i + 1]));
            a1 = __vimax3_s32(a1, __float_as_int(S[4 * i + 2]), __float_as_int(S[4 * i + 3]));
          }
          if (__any_sync(0xffffffffu, max(a0, a1) > TAU)) {
            a0 = max(a0, 0); a1 = max(a1, 0);
            a0 = max(a0, __shfl_xor_sync(0xffffffffu, a0, 1)); a1 = max(a1, __shfl_xor_sync(0xffffffffu, a1, 1));
            a0 = max(a0, __shfl_xor_sync(0xffffffffu, a0, 2)); a1 = max(a1, __shfl_xor_sync(0xffffffffu, a1, 2));
            const float d0 = __int_as_float(a0), d1 = __int_as_float(a1);
#pragma unroll
            for (int i = 0; i < 16; i++) { S[4 * i] -= d0; S[4 * i + 1] -= d0; S[4 * i + 2] -= d1; S[4 * i + 3] -= d1; }
            m0 += d0; m1 += d1;
            f0 = ex2(-d0); f1 = ex2(-d1);
            l0 *= f0; l1 *= f1;
            resc = true;
          }
        }
        exps(0, 4);
        wg_wait<0>();
        fence_regs(O);
        fence_regs(P);
        ring.release(tv & 3);
        if (resc) {
#pragma unroll
          for (int i = 0; i < 16; i++) {
            O[4 * i] *= f0; O[4 * i + 1] *= f0; O[4 * i + 2] *= f1; O[4 * i + 3] *= f1;
          }
          if (newhead) {
#pragma unroll
            for (int i = 0; i < 8; i++) {
              uint32_t o[4];
              pack8(o, O + 8 * i);
              sts128(wprv + ((n >> 2) - 1) * SLOT + i * 512, o[0], o[1], o[2], o[3]);
            }
          }
        }
        exps(4, 16);
#pragma unroll
        for (int i = 0; i < 8; i++) pack8(P[i], S + 8 * i);
        fence_regs(P);
        fence_regs(O);
      }
      {
        const uint32_t bv = ring.wait_full(3, 1);
        if (wg == 0) bar_sync(2, 256);
        wg_fence();
        static_for<0, 8>([&](auto K) { wgmma_rs_n128_tb1<LB_MN128 + K * 128, HI128>(O, P[K], bv, 1); });
        wg_commit();
        l0 += __shfl_xor_sync(0xffffffffu, l0, 1); l1 += __shfl_xor_sync(0xffffffffu, l1, 1);
        l0 += __shfl_xor_sync(0xffffffffu, l0, 2); l1 += __shfl_xor_sync(0xffffffffu, l1, 2);
        const float f0 = rcp_hw(l0), f1 = rcp_hw(l1);
        wg_wait<0>();
        fence_regs(O);
        ring.release(3);
#pragma unroll
        for (int i = 0; i < 8; i++) {
          qf[i][0] = pack_bf16(O[8 * i] * f0, O[8 * i + 1] * f0); qf[i][1] = pack_bf16(O[8 * i + 2] * f1, O[8 * i + 3] * f1);
          qf[i][2] = pack_bf16(O[8 * i + 4] * f0, O[8 * i + 5] * f0); qf[i][3] = pack_bf16(O[8 * i + 6] * f1, O[8 * i + 7] * f1);
        }
      }
    }
    fence_regs(qf);
    TS(4);
    asm volatile("setmaxnreg.dec.sync.aligned.u32 200;");
    bar_arrive(NB_PARK, 384);

    uint4* const Pout = p.s->P + ((size_t)(rt * 8 + warp) * 8 + j) * 1024 + lane;
    const uint32_t tag = *(volatile uint32_t*)(smem_raw + SM_BAR + BAR_TAG);

    float acc2[32];
    uint32_t pk[4][4];
    auto pack_partial = [&](auto TAGC) {
      fence_regs(acc2);
#pragma unroll
      for (int i = 0; i < 4; i++) {
#pragma unroll
        for (int e = 0; e < 4; e++) pk[i][e] = pack_trunc(acc2[8 * i + 2 * e], acc2[8 * i + 2 * e + 1]);
        pk[i][0] = TAGC ? (pk[i][0] | 1u) : (pk[i][0] & ~1u);
      }
      fence_regs(pk);
    };
    auto store_partial = [&](int step) {
#pragma unroll
      for (int i = 0; i < 4; i++) st_pkt(Pout + ((step & 7) * 4 + i) * 32, pk[i][0], pk[i][1], pk[i][2], pk[i][3]);
    };
    auto chunk_sent = [&](int step) { warp_arrive(sb + SM_SBAR + step * 8); };
    const uint4* const Gin = Gw + lane;
    auto g_issue = [&](int u) { warp_bulk_load(wblk + 2 * SLOT + (u & 1) * 2048, Gw + u * 128, 2048, wbar + (u & 1) * 8); };

    uint32_t tl = 0, b = ring.wait_full(0, 0);
    auto next_tile = [&]() {
      const uint32_t cur = tl & 3;
      tl++;
      b = ring.wait_full(tl & 3, (tl >> 2) & 1);
      wg_wait<0>();
      TR(4);
      ring.release(cur);
    };
    {
      uint32_t o[24][4];
#pragma unroll
      for (int i = 0; i < 24; i++) lds128(wprv + (i >> 3) * SLOT + (i & 7) * 512, o[i]);
#pragma unroll 1
      for (int cc = 0; cc < 8; cc++) {
        wg_fence();
        static_for<0, 16>([&](auto K) { wgmma_rs_n64_tb1<K * 128, HI128>(acc2, o[K], b, K != 0); });
        wg_commit();
        if (cc > 0) store_partial(cc - 1);
        next_tile();
        wg_fence();
        static_for<0, 16>([&](auto K) { wgmma_rs_n64_tb1<K * 128, HI128>(acc2, K < 8 ? o[16 + (K & 7)] : qf[K & 7], b, 1); });
        wg_commit();
        if (cc > 0) chunk_sent(cc - 1);
        if (cc == 6) { g_issue(0); g_issue(1); }
        next_tile();
        pack_partial(IC<1>{});
      }
    }
    TS(5);

    uint32_t H[14][4];
    {
      float acca[96], accb[16];
      const uint4* const statp = &p.s->stat[(rt * 8 + warp) * 8];
#pragma unroll 1
      for (int u = 0; u < 8; u++) {
        uint32_t fa[4][4];
        mbar_wait(wbar + (u & 1) * 8, ((u >> 1) + (u & 1)) & 1);
#pragma unroll
        for (int i = 0; i < 4; i++) lds128(wprv + 2 * SLOT + (u & 1) * 2048 + i * 512, fa[i]);
        verify4_tag0<512>(Gin + u * 128, fa);
        wg_fence();
        const uint32_t ba = b + (j & 1) * 512, bb = b + ((j & 1) ? 4 : 1536);
        static_for<0, 4>([&](auto K) { wgmma_rs_n32_tb1<LB_W1 + K * 128, HI128>(accb, fa[K], bb, (u | K) != 0); });
        static_for<0, 4>([&](auto K) { wgmma_rs_n192_tb1<LB_W1 + K * 128, HI128>(acca, fa[K], ba, (u | K) != 0); });
        wg_commit();
        if (u == 0) store_partial(7);
        if (u == 1) chunk_sent(7);
        if (u < 5) g_issue(u + 2);
        if (u == 7) warp_bulk_load(wblk + 2 * SLOT, statp, 128, wbar + 16);
        next_tile();
        if (u == 5) g_issue(7);
      }
      fence_regs(acca);
      fence_regs(accb);
      TS(9);
      mbar_wait(bars + BAR_UV, 0);
      uint32_t xr[4];
      mbar_wait(wbar + 16, 1);
      lds128(wblk + 2 * SLOT + gq * 16, xr);
      {
        int spins = 0;
        while (((xr[0] ^ tag) & 1u) && ++spins < SPIN_LIMIT) ld_pkt(statp + gq, xr);
      }
      const float ra0 = __uint_as_float(xr[0]), rb0 = __uint_as_float(xr[1]), ra1 = __uint_as_float(xr[2]),
                  rb1 = __uint_as_float(xr[3]);
#pragma unroll
      for (int i = 0; i < 28; i++) {
        uint32_t m[4];
        lds128(sb + SM_TAB + (i * 4 + q) * 16, m);
        const float u0 = __uint_as_float(m[0]), u1 = __uint_as_float(m[1]), w0 = __uint_as_float(m[2]), w1 = __uint_as_float(m[3]);
        const float* acc = i < 24 ? acca + 4 * i : accb + 4 * (i - 24);
        const float z0 = fmaf(acc[0], ra0, fmaf(u0, rb0, w0)), z1 = fmaf(acc[1], ra0, fmaf(u1, rb0, w1));
        const float z2 = fmaf(acc[2], ra1, fmaf(u0, rb1, w0)), z3 = fmaf(acc[3], ra1, fmaf(u1, rb1, w1));
        H[i >> 1][(i & 1) * 2] = pack_bf16(fmaf(z0, tanh_hw(z0), z0), fmaf(z1, tanh_hw(z1), z1));
        H[i >> 1][(i & 1) * 2 + 1] = pack_bf16(fmaf(z2, tanh_hw(z2), z2), fmaf(z3, tanh_hw(z3), z3));
      }
    }
    fence_regs(H);
    TS(10);
    const int go = 24 + (warp ^ 4);
#pragma unroll 1
    for (int cc = 0; cc < 8; cc++) {
      wg_fence();
      const uint32_t ba = b + (j & 1) * 256, bb = b - (j & 1) * 1536;
      static_for<0, 14>([&](auto K) { wgmma_rs_n64_tb1<K * 128, HI128>(acc2, H[K], K < 12 ? ba : bb, K != 0); });
      wg_commit();
      if (cc > 1) chunk_sent(8 + cc - 2);
      if (cc > 0) store_partial(cc - 1);
      if (cc < 7) next_tile();
      wg_wait<0>();
      pack_partial(IC<0>{});
    }
    store_partial(7);
    TS(11);
    {
      const uint4* const Pown = p.s->P + (size_t)(rt * 8 + j) * 8192 + go * 32 + lane;
      uint32_t r[8][4];
      float y[8];
      mbar_wait(bars + BAR_X2, 0);
      spin_cycles(wg ? FIN_DELAY1 : FIN_DELAY0);
      issue_pkts<0, 8>(Pown, 1024, r);
      verify8_rt<16384>(Pown, r, 0);
      TS(13);
#pragma unroll
      for (int s = 0; s < 8; s++) add_partial(y, r[s], 0x10000u, s == 0);
      const uint32_t gt = sb + SM_TAB + 1792 + ((go - 24) * 4 + q) * 8;
      store_out(p.out, (uint32_t)(rt * 128 + 16 * j + gq) * 256 + go * 8 + q, sb + SM_PARK + SLOT + (go >> 2) * 4096 + (go & 3) * 512 + lane * 16,
                lds32(gt), lds32(gt + 4), y);
    }
    TS(12);
    if (bid == 0 && tid == 0) asm volatile("st.relaxed.gpu.global.u32 [%0], %1;" ::"l"(&p.s->epoch), "r"(tag) : "memory");
  }
}

typedef CUresult (*EncodeFn)(CUtensorMap*, CUtensorMapDataType, cuuint32_t, void*, const cuuint64_t*, const cuuint64_t*,
                             const cuuint32_t*, const cuuint32_t*, CUtensorMapInterleave, CUtensorMapSwizzle,
                             CUtensorMapL2promotion, CUtensorMapFloatOOBfill);

static void make_map(EncodeFn fn, CUtensorMap* tm, const void* ptr, int inner, int rows, int cols, int box_rows, int box_outer,
                     CUtensorMapSwizzle swz) {
  cuuint64_t gd[3] = {(cuuint64_t)inner, (cuuint64_t)rows, (cuuint64_t)(cols / inner)};
  cuuint64_t gs[2] = {(cuuint64_t)cols * 2, (cuuint64_t)inner * 2};
  cuuint32_t bx[3] = {(cuuint32_t)inner, (cuuint32_t)box_rows, (cuuint32_t)box_outer};
  cuuint32_t es[3] = {1, 1, 1};
  fn(tm, CU_TENSOR_MAP_DATA_TYPE_BFLOAT16, 3, const_cast<void*>(ptr), gd, gs, bx, es, CU_TENSOR_MAP_INTERLEAVE_NONE, swz,
     CU_TENSOR_MAP_L2_PROMOTION_L2_128B, CU_TENSOR_MAP_FLOAT_OOB_FILL_NONE);
}

extern "C" void kernel_launch(void* const* d_in, const int* in_sizes, int n_in, void* d_out, int out_size) {
  (void)in_sizes; (void)n_in; (void)out_size;
  void* fnp = nullptr;
  cudaDriverEntryPointQueryResult qr;
  cudaGetDriverEntryPoint("cuTensorMapEncodeTiled", &fnp, cudaEnableDefault, &qr);
  EncodeFn fn = (EncodeFn)fnp;
  CUtensorMap tmWq, tmK, tmV, tmWo, tmW1, tmW2, tmWm, tmP, tmX;
  make_map(fn, &tmWq, d_in[3], 64, 512, 4096, 128, 2, CU_TENSOR_MAP_SWIZZLE_128B);
  make_map(fn, &tmK, d_in[1], 64, 8 * SK, 128, 128, 2, CU_TENSOR_MAP_SWIZZLE_128B);
  make_map(fn, &tmV, d_in[2], 64, 8 * SK, 128, 128, 2, CU_TENSOR_MAP_SWIZZLE_128B);
  make_map(fn, &tmWo, d_in[4], 64, 4096, 512, 256, 1, CU_TENSOR_MAP_SWIZZLE_128B);
  make_map(fn, &tmW1, d_in[6], 64, 512, FF, 64, 4, CU_TENSOR_MAP_SWIZZLE_128B);
  make_map(fn, &tmW2, d_in[7], 64, FF, 512, 224, 1, CU_TENSOR_MAP_SWIZZLE_128B);
  make_map(fn, &tmWm, d_in[9], 8, 512, 3072, 256, 1, CU_TENSOR_MAP_SWIZZLE_NONE);
  make_map(fn, &tmX, d_in[0], 16, 2048, 512, 16, 4, CU_TENSOR_MAP_SWIZZLE_NONE);
  Params p;
  p.x = (const __nv_bfloat16*)d_in[0];
  p.c = (const __nv_bfloat16*)d_in[8];
  p.wmod = (const __nv_bfloat16*)d_in[9];
  p.wo = (const __nv_bfloat16*)d_in[4];
  p.w1 = (const __nv_bfloat16*)d_in[6];
  p.w2 = (const __nv_bfloat16*)d_in[7];
  p.out = (__nv_bfloat16*)d_out;
  cudaGetSymbolAddress((void**)&p.s, g_scratch);
  {
    cuuint64_t gd[3] = {256, 32, 1024};
    cuuint64_t gs[2] = {512, 16384};
    cuuint32_t bx[3] = {256, 4, 8};
    cuuint32_t es[3] = {1, 1, 1};
    fn(&tmP, CU_TENSOR_MAP_DATA_TYPE_BFLOAT16, 3, (void*)p.s->P, gd, gs, bx, es, CU_TENSOR_MAP_INTERLEAVE_NONE,
       CU_TENSOR_MAP_SWIZZLE_NONE, CU_TENSOR_MAP_L2_PROMOTION_NONE, CU_TENSOR_MAP_FLOAT_OOB_FILL_NONE);
  }
  cudaFuncSetAttribute(adaln_block_kernel, cudaFuncAttributeMaxDynamicSharedMemorySize, SM_TOTAL);
  adaln_block_kernel<<<128, 512, SM_TOTAL>>>(tmWq, tmK, tmV, tmWo, tmW1, tmW2, tmWm, tmP, tmX, p);
}
```

```cpp
#include <cuda_runtime.h>
#include <cuda_bf16.h>
#include <cuda.h>
#include <stdint.h>

template <int OFF, uint32_t HI>
__device__ __forceinline__ void wgmma_rs_n128_tb0(float (&d)[64], const uint32_t (&a)[4], uint32_t lo, int sd) {
  asm volatile("{\n.reg .pred p;\n.reg .b32 l;\n.reg .b64 db;\nsetp.ne.b32 p, %69, 0;\n"
    "add.u32 l, %68, %70;\nmov.b64 db, {l, %71};\n"
    "wgmma.mma_async.sync.aligned.m64n128k16.f32.bf16.bf16 "
    "{%0,%1,%2,%3,%4,%5,%6,%7,%8,%9,%10,%11,%12,%13,%14,%15,"
    "%16,%17,%18,%19,%20,%21,%22,%23,%24,%25,%26,%27,%28,%29,%30,%31,"
    "%32,%33,%34,%35,%36,%37,%38,%39,%40,%41,%42,%43,%44,%45,%46,%47,"
    "%48,%49,%50,%51,%52,%53,%54,%55,%56,%57,%58,%59,%60,%61,%62,%63}, "
    "{%64,%65,%66,%67}, db, p, 1, 1, 0;\n}\n"
    : "+f"(d[0]), "+f"(d[1]), "+f"(d[2]), "+f"(d[3]), "+f"(d[4]), "+f"(d[5]), "+f"(d[6]), "+f"(d[7]),
      "+f"(d[8]), "+f"(d[9]), "+f"(d[10]), "+f"(d[11]), "+f"(d[12]), "+f"(d[13]), "+f"(d[14]), "+f"(d[15]),
      "+f"(d[16]), "+f"(d[17]), "+f"(d[18]), "+f"(d[19]), "+f"(d[20]), "+f"(d[21]), "+f"(d[22]), "+f"(d[23]),
      "+f"(d[24]), "+f"(d[25]), "+f"(d[26]), "+f"(d[27]), "+f"(d[28]), "+f"(d[29]), "+f"(d[30]), "+f"(d[31]),
      "+f"(d[32]), "+f"(d[33]), "+f"(d[34]), "+f"(d[35]), "+f"(d[36]), "+f"(d[37]), "+f"(d[38]), "+f"(d[39]),
      "+f"(d[40]), "+f"(d[41]), "+f"(d[42]), "+f"(d[43]), "+f"(d[44]), "+f"(d[45]), "+f"(d[46]), "+f"(d[47]),
      "+f"(d[48]), "+f"(d[49]), "+f"(d[50]), "+f"(d[51]), "+f"(d[52]), "+f"(d[53]), "+f"(d[54]), "+f"(d[55]),
      "+f"(d[56]), "+f"(d[57]), "+f"(d[58]), "+f"(d[59]), "+f"(d[60]), "+f"(d[61]), "+f"(d[62]), "+f"(d[63])
    : "r"(a[0]), "r"(a[1]), "r"(a[2]), "r"(a[3]), "r"(lo), "r"(sd), "n"(OFF), "n"(HI));
}

template <int OFF, uint32_t HI>
__device__ __forceinline__ void wgmma_rs_n128_tb1(float (&d)[64], const uint32_t (&a)[4], uint32_t lo, int sd) {
  asm volatile("{\n.reg .pred p;\n.reg .b32 l;\n.reg .b64 db;\nsetp.ne.b32 p, %69, 0;\n"
    "add.u32 l, %68, %70;\nmov.b64 db, {l, %71};\n"
    "wgmma.mma_async.sync.aligned.m64n128k16.f32.bf16.bf16 "
    "{%0,%1,%2,%3,%4,%5,%6,%7,%8,%9,%10,%11,%12,%13,%14,%15,"
    "%16,%17,%18,%19,%20,%21,%22,%23,%24,%25,%26,%27,%28,%29,%30,%31,"
    "%32,%33,%34,%35,%36,%37,%38,%39,%40,%41,%42,%43,%44,%45,%46,%47,"
    "%48,%49,%50,%51,%52,%53,%54,%55,%56,%57,%58,%59,%60,%61,%62,%63}, "
    "{%64,%65,%66,%67}, db, p, 1, 1, 1;\n}\n"
    : "+f"(d[0]), "+f"(d[1]), "+f"(d[2]), "+f"(d[3]), "+f"(d[4]), "+f"(d[5]), "+f"(d[6]), "+f"(d[7]),
      "+f"(d[8]), "+f"(d[9]), "+f"(d[10]), "+f"(d[11]), "+f"(d[12]), "+f"(d[13]), "+f"(d[14]), "+f"(d[15]),
      "+f"(d[16]), "+f"(d[17]), "+f"(d[18]), "+f"(d[19]), "+f"(d[20]), "+f"(d[21]), "+f"(d[22]), "+f"(d[23]),
      "+f"(d[24]), "+f"(d[25]), "+f"(d[26]), "+f"(d[27]), "+f"(d[28]), "+f"(d[29]), "+f"(d[30]), "+f"(d[31]),
      "+f"(d[32]), "+f"(d[33]), "+f"(d[34]), "+f"(d[35]), "+f"(d[36]), "+f"(d[37]), "+f"(d[38]), "+f"(d[39]),
      "+f"(d[40]), "+f"(d[41]), "+f"(d[42]), "+f"(d[43]), "+f"(d[44]), "+f"(d[45]), "+f"(d[46]), "+f"(d[47]),
      "+f"(d[48]), "+f"(d[49]), "+f"(d[50]), "+f"(d[51]), "+f"(d[52]), "+f"(d[53]), "+f"(d[54]), "+f"(d[55]),
      "+f"(d[56]), "+f"(d[57]), "+f"(d[58]), "+f"(d[59]), "+f"(d[60]), "+f"(d[61]), "+f"(d[62]), "+f"(d[63])
    : "r"(a[0]), "r"(a[1]), "r"(a[2]), "r"(a[3]), "r"(lo), "r"(sd), "n"(OFF), "n"(HI));
}

template <int OFF, uint32_t HI>
__device__ __forceinline__ void wgmma_rs_n192_tb1(float (&d)[96], const uint32_t (&a)[4], uint32_t lo, int sd) {
  asm volatile("{\n.reg .pred p;\n.reg .b32 l;\n.reg .b64 db;\nsetp.ne.b32 p, %101, 0;\n"
    "add.u32 l, %100, %102;\nmov.b64 db, {l, %103};\n"
    "wgmma.mma_async.sync.aligned.m64n192k16.f32.bf16.bf16 "
    "{%0,%1,%2,%3,%4,%5,%6,%7,%8,%9,%10,%11,%12,%13,%14,%15,"
    "%16,%17,%18,%19,%20,%21,%22,%23,%24,%25,%26,%27,%28,%29,%30,%31,"
    "%32,%33,%34,%35,%36,%37,%38,%39,%40,%41,%42,%43,%44,%45,%46,%47,"
    "%48,%49,%50,%51,%52,%53,%54,%55,%56,%57,%58,%59,%60,%61,%62,%63,"
    "%64,%65,%66,%67,%68,%69,%70,%71,%72,%73,%74,%75,%76,%77,%78,%79,"
    "%80,%81,%82,%83,%84,%85,%86,%87,%88,%89,%90,%91,%92,%93,%94,%95}, "
    "{%96,%97,%98,%99}, db, p, 1, 1, 1;\n}\n"
    : "+f"(d[0]), "+f"(d[1]), "+f"(d[2]), "+f"(d[3]), "+f"(d[4]), "+f"(d[5]), "+f"(d[6]), "+f"(d[7]),
      "+f"(d[8]), "+f"(d[9]), "+f"(d[10]), "+f"(d[11]), "+f"(d[12]), "+f"(d[13]), "+f"(d[14]), "+f"(d[15]),
      "+f"(d[16]), "+f"(d[17]), "+f"(d[18]), "+f"(d[19]), "+f"(d[20]), "+f"(d[21]), "+f"(d[22]), "+f"(d[23]),
      "+f"(d[24]), "+f"(d[25]), "+f"(d[26]), "+f"(d[27]), "+f"(d[28]), "+f"(d[29]), "+f"(d[30]), "+f"(d[31]),
      "+f"(d[32]), "+f"(d[33]), "+f"(d[34]), "+f"(d[35]), "+f"(d[36]), "+f"(d[37]), "+f"(d[38]), "+f"(d[39]),
      "+f"(d[40]), "+f"(d[41]), "+f"(d[42]), "+f"(d[43]), "+f"(d[44]), "+f"(d[45]), "+f"(d[46]), "+f"(d[47]),
      "+f"(d[48]), "+f"(d[49]), "+f"(d[50]), "+f"(d[51]), "+f"(d[52]), "+f"(d[53]), "+f"(d[54]), "+f"(d[55]),
      "+f"(d[56]), "+f"(d[57]), "+f"(d[58]), "+f"(d[59]), "+f"(d[60]), "+f"(d[61]), "+f"(d[62]), "+f"(d[63]),
      "+f"(d[64]), "+f"(d[65]), "+f"(d[66]), "+f"(d[67]), "+f"(d[68]), "+f"(d[69]), "+f"(d[70]), "+f"(d[71]),
      "+f"(d[72]), "+f"(d[73]), "+f"(d[74]), "+f"(d[75]), "+f"(d[76]), "+f"(d[77]), "+f"(d[78]), "+f"(d[79]),
      "+f"(d[80]), "+f"(d[81]), "+f"(d[82]), "+f"(d[83]), "+f"(d[84]), "+f"(d[85]), "+f"(d[86]), "+f"(d[87]),
      "+f"(d[88]), "+f"(d[89]), "+f"(d[90]), "+f"(d[91]), "+f"(d[92]), "+f"(d[93]), "+f"(d[94]), "+f"(d[95])
    : "r"(a[0]), "r"(a[1]), "r"(a[2]), "r"(a[3]), "r"(lo), "r"(sd), "n"(OFF), "n"(HI));
}

template <int OFF, uint32_t HI>
__device__ __forceinline__ void wgmma_rs_n32_tb1(float (&d)[16], const uint32_t (&a)[4], uint32_t lo, int sd) {
  asm volatile("{\n.reg .pred p;\n.reg .b32 l;\n.reg .b64 db;\nsetp.ne.b32 p, %21, 0;\n"
    "add.u32 l, %20, %22;\nmov.b64 db, {l, %23};\n"
    "wgmma.mma_async.sync.aligned.m64n32k16.f32.bf16.bf16 "
    "{%0,%1,%2,%3,%4,%5,%6,%7,%8,%9,%10,%11,%12,%13,%14,%15}, "
    "{%16,%17,%18,%19}, db, p, 1, 1, 1;\n}\n"
    : "+f"(d[0]), "+f"(d[1]), "+f"(d[2]), "+f"(d[3]), "+f"(d[4]), "+f"(d[5]), "+f"(d[6]), "+f"(d[7]),
      "+f"(d[8]), "+f"(d[9]), "+f"(d[10]), "+f"(d[11]), "+f"(d[12]), "+f"(d[13]), "+f"(d[14]), "+f"(d[15])
    : "r"(a[0]), "r"(a[1]), "r"(a[2]), "r"(a[3]), "r"(lo), "r"(sd), "n"(OFF), "n"(HI));
}

template <int OFF, uint32_t HI>
__device__ __forceinline__ void wgmma_rs_n64_tb1(float (&d)[32], const uint32_t (&a)[4], uint32_t lo, int sd) {
  asm volatile("{\n.reg .pred p;\n.reg .b32 l;\n.reg .b64 db;\nsetp.ne.b32 p, %37, 0;\n"
    "add.u32 l, %36, %38;\nmov.b64 db, {l, %39};\n"
    "wgmma.mma_async.sync.aligned.m64n64k16.f32.bf16.bf16 "
    "{%0,%1,%2,%3,%4,%5,%6,%7,%8,%9,%10,%11,%12,%13,%14,%15,"
    "%16,%17,%18,%19,%20,%21,%22,%23,%24,%25,%26,%27,%28,%29,%30,%31}, "
    "{%32,%33,%34,%35}, db, p, 1, 1, 1;\n}\n"
    : "+f"(d[0]), "+f"(d[1]), "+f"(d[2]), "+f"(d[3]), "+f"(d[4]), "+f"(d[5]), "+f"(d[6]), "+f"(d[7]),
      "+f"(d[8]), "+f"(d[9]), "+f"(d[10]), "+f"(d[11]), "+f"(d[12]), "+f"(d[13]), "+f"(d[14]), "+f"(d[15]),
      "+f"(d[16]), "+f"(d[17]), "+f"(d[18]), "+f"(d[19]), "+f"(d[20]), "+f"(d[21]), "+f"(d[22]), "+f"(d[23]),
      "+f"(d[24]), "+f"(d[25]), "+f"(d[26]), "+f"(d[27]), "+f"(d[28]), "+f"(d[29]), "+f"(d[30]), "+f"(d[31])
    : "r"(a[0]), "r"(a[1]), "r"(a[2]), "r"(a[3]), "r"(lo), "r"(sd), "n"(OFF), "n"(HI));
}

template <int STR>
__device__ __forceinline__ void verify8_tag1(const uint4* p, uint32_t (*r)[4]) {
  asm volatile("{\n.reg .pred p, q;\n.reg .b32 a, n;\nmov.u32 n, 0;\n"
    "LAB_CHK:\n"
    "and.b32 a, %0, %4;\n"
    "and.b32 a, a, %8;\n"
    "and.b32 a, a, %12;\n"
    "and.b32 a, a, %16;\n"
    "and.b32 a, a, %20;\n"
    "and.b32 a, a, %24;\n"
    "and.b32 a, a, %28;\n"
    "and.b32 a, a, 1;\nsetp.eq.u32 p, a, 1;\nvote.sync.all.pred p, p, 0xffffffff;\n"
    "@p bra.uni LAB_OK;\n"
    "and.b32 a, %0, 1;\nsetp.ne.u32 q, a, 1;\n"
    "@q ld.relaxed.gpu.global.v4.b32 {%0,%1,%2,%3}, [%32+%33];\n"
    "and.b32 a, %4, 1;\nsetp.ne.u32 q, a, 1;\n"
    "@q ld.relaxed.gpu.global.v4.b32 {%4,%5,%6,%7}, [%32+%34];\n"
    "and.b32 a, %8, 1;\nsetp.ne.u32 q, a, 1;\n"
    "@q ld.relaxed.gpu.global.v4.b32 {%8,%9,%10,%11}, [%32+%35];\n"
    "and.b32 a, %12, 1;\nsetp.ne.u32 q, a, 1;\n"
    "@q ld.relaxed.gpu.global.v4.b32 {%12,%13,%14,%15}, [%32+%36];\n"
    "and.b32 a, %16, 1;\nsetp.ne.u32 q, a, 1;\n"
    "@q ld.relaxed.gpu.global.v4.b32 {%16,%17,%18,%19}, [%32+%37];\n"
    "and.b32 a, %20, 1;\nsetp.ne.u32 q, a, 1;\n"
    "@q ld.relaxed.gpu.global.v4.b32 {%20,%21,%22,%23}, [%32+%38];\n"
    "and.b32 a, %24, 1;\nsetp.ne.u32 q, a, 1;\n"
    "@q ld.relaxed.gpu.global.v4.b32 {%24,%25,%26,%27}, [%32+%39];\n"
    "and.b32 a, %28, 1;\nsetp.ne.u32 q, a, 1;\n"
    "@q ld.relaxed.gpu.global.v4.b32 {%28,%29,%30,%31}, [%32+%40];\n"
    "add.u32 n, n, 1;\nsetp.lt.u32 q, n, 262144;\n@q bra.uni LAB_CHK;\n"
    "LAB_OK:\n"
    "}\n"
    : "+r"(r[0][0]), "+r"(r[0][1]), "+r"(r[0][2]), "+r"(r[0][3]), "+r"(r[1][0]), "+r"(r[1][1]), "+r"(r[1][2]), "+r"(r[1][3]),
      "+r"(r[2][0]), "+r"(r[2][1]), "+r"(r[2][2]), "+r"(r[2][3]), "+r"(r[3][0]), "+r"(r[3][1]), "+r"(r[3][2]), "+r"(r[3][3]),
      "+r"(r[4][0]), "+r"(r[4][1]), "+r"(r[4][2]), "+r"(r[4][3]), "+r"(r[5][0]), "+r"(r[5][1]), "+r"(r[5][2]), "+r"(r[5][3]),
      "+r"(r[6][0]), "+r"(r[6][1]), "+r"(r[6][2]), "+r"(r[6][3]), "+r"(r[7][0]), "+r"(r[7][1]), "+r"(r[7][2]), "+r"(r[7][3])
    : "l"(p), "n"(0 * STR), "n"(1 * STR), "n"(2 * STR), "n"(3 * STR), "n"(4 * STR), "n"(5 * STR), "n"(6 * STR), "n"(7 * STR)
    : "memory");
}

template <int STR>
__device__ __forceinline__ void verify8_rt(const uint4* p, uint32_t (*r)[4], uint32_t tag) {
  asm volatile("{\n.reg .pred p, q;\n.reg .b32 a, b, n;\nmov.u32 n, 0;\n"
    "LAB_CHK:\n"
    "lop3.b32 a, %0, %4, %41, 0x7e;\n"
    "lop3.b32 b, %8, %12, %41, 0x7e;\nor.b32 a, a, b;\n"
    "lop3.b32 b, %16, %20, %41, 0x7e;\nor.b32 a, a, b;\n"
    "lop3.b32 b, %24, %28, %41, 0x7e;\nor.b32 a, a, b;\n"
    "and.b32 a, a, 1;\nsetp.eq.u32 p, a, 0;\nvote.sync.all.pred p, p, 0xffffffff;\n"
    "@p bra.uni LAB_OK;\n"
    "and.b32 a, %0, 1;\nsetp.ne.u32 q, a, %41;\n"
    "@q ld.relaxed.gpu.global.v4.b32 {%0,%1,%2,%3}, [%32+%33];\n"
    "and.b32 a, %4, 1;\nsetp.ne.u32 q, a, %41;\n"
    "@q ld.relaxed.gpu.global.v4.b32 {%4,%5,%6,%7}, [%32+%34];\n"
    "and.b32 a, %8, 1;\nsetp.ne.u32 q, a, %41;\n"
    "@q ld.relaxed.gpu.global.v4.b32 {%8,%9,%10,%11}, [%32+%35];\n"
    "and.b32 a, %12, 1;\nsetp.ne.u32 q, a, %41;\n"
    "@q ld.relaxed.gpu.global.v4.b32 {%12,%13,%14,%15}, [%32+%36];\n"
    "and.b32 a, %16, 1;\nsetp.ne.u32 q, a, %41;\n"
    "@q ld.relaxed.gpu.global.v4.b32 {%16,%17,%18,%19}, [%32+%37];\n"
    "and.b32 a, %20, 1;\nsetp.ne.u32 q, a, %41;\n"
    "@q ld.relaxed.gpu.global.v4.b32 {%20,%21,%22,%23}, [%32+%38];\n"
    "and.b32 a, %24, 1;\nsetp.ne.u32 q, a, %41;\n"
    "@q ld.relaxed.gpu.global.v4.b32 {%24,%25,%26,%27}, [%32+%39];\n"
    "and.b32 a, %28, 1;\nsetp.ne.u32 q, a, %41;\n"
    "@q ld.relaxed.gpu.global.v4.b32 {%28,%29,%30,%31}, [%32+%40];\n"
    "add.u32 n, n, 1;\nsetp.lt.u32 q, n, 262144;\n@q bra.uni LAB_CHK;\n"
    "LAB_OK:\n}\n"
    : "+r"(r[0][0]), "+r"(r[0][1]), "+r"(r[0][2]), "+r"(r[0][3]), "+r"(r[1][0]), "+r"(r[1][1]), "+r"(r[1][2]), "+r"(r[1][3]),
      "+r"(r[2][0]), "+r"(r[2][1]), "+r"(r[2][2]), "+r"(r[2][3]), "+r"(r[3][0]), "+r"(r[3][1]), "+r"(r[3][2]), "+r"(r[3][3]),
      "+r"(r[4][0]), "+r"(r[4][1]), "+r"(r[4][2]), "+r"(r[4][3]), "+r"(r[5][0]), "+r"(r[5][1]), "+r"(r[5][2]), "+r"(r[5][3]),
      "+r"(r[6][0]), "+r"(r[6][1]), "+r"(r[6][2]), "+r"(r[6][3]), "+r"(r[7][0]), "+r"(r[7][1]), "+r"(r[7][2]), "+r"(r[7][3])
    : "l"(p), "n"(0 * STR), "n"(1 * STR), "n"(2 * STR), "n"(3 * STR), "n"(4 * STR), "n"(5 * STR), "n"(6 * STR), "n"(7 * STR), "r"(tag)
    : "memory");
}

template <int STR>
__device__ __forceinline__ void verify4_tag0(const uint4* p, uint32_t (*r)[4]) {
  asm volatile("{\n.reg .pred p, q;\n.reg .b32 a, n;\nmov.u32 n, 0;\n"
    "LAB_CHK:\n"
    "or.b32 a, %0, %4;\n"
    "or.b32 a, a, %8;\n"
    "or.b32 a, a, %12;\n"
    "and.b32 a, a, 1;\nsetp.eq.u32 p, a, 0;\nvote.sync.all.pred p, p, 0xffffffff;\n"
    "@p bra.uni LAB_OK;\n"
    "and.b32 a, %0, 1;\nsetp.ne.u32 q, a, 0;\n"
    "@q ld.relaxed.gpu.global.v4.b32 {%0,%1,%2,%3}, [%16+%17];\n"
    "and.b32 a, %4, 1;\nsetp.ne.u32 q, a, 0;\n"
    "@q ld.relaxed.gpu.global.v4.b32 {%4,%5,%6,%7}, [%16+%18];\n"
    "and.b32 a, %8, 1;\nsetp.ne.u32 q, a, 0;\n"
    "@q ld.relaxed.gpu.global.v4.b32 {%8,%9,%10,%11}, [%16+%19];\n"
    "and.b32 a, %12, 1;\nsetp.ne.u32 q, a, 0;\n"
    "@q ld.relaxed.gpu.global.v4.b32 {%12,%13,%14,%15}, [%16+%20];\n"
    "add.u32 n, n, 1;\nsetp.lt.u32 q, n, 262144;\n@q bra.uni LAB_CHK;\n"
    "LAB_OK:\n"
    "or.b32 %0, %0, 1;\n"
    "or.b32 %4, %4, 1;\n"
    "or.b32 %8, %8, 1;\n"
    "or.b32 %12, %12, 1;\n"
    "}\n"
    : "+r"(r[0][0]), "+r"(r[0][1]), "+r"(r[0][2]), "+r"(r[0][3]), "+r"(r[1][0]), "+r"(r[1][1]), "+r"(r[1][2]), "+r"(r[1][3]),
      "+r"(r[2][0]), "+r"(r[2][1]), "+r"(r[2][2]), "+r"(r[2][3]), "+r"(r[3][0]), "+r"(r[3][1]), "+r"(r[3][2]), "+r"(r[3][3])
    : "l"(p), "n"(0 * STR), "n"(1 * STR), "n"(2 * STR), "n"(3 * STR)
    : "memory");
}

#define SPIN_LIMIT (1 << 18)

__device__ __forceinline__ uint32_t smem_u32(const void* p) { return (uint32_t)__cvta_generic_to_shared(p); }
__device__ __forceinline__ void mbar_init(uint32_t a, uint32_t c) {
  asm volatile("mbarrier.init.shared::cta.b64 [%0], %1;" ::"r"(a), "r"(c) : "memory");
}
__device__ __forceinline__ void mbar_expect(uint32_t a, uint32_t b) {
  asm volatile("mbarrier.arrive.expect_tx.shared::cta.b64 _, [%0], %1;" ::"r"(a), "r"(b) : "memory");
}
__device__ __forceinline__ void mbar_arrive(uint32_t a) {
  asm volatile("mbarrier.arrive.shared::cta.b64 _, [%0];" ::"r"(a) : "memory");
}
__device__ __forceinline__ void mbar_wait(uint32_t a, uint32_t parity) {
  asm volatile(
      "{\n.reg .pred p;\n.reg .u32 n;\nmov.u32 n, 0;\n"
      "LAB_WAIT:\n"
      "mbarrier.try_wait.parity.shared::cta.b64 p, [%0], %1;\n"
      "@p bra LAB_DONE;\n"
      "add.u32 n, n, 1;\n"
      "setp.lt.u32 p, n, 262144;\n"
      "@p bra LAB_WAIT;\n"
      "LAB_DONE:\n}\n" ::"r"(a), "r"(parity) : "memory");
}
__device__ __forceinline__ bool mbar_test(uint32_t a, uint32_t parity) {
  uint32_t ok;
  asm volatile("{\n.reg .pred p;\nmbarrier.test_wait.parity.shared::cta.b64 p, [%1], %2;\nselp.u32 %0, 1, 0, p;\n}\n"
               : "=r"(ok) : "r"(a), "r"(parity) : "memory");
  return ok;
}
__device__ __forceinline__ void tma3d(uint32_t dst, const CUtensorMap* tm, uint32_t bar, int c0, int c1, int c2) {
  asm volatile(
      "cp.async.bulk.tensor.3d.shared::cluster.global.mbarrier::complete_tx::bytes [%0], [%1, {%3,%4,%5}], [%2];"
      ::"r"(dst), "l"(tm), "r"(bar), "r"(c0), "r"(c1), "r"(c2) : "memory");
}
__device__ __forceinline__ void wg_fence() { asm volatile("wgmma.fence.sync.aligned;" ::: "memory"); }
__device__ __forceinline__ void wg_commit() { asm volatile("wgmma.commit_group.sync.aligned;" ::: "memory"); }
template <int N> __device__ __forceinline__ void wg_wait() {
  asm volatile("wgmma.wait_group.sync.aligned %0;" ::"n"(N) : "memory");
}
template <int N> __device__ __forceinline__ void fence_regs(float (&d)[N]) {
#pragma unroll
  for (int i = 0; i < N; i++) asm volatile("" : "+f"(d[i])::"memory");
}
template <int N> __device__ __forceinline__ void fence_regs(uint32_t (&d)[N][4]) {
#pragma unroll
  for (int i = 0; i < N; i++) asm volatile("" : "+r"(d[i][0]), "+r"(d[i][1]), "+r"(d[i][2]), "+r"(d[i][3])::"memory");
}
template <int N> __device__ __forceinline__ void fence_frags(uint32_t (*d)[4]) {
#pragma unroll
  for (int i = 0; i < N; i++) asm volatile("" : "+r"(d[i][0]), "+r"(d[i][1]), "+r"(d[i][2]), "+r"(d[i][3])::"memory");
}
__device__ __forceinline__ void bar_sync(int id, int n) { asm volatile("bar.sync %0, %1;" ::"r"(id), "r"(n) : "memory"); }
__device__ __forceinline__ void bar_arrive(int id, int n) { asm volatile("bar.arrive %0, %1;" ::"r"(id), "r"(n) : "memory"); }

__device__ __forceinline__ uint32_t pack_bf16(float lo, float hi) {
  uint32_t r;
  asm("cvt.rn.bf16x2.f32 %0, %1, %2;" : "=r"(r) : "f"(hi), "f"(lo));
  return r;
}
__device__ __forceinline__ float bf_lo(uint32_t w) { return __uint_as_float(w << 16); }
__device__ __forceinline__ float bf_hi(uint32_t w) { return __uint_as_float(w & 0xFFFF0000u); }
__device__ __forceinline__ float round_bf16(float x) { return bf_lo(pack_bf16(x, 0.f)); }
__device__ __forceinline__ uint32_t hfma2_bf16(uint32_t a, uint32_t b, uint32_t c) {
  uint32_t r;
  asm("fma.rn.bf16x2 %0, %1, %2, %3;" : "=r"(r) : "r"(a), "r"(b), "r"(c));
  return r;
}
__device__ __forceinline__ float ex2(float x) {
  float r;
  asm("ex2.approx.ftz.f32 %0, %1;" : "=f"(r) : "f"(x));
  return r;
}
__device__ __forceinline__ float tanh_hw(float x) {
  float r;
  asm("tanh.approx.f32 %0, %1;" : "=f"(r) : "f"(x));
  return r;
}
template <int TAG> __device__ __forceinline__ uint32_t pack_tag(float lo, float hi) {
  uint32_t w = __byte_perm(__float_as_uint(lo), pack_bf16(lo, hi), 0x7632);
  return TAG ? (w | 1u) : (w & ~1u);
}
__device__ __forceinline__ void st_pkt(uint4* p, uint32_t a, uint32_t b, uint32_t c, uint32_t d) {
  asm volatile(
      "st.relaxed.gpu.global.v4.b32 [%0], {%1,%2,%3,%4};" ::"l"(p), "r"(a), "r"(b), "r"(c), "r"(d) : "memory");
}
__device__ __forceinline__ void ld_pkt(const uint4* p, uint32_t (&r)[4]) {
  asm volatile(
      "ld.relaxed.gpu.global.v4.b32 {%0,%1,%2,%3}, [%4];"
      : "=r"(r[0]), "=r"(r[1]), "=r"(r[2]), "=r"(r[3]) : "l"(p) : "memory");
}
__device__ __forceinline__ uint32_t ldg32(const void* p) {
  uint32_t r;
  asm volatile("ld.global.nc.b32 %0, [%1];" : "=r"(r) : "l"(p));
  return r;
}
__device__ __forceinline__ uint32_t ldg16(const void* p) {
  uint16_t r;
  asm volatile("ld.global.nc.b16 %0, [%1];" : "=h"(r) : "l"(p));
  return r;
}
__device__ __forceinline__ uint4 ldg128(const void* p) {
  uint4 r;
  asm volatile("ld.global.nc.v4.b32 {%0,%1,%2,%3}, [%4];" : "=r"(r.x), "=r"(r.y), "=r"(r.z), "=r"(r.w) : "l"(p));
  return r;
}
__device__ __forceinline__ void l2_prefetch(const void* p, uint32_t bytes) {
  asm volatile("cp.async.bulk.prefetch.L2.global [%0], %1;" ::"l"(p), "r"(bytes) : "memory");
}
__device__ __forceinline__ float rcp_hw(float x) {
  float r;
  asm("rcp.approx.ftz.f32 %0, %1;" : "=f"(r) : "f"(x));
  return r;
}
__device__ __forceinline__ void warp_bulk_load(uint32_t sdst, const void* gsrc, uint32_t bytes, uint32_t bar) {
  asm volatile(
      "{\n.reg .pred p;\nelect.sync _|p, 0xffffffff;\n"
      "@p mbarrier.arrive.expect_tx.shared::cta.b64 _, [%3], %2;\n"
      "@p cp.async.bulk.shared::cluster.global.mbarrier::complete_tx::bytes [%0], [%1], %2, [%3];\n}\n"
      ::"r"(sdst), "l"(gsrc), "r"(bytes), "r"(bar) : "memory");
}
__device__ __forceinline__ void warp_tma3d(uint32_t dst, const CUtensorMap* tm, uint32_t bar, uint32_t bytes, int c1, int c2) {
  asm volatile(
      "{\n.reg .pred p;\nelect.sync _|p, 0xffffffff;\n"
      "@p mbarrier.arrive.expect_tx.shared::cta.b64 _, [%2], %3;\n"
      "@p cp.async.bulk.tensor.3d.shared::cluster.global.mbarrier::complete_tx::bytes [%0], [%1, {%6,%4,%5}], [%2];\n}\n"
      ::"r"(dst), "l"(tm), "r"(bar), "r"(bytes), "r"(c1), "r"(c2), "r"(0) : "memory");
}
__device__ __forceinline__ bool elect_one() {
  uint32_t r;
  asm volatile("{\n.reg .pred p;\nelect.sync _|p, 0xffffffff;\nselp.u32 %0, 1, 0, p;\n}\n" : "=r"(r));
  return r;
}
__device__ __forceinline__ void warp_arrive(uint32_t bar) {
  asm volatile("{\n.reg .pred p;\nelect.sync _|p, 0xffffffff;\n@p mbarrier.arrive.shared::cta.b64 _, [%0];\n}\n" ::"r"(bar) : "memory");
}
__device__ __forceinline__ uint32_t pack_trunc(float lo, float hi) {
  return __byte_perm(__float_as_uint(lo), __float_as_uint(hi), 0x7632);
}
__device__ __forceinline__ void add_partial(float (&y)[8], const uint32_t (&r)[4], uint32_t c0, bool first) {
#pragma unroll
  for (int e = 0; e < 4; e++) {
    const float lo = __uint_as_float(r[e] * 65536u + (e ? 0x8000u : c0)), hi = __uint_as_float(r[e]);
    y[2 * e] = first ? lo : y[2 * e] + lo;
    y[2 * e + 1] = first ? hi : y[2 * e + 1] + hi;
  }
}
__device__ __forceinline__ void spin_cycles(uint32_t n) {
  uint32_t t0, t;
  asm volatile("mov.u32 %0, %%clock;" : "=r"(t0));
  do { asm volatile("mov.u32 %0, %%clock;" : "=r"(t)); } while (t - t0 < n);
}
__device__ __forceinline__ void sts128(uint32_t a, uint32_t x, uint32_t y, uint32_t z, uint32_t w) {
  asm volatile("st.shared.v4.b32 [%0], {%1,%2,%3,%4};" ::"r"(a), "r"(x), "r"(y), "r"(z), "r"(w) : "memory");
}
__device__ __forceinline__ void lds128(uint32_t a, uint32_t (&r)[4]) {
  asm volatile("ld.shared.v4.b32 {%0,%1,%2,%3}, [%4];" : "=r"(r[0]), "=r"(r[1]), "=r"(r[2]), "=r"(r[3]) : "r"(a) : "memory");
}

__device__ __forceinline__ uint32_t lds32(uint32_t a) {
  uint32_t r;
  asm volatile("ld.shared.b32 %0, [%1];" : "=r"(r) : "r"(a) : "memory");
  return r;
}
__device__ __forceinline__ void store_out(__nv_bfloat16* out, uint32_t woff, uint32_t x2s, uint32_t gb0, uint32_t gb1,
                                          const float (&y)[8]) {
  const uint32_t gb[2] = {gb0, gb1};
  uint32_t xa[2][4];
  lds128(x2s, xa[0]);
  lds128(x2s + 2048, xa[1]);
  uint32_t* const oo = (uint32_t*)out + woff;
#pragma unroll
  for (int e = 0; e < 4; e++)
    oo[(e >> 1) * 4 + (e & 1) * 8 * 256] =
        pack_bf16(fmaf(bf_lo(gb[e >> 1]), y[2 * e], __uint_as_float(xa[e >> 1][(e & 1) * 2])),
                  fmaf(bf_hi(gb[e >> 1]), y[2 * e + 1], __uint_as_float(xa[e >> 1][(e & 1) * 2 + 1])));
}

constexpr int SK = 2048, WIN = 512;
constexpr int FF = 1792, FSL = 224;
constexpr int NTILES = 80;
constexpr int NSLOT = 4;
constexpr uint32_t SLOT = 32768;
constexpr uint32_t SM_PARK = 0;
constexpr uint32_t SM_RING = 3 * SLOT;
constexpr uint32_t SM_TAB = 7 * SLOT;
constexpr uint32_t SM_RED = SM_TAB + 2048;
constexpr uint32_t SM_BAR = SM_RED + 256;
constexpr uint32_t SM_WBAR = SM_BAR + 128;
constexpr uint32_t SM_SBAR = SM_WBAR + 256;
constexpr uint32_t BAR_SLAB = 64, BAR_UV = 72, BAR_X2 = 80, BAR_TAG = 88;
constexpr uint32_t SM_TOTAL = SM_SBAR + 16;

struct Scratch {
  uint4 P[16 * 8 * 8 * 1024];
  uint4 G[16 * 8 * 32 * 32];
  uint4 mod1[8 * 256];
  uint4 mod2[512];
  uint4 uv[2 * 448];
  uint4 stat[16 * 8 * 8];
  uint32_t sent[16 * 8 * 8];
  uint32_t epoch;
};
__device__ Scratch g_scratch;

#define TS(i) do { } while (0)
#define TR(code)
#define CK_(v)
#define CKS(i, v)

struct Params {
  const __nv_bfloat16* x;
  const __nv_bfloat16* c;
  const __nv_bfloat16* wmod;
  const __nv_bfloat16* wo;
  const __nv_bfloat16* w1;
  const __nv_bfloat16* w2;
  __nv_bfloat16* out;
  Scratch* s;
};

constexpr uint32_t HI128 = (1024 >> 4) | (1u << 30);
constexpr int LB_MN128 = (16384 >> 4) << 16;
constexpr int LB_K128 = 1 << 16;
constexpr int LB_W1 = (8192 >> 4) << 16;

template <int I> struct IC {
  __host__ __device__ constexpr operator int() const { return I; }
};
template <int I, int N, typename F> __device__ __forceinline__ void static_for(F&& f) {
  if constexpr (I < N) {
    f(IC<I>{});
    static_for<I + 1, N>(f);
  }
}

struct Ring {
  uint32_t base16, bars;
  __device__ __forceinline__ uint32_t wait_full(uint32_t slot, uint32_t parity) const {
    mbar_wait(bars + slot * 8, parity);
    return base16 + slot * (SLOT >> 4);
  }
  __device__ __forceinline__ void release(uint32_t slot) const {
    warp_arrive(bars + 32 + slot * 8);
  }
};

__device__ __forceinline__ float silu_c(uint32_t bits) {
  float x = bf_lo(bits);
  return round_bf16(x * rcp_hw(1.f + ex2(-1.4426950408889634f * x)));
}
__device__ __forceinline__ void pack8(uint32_t (&o)[4], const float* v) {
  o[0] = pack_bf16(v[0], v[1]); o[1] = pack_bf16(v[2], v[3]); o[2] = pack_bf16(v[4], v[5]); o[3] = pack_bf16(v[6], v[7]);
}

template <int TAG, int N>
__device__ __forceinline__ void issue_pkts(const uint4* p, int stride, uint32_t (*r)[4]) {
#pragma unroll
  for (int i = 0; i < N; i++) ld_pkt(p + i * stride, r[i]);
}
__device__ __forceinline__ void wait_sent(const uint32_t* p, uint32_t tag, uint32_t step) {
#pragma unroll 1
  for (int spins = 0; spins < SPIN_LIMIT; spins++) {
    uint32_t v;
    asm volatile("ld.relaxed.gpu.global.u32 %0, [%1];" : "=r"(v) : "l"(p) : "memory");
    if (__all_sync(0xffffffffu, v - (tag * 32 + step + 1) < 16u)) break;
  }
}
__device__ __forceinline__ void ld_mod(const uint4* p, uint32_t tag, uint32_t (&r)[4]) {
  int spins = 0;
  ld_pkt(p, r);
  while (r[2] != tag && ++spins < SPIN_LIMIT) ld_pkt(p, r);
}

#define EARLY_TILES 2
#define PF_WMOD 1
#define MOD1_DELAY 500
#define RED3_UNIT 3
#define JLO 2
#define NITEM2 24
#define FIN_DELAY0 800
#define FIN_DELAY1 0
#define G_DELAY 300

__device__ __forceinline__ float reduce8(float (&a)[8], int lane) {
  const bool h16 = lane & 16, h8 = lane & 8, h4 = lane & 4;
#pragma unroll
  for (int k = 0; k < 4; k++) a[k] = (h16 ? a[k + 4] : a[k]) + __shfl_xor_sync(0xffffffffu, h16 ? a[k] : a[k + 4], 16);
#pragma unroll
  for (int k = 0; k < 2; k++) a[k] = (h8 ? a[k + 2] : a[k]) + __shfl_xor_sync(0xffffffffu, h8 ? a[k] : a[k + 2], 8);
  const float r = (h4 ? a[1] : a[0]) + __shfl_xor_sync(0xffffffffu, h4 ? a[0] : a[1], 4);
  return r + __shfl_xor_sync(0xffffffffu, r, 2);
}
__device__ __forceinline__ void fma8(float (&a)[8], float s, uint32_t w0, uint32_t w1, uint32_t w2, uint32_t w3) {
  a[0] = fmaf(s, bf_lo(w0), a[0]); a[1] = fmaf(s, bf_hi(w0), a[1]);
  a[2] = fmaf(s, bf_lo(w1), a[2]); a[3] = fmaf(s, bf_hi(w1), a[3]);
  a[4] = fmaf(s, bf_lo(w2), a[4]); a[5] = fmaf(s, bf_hi(w2), a[5]);
  a[6] = fmaf(s, bf_lo(w3), a[6]); a[7] = fmaf(s, bf_hi(w3), a[7]);
}

enum { NB_TAB = 1, NB_WG0 = 2, NB_WG1 = 3, NB_HELP = 4, NB_INIT = 5, NB_PASS0 = 6, NB_GATHER = 7, NB_PARK = 8, NB_PROD = 9 };

__global__ void __launch_bounds__(512, 1)
adaln_block_kernel(const __grid_constant__ CUtensorMap tmWq, const __grid_constant__ CUtensorMap tmK,
                   const __grid_constant__ CUtensorMap tmV, const __grid_constant__ CUtensorMap tmWo,
                   const __grid_constant__ CUtensorMap tmW1, const __grid_constant__ CUtensorMap tmW2,
                   const __grid_constant__ CUtensorMap tmWm, const __grid_constant__ CUtensorMap tmP,
                   const __grid_constant__ CUtensorMap tmX, const Params p) {
  extern __shared__ __align__(1024) uint8_t smem_raw[];
  const uint32_t sb = smem_u32(smem_raw);
  const int tid = threadIdx.x, lane = tid & 31;
  const int warp = __shfl_sync(0xffffffffu, tid >> 5, 0);
  const int bid = blockIdx.x;
  const int j = ((bid >> (4 + JLO)) << JLO) | (bid & ((1 << JLO) - 1)), rt = (bid >> JLO) & 15;
  const uint32_t bars = sb + SM_BAR;

  if (warp >= 12) {
    asm volatile("setmaxnreg.dec.sync.aligned.u32 24;");
    if (warp == 13) {
      if (elect_one()) {
#pragma unroll
        for (int i = 0; i < 28; i++) mbar_init(sb + SM_WBAR + i * 8, i < 26 ? 1 : 4);
        mbar_init(sb + SM_SBAR, 8);
        asm volatile("fence.mbarrier_init.release.cluster;" ::: "memory");
      }
      __syncwarp();
      bar_arrive(NB_INIT, 192);
      mbar_wait(sb + SM_SBAR, 0);
      const uint32_t tag = *(volatile uint32_t*)(smem_raw + SM_BAR + BAR_TAG);
#pragma unroll 1
      for (int n = 0; n < 14; n++) {
        const uint32_t lb = sb + SM_WBAR + 192 + (n & 1) * 8;
        mbar_wait(lb + 16, ((n >> 1) & 1) ^ 1);
        wait_sent(&p.s->sent[(rt * 8 + j) * 8 + (lane & 7)], tag, n);
        warp_tma3d(sb + SM_PARK + (n & 1) * 16384, &tmP, lb, n < 8 ? 16384 + 2048 : 16384, (n & 7) * 4, (rt * 8 + j) * 8);
        if (n < 8 && elect_one()) tma3d(sb + SM_PARK + SLOT + n * 4096, &tmX, lb, 0, rt * 128 + j * 16, n * 4);
      }
    } else if (warp == 14) {
      if (elect_one()) {
        asm volatile("prefetch.tensormap [%0];" ::"l"(&tmWq) : "memory");
        asm volatile("prefetch.tensormap [%0];" ::"l"(&tmK) : "memory");
        asm volatile("prefetch.tensormap [%0];" ::"l"(&tmV) : "memory");
        asm volatile("prefetch.tensormap [%0];" ::"l"(&tmWo) : "memory");
        asm volatile("prefetch.tensormap [%0];" ::"l"(&tmP) : "memory");
        asm volatile("prefetch.tensormap [%0];" ::"l"(&tmX) : "memory");
        asm volatile("prefetch.tensormap [%0];" ::"l"(&tmW1) : "memory");
        asm volatile("prefetch.tensormap [%0];" ::"l"(&tmW2) : "memory");
      }
    } else if (warp == 12) {
      if (elect_one()) {
        mbar_init(bars + BAR_SLAB, 1);
        asm volatile("fence.mbarrier_init.release.cluster;" ::: "memory");
        mbar_expect(bars + BAR_SLAB, 8192);
        tma3d(sb + SM_RING + 3 * SLOT, &tmWm, bars + BAR_SLAB, 0, 0, bid);
        tma3d(sb + SM_RING + 3 * SLOT + 4096, &tmWm, bars + BAR_SLAB, 0, 256, bid);
#pragma unroll
        for (int i = 0; i < 4; i++) { mbar_init(bars + i * 8, 1); mbar_init(bars + 32 + i * 8, 8); }
        mbar_init(bars + BAR_UV, 4);
        mbar_init(bars + BAR_X2, 1);
        asm volatile("fence.mbarrier_init.release.cluster;" ::: "memory");
      }
      __syncwarp();
      bar_arrive(NB_INIT, 192);
      mbar_wait(bars + BAR_SLAB, 0);
      uint32_t s = 0, ph = 1;
#pragma unroll 1
      for (int tt = 0; tt < NTILES; tt++) {
        const CUtensorMap* tm;
        int c1, c2;
        uint32_t bytes = SLOT;
        if (tt < 16) {
          tm = &tmWq; c1 = (tt & 3) * 128; c2 = (j * 4 + (((tt >> 2) + 1) & 3)) * 2;
        } else if (tt < 48) {
          const int u = tt - 16;
          const bool isK = (u == 0) || ((u & 1) && u != 31);
          const int n = isK ? ((u + 1) >> 1) : (u == 31 ? 15 : (u >> 1) - 1);
          tm = isK ? &tmK : &tmV; c1 = j * SK + (SK - WIN) + (n & 3) * 128; c2 = 0;
        } else if (tt < 64) {
          const int u = tt - 48;
          tm = &tmWo; c1 = j * 512 + (u & 1) * 256; c2 = u >> 1;
        } else if (tt < 72) {
          tm = &tmW1; c1 = (tt - 64) * 64; c2 = (j * 7) >> 1;
        } else {
          tm = &tmW2; c1 = j * FSL; c2 = tt - 72; bytes = 28672;
        }
        if (tt == EARLY_TILES) bar_sync(NB_PROD, 160);
        mbar_wait(bars + 32 + s * 8, ph);
        warp_tma3d(sb + SM_RING + s * SLOT, tm, bars + s * 8, bytes, c1, c2);
        if (++s == 4) { s = 0; ph ^= 1; }
      }
    }
  } else if (warp >= 8) {
    CK_(c0);
    asm volatile("setmaxnreg.dec.sync.aligned.u32 40;");
    const int t = tid - 256, hw = warp - 8, q = lane & 3;
    float* const red = (float*)(smem_raw + SM_RED);
    uint32_t tag;
    float a[8];
    {
      uint32_t cb[4];
#pragma unroll
      for (int i = 0; i < 4; i++) cb[i] = ldg16(p.c + t + 128 * i);
      asm volatile("ld.relaxed.gpu.global.u32 %0, [%1];" : "=r"(tag) : "l"(&p.s->epoch) : "memory");
      bar_sync(NB_INIT, 192);
      CK_(c2);
      tag += 1;
      float sc[4];
#pragma unroll
      for (int i = 0; i < 4; i++) sc[i] = silu_c(cb[i]);
#pragma unroll
      for (int k = 0; k < 8; k++) a[k] = 0.f;
      if (t == 0) *(uint32_t*)(smem_raw + SM_BAR + BAR_TAG) = tag;
      mbar_wait(bars + BAR_SLAB, 0);
      CK_(c3);
      bar_arrive(NB_GATHER, 384);
#pragma unroll
      for (int i = 0; i < 4; i++) {
        uint32_t w[4];
        lds128(sb + SM_RING + 3 * SLOT + (t + 128 * i) * 16, w);
        fma8(a, sc[i], w[0], w[1], w[2], w[3]);
      }
      float r = reduce8(a, lane);
      r += __shfl_xor_sync(0xffffffffu, r, 1);
      if (q == 0) red[hw * 8 + (lane >> 2)] = r;
      CK_(c4);
      bar_sync(NB_HELP, 128);
      CK_(c5);
      if (hw == 0) {
        const int cl = lane & 7;
        float v = round_bf16(red[cl] + red[8 + cl] + red[16 + cl] + red[24 + cl]);
        if (bid >= 64) v = 1.f + v;
        float vn = __shfl_down_sync(0xffffffffu, v, 1);
        uint32_t wd = pack_bf16(v, vn);
        uint32_t w0 = __shfl_sync(0xffffffffu, wd, (lane & 1) * 4);
        uint32_t w1 = __shfl_sync(0xffffffffu, wd, (lane & 1) * 4 + 2);
        if (lane < 16) st_pkt(&p.s->mod1[(lane >> 1) * 256 + bid * 2 + (lane & 1)], w0, w1, tag, 0);
      }
      uint32_t r0[4], r1[4];
      const uint4* src = &p.s->mod1[j * 256 + t];
      CK_(c6);
      spin_cycles(MOD1_DELAY);
      CK_(c7);
      int spins = 0;
      do {
        ld_pkt(src, r0);
        ld_pkt(src + 128, r1);
      } while ((r0[2] != tag || r1[2] != tag) && ++spins < SPIN_LIMIT);
      const int g = t >> 2, pp = q * 2;
      const uint32_t ad = sb + SM_TAB + (uint32_t)(g * 4 + (pp & 3)) * 16 + (pp >> 2) * 4;
      asm volatile("st.shared.b32 [%0], %1;" ::"r"(ad + 8), "r"(r0[0]) : "memory");
      asm volatile("st.shared.b32 [%0], %1;" ::"r"(ad + 24), "r"(r0[1]) : "memory");
      asm volatile("st.shared.b32 [%0], %1;" ::"r"(ad), "r"(r1[0]) : "memory");
      asm volatile("st.shared.b32 [%0], %1;" ::"r"(ad + 16), "r"(r1[1]) : "memory");
      bar_arrive(NB_TAB, 384);
      bar_arrive(NB_PROD, 160);
      CK_(c8);
      CKS(0, c0); CKS(2, c2); CKS(3, c3); CKS(4, c4); CKS(5, c5); CKS(6, c6); CKS(7, c7); CKS(8, c8);
    }
    bar_sync(NB_PASS0, 384);
    if (t < 8) l2_prefetch((const char*)p.wo + (size_t)bid * 32768 + t * 4096, 4096);
    else if (t < 12) l2_prefetch((const char*)p.w1 + (size_t)bid * 14336 + (t - 8) * 3584, 3584);
    else if (t < 16) l2_prefetch((const char*)p.w2 + (size_t)bid * 14336 + (t - 12) * 3584, 3584);
    {
#pragma unroll
      for (int k = 0; k < 8; k++) a[k] = 0.f;
#pragma unroll 1
      for (int b = 0; b < 4; b++) {
        const int row = b * 128 + (t >> 1);
        const __nv_bfloat16* wp = p.wmod + (size_t)row * 3072 + 1024 + bid * 16 + (t & 1) * 8;
        const uint4 w0 = ldg128(wp), w1 = ldg128(wp + 64 * 3072);
        const uint32_t c0 = ldg16(p.c + row), c1 = ldg16(p.c + row + 64);
        fma8(a, silu_c(c0), w0.x, w0.y, w0.z, w0.w);
        fma8(a, silu_c(c1), w1.x, w1.y, w1.z, w1.w);
      }
      const float r = reduce8(a, lane);
      if ((lane & 2) == 0) red[hw * 16 + (lane & 1) * 8 + (lane >> 2)] = r;
      bar_sync(NB_HELP, 128);
      if (hw == 0) {
        const int cl = lane & 15;
        float v = round_bf16(red[cl] + red[16 + cl] + red[32 + cl] + red[48 + cl]);
        if ((bid >> 5) == 2) v = 1.f + v;
        float vn = __shfl_down_sync(0xffffffffu, v, 1);
        uint32_t wd = pack_bf16(v, vn);
        uint32_t w0 = __shfl_sync(0xffffffffu, wd, q * 2);
        uint32_t w1 = __shfl_sync(0xffffffffu, wd, q * 2 + 8);
        const int vec = (0x2130 >> ((bid >> 5) * 4)) & 3;
        if (lane < 4) st_pkt(&p.s->mod2[((bid & 31) * 4 + vec) * 4 + lane], w0, w1, tag, 0);
      }
    }
    {
      const int isv = hw & 1, kh = hw >> 1;
      if (bid < 112) {
        const int kk = lane >> 1;
        uint32_t m0[4], m1[4];
        const uint4* mp = &p.s->mod2[(kh * 16 + (lane >> 2)) * 16 + (isv ? 12 : 4) + q];
        ld_mod(mp, tag, m0);
        ld_mod(mp + 128, tag, m1);
#pragma unroll
        for (int k = 0; k < 8; k++) a[k] = 0.f;
#pragma unroll 1
        for (int g0 = 0; g0 < 16; g0 += 2) {
          uint4 w[2];
#pragma unroll
          for (int i = 0; i < 2; i++) w[i] = ldg128(p.w1 + (size_t)((kh * 16 + g0 + i) * 16 + kk) * FF + bid * 16 + (lane & 1) * 8);
#pragma unroll
          for (int i = 0; i < 2; i++) {
            const int sl = ((g0 + i) & 7) * 4 + ((kk & 7) >> 1);
            const uint32_t wa = __shfl_sync(0xffffffffu, g0 < 8 ? m0[0] : m1[0], sl), wb = __shfl_sync(0xffffffffu, g0 < 8 ? m0[1] : m1[1], sl);
            const uint32_t mw = (kk & 8) ? wb : wa;
            fma8(a, (kk & 1) ? bf_hi(mw) : bf_lo(mw), w[i].x, w[i].y, w[i].z, w[i].w);
          }
        }
        float r = reduce8(a, lane);
        bar_sync(NB_HELP, 128);
        if (kh) red[isv * 32 + lane] = r;
        bar_sync(NB_HELP, 128);
        if (!kh) {
          r = (r + red[isv * 32 + lane]) * (isv ? 0.5f : 1.f);
          const float r1 = __shfl_down_sync(0xffffffffu, r, 4), r2 = __shfl_down_sync(0xffffffffu, r, 8),
                      r3 = __shfl_down_sync(0xffffffffu, r, 12);
          if ((lane & 14) == 0)
            st_pkt(&p.s->uv[isv * 448 + bid * 4 + (lane & 1) * 2 + (lane >> 4)], (__float_as_uint(r) & ~1u) | (tag & 1u),
                   __float_as_uint(r1), __float_as_uint(r2), __float_as_uint(r3));
        }
      }
      const int i = kh * 32 + lane;
      if (i < 56) {
        uint32_t m[4];
        int spins = 0;
        while (true) {
          ld_pkt(&p.s->uv[isv * 448 + j * 56 + i], m);
          if (!((m[0] ^ tag) & 1u) || ++spins >= SPIN_LIMIT) break;
          __nanosleep(200);
        }
        const int ip = (j & 1) ? (i < 8 ? i + 48 : i - 8) : i;
        const uint32_t ad = sb + SM_TAB + ip * 32 + isv * 8;
        asm volatile("st.shared.v2.b32 [%0], {%1,%2};" ::"r"(ad), "r"(m[0]), "r"(m[1]) : "memory");
        asm volatile("st.shared.v2.b32 [%0], {%1,%2};" ::"r"(ad + 16), "r"(m[2]), "r"(m[3]) : "memory");
      }
      __syncwarp();
      warp_arrive(bars + BAR_UV);
      TS(9);
    }
    {
      uint32_t mga[4], mg2[4], mgb[4];
      const uint4* mp = &p.s->mod2[((lane >> 2) * 4 + hw) * 16 + q];
      ld_mod(mp, tag, mga);
      ld_mod(mp + 4, tag, mg2);
      ld_mod(mp + 8, tag, mgb);
      if (lane >= 24) asm volatile("st.shared.v2.b32 [%0], {%1,%2};" ::"r"(sb + SM_TAB + 1792 + ((((lane >> 2) & 1) * 4 + hw) * 4 + q) * 8),
                                   "r"(mgb[0]), "r"(mgb[1]) : "memory");
      const uint32_t x2s = sb + SM_PARK + SLOT + hw * 512 + lane * 16;
      const uint4* const Pown = p.s->P + (size_t)(rt * 8 + j) * 8192 + hw * 32 + lane;
      float s0 = 0.f, s1 = 0.f, v0 = 0.f, v1 = 0.f;
      bar_sync(NB_PARK, 384);
      asm volatile("setmaxnreg.inc.sync.aligned.u32 88;");
#pragma unroll 1
      for (int n = 0; n < 14; n++) {
        const int cc = n & 7;
        const bool ex1 = n < 8;
        const uint32_t lb = sb + SM_WBAR + 192 + (n & 1) * 8;
        uint32_t r[8][4];
        float y[8];
        mbar_wait(lb, (n >> 1) & 1);
#pragma unroll
        for (int i = 0; i < 8; i++) lds128(sb + SM_PARK + (n & 1) * 16384 + i * 2048 + hw * 512 + lane * 16, r[i]);
        verify8_rt<16384>(Pown + cc * 128, r, ex1);
        warp_arrive(lb + 16);
#pragma unroll
        for (int i = 0; i < 8; i++) add_partial(y, r[i], ex1 ? 0u : 0x10000u, i == 0);
        const int src = cc * 4 + q;
        const uint32_t ma = __shfl_sync(0xffffffffu, ex1 ? mga[0] : mgb[0], src), mb = __shfl_sync(0xffffffffu, ex1 ? mga[1] : mgb[1], src);
        if (ex1) {
          uint32_t xr[4];
          asm volatile("ldmatrix.sync.aligned.m8n8.x4.shared.b16 {%0,%1,%2,%3}, [%4];"
                       : "=r"(xr[0]), "=r"(xr[1]), "=r"(xr[2]), "=r"(xr[3])
                       : "r"(sb + SM_PARK + SLOT + hw * 512 + cc * 4096 + (lane & 15) * 32 + (lane >> 4) * 16) : "memory");
          const uint32_t mc = __shfl_sync(0xffffffffu, mg2[0], src), md = __shfl_sync(0xffffffffu, mg2[1], src);
#pragma unroll
          for (int e = 0; e < 4; e++) {
            const uint32_t m = e < 2 ? ma : mb;
            const float u = fmaf(bf_lo(m), y[2 * e], bf_lo(xr[e])), v = fmaf(bf_hi(m), y[2 * e + 1], bf_hi(xr[e]));
            y[2 * e] = u; y[2 * e + 1] = v;
            if (e & 1) { s1 += u + v; v1 = fmaf(u, u, fmaf(v, v, v1)); }
            else { s0 += u + v; v0 = fmaf(u, u, fmaf(v, v, v0)); }
          }
          st_pkt(p.s->G + ((rt * 8 + j) * 32 + cc * 4 + hw) * 32 + lane, pack_tag<0>(y[0] * bf_lo(mc), y[1] * bf_hi(mc)),
                 pack_bf16(y[2] * bf_lo(mc), y[3] * bf_hi(mc)), pack_bf16(y[4] * bf_lo(md), y[5] * bf_hi(md)),
                 pack_bf16(y[6] * bf_lo(md), y[7] * bf_hi(md)));
          sts128(x2s + cc * 4096, __float_as_uint(y[0]), __float_as_uint(y[1]), __float_as_uint(y[2]), __float_as_uint(y[3]));
          sts128(x2s + cc * 4096 + 2048, __float_as_uint(y[4]), __float_as_uint(y[5]), __float_as_uint(y[6]), __float_as_uint(y[7]));
          if (n == 7) {
            const bool o1 = lane & 1, o2 = lane & 2;
            float c0 = (o1 ? v0 : s0) + __shfl_xor_sync(0xffffffffu, o1 ? s0 : v0, 1);
            float c1 = (o1 ? v1 : s1) + __shfl_xor_sync(0xffffffffu, o1 ? s1 : v1, 1);
            c0 = (o2 ? c1 : c0) + __shfl_xor_sync(0xffffffffu, o2 ? c0 : c1, 2);
            *(float*)(smem_raw + SM_PARK + 16384 + hw * 512 + lane * 4) = c0;
            bar_sync(NB_HELP, 128);
            if (hw == 0) {
              const float* ps = (const float*)(smem_raw + SM_PARK + 16384) + lane;
              const float m = (c0 + ps[128] + ps[256] + ps[384]) * (1.f / 512.f);
              const float mean = __shfl_sync(0xffffffffu, m, lane & ~1), sq = __shfl_sync(0xffffffffu, m, lane | 1);
              const float rs = 0.5f * rsqrtf(fmaxf(fmaf(-mean, mean, sq), 0.f) + 1e-5f), mr = -mean * rs;
              const float rs1 = __shfl_down_sync(0xffffffffu, rs, 2), mr1 = __shfl_down_sync(0xffffffffu, mr, 2);
              if (q == 0)
                st_pkt(&p.s->stat[(rt * 8 + j) * 8 + (lane >> 2)], (__float_as_uint(rs) & ~1u) | (tag & 1u), __float_as_uint(mr),
                       __float_as_uint(rs1), __float_as_uint(mr1));
              warp_arrive(bars + BAR_X2);
            }
          }
        } else {
          store_out(p.out, (uint32_t)(rt * 128 + 16 * j + (lane >> 2)) * 256 + (cc * 4 + hw) * 8 + q, x2s + cc * 4096, ma, mb, y);
        }
      }
    }
  } else {
    const int wg = warp >> 2;
    const int q = lane & 3, gq = lane >> 2;
    const Ring ring{(sb + SM_RING) >> 4, bars};
    const uint32_t xoff = (uint32_t)(rt * 128 + 16 * j + warp) * 256 + gq * 8 + q;
    const uint32_t ooff = ((uint32_t)(rt * 8 + j) * 32 + gq) * 32 + warp * 4 + q;
    const uint32_t wblk = sb + SM_PARK + warp * 4096, wprv = wblk + lane * 16;
    const uint32_t wbar = sb + SM_WBAR + warp * 24;
    const uint4* const Gw = p.s->G + (rt * 8 + warp) * 1024;

    {
      const uint32_t* xo = (const uint32_t*)p.x + xoff;
      uint32_t xr[4][4];
      CK_(d0);
#pragma unroll
      for (int c = 0; c < 4; c++) {
        xr[c][0] = ldg32(xo + c * 64);
        xr[c][1] = ldg32(xo + c * 64 + 8 * 256);
        xr[c][2] = ldg32(xo + c * 64 + 4);
        xr[c][3] = ldg32(xo + c * 64 + 4 + 8 * 256);
      }
      CK_(d1);
      fence_regs(xr);
      CK_(d2);
      float s0 = 0.f, s1 = 0.f, v0 = 0.f, v1 = 0.f;
#pragma unroll
      for (int c = 0; c < 4; c++) {
#pragma unroll
        for (int e = 0; e < 4; e++) {
          const float a = bf_lo(xr[c][e]), b = bf_hi(xr[c][e]);
          if (e & 1) { s1 += a + b; v1 = fmaf(a, a, fmaf(b, b, v1)); }
          else { s0 += a + b; v0 = fmaf(a, a, fmaf(b, b, v0)); }
        }
      }
#pragma unroll
      for (int o = 16; o > 0; o >>= 1) {
        s0 += __shfl_xor_sync(0xffffffffu, s0, o);
        s1 += __shfl_xor_sync(0xffffffffu, s1, o);
        v0 += __shfl_xor_sync(0xffffffffu, v0, o);
        v1 += __shfl_xor_sync(0xffffffffu, v1, o);
      }
      const float m0 = s0 * (1.f / 512.f), m1 = s1 * (1.f / 512.f);
      const float r0 = rsqrtf(fmaxf(fmaf(-m0, m0, v0 * (1.f / 512.f)), 0.f) + 1e-5f);
      const float r1 = rsqrtf(fmaxf(fmaf(-m1, m1, v1 * (1.f / 512.f)), 0.f) + 1e-5f);
#pragma unroll
      for (int c = 0; c < 4; c++) {
        st_pkt(p.s->G + ooff + c * 256,
               pack_tag<1>((bf_lo(xr[c][0]) - m0) * r0, (bf_hi(xr[c][0]) - m0) * r0),
               pack_bf16((bf_lo(xr[c][1]) - m1) * r1, (bf_hi(xr[c][1]) - m1) * r1),
               pack_bf16((bf_lo(xr[c][2]) - m0) * r0, (bf_hi(xr[c][2]) - m0) * r0),
               pack_bf16((bf_lo(xr[c][3]) - m1) * r1, (bf_hi(xr[c][3]) - m1) * r1));
      }
      CK_(d3);
      CKS(16, d0); CKS(17, d1); CKS(18, d2); CKS(19, d3);

    }
    asm volatile("setmaxnreg.inc.sync.aligned.u32 224;");
    uint32_t qf[8][4];
    {
      uint32_t h[32][4];
      float acc[64];
      const uint4* Gin = Gw + lane;
      bar_sync(NB_GATHER, 384);
      if (G_DELAY) spin_cycles(G_DELAY);
#pragma unroll
      for (int c = 0; c < 3; c++) warp_bulk_load(wblk + c * SLOT, Gw + c * 256, 4096, wbar + c * 8);
#pragma unroll
      for (int c = 0; c < 4; c++) {
        mbar_wait(wbar + (c % 3) * 8, c / 3);
#pragma unroll
        for (int i = 0; i < 8; i++) lds128(wprv + (c % 3) * SLOT + i * 512, h[c * 8 + i]);
        verify8_tag1<512>(Gin + c * 256, h + c * 8);
        if (c == 0) {
          warp_bulk_load(wblk, Gw + 768, 4096, wbar);
          TS(1);
          bar_sync(NB_TAB, 384);
        }
#pragma unroll
        for (int i = 0; i < 8; i++) {
          uint32_t m[4];
          lds128(sb + SM_TAB + (uint32_t)((c * 8 + i) * 4 + q) * 16, m);
          uint32_t* hh = h[c * 8 + i];
          hh[0] = hfma2_bf16(hh[0], m[0], m[2]);
          hh[1] = hfma2_bf16(hh[1], m[0], m[2]);
          hh[2] = hfma2_bf16(hh[2], m[1], m[3]);
          hh[3] = hfma2_bf16(hh[3], m[1], m[3]);
        }
        fence_frags<8>(h + c * 8);
        const uint32_t b = ring.wait_full(c, 0);
        if (c > 0) { wg_wait<0>(); ring.release(c - 1); }
        if (c == 0) TS(2);
        wg_fence();
        static_for<0, 8>([&](auto K) { wgmma_rs_n128_tb1<LB_MN128 + K * 128, HI128>(acc, h[c * 8 + K], b, (c | K) != 0); });
        wg_commit();
      }
      bar_arrive(NB_PASS0, 384);
#pragma unroll 1
      for (int ps = 1; ps < 4; ps++) {
        wg_wait<0>();
        ring.release(3);
        fence_regs(acc);
#pragma unroll
        for (int i = 0; i < 8; i++) {
          uint32_t o[4];
          pack8(o, acc + 8 * i);
          sts128(wprv + (ps - 1) * SLOT + i * 512, o[0], o[1], o[2], o[3]);
        }
#pragma unroll
        for (int c = 0; c < 4; c++) {
          const uint32_t b = ring.wait_full(c, ps & 1);
          if (c > 0) { wg_wait<0>(); ring.release(c - 1); }
          wg_fence();
          static_for<0, 8>([&](auto K) { wgmma_rs_n128_tb1<LB_MN128 + K * 128, HI128>(acc, h[c * 8 + K], b, (c | K) != 0); });
          wg_commit();
        }
      }
      wg_wait<0>();
      ring.release(3);
      fence_regs(acc);
#pragma unroll
      for (int i = 0; i < 8; i++) pack8(qf[i], acc + 8 * i);
    }
    fence_regs(qf);
    TS(3);

    float S[64];
    {
      float O[64];
      uint32_t P[8][4];
      const float cs = 0.08838834764831845f * 1.4426950408889634f;
      const int TAU = 0x41800000;
      float m0, m1, l0, l1;

      auto float_block_max = [&]() {
        float b0 = fmaxf(S[0], S[1]), b1 = fmaxf(S[2], S[3]);
#pragma unroll
        for (int i = 1; i < 16; i++) {
          b0 = fmaxf(b0, fmaxf(S[4 * i], S[4 * i + 1]));
          b1 = fmaxf(b1, fmaxf(S[4 * i + 2], S[4 * i + 3]));
        }
        b0 = fmaxf(b0, __shfl_xor_sync(0xffffffffu, b0, 1)); b1 = fmaxf(b1, __shfl_xor_sync(0xffffffffu, b1, 1));
        b0 = fmaxf(b0, __shfl_xor_sync(0xffffffffu, b0, 2)); b1 = fmaxf(b1, __shfl_xor_sync(0xffffffffu, b1, 2));
        m0 = b0 * cs; m1 = b1 * cs;
      };
      auto first_block_max = [&]() {
        int a0 = max(__float_as_int(S[0]), __float_as_int(S[1]));
        int a1 = max(__float_as_int(S[2]), __float_as_int(S[3]));
#pragma unroll
        for (int i = 1; i < 16; i++) {
          a0 = __vimax3_s32(a0, __float_as_int(S[4 * i]), __float_as_int(S[4 * i + 1]));
          a1 = __vimax3_s32(a1, __float_as_int(S[4 * i + 2]), __float_as_int(S[4 * i + 3]));
        }
        a0 = max(a0, __shfl_xor_sync(0xffffffffu, a0, 1)); a1 = max(a1, __shfl_xor_sync(0xffffffffu, a1, 1));
        a0 = max(a0, __shfl_xor_sync(0xffffffffu, a0, 2)); a1 = max(a1, __shfl_xor_sync(0xffffffffu, a1, 2));
        m0 = __int_as_float(a0) * cs; m1 = __int_as_float(a1) * cs;
        if (__any_sync(0xffffffffu, (a0 | a1) < 0)) float_block_max();
      };
      auto scale_sub = [&]() {
#pragma unroll
        for (int i = 0; i < 16; i++) {
          S[4 * i] = fmaf(S[4 * i], cs, -m0); S[4 * i + 1] = fmaf(S[4 * i + 1], cs, -m0);
          S[4 * i + 2] = fmaf(S[4 * i + 2], cs, -m1); S[4 * i + 3] = fmaf(S[4 * i + 3], cs, -m1);
        }
      };
      auto exps = [&](int i0, int i1) {
#pragma unroll
        for (int i = i0; i < i1; i++) {
          S[4 * i] = ex2(S[4 * i]); S[4 * i + 1] = ex2(S[4 * i + 1]);
          S[4 * i + 2] = ex2(S[4 * i + 2]); S[4 * i + 3] = ex2(S[4 * i + 3]);
          l0 += S[4 * i]; l1 += S[4 * i + 2]; l0 += S[4 * i + 1]; l1 += S[4 * i + 3];
        }
      };
      {
        const uint32_t b = ring.wait_full(0, 0);
        wg_fence();
        static_for<0, 8>([&](auto K) { wgmma_rs_n128_tb0<LB_K128 + (K >> 2) * 1024 + (K & 3) * 2, HI128>(S, qf[K], b, K != 0); });
        wg_commit();
        wg_wait<0>();
        fence_regs(S);
        ring.release(0);
        float_block_max();
        scale_sub();
        l0 = 0.f; l1 = 0.f;
        exps(0, 16);
#pragma unroll
        for (int i = 0; i < 8; i++) pack8(P[i], S + 8 * i);
      }
      fence_regs(P);
      if (wg == 1) bar_arrive(2, 256);
#pragma unroll 1
      for (int n = 1; n < 16; n++) {
        const uint32_t tk = 2 * n - 1, tv = 2 * n;
        const bool newhead = (n & 3) == 0;
        const uint32_t bk = ring.wait_full(tk & 3, (tk >> 2) & 1);
        const uint32_t bv = ring.wait_full(tv & 3, (tv >> 2) & 1);
        bar_sync(2 + wg, 256);
        wg_fence();
        static_for<0, 8>([&](auto K) { wgmma_rs_n128_tb0<LB_K128 + (K >> 2) * 1024 + (K & 3) * 2, HI128>(S, qf[K], bk, K != 0); });
        wg_commit();
        static_for<0, 8>([&](auto K) { wgmma_rs_n128_tb1<LB_MN128 + K * 128, HI128>(O, P[K], bv, K != 0 || (n & 3) != 1); });
        wg_commit();
        bar_arrive(2 + (wg ^ 1), 256);
        wg_wait<1>();
        fence_regs(S);
        ring.release(tk & 3);
        if ((n & 3) == 3 && n != 15) {
          fence_regs(qf);
#pragma unroll
          for (int i = 0; i < 8; i++) lds128(wprv + (n >> 2) * SLOT + i * 512, qf[i]);
        }
        float f0 = 1.f, f1 = 1.f;
        bool resc = newhead;
        if (newhead) {
          l0 += __shfl_xor_sync(0xffffffffu, l0, 1); l1 += __shfl_xor_sync(0xffffffffu, l1, 1);
          l0 += __shfl_xor_sync(0xffffffffu, l0, 2); l1 += __shfl_xor_sync(0xffffffffu, l1, 2);
          f0 = rcp_hw(l0); f1 = rcp_hw(l1);
          l0 = 0.f; l1 = 0.f;
          first_block_max();
          scale_sub();
        } else {
          scale_sub();
          int a0 = __vimax3_s32(__float_as_int(S[0]), __float_as_int(S[1]), __float_as_int(S[1]));
          int a1 = __vimax3_s32(__float_as_int(S[2]), __float_as_int(S[3]), __float_as_int(S[3]));
#pragma unroll
          for (int i = 1; i < 16; i++) {
            a0 = __vimax3_s32(a0, __float_as_int(S[4 * i]), __float_as_int(S[4 * i + 1]));
            a1 = __vimax3_s32(a1, __float_as_int(S[4 * i + 2]), __float_as_int(S[4 * i + 3]));
          }
          if (__any_sync(0xffffffffu, max(a0, a1) > TAU)) {
            a0 = max(a0, 0); a1 = max(a1, 0);
            a0 = max(a0, __shfl_xor_sync(0xffffffffu, a0, 1)); a1 = max(a1, __shfl_xor_sync(0xffffffffu, a1, 1));
            a0 = max(a0, __shfl_xor_sync(0xffffffffu, a0, 2)); a1 = max(a1, __shfl_xor_sync(0xffffffffu, a1, 2));
            const float d0 = __int_as_float(a0), d1 = __int_as_float(a1);
#pragma unroll
            for (int i = 0; i < 16; i++) { S[4 * i] -= d0; S[4 * i + 1] -= d0; S[4 * i + 2] -= d1; S[4 * i + 3] -= d1; }
            m0 += d0; m1 += d1;
            f0 = ex2(-d0); f1 = ex2(-d1);
            l0 *= f0; l1 *= f1;
            resc = true;
          }
        }
        exps(0, 4);
        wg_wait<0>();
        fence_regs(O);
        fence_regs(P);
        ring.release(tv & 3);
        if (resc) {
#pragma unroll
          for (int i = 0; i < 16; i++) {
            O[4 * i] *= f0; O[4 * i + 1] *= f0; O[4 * i + 2] *= f1; O[4 * i + 3] *= f1;
          }
          if (newhead) {
#pragma unroll
            for (int i = 0; i < 8; i++) {
              uint32_t o[4];
              pack8(o, O + 8 * i);
              sts128(wprv + ((n >> 2) - 1) * SLOT + i * 512, o[0], o[1], o[2], o[3]);
            }
          }
        }
        exps(4, 16);
#pragma unroll
        for (int i = 0; i < 8; i++) pack8(P[i], S + 8 * i);
        fence_regs(P);
        fence_regs(O);
      }
      {
        const uint32_t bv = ring.wait_full(3, 1);
        if (wg == 0) bar_sync(2, 256);
        wg_fence();
        static_for<0, 8>([&](auto K) { wgmma_rs_n128_tb1<LB_MN128 + K * 128, HI128>(O, P[K], bv, 1); });
        wg_commit();
        l0 += __shfl_xor_sync(0xffffffffu, l0, 1); l1 += __shfl_xor_sync(0xffffffffu, l1, 1);
        l0 += __shfl_xor_sync(0xffffffffu, l0, 2); l1 += __shfl_xor_sync(0xffffffffu, l1, 2);
        const float f0 = rcp_hw(l0), f1 = rcp_hw(l1);
        wg_wait<0>();
        fence_regs(O);
        ring.release(3);
#pragma unroll
        for (int i = 0; i < 8; i++) {
          qf[i][0] = pack_bf16(O[8 * i] * f0, O[8 * i + 1] * f0); qf[i][1] = pack_bf16(O[8 * i + 2] * f1, O[8 * i + 3] * f1);
          qf[i][2] = pack_bf16(O[8 * i + 4] * f0, O[8 * i + 5] * f0); qf[i][3] = pack_bf16(O[8 * i + 6] * f1, O[8 * i + 7] * f1);
        }
      }
    }
    fence_regs(qf);
    TS(4);
    asm volatile("setmaxnreg.dec.sync.aligned.u32 200;");
    bar_arrive(NB_PARK, 384);

    uint4* const Pout = p.s->P + ((size_t)(rt * 8 + warp) * 8 + j) * 1024 + lane;
    const uint32_t tag = *(volatile uint32_t*)(smem_raw + SM_BAR + BAR_TAG);

    float acc2[32];
    uint32_t pk[4][4];
    auto pack_partial = [&](auto TAGC) {
      fence_regs(acc2);
#pragma unroll
      for (int i = 0; i < 4; i++) {
#pragma unroll
        for (int e = 0; e < 4; e++) pk[i][e] = pack_trunc(acc2[8 * i + 2 * e], acc2[8 * i + 2 * e + 1]);
        pk[i][0] = TAGC ? (pk[i][0] | 1u) : (pk[i][0] & ~1u);
      }
      fence_regs(pk);
    };
    auto store_partial = [&](int step) {
#pragma unroll
      for (int i = 0; i < 4; i++) st_pkt(Pout + ((step & 7) * 4 + i) * 32, pk[i][0], pk[i][1], pk[i][2], pk[i][3]);
      if (lane == 0)
        asm volatile("st.relaxed.gpu.global.u32 [%0], %1;" ::"l"(&p.s->sent[(rt * 8 + warp) * 8 + j]), "r"(tag * 32 + step + 1) : "memory");
    };
    const uint4* const Gin = Gw + lane;
    auto g_issue = [&](int u) { warp_bulk_load(wblk + 2 * SLOT + (u & 1) * 2048, Gw + u * 128, 2048, wbar + (u & 1) * 8); };

    uint32_t tl = 0, b = ring.wait_full(0, 0);
    auto next_tile = [&]() {
      const uint32_t cur = tl & 3;
      tl++;
      b = ring.wait_full(tl & 3, (tl >> 2) & 1);
      wg_wait<0>();
      TR(4);
      ring.release(cur);
    };
    {
      uint32_t o[24][4];
#pragma unroll
      for (int i = 0; i < 24; i++) lds128(wprv + (i >> 3) * SLOT + (i & 7) * 512, o[i]);
#pragma unroll 1
      for (int cc = 0; cc < 8; cc++) {
        wg_fence();
        static_for<0, 16>([&](auto K) { wgmma_rs_n64_tb1<K * 128, HI128>(acc2, o[K], b, K != 0); });
        wg_commit();
        if (cc > 0) store_partial(cc - 1);
        next_tile();
        wg_fence();
        static_for<0, 16>([&](auto K) { wgmma_rs_n64_tb1<K * 128, HI128>(acc2, K < 8 ? o[16 + (K & 7)] : qf[K & 7], b, 1); });
        wg_commit();
        if (cc == 0) warp_arrive(sb + SM_SBAR);
        if (cc == 6) { g_issue(0); g_issue(1); }
        next_tile();
        pack_partial(IC<1>{});
      }
    }
    TS(5);

    uint32_t H[14][4];
    {
      float acca[96], accb[16];
      const uint4* const statp = &p.s->stat[(rt * 8 + warp) * 8];
#pragma unroll 1
      for (int u = 0; u < 8; u++) {
        uint32_t fa[4][4];
        mbar_wait(wbar + (u & 1) * 8, ((u >> 1) + (u & 1)) & 1);
#pragma unroll
        for (int i = 0; i < 4; i++) lds128(wprv + 2 * SLOT + (u & 1) * 2048 + i * 512, fa[i]);
        verify4_tag0<512>(Gin + u * 128, fa);
        wg_fence();
        const uint32_t ba = b + (j & 1) * 512, bb = b + ((j & 1) ? 4 : 1536);
        static_for<0, 4>([&](auto K) { wgmma_rs_n32_tb1<LB_W1 + K * 128, HI128>(accb, fa[K], bb, (u | K) != 0); });
        static_for<0, 4>([&](auto K) { wgmma_rs_n192_tb1<LB_W1 + K * 128, HI128>(acca, fa[K], ba, (u | K) != 0); });
        wg_commit();
        if (u == 0) store_partial(7);
        if (u < 5) g_issue(u + 2);
        if (u == 7) warp_bulk_load(wblk + 2 * SLOT, statp, 128, wbar + 16);
        next_tile();
        if (u == 5) g_issue(7);
      }
      fence_regs(acca);
      fence_regs(accb);
      TS(9);
      mbar_wait(bars + BAR_UV, 0);
      uint32_t xr[4];
      mbar_wait(wbar + 16, 1);
      lds128(wblk + 2 * SLOT + gq * 16, xr);
      {
        int spins = 0;
        while (((xr[0] ^ tag) & 1u) && ++spins < SPIN_LIMIT) ld_pkt(statp + gq, xr);
      }
      const float ra0 = __uint_as_float(xr[0]), rb0 = __uint_as_float(xr[1]), ra1 = __uint_as_float(xr[2]),
                  rb1 = __uint_as_float(xr[3]);
#pragma unroll
      for (int i = 0; i < 28; i++) {
        uint32_t m[4];
        lds128(sb + SM_TAB + (i * 4 + q) * 16, m);
        const float u0 = __uint_as_float(m[0]), u1 = __uint_as_float(m[1]), w0 = __uint_as_float(m[2]), w1 = __uint_as_float(m[3]);
        const float* acc = i < 24 ? acca + 4 * i : accb + 4 * (i - 24);
        const float z0 = fmaf(acc[0], ra0, fmaf(u0, rb0, w0)), z1 = fmaf(acc[1], ra0, fmaf(u1, rb0, w1));
        const float z2 = fmaf(acc[2], ra1, fmaf(u0, rb1, w0)), z3 = fmaf(acc[3], ra1, fmaf(u1, rb1, w1));
        H[i >> 1][(i & 1) * 2] = pack_bf16(fmaf(z0, tanh_hw(z0), z0), fmaf(z1, tanh_hw(z1), z1));
        H[i >> 1][(i & 1) * 2 + 1] = pack_bf16(fmaf(z2, tanh_hw(z2), z2), fmaf(z3, tanh_hw(z3), z3));
      }
    }
    fence_regs(H);
    TS(10);
    const int go = 24 + (warp ^ 4);
#pragma unroll 1
    for (int cc = 0; cc < 8; cc++) {
      wg_fence();
      const uint32_t ba = b + (j & 1) * 256, bb = b - (j & 1) * 1536;
      static_for<0, 14>([&](auto K) { wgmma_rs_n64_tb1<K * 128, HI128>(acc2, H[K], K < 12 ? ba : bb, K != 0); });
      wg_commit();
      if (cc > 0) store_partial(8 + cc - 1);
      if (cc < 7) next_tile();
      wg_wait<0>();
      pack_partial(IC<0>{});
    }
    store_partial(15);
    TS(11);
    {
      const uint4* const Pown = p.s->P + (size_t)(rt * 8 + j) * 8192 + go * 32 + lane;
      uint32_t r[8][4];
      float y[8];
      mbar_wait(bars + BAR_X2, 0);
      wait_sent(&p.s->sent[(rt * 8 + j) * 8 + (lane & 7)], tag, 15 - wg);
      issue_pkts<0, 8>(Pown, 1024, r);
      verify8_rt<16384>(Pown, r, 0);
      TS(13);
#pragma unroll
      for (int s = 0; s < 8; s++) add_partial(y, r[s], 0x10000u, s == 0);
      const uint32_t gt = sb + SM_TAB + 1792 + ((go - 24) * 4 + q) * 8;
      store_out(p.out, (uint32_t)(rt * 128 + 16 * j + gq) * 256 + go * 8 + q, sb + SM_PARK + SLOT + (go >> 2) * 4096 + (go & 3) * 512 + lane * 16,
                lds32(gt), lds32(gt + 4), y);
    }
    TS(12);
    if (bid == 0 && tid == 0) asm volatile("st.relaxed.gpu.global.u32 [%0], %1;" ::"l"(&p.s->epoch), "r"(tag) : "memory");
  }
}

typedef CUresult (*EncodeFn)(CUtensorMap*, CUtensorMapDataType, cuuint32_t, void*, const cuuint64_t*, const cuuint64_t*,
                             const cuuint32_t*, const cuuint32_t*, CUtensorMapInterleave, CUtensorMapSwizzle,
                             CUtensorMapL2promotion, CUtensorMapFloatOOBfill);

static void make_map(EncodeFn fn, CUtensorMap* tm, const void* ptr, int inner, int rows, int cols, int box_rows, int box_outer,
                     CUtensorMapSwizzle swz) {
  cuuint64_t gd[3] = {(cuuint64_t)inner, (cuuint64_t)rows, (cuuint64_t)(cols / inner)};
  cuuint64_t gs[2] = {(cuuint64_t)cols * 2, (cuuint64_t)inner * 2};
  cuuint32_t bx[3] = {(cuuint32_t)inner, (cuuint32_t)box_rows, (cuuint32_t)box_outer};
  cuuint32_t es[3] = {1, 1, 1};
  fn(tm, CU_TENSOR_MAP_DATA_TYPE_BFLOAT16, 3, const_cast<void*>(ptr), gd, gs, bx, es, CU_TENSOR_MAP_INTERLEAVE_NONE, swz,
     CU_TENSOR_MAP_L2_PROMOTION_L2_128B, CU_TENSOR_MAP_FLOAT_OOB_FILL_NONE);
}

extern "C" void kernel_launch(void* const* d_in, const int* in_sizes, int n_in, void* d_out, int out_size) {
  (void)in_sizes; (void)n_in; (void)out_size;
  void* fnp = nullptr;
  cudaDriverEntryPointQueryResult qr;
  cudaGetDriverEntryPoint("cuTensorMapEncodeTiled", &fnp, cudaEnableDefault, &qr);
  EncodeFn fn = (EncodeFn)fnp;
  CUtensorMap tmWq, tmK, tmV, tmWo, tmW1, tmW2, tmWm, tmP, tmX;
  make_map(fn, &tmWq, d_in[3], 64, 512, 4096, 128, 2, CU_TENSOR_MAP_SWIZZLE_128B);
  make_map(fn, &tmK, d_in[1], 64, 8 * SK, 128, 128, 2, CU_TENSOR_MAP_SWIZZLE_128B);
  make_map(fn, &tmV, d_in[2], 64, 8 * SK, 128, 128, 2, CU_TENSOR_MAP_SWIZZLE_128B);
  make_map(fn, &tmWo, d_in[4], 64, 4096, 512, 256, 1, CU_TENSOR_MAP_SWIZZLE_128B);
  make_map(fn, &tmW1, d_in[6], 64, 512, FF, 64, 4, CU_TENSOR_MAP_SWIZZLE_128B);
  make_map(fn, &tmW2, d_in[7], 64, FF, 512, 224, 1, CU_TENSOR_MAP_SWIZZLE_128B);
  make_map(fn, &tmWm, d_in[9], 8, 512, 3072, 256, 1, CU_TENSOR_MAP_SWIZZLE_NONE);
  make_map(fn, &tmX, d_in[0], 16, 2048, 512, 16, 4, CU_TENSOR_MAP_SWIZZLE_NONE);
  Params p;
  p.x = (const __nv_bfloat16*)d_in[0];
  p.c = (const __nv_bfloat16*)d_in[8];
  p.wmod = (const __nv_bfloat16*)d_in[9];
  p.wo = (const __nv_bfloat16*)d_in[4];
  p.w1 = (const __nv_bfloat16*)d_in[6];
  p.w2 = (const __nv_bfloat16*)d_in[7];
  p.out = (__nv_bfloat16*)d_out;
  cudaGetSymbolAddress((void**)&p.s, g_scratch);
  {
    cuuint64_t gd[3] = {256, 32, 1024};
    cuuint64_t gs[2] = {512, 16384};
    cuuint32_t bx[3] = {256, 4, 8};
    cuuint32_t es[3] = {1, 1, 1};
    fn(&tmP, CU_TENSOR_MAP_DATA_TYPE_BFLOAT16, 3, (void*)p.s->P, gd, gs, bx, es, CU_TENSOR_MAP_INTERLEAVE_NONE,
       CU_TENSOR_MAP_SWIZZLE_NONE, CU_TENSOR_MAP_L2_PROMOTION_NONE, CU_TENSOR_MAP_FLOAT_OOB_FILL_NONE);
  }
  cudaFuncSetAttribute(adaln_block_kernel, cudaFuncAttributeMaxDynamicSharedMemorySize, SM_TOTAL);
  adaln_block_kernel<<<128, 512, SM_TOTAL>>>(tmWq, tmK, tmV, tmWo, tmW1, tmW2, tmWm, tmP, tmX, p);
}
```

```cpp
#include <cuda_runtime.h>
#include <cuda_bf16.h>
#include <cuda.h>
#include <stdint.h>

template <int OFF, uint32_t HI>
__device__ __forceinline__ void wgmma_rs_n128_tb0(float (&d)[64], const uint32_t (&a)[4], uint32_t lo, int sd) {
  asm volatile("{\n.reg .pred p;\n.reg .b32 l;\n.reg .b64 db;\nsetp.ne.b32 p, %69, 0;\n"
    "add.u32 l, %68, %70;\nmov.b64 db, {l, %71};\n"
    "wgmma.mma_async.sync.aligned.m64n128k16.f32.bf16.bf16 "
    "{%0,%1,%2,%3,%4,%5,%6,%7,%8,%9,%10,%11,%12,%13,%14,%15,"
    "%16,%17,%18,%19,%20,%21,%22,%23,%24,%25,%26,%27,%28,%29,%30,%31,"
    "%32,%33,%34,%35,%36,%37,%38,%39,%40,%41,%42,%43,%44,%45,%46,%47,"
    "%48,%49,%50,%51,%52,%53,%54,%55,%56,%57,%58,%59,%60,%61,%62,%63}, "
    "{%64,%65,%66,%67}, db, p, 1, 1, 0;\n}\n"
    : "+f"(d[0]), "+f"(d[1]), "+f"(d[2]), "+f"(d[3]), "+f"(d[4]), "+f"(d[5]), "+f"(d[6]), "+f"(d[7]),
      "+f"(d[8]), "+f"(d[9]), "+f"(d[10]), "+f"(d[11]), "+f"(d[12]), "+f"(d[13]), "+f"(d[14]), "+f"(d[15]),
      "+f"(d[16]), "+f"(d[17]), "+f"(d[18]), "+f"(d[19]), "+f"(d[20]), "+f"(d[21]), "+f"(d[22]), "+f"(d[23]),
      "+f"(d[24]), "+f"(d[25]), "+f"(d[26]), "+f"(d[27]), "+f"(d[28]), "+f"(d[29]), "+f"(d[30]), "+f"(d[31]),
      "+f"(d[32]), "+f"(d[33]), "+f"(d[34]), "+f"(d[35]), "+f"(d[36]), "+f"(d[37]), "+f"(d[38]), "+f"(d[39]),
      "+f"(d[40]), "+f"(d[41]), "+f"(d[42]), "+f"(d[43]), "+f"(d[44]), "+f"(d[45]), "+f"(d[46]), "+f"(d[47]),
      "+f"(d[48]), "+f"(d[49]), "+f"(d[50]), "+f"(d[51]), "+f"(d[52]), "+f"(d[53]), "+f"(d[54]), "+f"(d[55]),
      "+f"(d[56]), "+f"(d[57]), "+f"(d[58]), "+f"(d[59]), "+f"(d[60]), "+f"(d[61]), "+f"(d[62]), "+f"(d[63])
    : "r"(a[0]), "r"(a[1]), "r"(a[2]), "r"(a[3]), "r"(lo), "r"(sd), "n"(OFF), "n"(HI));
}

template <int OFF, uint32_t HI>
__device__ __forceinline__ void wgmma_rs_n128_tb1(float (&d)[64], const uint32_t (&a)[4], uint32_t lo, int sd) {
  asm volatile("{\n.reg .pred p;\n.reg .b32 l;\n.reg .b64 db;\nsetp.ne.b32 p, %69, 0;\n"
    "add.u32 l, %68, %70;\nmov.b64 db, {l, %71};\n"
    "wgmma.mma_async.sync.aligned.m64n128k16.f32.bf16.bf16 "
    "{%0,%1,%2,%3,%4,%5,%6,%7,%8,%9,%10,%11,%12,%13,%14,%15,"
    "%16,%17,%18,%19,%20,%21,%22,%23,%24,%25,%26,%27,%28,%29,%30,%31,"
    "%32,%33,%34,%35,%36,%37,%38,%39,%40,%41,%42,%43,%44,%45,%46,%47,"
    "%48,%49,%50,%51,%52,%53,%54,%55,%56,%57,%58,%59,%60,%61,%62,%63}, "
    "{%64,%65,%66,%67}, db, p, 1, 1, 1;\n}\n"
    : "+f"(d[0]), "+f"(d[1]), "+f"(d[2]), "+f"(d[3]), "+f"(d[4]), "+f"(d[5]), "+f"(d[6]), "+f"(d[7]),
      "+f"(d[8]), "+f"(d[9]), "+f"(d[10]), "+f"(d[11]), "+f"(d[12]), "+f"(d[13]), "+f"(d[14]), "+f"(d[15]),
      "+f"(d[16]), "+f"(d[17]), "+f"(d[18]), "+f"(d[19]), "+f"(d[20]), "+f"(d[21]), "+f"(d[22]), "+f"(d[23]),
      "+f"(d[24]), "+f"(d[25]), "+f"(d[26]), "+f"(d[27]), "+f"(d[28]), "+f"(d[29]), "+f"(d[30]), "+f"(d[31]),
      "+f"(d[32]), "+f"(d[33]), "+f"(d[34]), "+f"(d[35]), "+f"(d[36]), "+f"(d[37]), "+f"(d[38]), "+f"(d[39]),
      "+f"(d[40]), "+f"(d[41]), "+f"(d[42]), "+f"(d[43]), "+f"(d[44]), "+f"(d[45]), "+f"(d[46]), "+f"(d[47]),
      "+f"(d[48]), "+f"(d[49]), "+f"(d[50]), "+f"(d[51]), "+f"(d[52]), "+f"(d[53]), "+f"(d[54]), "+f"(d[55]),
      "+f"(d[56]), "+f"(d[57]), "+f"(d[58]), "+f"(d[59]), "+f"(d[60]), "+f"(d[61]), "+f"(d[62]), "+f"(d[63])
    : "r"(a[0]), "r"(a[1]), "r"(a[2]), "r"(a[3]), "r"(lo), "r"(sd), "n"(OFF), "n"(HI));
}

template <int OFF, uint32_t HI>
__device__ __forceinline__ void wgmma_rs_n192_tb1(float (&d)[96], const uint32_t (&a)[4], uint32_t lo, int sd) {
  asm volatile("{\n.reg .pred p;\n.reg .b32 l;\n.reg .b64 db;\nsetp.ne.b32 p, %101, 0;\n"
    "add.u32 l, %100, %102;\nmov.b64 db, {l, %103};\n"
    "wgmma.mma_async.sync.aligned.m64n192k16.f32.bf16.bf16 "
    "{%0,%1,%2,%3,%4,%5,%6,%7,%8,%9,%10,%11,%12,%13,%14,%15,"
    "%16,%17,%18,%19,%20,%21,%22,%23,%24,%25,%26,%27,%28,%29,%30,%31,"
    "%32,%33,%34,%35,%36,%37,%38,%39,%40,%41,%42,%43,%44,%45,%46,%47,"
    "%48,%49,%50,%51,%52,%53,%54,%55,%56,%57,%58,%59,%60,%61,%62,%63,"
    "%64,%65,%66,%67,%68,%69,%70,%71,%72,%73,%74,%75,%76,%77,%78,%79,"
    "%80,%81,%82,%83,%84,%85,%86,%87,%88,%89,%90,%91,%92,%93,%94,%95}, "
    "{%96,%97,%98,%99}, db, p, 1, 1, 1;\n}\n"
    : "+f"(d[0]), "+f"(d[1]), "+f"(d[2]), "+f"(d[3]), "+f"(d[4]), "+f"(d[5]), "+f"(d[6]), "+f"(d[7]),
      "+f"(d[8]), "+f"(d[9]), "+f"(d[10]), "+f"(d[11]), "+f"(d[12]), "+f"(d[13]), "+f"(d[14]), "+f"(d[15]),
      "+f"(d[16]), "+f"(d[17]), "+f"(d[18]), "+f"(d[19]), "+f"(d[20]), "+f"(d[21]), "+f"(d[22]), "+f"(d[23]),
      "+f"(d[24]), "+f"(d[25]), "+f"(d[26]), "+f"(d[27]), "+f"(d[28]), "+f"(d[29]), "+f"(d[30]), "+f"(d[31]),
      "+f"(d[32]), "+f"(d[33]), "+f"(d[34]), "+f"(d[35]), "+f"(d[36]), "+f"(d[37]), "+f"(d[38]), "+f"(d[39]),
      "+f"(d[40]), "+f"(d[41]), "+f"(d[42]), "+f"(d[43]), "+f"(d[44]), "+f"(d[45]), "+f"(d[46]), "+f"(d[47]),
      "+f"(d[48]), "+f"(d[49]), "+f"(d[50]), "+f"(d[51]), "+f"(d[52]), "+f"(d[53]), "+f"(d[54]), "+f"(d[55]),
      "+f"(d[56]), "+f"(d[57]), "+f"(d[58]), "+f"(d[59]), "+f"(d[60]), "+f"(d[61]), "+f"(d[62]), "+f"(d[63]),
      "+f"(d[64]), "+f"(d[65]), "+f"(d[66]), "+f"(d[67]), "+f"(d[68]), "+f"(d[69]), "+f"(d[70]), "+f"(d[71]),
      "+f"(d[72]), "+f"(d[73]), "+f"(d[74]), "+f"(d[75]), "+f"(d[76]), "+f"(d[77]), "+f"(d[78]), "+f"(d[79]),
      "+f"(d[80]), "+f"(d[81]), "+f"(d[82]), "+f"(d[83]), "+f"(d[84]), "+f"(d[85]), "+f"(d[86]), "+f"(d[87]),
      "+f"(d[88]), "+f"(d[89]), "+f"(d[90]), "+f"(d[91]), "+f"(d[92]), "+f"(d[93]), "+f"(d[94]), "+f"(d[95])
    : "r"(a[0]), "r"(a[1]), "r"(a[2]), "r"(a[3]), "r"(lo), "r"(sd), "n"(OFF), "n"(HI));
}

template <int OFF, uint32_t HI>
__device__ __forceinline__ void wgmma_rs_n32_tb1(float (&d)[16], const uint32_t (&a)[4], uint32_t lo, int sd) {
  asm volatile("{\n.reg .pred p;\n.reg .b32 l;\n.reg .b64 db;\nsetp.ne.b32 p, %21, 0;\n"
    "add.u32 l, %20, %22;\nmov.b64 db, {l, %23};\n"
    "wgmma.mma_async.sync.aligned.m64n32k16.f32.bf16.bf16 "
    "{%0,%1,%2,%3,%4,%5,%6,%7,%8,%9,%10,%11,%12,%13,%14,%15}, "
    "{%16,%17,%18,%19}, db, p, 1, 1, 1;\n}\n"
    : "+f"(d[0]), "+f"(d[1]), "+f"(d[2]), "+f"(d[3]), "+f"(d[4]), "+f"(d[5]), "+f"(d[6]), "+f"(d[7]),
      "+f"(d[8]), "+f"(d[9]), "+f"(d[10]), "+f"(d[11]), "+f"(d[12]), "+f"(d[13]), "+f"(d[14]), "+f"(d[15])
    : "r"(a[0]), "r"(a[1]), "r"(a[2]), "r"(a[3]), "r"(lo), "r"(sd), "n"(OFF), "n"(HI));
}

template <int OFF, uint32_t HI>
__device__ __forceinline__ void wgmma_rs_n64_tb1(float (&d)[32], const uint32_t (&a)[4], uint32_t lo, int sd) {
  asm volatile("{\n.reg .pred p;\n.reg .b32 l;\n.reg .b64 db;\nsetp.ne.b32 p, %37, 0;\n"
    "add.u32 l, %36, %38;\nmov.b64 db, {l, %39};\n"
    "wgmma.mma_async.sync.aligned.m64n64k16.f32.bf16.bf16 "
    "{%0,%1,%2,%3,%4,%5,%6,%7,%8,%9,%10,%11,%12,%13,%14,%15,"
    "%16,%17,%18,%19,%20,%21,%22,%23,%24,%25,%26,%27,%28,%29,%30,%31}, "
    "{%32,%33,%34,%35}, db, p, 1, 1, 1;\n}\n"
    : "+f"(d[0]), "+f"(d[1]), "+f"(d[2]), "+f"(d[3]), "+f"(d[4]), "+f"(d[5]), "+f"(d[6]), "+f"(d[7]),
      "+f"(d[8]), "+f"(d[9]), "+f"(d[10]), "+f"(d[11]), "+f"(d[12]), "+f"(d[13]), "+f"(d[14]), "+f"(d[15]),
      "+f"(d[16]), "+f"(d[17]), "+f"(d[18]), "+f"(d[19]), "+f"(d[20]), "+f"(d[21]), "+f"(d[22]), "+f"(d[23]),
      "+f"(d[24]), "+f"(d[25]), "+f"(d[26]), "+f"(d[27]), "+f"(d[28]), "+f"(d[29]), "+f"(d[30]), "+f"(d[31])
    : "r"(a[0]), "r"(a[1]), "r"(a[2]), "r"(a[3]), "r"(lo), "r"(sd), "n"(OFF), "n"(HI));
}

template <int STR>
__device__ __forceinline__ void verify8_tag1(const uint4* p, uint32_t (*r)[4]) {
  asm volatile("{\n.reg .pred p, q;\n.reg .b32 a, n;\nmov.u32 n, 0;\n"
    "LAB_CHK:\n"
    "and.b32 a, %0, %4;\n"
    "and.b32 a, a, %8;\n"
    "and.b32 a, a, %12;\n"
    "and.b32 a, a, %16;\n"
    "and.b32 a, a, %20;\n"
    "and.b32 a, a, %24;\n"
    "and.b32 a, a, %28;\n"
    "and.b32 a, a, 1;\nsetp.eq.u32 p, a, 1;\nvote.sync.all.pred p, p, 0xffffffff;\n"
    "@p bra.uni LAB_OK;\n"
    "and.b32 a, %0, 1;\nsetp.ne.u32 q, a, 1;\n"
    "@q ld.relaxed.gpu.global.v4.b32 {%0,%1,%2,%3}, [%32+%33];\n"
    "and.b32 a, %4, 1;\nsetp.ne.u32 q, a, 1;\n"
    "@q ld.relaxed.gpu.global.v4.b32 {%4,%5,%6,%7}, [%32+%34];\n"
    "and.b32 a, %8, 1;\nsetp.ne.u32 q, a, 1;\n"
    "@q ld.relaxed.gpu.global.v4.b32 {%8,%9,%10,%11}, [%32+%35];\n"
    "and.b32 a, %12, 1;\nsetp.ne.u32 q, a, 1;\n"
    "@q ld.relaxed.gpu.global.v4.b32 {%12,%13,%14,%15}, [%32+%36];\n"
    "and.b32 a, %16, 1;\nsetp.ne.u32 q, a, 1;\n"
    "@q ld.relaxed.gpu.global.v4.b32 {%16,%17,%18,%19}, [%32+%37];\n"
    "and.b32 a, %20, 1;\nsetp.ne.u32 q, a, 1;\n"
    "@q ld.relaxed.gpu.global.v4.b32 {%20,%21,%22,%23}, [%32+%38];\n"
    "and.b32 a, %24, 1;\nsetp.ne.u32 q, a, 1;\n"
    "@q ld.relaxed.gpu.global.v4.b32 {%24,%25,%26,%27}, [%32+%39];\n"
    "and.b32 a, %28, 1;\nsetp.ne.u32 q, a, 1;\n"
    "@q ld.relaxed.gpu.global.v4.b32 {%28,%29,%30,%31}, [%32+%40];\n"
    "add.u32 n, n, 1;\nsetp.lt.u32 q, n, 262144;\n@q bra.uni LAB_CHK;\n"
    "LAB_OK:\n"
    "}\n"
    : "+r"(r[0][0]), "+r"(r[0][1]), "+r"(r[0][2]), "+r"(r[0][3]), "+r"(r[1][0]), "+r"(r[1][1]), "+r"(r[1][2]), "+r"(r[1][3]),
      "+r"(r[2][0]), "+r"(r[2][1]), "+r"(r[2][2]), "+r"(r[2][3]), "+r"(r[3][0]), "+r"(r[3][1]), "+r"(r[3][2]), "+r"(r[3][3]),
      "+r"(r[4][0]), "+r"(r[4][1]), "+r"(r[4][2]), "+r"(r[4][3]), "+r"(r[5][0]), "+r"(r[5][1]), "+r"(r[5][2]), "+r"(r[5][3]),
      "+r"(r[6][0]), "+r"(r[6][1]), "+r"(r[6][2]), "+r"(r[6][3]), "+r"(r[7][0]), "+r"(r[7][1]), "+r"(r[7][2]), "+r"(r[7][3])
    : "l"(p), "n"(0 * STR), "n"(1 * STR), "n"(2 * STR), "n"(3 * STR), "n"(4 * STR), "n"(5 * STR), "n"(6 * STR), "n"(7 * STR)
    : "memory");
}

template <int STR>
__device__ __forceinline__ void verify4_rt(const uint4* p, uint32_t (*r)[4], uint32_t tag) {
  asm volatile("{\n.reg .pred p, q;\n.reg .b32 a, b, n;\nmov.u32 n, 0;\n"
    "LAB_CHK:\n"
    "lop3.b32 a, %0, %4, %21, 0x7e;\n"
    "lop3.b32 b, %8, %12, %21, 0x7e;\nor.b32 a, a, b;\n"
    "and.b32 a, a, 1;\nsetp.eq.u32 p, a, 0;\nvote.sync.all.pred p, p, 0xffffffff;\n"
    "@p bra.uni LAB_OK;\n"
    "and.b32 a, %0, 1;\nsetp.ne.u32 q, a, %21;\n"
    "@q ld.relaxed.gpu.global.v4.b32 {%0,%1,%2,%3}, [%16+%17];\n"
    "and.b32 a, %4, 1;\nsetp.ne.u32 q, a, %21;\n"
    "@q ld.relaxed.gpu.global.v4.b32 {%4,%5,%6,%7}, [%16+%18];\n"
    "and.b32 a, %8, 1;\nsetp.ne.u32 q, a, %21;\n"
    "@q ld.relaxed.gpu.global.v4.b32 {%8,%9,%10,%11}, [%16+%19];\n"
    "and.b32 a, %12, 1;\nsetp.ne.u32 q, a, %21;\n"
    "@q ld.relaxed.gpu.global.v4.b32 {%12,%13,%14,%15}, [%16+%20];\n"
    "add.u32 n, n, 1;\nsetp.lt.u32 q, n, 262144;\n@q bra.uni LAB_CHK;\n"
    "LAB_OK:\n}\n"
    : "+r"(r[0][0]), "+r"(r[0][1]), "+r"(r[0][2]), "+r"(r[0][3]), "+r"(r[1][0]), "+r"(r[1][1]), "+r"(r[1][2]), "+r"(r[1][3]),
      "+r"(r[2][0]), "+r"(r[2][1]), "+r"(r[2][2]), "+r"(r[2][3]), "+r"(r[3][0]), "+r"(r[3][1]), "+r"(r[3][2]), "+r"(r[3][3])
    : "l"(p), "n"(0 * STR), "n"(1 * STR), "n"(2 * STR), "n"(3 * STR), "r"(tag)
    : "memory");
}

template <int STR>
__device__ __forceinline__ void verify4_tag0(const uint4* p, uint32_t (*r)[4]) {
  asm volatile("{\n.reg .pred p, q;\n.reg .b32 a, n;\nmov.u32 n, 0;\n"
    "LAB_CHK:\n"
    "or.b32 a, %0, %4;\n"
    "or.b32 a, a, %8;\n"
    "or.b32 a, a, %12;\n"
    "and.b32 a, a, 1;\nsetp.eq.u32 p, a, 0;\nvote.sync.all.pred p, p, 0xffffffff;\n"
    "@p bra.uni LAB_OK;\n"
    "and.b32 a, %0, 1;\nsetp.ne.u32 q, a, 0;\n"
    "@q ld.relaxed.gpu.global.v4.b32 {%0,%1,%2,%3}, [%16+%17];\n"
    "and.b32 a, %4, 1;\nsetp.ne.u32 q, a, 0;\n"
    "@q ld.relaxed.gpu.global.v4.b32 {%4,%5,%6,%7}, [%16+%18];\n"
    "and.b32 a, %8, 1;\nsetp.ne.u32 q, a, 0;\n"
    "@q ld.relaxed.gpu.global.v4.b32 {%8,%9,%10,%11}, [%16+%19];\n"
    "and.b32 a, %12, 1;\nsetp.ne.u32 q, a, 0;\n"
    "@q ld.relaxed.gpu.global.v4.b32 {%12,%13,%14,%15}, [%16+%20];\n"
    "add.u32 n, n, 1;\nsetp.lt.u32 q, n, 262144;\n@q bra.uni LAB_CHK;\n"
    "LAB_OK:\n"
    "or.b32 %0, %0, 1;\n"
    "or.b32 %4, %4, 1;\n"
    "or.b32 %8, %8, 1;\n"
    "or.b32 %12, %12, 1;\n"
    "}\n"
    : "+r"(r[0][0]), "+r"(r[0][1]), "+r"(r[0][2]), "+r"(r[0][3]), "+r"(r[1][0]), "+r"(r[1][1]), "+r"(r[1][2]), "+r"(r[1][3]),
      "+r"(r[2][0]), "+r"(r[2][1]), "+r"(r[2][2]), "+r"(r[2][3]), "+r"(r[3][0]), "+r"(r[3][1]), "+r"(r[3][2]), "+r"(r[3][3])
    : "l"(p), "n"(0 * STR), "n"(1 * STR), "n"(2 * STR), "n"(3 * STR)
    : "memory");
}

#define SPIN_LIMIT (1 << 18)

__device__ __forceinline__ uint32_t smem_u32(const void* p) { return (uint32_t)__cvta_generic_to_shared(p); }
__device__ __forceinline__ void mbar_init(uint32_t a, uint32_t c) {
  asm volatile("mbarrier.init.shared::cta.b64 [%0], %1;" ::"r"(a), "r"(c) : "memory");
}
__device__ __forceinline__ void mbar_expect(uint32_t a, uint32_t b) {
  asm volatile("mbarrier.arrive.expect_tx.shared::cta.b64 _, [%0], %1;" ::"r"(a), "r"(b) : "memory");
}
__device__ __forceinline__ void mbar_arrive(uint32_t a) {
  asm volatile("mbarrier.arrive.shared::cta.b64 _, [%0];" ::"r"(a) : "memory");
}
__device__ __forceinline__ void mbar_wait(uint32_t a, uint32_t parity) {
  asm volatile(
      "{\n.reg .pred p;\n.reg .u32 n;\nmov.u32 n, 0;\n"
      "LAB_WAIT:\n"
      "mbarrier.try_wait.parity.shared::cta.b64 p, [%0], %1;\n"
      "@p bra LAB_DONE;\n"
      "add.u32 n, n, 1;\n"
      "setp.lt.u32 p, n, 262144;\n"
      "@p bra LAB_WAIT;\n"
      "LAB_DONE:\n}\n" ::"r"(a), "r"(parity) : "memory");
}
__device__ __forceinline__ bool mbar_test(uint32_t a, uint32_t parity) {
  uint32_t ok;
  asm volatile("{\n.reg .pred p;\nmbarrier.test_wait.parity.shared::cta.b64 p, [%1], %2;\nselp.u32 %0, 1, 0, p;\n}\n"
               : "=r"(ok) : "r"(a), "r"(parity) : "memory");
  return ok;
}
__device__ __forceinline__ void tma3d(uint32_t dst, const CUtensorMap* tm, uint32_t bar, int c0, int c1, int c2) {
  asm volatile(
      "cp.async.bulk.tensor.3d.shared::cluster.global.mbarrier::complete_tx::bytes [%0], [%1, {%3,%4,%5}], [%2];"
      ::"r"(dst), "l"(tm), "r"(bar), "r"(c0), "r"(c1), "r"(c2) : "memory");
}
__device__ __forceinline__ void wg_fence() { asm volatile("wgmma.fence.sync.aligned;" ::: "memory"); }
__device__ __forceinline__ void wg_commit() { asm volatile("wgmma.commit_group.sync.aligned;" ::: "memory"); }
template <int N> __device__ __forceinline__ void wg_wait() {
  asm volatile("wgmma.wait_group.sync.aligned %0;" ::"n"(N) : "memory");
}
template <int N> __device__ __forceinline__ void fence_regs(float (&d)[N]) {
#pragma unroll
  for (int i = 0; i < N; i++) asm volatile("" : "+f"(d[i])::"memory");
}
template <int N> __device__ __forceinline__ void fence_regs(uint32_t (&d)[N][4]) {
#pragma unroll
  for (int i = 0; i < N; i++) asm volatile("" : "+r"(d[i][0]), "+r"(d[i][1]), "+r"(d[i][2]), "+r"(d[i][3])::"memory");
}
template <int N> __device__ __forceinline__ void fence_frags(uint32_t (*d)[4]) {
#pragma unroll
  for (int i = 0; i < N; i++) asm volatile("" : "+r"(d[i][0]), "+r"(d[i][1]), "+r"(d[i][2]), "+r"(d[i][3])::"memory");
}
__device__ __forceinline__ void bar_sync(int id, int n) { asm volatile("bar.sync %0, %1;" ::"r"(id), "r"(n) : "memory"); }
__device__ __forceinline__ void bar_arrive(int id, int n) { asm volatile("bar.arrive %0, %1;" ::"r"(id), "r"(n) : "memory"); }

__device__ __forceinline__ uint32_t pack_bf16(float lo, float hi) {
  uint32_t r;
  asm("cvt.rn.bf16x2.f32 %0, %1, %2;" : "=r"(r) : "f"(hi), "f"(lo));
  return r;
}
__device__ __forceinline__ float bf_lo(uint32_t w) { return __uint_as_float(w << 16); }
__device__ __forceinline__ float bf_hi(uint32_t w) { return __uint_as_float(w & 0xFFFF0000u); }
__device__ __forceinline__ float round_bf16(float x) { return bf_lo(pack_bf16(x, 0.f)); }
__device__ __forceinline__ uint32_t hfma2_bf16(uint32_t a, uint32_t b, uint32_t c) {
  uint32_t r;
  asm("fma.rn.bf16x2 %0, %1, %2, %3;" : "=r"(r) : "r"(a), "r"(b), "r"(c));
  return r;
}
__device__ __forceinline__ float ex2(float x) {
  float r;
  asm("ex2.approx.ftz.f32 %0, %1;" : "=f"(r) : "f"(x));
  return r;
}
__device__ __forceinline__ float tanh_hw(float x) {
  float r;
  asm("tanh.approx.f32 %0, %1;" : "=f"(r) : "f"(x));
  return r;
}
template <int TAG> __device__ __forceinline__ uint32_t pack_tag(float lo, float hi) {
  uint32_t w = __byte_perm(__float_as_uint(lo), pack_bf16(lo, hi), 0x7632);
  return TAG ? (w | 1u) : (w & ~1u);
}
__device__ __forceinline__ void st_pkt(uint4* p, uint32_t a, uint32_t b, uint32_t c, uint32_t d) {
  asm volatile(
      "st.relaxed.gpu.global.v4.b32 [%0], {%1,%2,%3,%4};" ::"l"(p), "r"(a), "r"(b), "r"(c), "r"(d) : "memory");
}
__device__ __forceinline__ void ld_pkt(const uint4* p, uint32_t (&r)[4]) {
  asm volatile(
      "ld.relaxed.gpu.global.v4.b32 {%0,%1,%2,%3}, [%4];"
      : "=r"(r[0]), "=r"(r[1]), "=r"(r[2]), "=r"(r[3]) : "l"(p) : "memory");
}
__device__ __forceinline__ uint32_t ldg32(const void* p) {
  uint32_t r;
  asm volatile("ld.global.nc.b32 %0, [%1];" : "=r"(r) : "l"(p));
  return r;
}
__device__ __forceinline__ uint32_t ldg16(const void* p) {
  uint16_t r;
  asm volatile("ld.global.nc.b16 %0, [%1];" : "=h"(r) : "l"(p));
  return r;
}
__device__ __forceinline__ uint4 ldg128(const void* p) {
  uint4 r;
  asm volatile("ld.global.nc.v4.b32 {%0,%1,%2,%3}, [%4];" : "=r"(r.x), "=r"(r.y), "=r"(r.z), "=r"(r.w) : "l"(p));
  return r;
}
__device__ __forceinline__ void l2_prefetch(const void* p, uint32_t bytes) {
  asm volatile("cp.async.bulk.prefetch.L2.global [%0], %1;" ::"l"(p), "r"(bytes) : "memory");
}
__device__ __forceinline__ float rcp_hw(float x) {
  float r;
  asm("rcp.approx.ftz.f32 %0, %1;" : "=f"(r) : "f"(x));
  return r;
}
__device__ __forceinline__ void warp_bulk_load(uint32_t sdst, const void* gsrc, uint32_t bytes, uint32_t bar) {
  asm volatile(
      "{\n.reg .pred p;\nelect.sync _|p, 0xffffffff;\n"
      "@p mbarrier.arrive.expect_tx.shared::cta.b64 _, [%3], %2;\n"
      "@p cp.async.bulk.shared::cluster.global.mbarrier::complete_tx::bytes [%0], [%1], %2, [%3];\n}\n"
      ::"r"(sdst), "l"(gsrc), "r"(bytes), "r"(bar) : "memory");
}
__device__ __forceinline__ void warp_tma3d(uint32_t dst, const CUtensorMap* tm, uint32_t bar, uint32_t bytes, int c1, int c2) {
  asm volatile(
      "{\n.reg .pred p;\nelect.sync _|p, 0xffffffff;\n"
      "@p mbarrier.arrive.expect_tx.shared::cta.b64 _, [%2], %3;\n"
      "@p cp.async.bulk.tensor.3d.shared::cluster.global.mbarrier::complete_tx::bytes [%0], [%1, {%6,%4,%5}], [%2];\n}\n"
      ::"r"(dst), "l"(tm), "r"(bar), "r"(bytes), "r"(c1), "r"(c2), "r"(0) : "memory");
}
__device__ __forceinline__ bool elect_one() {
  uint32_t r;
  asm volatile("{\n.reg .pred p;\nelect.sync _|p, 0xffffffff;\nselp.u32 %0, 1, 0, p;\n}\n" : "=r"(r));
  return r;
}
__device__ __forceinline__ void warp_arrive(uint32_t bar) {
  asm volatile("{\n.reg .pred p;\nelect.sync _|p, 0xffffffff;\n@p mbarrier.arrive.shared::cta.b64 _, [%0];\n}\n" ::"r"(bar) : "memory");
}
__device__ __forceinline__ uint32_t pack_trunc(float lo, float hi) {
  return __byte_perm(__float_as_uint(lo), __float_as_uint(hi), 0x7632);
}
__device__ __forceinline__ void add_partial(float (&y)[8], const uint32_t (&r)[4], uint32_t c0, bool first) {
#pragma unroll
  for (int e = 0; e < 4; e++) {
    const float lo = __uint_as_float(r[e] * 65536u + (e ? 0x8000u : c0)), hi = __uint_as_float(r[e]);
    y[2 * e] = first ? lo : y[2 * e] + lo;
    y[2 * e + 1] = first ? hi : y[2 * e + 1] + hi;
  }
}
__device__ __forceinline__ void spin_cycles(uint32_t n) {
  uint32_t t0, t;
  asm volatile("mov.u32 %0, %%clock;" : "=r"(t0));
  do { asm volatile("mov.u32 %0, %%clock;" : "=r"(t)); } while (t - t0 < n);
}
__device__ __forceinline__ void sts128(uint32_t a, uint32_t x, uint32_t y, uint32_t z, uint32_t w) {
  asm volatile("st.shared.v4.b32 [%0], {%1,%2,%3,%4};" ::"r"(a), "r"(x), "r"(y), "r"(z), "r"(w) : "memory");
}
__device__ __forceinline__ void lds128(uint32_t a, uint32_t (&r)[4]) {
  asm volatile("ld.shared.v4.b32 {%0,%1,%2,%3}, [%4];" : "=r"(r[0]), "=r"(r[1]), "=r"(r[2]), "=r"(r[3]) : "r"(a) : "memory");
}

__device__ __forceinline__ uint32_t lds32(uint32_t a) {
  uint32_t r;
  asm volatile("ld.shared.b32 %0, [%1];" : "=r"(r) : "r"(a) : "memory");
  return r;
}
__device__ __forceinline__ void store_out(__nv_bfloat16* out, uint32_t woff, uint32_t x2s, uint32_t gb0, uint32_t gb1,
                                          const float (&y)[8]) {
  const uint32_t gb[2] = {gb0, gb1};
  uint32_t xa[2][4];
  lds128(x2s, xa[0]);
  lds128(x2s + 2048, xa[1]);
  uint32_t* const oo = (uint32_t*)out + woff;
#pragma unroll
  for (int e = 0; e < 4; e++)
    oo[(e >> 1) * 4 + (e & 1) * 8 * 256] =
        pack_bf16(fmaf(bf_lo(gb[e >> 1]), y[2 * e], __uint_as_float(xa[e >> 1][(e & 1) * 2])),
                  fmaf(bf_hi(gb[e >> 1]), y[2 * e + 1], __uint_as_float(xa[e >> 1][(e & 1) * 2 + 1])));
}

constexpr int SK = 2048, WIN = 512;
constexpr int FF = 1792, FSL = 224;
constexpr int NTILES = 80;
constexpr int NSLOT = 4;
constexpr uint32_t SLOT = 32768;
constexpr uint32_t SM_PARK = 0;
constexpr uint32_t SM_RING = 3 * SLOT;
constexpr uint32_t SM_TAB = 7 * SLOT;
constexpr uint32_t SM_RED = SM_TAB + 2048;
constexpr uint32_t SM_BAR = SM_RED + 256;
constexpr uint32_t SM_WBAR = SM_BAR + 128;
constexpr uint32_t SM_SBAR = SM_WBAR + 256;
constexpr uint32_t BAR_SLAB = 64, BAR_UV = 72, BAR_X2 = 80, BAR_TAG = 88;
constexpr uint32_t SM_DBAR = SM_SBAR + 16;
constexpr uint32_t SM_TOTAL = SM_DBAR + 128;

struct Scratch {
  uint4 P[16 * 8 * 4 * 1024];
  uint4 G[16 * 8 * 32 * 32];
  uint4 mod1[8 * 256];
  uint4 mod2[512];
  uint4 uv[2 * 448];
  uint4 stat[16 * 8 * 8];
  uint32_t sent[16 * 8 * 8];
  uint32_t epoch;
};
__device__ Scratch g_scratch;

#define TS(i) do { } while (0)
#define TR(code)
#define CK_(v)
#define CKS(i, v)

struct Params {
  const __nv_bfloat16* x;
  const __nv_bfloat16* c;
  const __nv_bfloat16* wmod;
  const __nv_bfloat16* wo;
  const __nv_bfloat16* w1;
  const __nv_bfloat16* w2;
  __nv_bfloat16* out;
  Scratch* s;
};

constexpr uint32_t HI128 = (1024 >> 4) | (1u << 30);
constexpr int LB_MN128 = (16384 >> 4) << 16;
constexpr int LB_K128 = 1 << 16;
constexpr int LB_W1 = (8192 >> 4) << 16;

template <int I> struct IC {
  __host__ __device__ constexpr operator int() const { return I; }
};
template <int I, int N, typename F> __device__ __forceinline__ void static_for(F&& f) {
  if constexpr (I < N) {
    f(IC<I>{});
    static_for<I + 1, N>(f);
  }
}

struct Ring {
  uint32_t base16, bars;
  __device__ __forceinline__ uint32_t wait_full(uint32_t slot, uint32_t parity) const {
    mbar_wait(bars + slot * 8, parity);
    return base16 + slot * (SLOT >> 4);
  }
  __device__ __forceinline__ void release(uint32_t slot) const {
    warp_arrive(bars + 32 + slot * 8);
  }
};

__device__ __forceinline__ float silu_c(uint32_t bits) {
  float x = bf_lo(bits);
  return round_bf16(x * rcp_hw(1.f + ex2(-1.4426950408889634f * x)));
}
__device__ __forceinline__ void pack8(uint32_t (&o)[4], const float* v) {
  o[0] = pack_bf16(v[0], v[1]); o[1] = pack_bf16(v[2], v[3]); o[2] = pack_bf16(v[4], v[5]); o[3] = pack_bf16(v[6], v[7]);
}

template <int TAG, int N>
__device__ __forceinline__ void issue_pkts(const uint4* p, int stride, uint32_t (*r)[4]) {
#pragma unroll
  for (int i = 0; i < N; i++) ld_pkt(p + i * stride, r[i]);
}
__device__ __forceinline__ void wait_sent(const uint32_t* p, uint32_t tag, uint32_t step) {
#pragma unroll 1
  for (int spins = 0; spins < SPIN_LIMIT; spins++) {
    uint32_t v;
    asm volatile("ld.relaxed.gpu.global.u32 %0, [%1];" : "=r"(v) : "l"(p) : "memory");
    if (__all_sync(0xffffffffu, v - (tag * 32 + step + 1) < 16u)) break;
  }
}
__device__ __forceinline__ void ld_mod(const uint4* p, uint32_t tag, uint32_t (&r)[4]) {
  int spins = 0;
  ld_pkt(p, r);
  while (r[2] != tag && ++spins < SPIN_LIMIT) ld_pkt(p, r);
}

#define EARLY_TILES 2
#define PF_WMOD 1
#define MOD1_DELAY 500
#define RED3_UNIT 3
#define NITEM2 24
#define FIN_DELAY0 800
#define FIN_DELAY1 0
#define G_DELAY 300

__device__ __forceinline__ float reduce8(float (&a)[8], int lane) {
  const bool h16 = lane & 16, h8 = lane & 8, h4 = lane & 4;
#pragma unroll
  for (int k = 0; k < 4; k++) a[k] = (h16 ? a[k + 4] : a[k]) + __shfl_xor_sync(0xffffffffu, h16 ? a[k] : a[k + 4], 16);
#pragma unroll
  for (int k = 0; k < 2; k++) a[k] = (h8 ? a[k + 2] : a[k]) + __shfl_xor_sync(0xffffffffu, h8 ? a[k] : a[k + 2], 8);
  const float r = (h4 ? a[1] : a[0]) + __shfl_xor_sync(0xffffffffu, h4 ? a[0] : a[1], 4);
  return r + __shfl_xor_sync(0xffffffffu, r, 2);
}
__device__ __forceinline__ void fma8(float (&a)[8], float s, uint32_t w0, uint32_t w1, uint32_t w2, uint32_t w3) {
  a[0] = fmaf(s, bf_lo(w0), a[0]); a[1] = fmaf(s, bf_hi(w0), a[1]);
  a[2] = fmaf(s, bf_lo(w1), a[2]); a[3] = fmaf(s, bf_hi(w1), a[3]);
  a[4] = fmaf(s, bf_lo(w2), a[4]); a[5] = fmaf(s, bf_hi(w2), a[5]);
  a[6] = fmaf(s, bf_lo(w3), a[6]); a[7] = fmaf(s, bf_hi(w3), a[7]);
}

enum { NB_TAB = 1, NB_WG0 = 2, NB_WG1 = 3, NB_HELP = 4, NB_INIT = 5, NB_PASS0 = 6, NB_GATHER = 7, NB_PARK = 8, NB_PROD = 9 };

__global__ void __launch_bounds__(512, 1)
adaln_block_kernel(const __grid_constant__ CUtensorMap tmWq, const __grid_constant__ CUtensorMap tmK,
                   const __grid_constant__ CUtensorMap tmV, const __grid_constant__ CUtensorMap tmWo,
                   const __grid_constant__ CUtensorMap tmW1, const __grid_constant__ CUtensorMap tmW2,
                   const __grid_constant__ CUtensorMap tmWm, const __grid_constant__ CUtensorMap tmX,
                   const Params p) {
  extern __shared__ __align__(1024) uint8_t smem_raw[];
  const uint32_t sb = smem_u32(smem_raw);
  const int tid = threadIdx.x, lane = tid & 31;
  const int warp = __shfl_sync(0xffffffffu, tid >> 5, 0);
  const int kp = blockIdx.x >> 1;
  const int bid = (kp < 4 ? kp : kp < 36 ? 4 + ((kp - 4) & 7) * 4 + ((kp - 4) >> 3) : 36 + ((kp - 36) % 7) * 4 + (kp - 36) / 7) * 2 +
                  (blockIdx.x & 1);
  const int j = bid & 7, rt = bid >> 3;
  const uint32_t bars = sb + SM_BAR;
  if (warp != 13) asm volatile("barrier.cluster.arrive.relaxed.aligned;" ::: "memory");

  if (warp >= 12) {
    asm volatile("setmaxnreg.dec.sync.aligned.u32 24;");
    if (warp == 13) {
      if (elect_one()) {
#pragma unroll
        for (int i = 0; i < 28; i++) mbar_init(sb + SM_WBAR + i * 8, i < 26 ? 1 : 4);
        mbar_init(sb + SM_SBAR, 8);
#pragma unroll
        for (int i = 0; i < 16; i++) mbar_init(sb + SM_DBAR + i * 8, 1);
        asm volatile("fence.mbarrier_init.release.cluster;" ::: "memory");
      }
      __syncwarp();
      asm volatile("barrier.cluster.arrive.relaxed.aligned;" ::: "memory");
      bar_arrive(NB_INIT, 192);
      mbar_wait(sb + SM_SBAR, 0);
      const uint32_t tag = *(volatile uint32_t*)(smem_raw + SM_BAR + BAR_TAG);
#pragma unroll 1
      for (int n = 0; n < 14; n++) {
        const uint32_t lb = sb + SM_WBAR + 192 + (n & 1) * 8;
        mbar_wait(lb + 16, ((n >> 1) & 1) ^ 1);
        wait_sent(&p.s->sent[(rt * 8 + j) * 8 + (lane & 6) + (n & 1)], tag, n >> 1);
        if (elect_one()) {
          mbar_expect(lb, n < 8 ? 8192 + 2048 : 8192);
#pragma unroll
          for (int m = 0; m < 4; m++)
            asm volatile("cp.async.bulk.shared::cluster.global.mbarrier::complete_tx::bytes [%0], [%1], 2048, [%2];"
                         ::"r"(sb + SM_PARK + ((n & 1) * 4 + m) * 4096 + 2048),
                           "l"(p.s->P + ((size_t)(rt * 8 + j) * 4 + m) * 1024 + (n & 7) * 128), "r"(lb) : "memory");
          if (n < 8) tma3d(sb + SM_PARK + SLOT + n * 4096, &tmX, lb, 0, rt * 128 + j * 16, n * 4);
        }
        __syncwarp();
      }
    } else if (warp == 14) {
      if (elect_one()) {
        asm volatile("prefetch.tensormap [%0];" ::"l"(&tmWq) : "memory");
        asm volatile("prefetch.tensormap [%0];" ::"l"(&tmK) : "memory");
        asm volatile("prefetch.tensormap [%0];" ::"l"(&tmV) : "memory");
        asm volatile("prefetch.tensormap [%0];" ::"l"(&tmWo) : "memory");
        asm volatile("prefetch.tensormap [%0];" ::"l"(&tmX) : "memory");
        asm volatile("prefetch.tensormap [%0];" ::"l"(&tmW1) : "memory");
        asm volatile("prefetch.tensormap [%0];" ::"l"(&tmW2) : "memory");
      }
    } else if (warp == 12) {
      if (elect_one()) {
        mbar_init(bars + BAR_SLAB, 1);
        asm volatile("fence.mbarrier_init.release.cluster;" ::: "memory");
        mbar_expect(bars + BAR_SLAB, 8192);
        tma3d(sb + SM_RING + 3 * SLOT, &tmWm, bars + BAR_SLAB, 0, 0, bid);
        tma3d(sb + SM_RING + 3 * SLOT + 4096, &tmWm, bars + BAR_SLAB, 0, 256, bid);
#pragma unroll
        for (int i = 0; i < 4; i++) { mbar_init(bars + i * 8, 1); mbar_init(bars + 32 + i * 8, 8); }
        mbar_init(bars + BAR_UV, 4);
        mbar_init(bars + BAR_X2, 1);
        asm volatile("fence.mbarrier_init.release.cluster;" ::: "memory");
      }
      __syncwarp();
      bar_arrive(NB_INIT, 192);
      mbar_wait(bars + BAR_SLAB, 0);
      uint32_t s = 0, ph = 1;
#pragma unroll 1
      for (int tt = 0; tt < NTILES; tt++) {
        const CUtensorMap* tm;
        int c1, c2;
        uint32_t bytes = SLOT;
        if (tt < 16) {
          tm = &tmWq; c1 = (tt & 3) * 128; c2 = (j * 4 + (((tt >> 2) + 1) & 3)) * 2;
        } else if (tt < 48) {
          const int u = tt - 16;
          const bool isK = (u == 0) || ((u & 1) && u != 31);
          const int n = isK ? ((u + 1) >> 1) : (u == 31 ? 15 : (u >> 1) - 1);
          tm = isK ? &tmK : &tmV; c1 = j * SK + (SK - WIN) + (n & 3) * 128; c2 = 0;
        } else if (tt < 64) {
          const int u = tt - 48;
          tm = &tmWo; c1 = j * 512 + (u & 1) * 256; c2 = (u >> 1) ^ (~j & 1);
        } else if (tt < 72) {
          tm = &tmW1; c1 = (tt - 64) * 64; c2 = (j * 7) >> 1;
        } else {
          tm = &tmW2; c1 = j * FSL; c2 = (tt - 72) ^ (~j & 1); bytes = 28672;
        }
        if (tt == EARLY_TILES) bar_sync(NB_PROD, 160);
        mbar_wait(bars + 32 + s * 8, ph);
        warp_tma3d(sb + SM_RING + s * SLOT, tm, bars + s * 8, bytes, c1, c2);
        if (++s == 4) { s = 0; ph ^= 1; }
      }
    }
  } else if (warp >= 8) {
    CK_(c0);
    asm volatile("setmaxnreg.dec.sync.aligned.u32 40;");
    const int t = tid - 256, hw = warp - 8, q = lane & 3;
    float* const red = (float*)(smem_raw + SM_RED);
    uint32_t tag;
    float a[8];
    {
      uint32_t cb[4];
#pragma unroll
      for (int i = 0; i < 4; i++) cb[i] = ldg16(p.c + t + 128 * i);
      asm volatile("ld.relaxed.gpu.global.u32 %0, [%1];" : "=r"(tag) : "l"(&p.s->epoch) : "memory");
      bar_sync(NB_INIT, 192);
      CK_(c2);
      tag += 1;
      float sc[4];
#pragma unroll
      for (int i = 0; i < 4; i++) sc[i] = silu_c(cb[i]);
#pragma unroll
      for (int k = 0; k < 8; k++) a[k] = 0.f;
      if (t == 0) *(uint32_t*)(smem_raw + SM_BAR + BAR_TAG) = tag;
      mbar_wait(bars + BAR_SLAB, 0);
      CK_(c3);
      bar_arrive(NB_GATHER, 384);
#pragma unroll
      for (int i = 0; i < 4; i++) {
        uint32_t w[4];
        lds128(sb + SM_RING + 3 * SLOT + (t + 128 * i) * 16, w);
        fma8(a, sc[i], w[0], w[1], w[2], w[3]);
      }
      float r = reduce8(a, lane);
      r += __shfl_xor_sync(0xffffffffu, r, 1);
      if (q == 0) red[hw * 8 + (lane >> 2)] = r;
      CK_(c4);
      bar_sync(NB_HELP, 128);
      CK_(c5);
      if (hw == 0) {
        const int cl = lane & 7;
        float v = round_bf16(red[cl] + red[8 + cl] + red[16 + cl] + red[24 + cl]);
        if (bid >= 64) v = 1.f + v;
        float vn = __shfl_down_sync(0xffffffffu, v, 1);
        uint32_t wd = pack_bf16(v, vn);
        uint32_t w0 = __shfl_sync(0xffffffffu, wd, (lane & 1) * 4);
        uint32_t w1 = __shfl_sync(0xffffffffu, wd, (lane & 1) * 4 + 2);
        if (lane < 16) st_pkt(&p.s->mod1[(lane >> 1) * 256 + bid * 2 + (lane & 1)], w0, w1, tag, 0);
      }
      uint32_t r0[4], r1[4];
      const uint4* src = &p.s->mod1[j * 256 + t];
      CK_(c6);
      spin_cycles(MOD1_DELAY);
      CK_(c7);
      int spins = 0;
      do {
        ld_pkt(src, r0);
        ld_pkt(src + 128, r1);
      } while ((r0[2] != tag || r1[2] != tag) && ++spins < SPIN_LIMIT);
      const int g = t >> 2, pp = q * 2;
      const uint32_t ad = sb + SM_TAB + (uint32_t)(g * 4 + (pp & 3)) * 16 + (pp >> 2) * 4;
      asm volatile("st.shared.b32 [%0], %1;" ::"r"(ad + 8), "r"(r0[0]) : "memory");
      asm volatile("st.shared.b32 [%0], %1;" ::"r"(ad + 24), "r"(r0[1]) : "memory");
      asm volatile("st.shared.b32 [%0], %1;" ::"r"(ad), "r"(r1[0]) : "memory");
      asm volatile("st.shared.b32 [%0], %1;" ::"r"(ad + 16), "r"(r1[1]) : "memory");
      bar_arrive(NB_TAB, 384);
      bar_arrive(NB_PROD, 160);
      CK_(c8);
      CKS(0, c0); CKS(2, c2); CKS(3, c3); CKS(4, c4); CKS(5, c5); CKS(6, c6); CKS(7, c7); CKS(8, c8);
    }
    bar_sync(NB_PASS0, 384);
    if (t < 8) l2_prefetch((const char*)p.wo + (size_t)bid * 32768 + t * 4096, 4096);
    else if (t < 12) l2_prefetch((const char*)p.w1 + (size_t)bid * 14336 + (t - 8) * 3584, 3584);
    else if (t < 16) l2_prefetch((const char*)p.w2 + (size_t)bid * 14336 + (t - 12) * 3584, 3584);
    {
#pragma unroll
      for (int k = 0; k < 8; k++) a[k] = 0.f;
#pragma unroll 1
      for (int b = 0; b < 4; b++) {
        const int row = b * 128 + (t >> 1);
        const __nv_bfloat16* wp = p.wmod + (size_t)row * 3072 + 1024 + bid * 16 + (t & 1) * 8;
        const uint4 w0 = ldg128(wp), w1 = ldg128(wp + 64 * 3072);
        const uint32_t c0 = ldg16(p.c + row), c1 = ldg16(p.c + row + 64);
        fma8(a, silu_c(c0), w0.x, w0.y, w0.z, w0.w);
        fma8(a, silu_c(c1), w1.x, w1.y, w1.z, w1.w);
      }
      const float r = reduce8(a, lane);
      if ((lane & 2) == 0) red[hw * 16 + (lane & 1) * 8 + (lane >> 2)] = r;
      bar_sync(NB_HELP, 128);
      if (hw == 0) {
        const int cl = lane & 15;
        float v = round_bf16(red[cl] + red[16 + cl] + red[32 + cl] + red[48 + cl]);
        if ((bid >> 5) == 2) v = 1.f + v;
        float vn = __shfl_down_sync(0xffffffffu, v, 1);
        uint32_t wd = pack_bf16(v, vn);
        uint32_t w0 = __shfl_sync(0xffffffffu, wd, q * 2);
        uint32_t w1 = __shfl_sync(0xffffffffu, wd, q * 2 + 8);
        const int vec = (0x2130 >> ((bid >> 5) * 4)) & 3;
        if (lane < 4) st_pkt(&p.s->mod2[((bid & 31) * 4 + vec) * 4 + lane], w0, w1, tag, 0);
      }
    }
    {
      const int isv = hw & 1, kh = hw >> 1;
      if (bid < 112) {
        const int kk = lane >> 1;
        uint32_t m0[4], m1[4];
        const uint4* mp = &p.s->mod2[(kh * 16 + (lane >> 2)) * 16 + (isv ? 12 : 4) + q];
        ld_mod(mp, tag, m0);
        ld_mod(mp + 128, tag, m1);
#pragma unroll
        for (int k = 0; k < 8; k++) a[k] = 0.f;
#pragma unroll 1
        for (int g0 = 0; g0 < 16; g0 += 2) {
          uint4 w[2];
#pragma unroll
          for (int i = 0; i < 2; i++) w[i] = ldg128(p.w1 + (size_t)((kh * 16 + g0 + i) * 16 + kk) * FF + bid * 16 + (lane & 1) * 8);
#pragma unroll
          for (int i = 0; i < 2; i++) {
            const int sl = ((g0 + i) & 7) * 4 + ((kk & 7) >> 1);
            const uint32_t wa = __shfl_sync(0xffffffffu, g0 < 8 ? m0[0] : m1[0], sl), wb = __shfl_sync(0xffffffffu, g0 < 8 ? m0[1] : m1[1], sl);
            const uint32_t mw = (kk & 8) ? wb : wa;
            fma8(a, (kk & 1) ? bf_hi(mw) : bf_lo(mw), w[i].x, w[i].y, w[i].z, w[i].w);
          }
        }
        float r = reduce8(a, lane);
        bar_sync(NB_HELP, 128);
        if (kh) red[isv * 32 + lane] = r;
        bar_sync(NB_HELP, 128);
        if (!kh) {
          r = (r + red[isv * 32 + lane]) * (isv ? 0.5f : 1.f);
          const float r1 = __shfl_down_sync(0xffffffffu, r, 4), r2 = __shfl_down_sync(0xffffffffu, r, 8),
                      r3 = __shfl_down_sync(0xffffffffu, r, 12);
          if ((lane & 14) == 0)
            st_pkt(&p.s->uv[isv * 448 + bid * 4 + (lane & 1) * 2 + (lane >> 4)], (__float_as_uint(r) & ~1u) | (tag & 1u),
                   __float_as_uint(r1), __float_as_uint(r2), __float_as_uint(r3));
        }
      }
      const int i = kh * 32 + lane;
      if (i < 56) {
        uint32_t m[4];
        int spins = 0;
        while (true) {
          ld_pkt(&p.s->uv[isv * 448 + j * 56 + i], m);
          if (!((m[0] ^ tag) & 1u) || ++spins >= SPIN_LIMIT) break;
          __nanosleep(200);
        }
        const int ip = (j & 1) ? (i < 8 ? i + 48 : i - 8) : i;
        const uint32_t ad = sb + SM_TAB + ip * 32 + isv * 8;
        asm volatile("st.shared.v2.b32 [%0], {%1,%2};" ::"r"(ad), "r"(m[0]), "r"(m[1]) : "memory");
        asm volatile("st.shared.v2.b32 [%0], {%1,%2};" ::"r"(ad + 16), "r"(m[2]), "r"(m[3]) : "memory");
      }
      __syncwarp();
      warp_arrive(bars + BAR_UV);
      TS(9);
    }
    {
      uint32_t mga[4], mg2[4], mgb[4];
      const uint4* mp = &p.s->mod2[((lane >> 2) * 4 + hw) * 16 + q];
      ld_mod(mp, tag, mga);
      ld_mod(mp + 4, tag, mg2);
      ld_mod(mp + 8, tag, mgb);
      if (lane >= 24) asm volatile("st.shared.v2.b32 [%0], {%1,%2};" ::"r"(sb + SM_TAB + 1792 + ((((lane >> 2) & 1) * 4 + hw) * 4 + q) * 8),
                                   "r"(mgb[0]), "r"(mgb[1]) : "memory");
      const uint32_t x2s = sb + SM_PARK + SLOT + hw * 512 + lane * 16;
      const uint4* const Pown = p.s->P + (size_t)(rt * 8 + j) * 4096 + hw * 32 + lane;
      float s0 = 0.f, s1 = 0.f, v0 = 0.f, v1 = 0.f;
      bar_sync(NB_PARK, 384);
      asm volatile("setmaxnreg.inc.sync.aligned.u32 88;");
#pragma unroll 1
      for (int n = 0; n < 14; n++) {
        const int cc = n & 7;
        const bool ex1 = n < 8;
        const uint32_t lb = sb + SM_WBAR + 192 + (n & 1) * 8;
        uint32_t r[4][4];
        float y[8];
        mbar_wait(lb, (n >> 1) & 1);
#pragma unroll
        for (int i = 0; i < 4; i++) lds128(sb + SM_PARK + ((n & 1) * 4 + i) * 4096 + 2048 + hw * 512 + lane * 16, r[i]);
        verify4_rt<16384>(Pown + cc * 128, r, ex1);
        warp_arrive(lb + 16);
#pragma unroll
        for (int i = 0; i < 4; i++) add_partial(y, r[i], ex1 ? 0u : 0x10000u, i == 0);
        const int src = cc * 4 + q;
        const uint32_t ma = __shfl_sync(0xffffffffu, ex1 ? mga[0] : mgb[0], src), mb = __shfl_sync(0xffffffffu, ex1 ? mga[1] : mgb[1], src);
        if (ex1) {
          uint32_t xr[4];
          asm volatile("ldmatrix.sync.aligned.m8n8.x4.shared.b16 {%0,%1,%2,%3}, [%4];"
                       : "=r"(xr[0]), "=r"(xr[1]), "=r"(xr[2]), "=r"(xr[3])
                       : "r"(sb + SM_PARK + SLOT + hw * 512 + cc * 4096 + (lane & 15) * 32 + (lane >> 4) * 16) : "memory");
          const uint32_t mc = __shfl_sync(0xffffffffu, mg2[0], src), md = __shfl_sync(0xffffffffu, mg2[1], src);
#pragma unroll
          for (int e = 0; e < 4; e++) {
            const uint32_t m = e < 2 ? ma : mb;
            const float u = fmaf(bf_lo(m), y[2 * e], bf_lo(xr[e])), v = fmaf(bf_hi(m), y[2 * e + 1], bf_hi(xr[e]));
            y[2 * e] = u; y[2 * e + 1] = v;
            if (e & 1) { s1 += u + v; v1 = fmaf(u, u, fmaf(v, v, v1)); }
            else { s0 += u + v; v0 = fmaf(u, u, fmaf(v, v, v0)); }
          }
          st_pkt(p.s->G + ((rt * 8 + j) * 32 + cc * 4 + hw) * 32 + lane, pack_tag<0>(y[0] * bf_lo(mc), y[1] * bf_hi(mc)),
                 pack_bf16(y[2] * bf_lo(mc), y[3] * bf_hi(mc)), pack_bf16(y[4] * bf_lo(md), y[5] * bf_hi(md)),
                 pack_bf16(y[6] * bf_lo(md), y[7] * bf_hi(md)));
          sts128(x2s + cc * 4096, __float_as_uint(y[0]), __float_as_uint(y[1]), __float_as_uint(y[2]), __float_as_uint(y[3]));
          sts128(x2s + cc * 4096 + 2048, __float_as_uint(y[4]), __float_as_uint(y[5]), __float_as_uint(y[6]), __float_as_uint(y[7]));
          if (n == 7) {
            const bool o1 = lane & 1, o2 = lane & 2;
            float c0 = (o1 ? v0 : s0) + __shfl_xor_sync(0xffffffffu, o1 ? s0 : v0, 1);
            float c1 = (o1 ? v1 : s1) + __shfl_xor_sync(0xffffffffu, o1 ? s1 : v1, 1);
            c0 = (o2 ? c1 : c0) + __shfl_xor_sync(0xffffffffu, o2 ? c0 : c1, 2);
            *(float*)(smem_raw + SM_PARK + 16384 + 2048 + hw * 512 + lane * 4) = c0;
            bar_sync(NB_HELP, 128);
            if (hw == 0) {
              const float* ps = (const float*)(smem_raw + SM_PARK + 16384 + 2048) + lane;
              const float m = (c0 + ps[128] + ps[256] + ps[384]) * (1.f / 512.f);
              const float mean = __shfl_sync(0xffffffffu, m, lane & ~1), sq = __shfl_sync(0xffffffffu, m, lane | 1);
              const float rs = 0.5f * rsqrtf(fmaxf(fmaf(-mean, mean, sq), 0.f) + 1e-5f), mr = -mean * rs;
              const float rs1 = __shfl_down_sync(0xffffffffu, rs, 2), mr1 = __shfl_down_sync(0xffffffffu, mr, 2);
              if (q == 0)
                st_pkt(&p.s->stat[(rt * 8 + j) * 8 + (lane >> 2)], (__float_as_uint(rs) & ~1u) | (tag & 1u), __float_as_uint(mr),
                       __float_as_uint(rs1), __float_as_uint(mr1));
              warp_arrive(bars + BAR_X2);
            }
          }
        } else {
          store_out(p.out, (uint32_t)(rt * 128 + 16 * j + (lane >> 2)) * 256 + (cc * 4 + hw) * 8 + q, x2s + cc * 4096, ma, mb, y);
        }
      }
    }
  } else {
    const int wg = warp >> 2;
    const int q = lane & 3, gq = lane >> 2;
    const Ring ring{((sb + SM_RING) & 0x3FFFF) >> 4, bars};
    const uint32_t xoff = (uint32_t)(rt * 128 + 16 * j + warp) * 256 + gq * 8 + q;
    const uint32_t ooff = ((uint32_t)(rt * 8 + j) * 32 + gq) * 32 + warp * 4 + q;
    const uint32_t wblk = sb + SM_PARK + warp * 4096, wprv = wblk + lane * 16;
    const uint32_t wbar = sb + SM_WBAR + warp * 24;
    const uint4* const Gw = p.s->G + (rt * 8 + warp) * 1024;

    {
      const uint32_t* xo = (const uint32_t*)p.x + xoff;
      uint32_t xr[4][4];
      CK_(d0);
#pragma unroll
      for (int c = 0; c < 4; c++) {
        xr[c][0] = ldg32(xo + c * 64);
        xr[c][1] = ldg32(xo + c * 64 + 8 * 256);
        xr[c][2] = ldg32(xo + c * 64 + 4);
        xr[c][3] = ldg32(xo + c * 64 + 4 + 8 * 256);
      }
      CK_(d1);
      fence_regs(xr);
      CK_(d2);
      float s0 = 0.f, s1 = 0.f, v0 = 0.f, v1 = 0.f;
#pragma unroll
      for (int c = 0; c < 4; c++) {
#pragma unroll
        for (int e = 0; e < 4; e++) {
          const float a = bf_lo(xr[c][e]), b = bf_hi(xr[c][e]);
          if (e & 1) { s1 += a + b; v1 = fmaf(a, a, fmaf(b, b, v1)); }
          else { s0 += a + b; v0 = fmaf(a, a, fmaf(b, b, v0)); }
        }
      }
#pragma unroll
      for (int o = 16; o > 0; o >>= 1) {
        s0 += __shfl_xor_sync(0xffffffffu, s0, o);
        s1 += __shfl_xor_sync(0xffffffffu, s1, o);
        v0 += __shfl_xor_sync(0xffffffffu, v0, o);
        v1 += __shfl_xor_sync(0xffffffffu, v1, o);
      }
      const float m0 = s0 * (1.f / 512.f), m1 = s1 * (1.f / 512.f);
      const float r0 = rsqrtf(fmaxf(fmaf(-m0, m0, v0 * (1.f / 512.f)), 0.f) + 1e-5f);
      const float r1 = rsqrtf(fmaxf(fmaf(-m1, m1, v1 * (1.f / 512.f)), 0.f) + 1e-5f);
#pragma unroll
      for (int c = 0; c < 4; c++) {
        st_pkt(p.s->G + ooff + c * 256,
               pack_tag<1>((bf_lo(xr[c][0]) - m0) * r0, (bf_hi(xr[c][0]) - m0) * r0),
               pack_bf16((bf_lo(xr[c][1]) - m1) * r1, (bf_hi(xr[c][1]) - m1) * r1),
               pack_bf16((bf_lo(xr[c][2]) - m0) * r0, (bf_hi(xr[c][2]) - m0) * r0),
               pack_bf16((bf_lo(xr[c][3]) - m1) * r1, (bf_hi(xr[c][3]) - m1) * r1));
      }
      CK_(d3);
      CKS(16, d0); CKS(17, d1); CKS(18, d2); CKS(19, d3);

    }
    asm volatile("setmaxnreg.inc.sync.aligned.u32 224;");
    uint32_t qf[8][4];
    {
      uint32_t h[32][4];
      float acc[64];
      const uint4* Gin = Gw + lane;
      asm volatile("barrier.cluster.wait.acquire.aligned;" ::: "memory");
      bar_sync(NB_GATHER, 384);
      if (G_DELAY) spin_cycles(G_DELAY);
#pragma unroll
      for (int c = 0; c < 3; c++) warp_bulk_load(wblk + c * SLOT, Gw + c * 256, 4096, wbar + c * 8);
#pragma unroll
      for (int c = 0; c < 4; c++) {
        mbar_wait(wbar + (c % 3) * 8, c / 3);
#pragma unroll
        for (int i = 0; i < 8; i++) lds128(wprv + (c % 3) * SLOT + i * 512, h[c * 8 + i]);
        verify8_tag1<512>(Gin + c * 256, h + c * 8);
        if (c == 0) {
          warp_bulk_load(wblk, Gw + 768, 4096, wbar);
          TS(1);
          bar_sync(NB_TAB, 384);
        }
#pragma unroll
        for (int i = 0; i < 8; i++) {
          uint32_t m[4];
          lds128(sb + SM_TAB + (uint32_t)((c * 8 + i) * 4 + q) * 16, m);
          uint32_t* hh = h[c * 8 + i];
          hh[0] = hfma2_bf16(hh[0], m[0], m[2]);
          hh[1] = hfma2_bf16(hh[1], m[0], m[2]);
          hh[2] = hfma2_bf16(hh[2], m[1], m[3]);
          hh[3] = hfma2_bf16(hh[3], m[1], m[3]);
        }
        fence_frags<8>(h + c * 8);
        const uint32_t b = ring.wait_full(c, 0);
        if (c > 0) { wg_wait<0>(); ring.release(c - 1); }
        if (c == 0) TS(2);
        wg_fence();
        static_for<0, 8>([&](auto K) { wgmma_rs_n128_tb1<LB_MN128 + K * 128, HI128>(acc, h[c * 8 + K], b, (c | K) != 0); });
        wg_commit();
      }
      bar_arrive(NB_PASS0, 384);
#pragma unroll 1
      for (int ps = 1; ps < 4; ps++) {
        wg_wait<0>();
        ring.release(3);
        fence_regs(acc);
#pragma unroll
        for (int i = 0; i < 8; i++) {
          uint32_t o[4];
          pack8(o, acc + 8 * i);
          sts128(wprv + (ps - 1) * SLOT + i * 512, o[0], o[1], o[2], o[3]);
        }
#pragma unroll
        for (int c = 0; c < 4; c++) {
          const uint32_t b = ring.wait_full(c, ps & 1);
          if (c > 0) { wg_wait<0>(); ring.release(c - 1); }
          wg_fence();
          static_for<0, 8>([&](auto K) { wgmma_rs_n128_tb1<LB_MN128 + K * 128, HI128>(acc, h[c * 8 + K], b, (c | K) != 0); });
          wg_commit();
        }
      }
      wg_wait<0>();
      ring.release(3);
      fence_regs(acc);
#pragma unroll
      for (int i = 0; i < 8; i++) pack8(qf[i], acc + 8 * i);
    }
    fence_regs(qf);
    TS(3);

    float S[64];
    {
      float O[64];
      uint32_t P[8][4];
      const float cs = 0.08838834764831845f * 1.4426950408889634f;
      const int TAU = 0x41800000;
      float m0, m1, l0, l1;

      auto float_block_max = [&]() {
        float b0 = fmaxf(S[0], S[1]), b1 = fmaxf(S[2], S[3]);
#pragma unroll
        for (int i = 1; i < 16; i++) {
          b0 = fmaxf(b0, fmaxf(S[4 * i], S[4 * i + 1]));
          b1 = fmaxf(b1, fmaxf(S[4 * i + 2], S[4 * i + 3]));
        }
        b0 = fmaxf(b0, __shfl_xor_sync(0xffffffffu, b0, 1)); b1 = fmaxf(b1, __shfl_xor_sync(0xffffffffu, b1, 1));
        b0 = fmaxf(b0, __shfl_xor_sync(0xffffffffu, b0, 2)); b1 = fmaxf(b1, __shfl_xor_sync(0xffffffffu, b1, 2));
        m0 = b0 * cs; m1 = b1 * cs;
      };
      auto first_block_max = [&]() {
        int a0 = max(__float_as_int(S[0]), __float_as_int(S[1]));
        int a1 = max(__float_as_int(S[2]), __float_as_int(S[3]));
#pragma unroll
        for (int i = 1; i < 16; i++) {
          a0 = __vimax3_s32(a0, __float_as_int(S[4 * i]), __float_as_int(S[4 * i + 1]));
          a1 = __vimax3_s32(a1, __float_as_int(S[4 * i + 2]), __float_as_int(S[4 * i + 3]));
        }
        a0 = max(a0, __shfl_xor_sync(0xffffffffu, a0, 1)); a1 = max(a1, __shfl_xor_sync(0xffffffffu, a1, 1));
        a0 = max(a0, __shfl_xor_sync(0xffffffffu, a0, 2)); a1 = max(a1, __shfl_xor_sync(0xffffffffu, a1, 2));
        m0 = __int_as_float(a0) * cs; m1 = __int_as_float(a1) * cs;
        if (__any_sync(0xffffffffu, (a0 | a1) < 0)) float_block_max();
      };
      auto scale_sub = [&]() {
#pragma unroll
        for (int i = 0; i < 16; i++) {
          S[4 * i] = fmaf(S[4 * i], cs, -m0); S[4 * i + 1] = fmaf(S[4 * i + 1], cs, -m0);
          S[4 * i + 2] = fmaf(S[4 * i + 2], cs, -m1); S[4 * i + 3] = fmaf(S[4 * i + 3], cs, -m1);
        }
      };
      auto exps = [&](int i0, int i1) {
#pragma unroll
        for (int i = i0; i < i1; i++) {
          S[4 * i] = ex2(S[4 * i]); S[4 * i + 1] = ex2(S[4 * i + 1]);
          S[4 * i + 2] = ex2(S[4 * i + 2]); S[4 * i + 3] = ex2(S[4 * i + 3]);
          l0 += S[4 * i]; l1 += S[4 * i + 2]; l0 += S[4 * i + 1]; l1 += S[4 * i + 3];
        }
      };
      {
        const uint32_t b = ring.wait_full(0, 0);
        wg_fence();
        static_for<0, 8>([&](auto K) { wgmma_rs_n128_tb0<LB_K128 + (K >> 2) * 1024 + (K & 3) * 2, HI128>(S, qf[K], b, K != 0); });
        wg_commit();
        wg_wait<0>();
        fence_regs(S);
        ring.release(0);
        float_block_max();
        scale_sub();
        l0 = 0.f; l1 = 0.f;
        exps(0, 16);
#pragma unroll
        for (int i = 0; i < 8; i++) pack8(P[i], S + 8 * i);
      }
      fence_regs(P);
      if (wg == 1) bar_arrive(2, 256);
#pragma unroll 1
      for (int n = 1; n < 16; n++) {
        const uint32_t tk = 2 * n - 1, tv = 2 * n;
        const bool newhead = (n & 3) == 0;
        const uint32_t bk = ring.wait_full(tk & 3, (tk >> 2) & 1);
        const uint32_t bv = ring.wait_full(tv & 3, (tv >> 2) & 1);
        bar_sync(2 + wg, 256);
        wg_fence();
        static_for<0, 8>([&](auto K) { wgmma_rs_n128_tb0<LB_K128 + (K >> 2) * 1024 + (K & 3) * 2, HI128>(S, qf[K], bk, K != 0); });
        wg_commit();
        static_for<0, 8>([&](auto K) { wgmma_rs_n128_tb1<LB_MN128 + K * 128, HI128>(O, P[K], bv, K != 0 || (n & 3) != 1); });
        wg_commit();
        bar_arrive(2 + (wg ^ 1), 256);
        wg_wait<1>();
        fence_regs(S);
        ring.release(tk & 3);
        if ((n & 3) == 3 && n != 15) {
          fence_regs(qf);
#pragma unroll
          for (int i = 0; i < 8; i++) lds128(wprv + (n >> 2) * SLOT + i * 512, qf[i]);
        }
        float f0 = 1.f, f1 = 1.f;
        bool resc = newhead;
        if (newhead) {
          l0 += __shfl_xor_sync(0xffffffffu, l0, 1); l1 += __shfl_xor_sync(0xffffffffu, l1, 1);
          l0 += __shfl_xor_sync(0xffffffffu, l0, 2); l1 += __shfl_xor_sync(0xffffffffu, l1, 2);
          f0 = rcp_hw(l0); f1 = rcp_hw(l1);
          l0 = 0.f; l1 = 0.f;
          first_block_max();
          scale_sub();
        } else {
          scale_sub();
          int a0 = __vimax3_s32(__float_as_int(S[0]), __float_as_int(S[1]), __float_as_int(S[1]));
          int a1 = __vimax3_s32(__float_as_int(S[2]), __float_as_int(S[3]), __float_as_int(S[3]));
#pragma unroll
          for (int i = 1; i < 16; i++) {
            a0 = __vimax3_s32(a0, __float_as_int(S[4 * i]), __float_as_int(S[4 * i + 1]));
            a1 = __vimax3_s32(a1, __float_as_int(S[4 * i + 2]), __float_as_int(S[4 * i + 3]));
          }
          if (__any_sync(0xffffffffu, max(a0, a1) > TAU)) {
            a0 = max(a0, 0); a1 = max(a1, 0);
            a0 = max(a0, __shfl_xor_sync(0xffffffffu, a0, 1)); a1 = max(a1, __shfl_xor_sync(0xffffffffu, a1, 1));
            a0 = max(a0, __shfl_xor_sync(0xffffffffu, a0, 2)); a1 = max(a1, __shfl_xor_sync(0xffffffffu, a1, 2));
            const float d0 = __int_as_float(a0), d1 = __int_as_float(a1);
#pragma unroll
            for (int i = 0; i < 16; i++) { S[4 * i] -= d0; S[4 * i + 1] -= d0; S[4 * i + 2] -= d1; S[4 * i + 3] -= d1; }
            m0 += d0; m1 += d1;
            f0 = ex2(-d0); f1 = ex2(-d1);
            l0 *= f0; l1 *= f1;
            resc = true;
          }
        }
        exps(0, 4);
        wg_wait<0>();
        fence_regs(O);
        fence_regs(P);
        ring.release(tv & 3);
        if (resc) {
#pragma unroll
          for (int i = 0; i < 16; i++) {
            O[4 * i] *= f0; O[4 * i + 1] *= f0; O[4 * i + 2] *= f1; O[4 * i + 3] *= f1;
          }
          if (newhead) {
#pragma unroll
            for (int i = 0; i < 8; i++) {
              uint32_t o[4];
              pack8(o, O + 8 * i);
              sts128(wprv + ((n >> 2) - 1) * SLOT + i * 512, o[0], o[1], o[2], o[3]);
            }
          }
        }
        exps(4, 16);
#pragma unroll
        for (int i = 0; i < 8; i++) pack8(P[i], S + 8 * i);
        fence_regs(P);
        fence_regs(O);
      }
      {
        const uint32_t bv = ring.wait_full(3, 1);
        if (wg == 0) bar_sync(2, 256);
        wg_fence();
        static_for<0, 8>([&](auto K) { wgmma_rs_n128_tb1<LB_MN128 + K * 128, HI128>(O, P[K], bv, 1); });
        wg_commit();
        l0 += __shfl_xor_sync(0xffffffffu, l0, 1); l1 += __shfl_xor_sync(0xffffffffu, l1, 1);
        l0 += __shfl_xor_sync(0xffffffffu, l0, 2); l1 += __shfl_xor_sync(0xffffffffu, l1, 2);
        const float f0 = rcp_hw(l0), f1 = rcp_hw(l1);
        wg_wait<0>();
        fence_regs(O);
        ring.release(3);
#pragma unroll
        for (int i = 0; i < 8; i++) {
          qf[i][0] = pack_bf16(O[8 * i] * f0, O[8 * i + 1] * f0); qf[i][1] = pack_bf16(O[8 * i + 2] * f1, O[8 * i + 3] * f1);
          qf[i][2] = pack_bf16(O[8 * i + 4] * f0, O[8 * i + 5] * f0); qf[i][3] = pack_bf16(O[8 * i + 6] * f1, O[8 * i + 7] * f1);
        }
      }
    }
    fence_regs(qf);
    TS(4);
    asm volatile("setmaxnreg.dec.sync.aligned.u32 200;");
    bar_arrive(NB_PARK, 384);

    uint4* const Pout = p.s->P + ((size_t)(rt * 8 + warp) * 4 + (j >> 1)) * 1024 + (j & 1) * 128 + lane;
    const uint32_t tag = *(volatile uint32_t*)(smem_raw + SM_BAR + BAR_TAG);
    const uint32_t rbar = sb + SM_DBAR + warp * 16;
    uint32_t peer_land, peer_bar;
    asm("mapa.shared::cluster.u32 %0, %1, %2;" : "=r"(peer_land) : "r"(wprv), "r"(~j & 1));
    asm("mapa.shared::cluster.u32 %0, %1, %2;" : "=r"(peer_bar) : "r"(rbar), "r"(~j & 1));
    float acc2[32];
    uint32_t pk[4][4];
    auto arm_and_ack = [&]() {
      asm volatile(
          "{\n.reg .pred p;\nelect.sync _|p, 0xffffffff;\n"
          "@p mbarrier.arrive.expect_tx.shared::cta.b64 _, [%0], 2048;\n"
          "@p mbarrier.arrive.shared::cluster.b64 _, [%1];\n}\n" ::"r"(rbar), "r"(peer_bar + 8) : "memory");
    };
    auto chunk_prepare = [&](int cp) {
      mbar_wait(rbar + ((cp & 1) ? 0 : 8), (cp >> 1) & 1);
      if (cp & 1) {
#pragma unroll
        for (int i = 0; i < 4; i++) lds128(wprv + i * 512, pk[i]);
      }
    };
    auto chunk_finish = [&](int cp) {
      fence_regs(acc2);
      if (cp & 1) {
#pragma unroll
        for (int i = 0; i < 4; i++) {
#pragma unroll
          for (int e = 0; e < 4; e++) {
            acc2[8 * i + 2 * e] += __uint_as_float(pk[i][e] * 65536u + 0x8000u);
            acc2[8 * i + 2 * e + 1] += __uint_as_float(pk[i][e]);
          }
        }
      }
#pragma unroll
      for (int i = 0; i < 4; i++) {
#pragma unroll
        for (int e = 0; e < 4; e++) pk[i][e] = pack_trunc(acc2[8 * i + 2 * e], acc2[8 * i + 2 * e + 1]);
      }
      if (!(cp & 1)) {
#pragma unroll
        for (int i = 0; i < 4; i++)
          asm volatile("st.async.weak.shared::cluster.mbarrier::complete_tx::bytes.v4.b32 [%0], {%1,%2,%3,%4}, [%5];"
                       ::"r"(peer_land + i * 512), "r"(pk[i][0]), "r"(pk[i][1]), "r"(pk[i][2]), "r"(pk[i][3]), "r"(peer_bar) : "memory");
      }
      fence_regs(pk);
    };
    auto store_partial = [&](int pair) {
      if (pair < 7) arm_and_ack();
      const uint32_t t1 = pair < 4;
#pragma unroll
      for (int i = 0; i < 4; i++) st_pkt(Pout + (pair & 3) * 256 + i * 32, (pk[i][0] & ~1u) | t1, pk[i][1], pk[i][2], pk[i][3]);
      if (lane == 0)
        asm volatile("st.relaxed.gpu.global.u32 [%0], %1;" ::"l"(&p.s->sent[(rt * 8 + warp) * 8 + j]), "r"(tag * 32 + pair + 1) : "memory");
    };
    const uint4* const Gin = Gw + lane;
    auto g_issue = [&](int u) { warp_bulk_load(wblk + 2 * SLOT + (u & 1) * 2048, Gw + u * 128, 2048, wbar + (u & 1) * 8); };

    uint32_t tl = 0, b = ring.wait_full(0, 0);
    auto next_tile = [&]() {
      const uint32_t cur = tl & 3;
      tl++;
      b = ring.wait_full(tl & 3, (tl >> 2) & 1);
      wg_wait<0>();
      ring.release(cur);
    };
    {
      uint32_t o[24][4];
#pragma unroll
      for (int i = 0; i < 24; i++) lds128(wprv + (i >> 3) * SLOT + (i & 7) * 512, o[i]);
#pragma unroll 1
      for (int cc = 0; cc < 8; cc++) {
        wg_fence();
        static_for<0, 16>([&](auto K) { wgmma_rs_n64_tb1<K * 128, HI128>(acc2, o[K], b, K != 0); });
        wg_commit();
        if (cc == 0) arm_and_ack();
        else if (!(cc & 1)) store_partial((cc >> 1) - 1);
        next_tile();
        wg_fence();
        static_for<0, 16>([&](auto K) { wgmma_rs_n64_tb1<K * 128, HI128>(acc2, K < 8 ? o[16 + (K & 7)] : qf[K & 7], b, 1); });
        wg_commit();
        if (cc == 0) warp_arrive(sb + SM_SBAR);
        if (cc == 6) { g_issue(0); g_issue(1); }
        chunk_prepare(cc);
        next_tile();
        chunk_finish(cc);
      }
    }
    TS(5);

    uint32_t H[14][4];
    {
      float acca[96], accb[16];
      const uint4* const statp = &p.s->stat[(rt * 8 + warp) * 8];
#pragma unroll 1
      for (int u = 0; u < 8; u++) {
        uint32_t fa[4][4];
        mbar_wait(wbar + (u & 1) * 8, ((u >> 1) + (u & 1)) & 1);
#pragma unroll
        for (int i = 0; i < 4; i++) lds128(wprv + 2 * SLOT + (u & 1) * 2048 + i * 512, fa[i]);
        verify4_tag0<512>(Gin + u * 128, fa);
        wg_fence();
        const uint32_t ba = b + (j & 1) * 512, bb = b + ((j & 1) ? 4 : 1536);
        static_for<0, 4>([&](auto K) { wgmma_rs_n32_tb1<LB_W1 + K * 128, HI128>(accb, fa[K], bb, (u | K) != 0); });
        static_for<0, 4>([&](auto K) { wgmma_rs_n192_tb1<LB_W1 + K * 128, HI128>(acca, fa[K], ba, (u | K) != 0); });
        wg_commit();
        if (u == 0) store_partial(3);
        if (u < 4) g_issue(u + 2);
        if (u == 7) warp_bulk_load(wblk + 2 * SLOT, statp, 128, wbar + 16);
        next_tile();
        if (u == 4 || u == 5) g_issue(u + 2);
      }
      fence_regs(acca);
      fence_regs(accb);
      TS(9);
      mbar_wait(bars + BAR_UV, 0);
      uint32_t xr[4];
      mbar_wait(wbar + 16, 1);
      lds128(wblk + 2 * SLOT + gq * 16, xr);
      {
        int spins = 0;
        while (((xr[0] ^ tag) & 1u) && ++spins < SPIN_LIMIT) ld_pkt(statp + gq, xr);
      }
      const float ra0 = __uint_as_float(xr[0]), rb0 = __uint_as_float(xr[1]), ra1 = __uint_as_float(xr[2]),
                  rb1 = __uint_as_float(xr[3]);
#pragma unroll
      for (int i = 0; i < 28; i++) {
        uint32_t m[4];
        lds128(sb + SM_TAB + (i * 4 + q) * 16, m);
        const float u0 = __uint_as_float(m[0]), u1 = __uint_as_float(m[1]), w0 = __uint_as_float(m[2]), w1 = __uint_as_float(m[3]);
        const float* acc = i < 24 ? acca + 4 * i : accb + 4 * (i - 24);
        const float z0 = fmaf(acc[0], ra0, fmaf(u0, rb0, w0)), z1 = fmaf(acc[1], ra0, fmaf(u1, rb0, w1));
        const float z2 = fmaf(acc[2], ra1, fmaf(u0, rb1, w0)), z3 = fmaf(acc[3], ra1, fmaf(u1, rb1, w1));
        H[i >> 1][(i & 1) * 2] = pack_bf16(fmaf(z0, tanh_hw(z0), z0), fmaf(z1, tanh_hw(z1), z1));
        H[i >> 1][(i & 1) * 2 + 1] = pack_bf16(fmaf(z2, tanh_hw(z2), z2), fmaf(z3, tanh_hw(z3), z3));
      }
    }
    fence_regs(H);
    TS(10);
    const int go = 24 + warp;
#pragma unroll 1
    for (int cc = 0; cc < 8; cc++) {
      wg_fence();
      const uint32_t ba = b + (j & 1) * 256, bb = b - (j & 1) * 1536;
      static_for<0, 14>([&](auto K) { wgmma_rs_n64_tb1<K * 128, HI128>(acc2, H[K], K < 12 ? ba : bb, K != 0); });
      wg_commit();
      if (cc > 0 && !(cc & 1)) store_partial(3 + (cc >> 1));
      chunk_prepare(8 + cc);
      if (cc < 7) next_tile();
      wg_wait<0>();
      chunk_finish(8 + cc);
    }
    store_partial(7);
    TS(11);
    {
      const uint4* const Pown = p.s->P + (size_t)(rt * 8 + j) * 4096 + go * 32 + lane;
      uint32_t r[4][4];
      float y[8];
      mbar_wait(bars + BAR_X2, 0);
      issue_pkts<0, 4>(Pown, 1024, r);
      verify4_rt<16384>(Pown, r, 0);
      TS(13);
#pragma unroll
      for (int s = 0; s < 4; s++) add_partial(y, r[s], 0x10000u, s == 0);
      const uint32_t gt = sb + SM_TAB + 1792 + ((go - 24) * 4 + q) * 8;
      store_out(p.out, (uint32_t)(rt * 128 + 16 * j + gq) * 256 + go * 8 + q, sb + SM_PARK + SLOT + (go >> 2) * 4096 + (go & 3) * 512 + lane * 16,
                lds32(gt), lds32(gt + 4), y);
    }
    TS(12);
    if (bid == 0 && tid == 0) asm volatile("st.relaxed.gpu.global.u32 [%0], %1;" ::"l"(&p.s->epoch), "r"(tag) : "memory");
  }
}

typedef CUresult (*EncodeFn)(CUtensorMap*, CUtensorMapDataType, cuuint32_t, void*, const cuuint64_t*, const cuuint64_t*,
                             const cuuint32_t*, const cuuint32_t*, CUtensorMapInterleave, CUtensorMapSwizzle,
                             CUtensorMapL2promotion, CUtensorMapFloatOOBfill);

static void make_map(EncodeFn fn, CUtensorMap* tm, const void* ptr, int inner, int rows, int cols, int box_rows, int box_outer,
                     CUtensorMapSwizzle swz) {
  cuuint64_t gd[3] = {(cuuint64_t)inner, (cuuint64_t)rows, (cuuint64_t)(cols / inner)};
  cuuint64_t gs[2] = {(cuuint64_t)cols * 2, (cuuint64_t)inner * 2};
  cuuint32_t bx[3] = {(cuuint32_t)inner, (cuuint32_t)box_rows, (cuuint32_t)box_outer};
  cuuint32_t es[3] = {1, 1, 1};
  fn(tm, CU_TENSOR_MAP_DATA_TYPE_BFLOAT16, 3, const_cast<void*>(ptr), gd, gs, bx, es, CU_TENSOR_MAP_INTERLEAVE_NONE, swz,
     CU_TENSOR_MAP_L2_PROMOTION_L2_128B, CU_TENSOR_MAP_FLOAT_OOB_FILL_NONE);
}

extern "C" void kernel_launch(void* const* d_in, const int* in_sizes, int n_in, void* d_out, int out_size) {
  (void)in_sizes; (void)n_in; (void)out_size;
  void* fnp = nullptr;
  cudaDriverEntryPointQueryResult qr;
  cudaGetDriverEntryPoint("cuTensorMapEncodeTiled", &fnp, cudaEnableDefault, &qr);
  EncodeFn fn = (EncodeFn)fnp;
  CUtensorMap tmWq, tmK, tmV, tmWo, tmW1, tmW2, tmWm, tmX;
  make_map(fn, &tmWq, d_in[3], 64, 512, 4096, 128, 2, CU_TENSOR_MAP_SWIZZLE_128B);
  make_map(fn, &tmK, d_in[1], 64, 8 * SK, 128, 128, 2, CU_TENSOR_MAP_SWIZZLE_128B);
  make_map(fn, &tmV, d_in[2], 64, 8 * SK, 128, 128, 2, CU_TENSOR_MAP_SWIZZLE_128B);
  make_map(fn, &tmWo, d_in[4], 64, 4096, 512, 256, 1, CU_TENSOR_MAP_SWIZZLE_128B);
  make_map(fn, &tmW1, d_in[6], 64, 512, FF, 64, 4, CU_TENSOR_MAP_SWIZZLE_128B);
  make_map(fn, &tmW2, d_in[7], 64, FF, 512, 224, 1, CU_TENSOR_MAP_SWIZZLE_128B);
  make_map(fn, &tmWm, d_in[9], 8, 512, 3072, 256, 1, CU_TENSOR_MAP_SWIZZLE_NONE);
  make_map(fn, &tmX, d_in[0], 16, 2048, 512, 16, 4, CU_TENSOR_MAP_SWIZZLE_NONE);
  Params p;
  p.x = (const __nv_bfloat16*)d_in[0];
  p.c = (const __nv_bfloat16*)d_in[8];
  p.wmod = (const __nv_bfloat16*)d_in[9];
  p.wo = (const __nv_bfloat16*)d_in[4];
  p.w1 = (const __nv_bfloat16*)d_in[6];
  p.w2 = (const __nv_bfloat16*)d_in[7];
  p.out = (__nv_bfloat16*)d_out;
  cudaGetSymbolAddress((void**)&p.s, g_scratch);
  cudaFuncSetAttribute(adaln_block_kernel, cudaFuncAttributeMaxDynamicSharedMemorySize, SM_TOTAL);
  cudaLaunchConfig_t cfg = {};
  cfg.gridDim = 128; cfg.blockDim = 512; cfg.dynamicSmemBytes = SM_TOTAL; cfg.stream = cudaStreamPerThread;
  cudaLaunchAttribute at[1];
  at[0].id = cudaLaunchAttributeClusterDimension; at[0].val.clusterDim.x = 2; at[0].val.clusterDim.y = 1; at[0].val.clusterDim.z = 1;
  cfg.attrs = at; cfg.numAttrs = 1;
  cudaLaunchKernelEx(&cfg, adaln_block_kernel, tmWq, tmK, tmV, tmWo, tmW1, tmW2, tmWm, tmX, p);
}
```

```cpp
#include <cuda_runtime.h>
#include <cuda_bf16.h>
#include <cuda.h>
#include <stdint.h>

template <int OFF, uint32_t HI>
__device__ __forceinline__ void wgmma_rs_n128_tb0(float (&d)[64], const uint32_t (&a)[4], uint32_t lo, int sd) {
  asm volatile("{\n.reg .pred p;\n.reg .b32 l;\n.reg .b64 db;\nsetp.ne.b32 p, %69, 0;\n"
    "add.u32 l, %68, %70;\nmov.b64 db, {l, %71};\n"
    "wgmma.mma_async.sync.aligned.m64n128k16.f32.bf16.bf16 "
    "{%0,%1,%2,%3,%4,%5,%6,%7,%8,%9,%10,%11,%12,%13,%14,%15,"
    "%16,%17,%18,%19,%20,%21,%22,%23,%24,%25,%26,%27,%28,%29,%30,%31,"
    "%32,%33,%34,%35,%36,%37,%38,%39,%40,%41,%42,%43,%44,%45,%46,%47,"
    "%48,%49,%50,%51,%52,%53,%54,%55,%56,%57,%58,%59,%60,%61,%62,%63}, "
    "{%64,%65,%66,%67}, db, p, 1, 1, 0;\n}\n"
    : "+f"(d[0]), "+f"(d[1]), "+f"(d[2]), "+f"(d[3]), "+f"(d[4]), "+f"(d[5]), "+f"(d[6]), "+f"(d[7]),
      "+f"(d[8]), "+f"(d[9]), "+f"(d[10]), "+f"(d[11]), "+f"(d[12]), "+f"(d[13]), "+f"(d[14]), "+f"(d[15]),
      "+f"(d[16]), "+f"(d[17]), "+f"(d[18]), "+f"(d[19]), "+f"(d[20]), "+f"(d[21]), "+f"(d[22]), "+f"(d[23]),
      "+f"(d[24]), "+f"(d[25]), "+f"(d[26]), "+f"(d[27]), "+f"(d[28]), "+f"(d[29]), "+f"(d[30]), "+f"(d[31]),
      "+f"(d[32]), "+f"(d[33]), "+f"(d[34]), "+f"(d[35]), "+f"(d[36]), "+f"(d[37]), "+f"(d[38]), "+f"(d[39]),
      "+f"(d[40]), "+f"(d[41]), "+f"(d[42]), "+f"(d[43]), "+f"(d[44]), "+f"(d[45]), "+f"(d[46]), "+f"(d[47]),
      "+f"(d[48]), "+f"(d[49]), "+f"(d[50]), "+f"(d[51]), "+f"(d[52]), "+f"(d[53]), "+f"(d[54]), "+f"(d[55]),
      "+f"(d[56]), "+f"(d[57]), "+f"(d[58]), "+f"(d[59]), "+f"(d[60]), "+f"(d[61]), "+f"(d[62]), "+f"(d[63])
    : "r"(a[0]), "r"(a[1]), "r"(a[2]), "r"(a[3]), "r"(lo), "r"(sd), "n"(OFF), "n"(HI));
}

template <int OFF, uint32_t HI>
__device__ __forceinline__ void wgmma_rs_n128_tb1(float (&d)[64], const uint32_t (&a)[4], uint32_t lo, int sd) {
  asm volatile("{\n.reg .pred p;\n.reg .b32 l;\n.reg .b64 db;\nsetp.ne.b32 p, %69, 0;\n"
    "add.u32 l, %68, %70;\nmov.b64 db, {l, %71};\n"
    "wgmma.mma_async.sync.aligned.m64n128k16.f32.bf16.bf16 "
    "{%0,%1,%2,%3,%4,%5,%6,%7,%8,%9,%10,%11,%12,%13,%14,%15,"
    "%16,%17,%18,%19,%20,%21,%22,%23,%24,%25,%26,%27,%28,%29,%30,%31,"
    "%32,%33,%34,%35,%36,%37,%38,%39,%40,%41,%42,%43,%44,%45,%46,%47,"
    "%48,%49,%50,%51,%52,%53,%54,%55,%56,%57,%58,%59,%60,%61,%62,%63}, "
    "{%64,%65,%66,%67}, db, p, 1, 1, 1;\n}\n"
    : "+f"(d[0]), "+f"(d[1]), "+f"(d[2]), "+f"(d[3]), "+f"(d[4]), "+f"(d[5]), "+f"(d[6]), "+f"(d[7]),
      "+f"(d[8]), "+f"(d[9]), "+f"(d[10]), "+f"(d[11]), "+f"(d[12]), "+f"(d[13]), "+f"(d[14]), "+f"(d[15]),
      "+f"(d[16]), "+f"(d[17]), "+f"(d[18]), "+f"(d[19]), "+f"(d[20]), "+f"(d[21]), "+f"(d[22]), "+f"(d[23]),
      "+f"(d[24]), "+f"(d[25]), "+f"(d[26]), "+f"(d[27]), "+f"(d[28]), "+f"(d[29]), "+f"(d[30]), "+f"(d[31]),
      "+f"(d[32]), "+f"(d[33]), "+f"(d[34]), "+f"(d[35]), "+f"(d[36]), "+f"(d[37]), "+f"(d[38]), "+f"(d[39]),
      "+f"(d[40]), "+f"(d[41]), "+f"(d[42]), "+f"(d[43]), "+f"(d[44]), "+f"(d[45]), "+f"(d[46]), "+f"(d[47]),
      "+f"(d[48]), "+f"(d[49]), "+f"(d[50]), "+f"(d[51]), "+f"(d[52]), "+f"(d[53]), "+f"(d[54]), "+f"(d[55]),
      "+f"(d[56]), "+f"(d[57]), "+f"(d[58]), "+f"(d[59]), "+f"(d[60]), "+f"(d[61]), "+f"(d[62]), "+f"(d[63])
    : "r"(a[0]), "r"(a[1]), "r"(a[2]), "r"(a[3]), "r"(lo), "r"(sd), "n"(OFF), "n"(HI));
}

template <int OFF, uint32_t HI>
__device__ __forceinline__ void wgmma_rs_n192_tb1(float (&d)[96], const uint32_t (&a)[4], uint32_t lo, int sd) {
  asm volatile("{\n.reg .pred p;\n.reg .b32 l;\n.reg .b64 db;\nsetp.ne.b32 p, %101, 0;\n"
    "add.u32 l, %100, %102;\nmov.b64 db, {l, %103};\n"
    "wgmma.mma_async.sync.aligned.m64n192k16.f32.bf16.bf16 "
    "{%0,%1,%2,%3,%4,%5,%6,%7,%8,%9,%10,%11,%12,%13,%14,%15,"
    "%16,%17,%18,%19,%20,%21,%22,%23,%24,%25,%26,%27,%28,%29,%30,%31,"
    "%32,%33,%34,%35,%36,%37,%38,%39,%40,%41,%42,%43,%44,%45,%46,%47,"
    "%48,%49,%50,%51,%52,%53,%54,%55,%56,%57,%58,%59,%60,%61,%62,%63,"
    "%64,%65,%66,%67,%68,%69,%70,%71,%72,%73,%74,%75,%76,%77,%78,%79,"
    "%80,%81,%82,%83,%84,%85,%86,%87,%88,%89,%90,%91,%92,%93,%94,%95}, "
    "{%96,%97,%98,%99}, db, p, 1, 1, 1;\n}\n"
    : "+f"(d[0]), "+f"(d[1]), "+f"(d[2]), "+f"(d[3]), "+f"(d[4]), "+f"(d[5]), "+f"(d[6]), "+f"(d[7]),
      "+f"(d[8]), "+f"(d[9]), "+f"(d[10]), "+f"(d[11]), "+f"(d[12]), "+f"(d[13]), "+f"(d[14]), "+f"(d[15]),
      "+f"(d[16]), "+f"(d[17]), "+f"(d[18]), "+f"(d[19]), "+f"(d[20]), "+f"(d[21]), "+f"(d[22]), "+f"(d[23]),
      "+f"(d[24]), "+f"(d[25]), "+f"(d[26]), "+f"(d[27]), "+f"(d[28]), "+f"(d[29]), "+f"(d[30]), "+f"(d[31]),
      "+f"(d[32]), "+f"(d[33]), "+f"(d[34]), "+f"(d[35]), "+f"(d[36]), "+f"(d[37]), "+f"(d[38]), "+f"(d[39]),
      "+f"(d[40]), "+f"(d[41]), "+f"(d[42]), "+f"(d[43]), "+f"(d[44]), "+f"(d[45]), "+f"(d[46]), "+f"(d[47]),
      "+f"(d[48]), "+f"(d[49]), "+f"(d[50]), "+f"(d[51]), "+f"(d[52]), "+f"(d[53]), "+f"(d[54]), "+f"(d[55]),
      "+f"(d[56]), "+f"(d[57]), "+f"(d[58]), "+f"(d[59]), "+f"(d[60]), "+f"(d[61]), "+f"(d[62]), "+f"(d[63]),
      "+f"(d[64]), "+f"(d[65]), "+f"(d[66]), "+f"(d[67]), "+f"(d[68]), "+f"(d[69]), "+f"(d[70]), "+f"(d[71]),
      "+f"(d[72]), "+f"(d[73]), "+f"(d[74]), "+f"(d[75]), "+f"(d[76]), "+f"(d[77]), "+f"(d[78]), "+f"(d[79]),
      "+f"(d[80]), "+f"(d[81]), "+f"(d[82]), "+f"(d[83]), "+f"(d[84]), "+f"(d[85]), "+f"(d[86]), "+f"(d[87]),
      "+f"(d[88]), "+f"(d[89]), "+f"(d[90]), "+f"(d[91]), "+f"(d[92]), "+f"(d[93]), "+f"(d[94]), "+f"(d[95])
    : "r"(a[0]), "r"(a[1]), "r"(a[2]), "r"(a[3]), "r"(lo), "r"(sd), "n"(OFF), "n"(HI));
}

template <int OFF, uint32_t HI>
__device__ __forceinline__ void wgmma_rs_n32_tb1(float (&d)[16], const uint32_t (&a)[4], uint32_t lo, int sd) {
  asm volatile("{\n.reg .pred p;\n.reg .b32 l;\n.reg .b64 db;\nsetp.ne.b32 p, %21, 0;\n"
    "add.u32 l, %20, %22;\nmov.b64 db, {l, %23};\n"
    "wgmma.mma_async.sync.aligned.m64n32k16.f32.bf16.bf16 "
    "{%0,%1,%2,%3,%4,%5,%6,%7,%8,%9,%10,%11,%12,%13,%14,%15}, "
    "{%16,%17,%18,%19}, db, p, 1, 1, 1;\n}\n"
    : "+f"(d[0]), "+f"(d[1]), "+f"(d[2]), "+f"(d[3]), "+f"(d[4]), "+f"(d[5]), "+f"(d[6]), "+f"(d[7]),
      "+f"(d[8]), "+f"(d[9]), "+f"(d[10]), "+f"(d[11]), "+f"(d[12]), "+f"(d[13]), "+f"(d[14]), "+f"(d[15])
    : "r"(a[0]), "r"(a[1]), "r"(a[2]), "r"(a[3]), "r"(lo), "r"(sd), "n"(OFF), "n"(HI));
}

template <int OFF, uint32_t HI>
__device__ __forceinline__ void wgmma_rs_n64_tb1(float (&d)[32], const uint32_t (&a)[4], uint32_t lo, int sd) {
  asm volatile("{\n.reg .pred p;\n.reg .b32 l;\n.reg .b64 db;\nsetp.ne.b32 p, %37, 0;\n"
    "add.u32 l, %36, %38;\nmov.b64 db, {l, %39};\n"
    "wgmma.mma_async.sync.aligned.m64n64k16.f32.bf16.bf16 "
    "{%0,%1,%2,%3,%4,%5,%6,%7,%8,%9,%10,%11,%12,%13,%14,%15,"
    "%16,%17,%18,%19,%20,%21,%22,%23,%24,%25,%26,%27,%28,%29,%30,%31}, "
    "{%32,%33,%34,%35}, db, p, 1, 1, 1;\n}\n"
    : "+f"(d[0]), "+f"(d[1]), "+f"(d[2]), "+f"(d[3]), "+f"(d[4]), "+f"(d[5]), "+f"(d[6]), "+f"(d[7]),
      "+f"(d[8]), "+f"(d[9]), "+f"(d[10]), "+f"(d[11]), "+f"(d[12]), "+f"(d[13]), "+f"(d[14]), "+f"(d[15]),
      "+f"(d[16]), "+f"(d[17]), "+f"(d[18]), "+f"(d[19]), "+f"(d[20]), "+f"(d[21]), "+f"(d[22]), "+f"(d[23]),
      "+f"(d[24]), "+f"(d[25]), "+f"(d[26]), "+f"(d[27]), "+f"(d[28]), "+f"(d[29]), "+f"(d[30]), "+f"(d[31])
    : "r"(a[0]), "r"(a[1]), "r"(a[2]), "r"(a[3]), "r"(lo), "r"(sd), "n"(OFF), "n"(HI));
}

template <int STR>
__device__ __forceinline__ void verify8_tag1(const uint4* p, uint32_t (*r)[4]) {
  asm volatile("{\n.reg .pred p, q;\n.reg .b32 a, n;\nmov.u32 n, 0;\n"
    "LAB_CHK:\n"
    "and.b32 a, %0, %4;\n"
    "and.b32 a, a, %8;\n"
    "and.b32 a, a, %12;\n"
    "and.b32 a, a, %16;\n"
    "and.b32 a, a, %20;\n"
    "and.b32 a, a, %24;\n"
    "and.b32 a, a, %28;\n"
    "and.b32 a, a, 1;\nsetp.eq.u32 p, a, 1;\nvote.sync.all.pred p, p, 0xffffffff;\n"
    "@p bra.uni LAB_OK;\n"
    "and.b32 a, %0, 1;\nsetp.ne.u32 q, a, 1;\n"
    "@q ld.relaxed.gpu.global.v4.b32 {%0,%1,%2,%3}, [%32+%33];\n"
    "and.b32 a, %4, 1;\nsetp.ne.u32 q, a, 1;\n"
    "@q ld.relaxed.gpu.global.v4.b32 {%4,%5,%6,%7}, [%32+%34];\n"
    "and.b32 a, %8, 1;\nsetp.ne.u32 q, a, 1;\n"
    "@q ld.relaxed.gpu.global.v4.b32 {%8,%9,%10,%11}, [%32+%35];\n"
    "and.b32 a, %12, 1;\nsetp.ne.u32 q, a, 1;\n"
    "@q ld.relaxed.gpu.global.v4.b32 {%12,%13,%14,%15}, [%32+%36];\n"
    "and.b32 a, %16, 1;\nsetp.ne.u32 q, a, 1;\n"
    "@q ld.relaxed.gpu.global.v4.b32 {%16,%17,%18,%19}, [%32+%37];\n"
    "and.b32 a, %20, 1;\nsetp.ne.u32 q, a, 1;\n"
    "@q ld.relaxed.gpu.global.v4.b32 {%20,%21,%22,%23}, [%32+%38];\n"
    "and.b32 a, %24, 1;\nsetp.ne.u32 q, a, 1;\n"
    "@q ld.relaxed.gpu.global.v4.b32 {%24,%25,%26,%27}, [%32+%39];\n"
    "and.b32 a, %28, 1;\nsetp.ne.u32 q, a, 1;\n"
    "@q ld.relaxed.gpu.global.v4.b32 {%28,%29,%30,%31}, [%32+%40];\n"
    "add.u32 n, n, 1;\nsetp.lt.u32 q, n, 262144;\n@q bra.uni LAB_CHK;\n"
    "LAB_OK:\n"
    "}\n"
    : "+r"(r[0][0]), "+r"(r[0][1]), "+r"(r[0][2]), "+r"(r[0][3]), "+r"(r[1][0]), "+r"(r[1][1]), "+r"(r[1][2]), "+r"(r[1][3]),
      "+r"(r[2][0]), "+r"(r[2][1]), "+r"(r[2][2]), "+r"(r[2][3]), "+r"(r[3][0]), "+r"(r[3][1]), "+r"(r[3][2]), "+r"(r[3][3]),
      "+r"(r[4][0]), "+r"(r[4][1]), "+r"(r[4][2]), "+r"(r[4][3]), "+r"(r[5][0]), "+r"(r[5][1]), "+r"(r[5][2]), "+r"(r[5][3]),
      "+r"(r[6][0]), "+r"(r[6][1]), "+r"(r[6][2]), "+r"(r[6][3]), "+r"(r[7][0]), "+r"(r[7][1]), "+r"(r[7][2]), "+r"(r[7][3])
    : "l"(p), "n"(0 * STR), "n"(1 * STR), "n"(2 * STR), "n"(3 * STR), "n"(4 * STR), "n"(5 * STR), "n"(6 * STR), "n"(7 * STR)
    : "memory");
}

template <int STR>
__device__ __forceinline__ void verify4_rt(const uint4* p, uint32_t (*r)[4], uint32_t tag) {
  asm volatile("{\n.reg .pred p, q;\n.reg .b32 a, b, n;\nmov.u32 n, 0;\n"
    "LAB_CHK:\n"
    "lop3.b32 a, %0, %4, %21, 0x7e;\n"
    "lop3.b32 b, %8, %12, %21, 0x7e;\nor.b32 a, a, b;\n"
    "and.b32 a, a, 1;\nsetp.eq.u32 p, a, 0;\nvote.sync.all.pred p, p, 0xffffffff;\n"
    "@p bra.uni LAB_OK;\n"
    "and.b32 a, %0, 1;\nsetp.ne.u32 q, a, %21;\n"
    "@q ld.relaxed.gpu.global.v4.b32 {%0,%1,%2,%3}, [%16+%17];\n"
    "and.b32 a, %4, 1;\nsetp.ne.u32 q, a, %21;\n"
    "@q ld.relaxed.gpu.global.v4.b32 {%4,%5,%6,%7}, [%16+%18];\n"
    "and.b32 a, %8, 1;\nsetp.ne.u32 q, a, %21;\n"
    "@q ld.relaxed.gpu.global.v4.b32 {%8,%9,%10,%11}, [%16+%19];\n"
    "and.b32 a, %12, 1;\nsetp.ne.u32 q, a, %21;\n"
    "@q ld.relaxed.gpu.global.v4.b32 {%12,%13,%14,%15}, [%16+%20];\n"
    "add.u32 n, n, 1;\nsetp.lt.u32 q, n, 262144;\n@q bra.uni LAB_CHK;\n"
    "LAB_OK:\n}\n"
    : "+r"(r[0][0]), "+r"(r[0][1]), "+r"(r[0][2]), "+r"(r[0][3]), "+r"(r[1][0]), "+r"(r[1][1]), "+r"(r[1][2]), "+r"(r[1][3]),
      "+r"(r[2][0]), "+r"(r[2][1]), "+r"(r[2][2]), "+r"(r[2][3]), "+r"(r[3][0]), "+r"(r[3][1]), "+r"(r[3][2]), "+r"(r[3][3])
    : "l"(p), "n"(0 * STR), "n"(1 * STR), "n"(2 * STR), "n"(3 * STR), "r"(tag)
    : "memory");
}

template <int STR>
__device__ __forceinline__ void verify8_tag0(const uint4* p, uint32_t (*r)[4]) {
  asm volatile("{\n.reg .pred p, q;\n.reg .b32 a, n;\nmov.u32 n, 0;\n"
    "LAB_CHK:\n"
    "or.b32 a, %0, %4;\n"
    "or.b32 a, a, %8;\n"
    "or.b32 a, a, %12;\n"
    "or.b32 a, a, %16;\n"
    "or.b32 a, a, %20;\n"
    "or.b32 a, a, %24;\n"
    "or.b32 a, a, %28;\n"
    "and.b32 a, a, 1;\nsetp.eq.u32 p, a, 0;\nvote.sync.all.pred p, p, 0xffffffff;\n"
    "@p bra.uni LAB_OK;\n"
    "and.b32 a, %0, 1;\nsetp.ne.u32 q, a, 0;\n"
    "@q ld.relaxed.gpu.global.v4.b32 {%0,%1,%2,%3}, [%32+%33];\n"
    "and.b32 a, %4, 1;\nsetp.ne.u32 q, a, 0;\n"
    "@q ld.relaxed.gpu.global.v4.b32 {%4,%5,%6,%7}, [%32+%34];\n"
    "and.b32 a, %8, 1;\nsetp.ne.u32 q, a, 0;\n"
    "@q ld.relaxed.gpu.global.v4.b32 {%8,%9,%10,%11}, [%32+%35];\n"
    "and.b32 a, %12, 1;\nsetp.ne.u32 q, a, 0;\n"
    "@q ld.relaxed.gpu.global.v4.b32 {%12,%13,%14,%15}, [%32+%36];\n"
    "and.b32 a, %16, 1;\nsetp.ne.u32 q, a, 0;\n"
    "@q ld.relaxed.gpu.global.v4.b32 {%16,%17,%18,%19}, [%32+%37];\n"
    "and.b32 a, %20, 1;\nsetp.ne.u32 q, a, 0;\n"
    "@q ld.relaxed.gpu.global.v4.b32 {%20,%21,%22,%23}, [%32+%38];\n"
    "and.b32 a, %24, 1;\nsetp.ne.u32 q, a, 0;\n"
    "@q ld.relaxed.gpu.global.v4.b32 {%24,%25,%26,%27}, [%32+%39];\n"
    "and.b32 a, %28, 1;\nsetp.ne.u32 q, a, 0;\n"
    "@q ld.relaxed.gpu.global.v4.b32 {%28,%29,%30,%31}, [%32+%40];\n"
    "add.u32 n, n, 1;\nsetp.lt.u32 q, n, 262144;\n@q bra.uni LAB_CHK;\n"
    "LAB_OK:\n"
    "or.b32 %0, %0, 1;\n"
    "or.b32 %4, %4, 1;\n"
    "or.b32 %8, %8, 1;\n"
    "or.b32 %12, %12, 1;\n"
    "or.b32 %16, %16, 1;\n"
    "or.b32 %20, %20, 1;\n"
    "or.b32 %24, %24, 1;\n"
    "or.b32 %28, %28, 1;\n"
    "}\n"
    : "+r"(r[0][0]), "+r"(r[0][1]), "+r"(r[0][2]), "+r"(r[0][3]), "+r"(r[1][0]), "+r"(r[1][1]), "+r"(r[1][2]), "+r"(r[1][3]),
      "+r"(r[2][0]), "+r"(r[2][1]), "+r"(r[2][2]), "+r"(r[2][3]), "+r"(r[3][0]), "+r"(r[3][1]), "+r"(r[3][2]), "+r"(r[3][3]),
      "+r"(r[4][0]), "+r"(r[4][1]), "+r"(r[4][2]), "+r"(r[4][3]), "+r"(r[5][0]), "+r"(r[5][1]), "+r"(r[5][2]), "+r"(r[5][3]),
      "+r"(r[6][0]), "+r"(r[6][1]), "+r"(r[6][2]), "+r"(r[6][3]), "+r"(r[7][0]), "+r"(r[7][1]), "+r"(r[7][2]), "+r"(r[7][3])
    : "l"(p), "n"(0 * STR), "n"(1 * STR), "n"(2 * STR), "n"(3 * STR), "n"(4 * STR), "n"(5 * STR), "n"(6 * STR), "n"(7 * STR)
    : "memory");
}

#define SPIN_LIMIT (1 << 18)

__device__ __forceinline__ uint32_t smem_u32(const void* p) { return (uint32_t)__cvta_generic_to_shared(p); }
__device__ __forceinline__ void mbar_init(uint32_t a, uint32_t c) {
  asm volatile("mbarrier.init.shared::cta.b64 [%0], %1;" ::"r"(a), "r"(c) : "memory");
}
__device__ __forceinline__ void mbar_expect(uint32_t a, uint32_t b) {
  asm volatile("mbarrier.arrive.expect_tx.shared::cta.b64 _, [%0], %1;" ::"r"(a), "r"(b) : "memory");
}
__device__ __forceinline__ void mbar_arrive(uint32_t a) {
  asm volatile("mbarrier.arrive.shared::cta.b64 _, [%0];" ::"r"(a) : "memory");
}
__device__ __forceinline__ void mbar_wait(uint32_t a, uint32_t parity) {
  asm volatile(
      "{\n.reg .pred p;\n.reg .u32 n;\nmov.u32 n, 0;\n"
      "LAB_WAIT:\n"
      "mbarrier.try_wait.parity.shared::cta.b64 p, [%0], %1;\n"
      "@p bra LAB_DONE;\n"
      "add.u32 n, n, 1;\n"
      "setp.lt.u32 p, n, 262144;\n"
      "@p bra LAB_WAIT;\n"
      "LAB_DONE:\n}\n" ::"r"(a), "r"(parity) : "memory");
}
__device__ __forceinline__ bool mbar_test(uint32_t a, uint32_t parity) {
  uint32_t ok;
  asm volatile("{\n.reg .pred p;\nmbarrier.test_wait.parity.shared::cta.b64 p, [%1], %2;\nselp.u32 %0, 1, 0, p;\n}\n"
               : "=r"(ok) : "r"(a), "r"(parity) : "memory");
  return ok;
}
__device__ __forceinline__ void tma3d(uint32_t dst, const CUtensorMap* tm, uint32_t bar, int c0, int c1, int c2) {
  asm volatile(
      "cp.async.bulk.tensor.3d.shared::cluster.global.mbarrier::complete_tx::bytes [%0], [%1, {%3,%4,%5}], [%2];"
      ::"r"(dst), "l"(tm), "r"(bar), "r"(c0), "r"(c1), "r"(c2) : "memory");
}
__device__ __forceinline__ void wg_fence() { asm volatile("wgmma.fence.sync.aligned;" ::: "memory"); }
__device__ __forceinline__ void wg_commit() { asm volatile("wgmma.commit_group.sync.aligned;" ::: "memory"); }
template <int N> __device__ __forceinline__ void wg_wait() {
  asm volatile("wgmma.wait_group.sync.aligned %0;" ::"n"(N) : "memory");
}
template <int N> __device__ __forceinline__ void fence_regs(float (&d)[N]) {
#pragma unroll
  for (int i = 0; i < N; i++) asm volatile("" : "+f"(d[i])::"memory");
}
template <int N> __device__ __forceinline__ void fence_regs(uint32_t (&d)[N][4]) {
#pragma unroll
  for (int i = 0; i < N; i++) asm volatile("" : "+r"(d[i][0]), "+r"(d[i][1]), "+r"(d[i][2]), "+r"(d[i][3])::"memory");
}
template <int N> __device__ __forceinline__ void fence_frags(uint32_t (*d)[4]) {
#pragma unroll
  for (int i = 0; i < N; i++) asm volatile("" : "+r"(d[i][0]), "+r"(d[i][1]), "+r"(d[i][2]), "+r"(d[i][3])::"memory");
}
__device__ __forceinline__ void bar_sync(int id, int n) { asm volatile("bar.sync %0, %1;" ::"r"(id), "r"(n) : "memory"); }
__device__ __forceinline__ void bar_arrive(int id, int n) { asm volatile("bar.arrive %0, %1;" ::"r"(id), "r"(n) : "memory"); }

__device__ __forceinline__ uint32_t pack_bf16(float lo, float hi) {
  uint32_t r;
  asm("cvt.rn.bf16x2.f32 %0, %1, %2;" : "=r"(r) : "f"(hi), "f"(lo));
  return r;
}
__device__ __forceinline__ float bf_lo(uint32_t w) { return __uint_as_float(w << 16); }
__device__ __forceinline__ float bf_hi(uint32_t w) { return __uint_as_float(w & 0xFFFF0000u); }
__device__ __forceinline__ float round_bf16(float x) { return bf_lo(pack_bf16(x, 0.f)); }
__device__ __forceinline__ uint32_t hfma2_bf16(uint32_t a, uint32_t b, uint32_t c) {
  uint32_t r;
  asm("fma.rn.bf16x2 %0, %1, %2, %3;" : "=r"(r) : "r"(a), "r"(b), "r"(c));
  return r;
}
__device__ __forceinline__ float ex2(float x) {
  float r;
  asm("ex2.approx.ftz.f32 %0, %1;" : "=f"(r) : "f"(x));
  return r;
}
__device__ __forceinline__ float tanh_hw(float x) {
  float r;
  asm("tanh.approx.f32 %0, %1;" : "=f"(r) : "f"(x));
  return r;
}
template <int TAG> __device__ __forceinline__ uint32_t pack_tag(float lo, float hi) {
  uint32_t w = __byte_perm(__float_as_uint(lo), pack_bf16(lo, hi), 0x7632);
  return TAG ? (w | 1u) : (w & ~1u);
}
__device__ __forceinline__ void st_pkt(uint4* p, uint32_t a, uint32_t b, uint32_t c, uint32_t d) {
  asm volatile(
      "st.relaxed.gpu.global.v4.b32 [%0], {%1,%2,%3,%4};" ::"l"(p), "r"(a), "r"(b), "r"(c), "r"(d) : "memory");
}
__device__ __forceinline__ void ld_pkt(const uint4* p, uint32_t (&r)[4]) {
  asm volatile(
      "ld.relaxed.gpu.global.v4.b32 {%0,%1,%2,%3}, [%4];"
      : "=r"(r[0]), "=r"(r[1]), "=r"(r[2]), "=r"(r[3]) : "l"(p) : "memory");
}
__device__ __forceinline__ uint32_t ldg32(const void* p) {
  uint32_t r;
  asm volatile("ld.global.nc.b32 %0, [%1];" : "=r"(r) : "l"(p));
  return r;
}
__device__ __forceinline__ uint32_t ldg16(const void* p) {
  uint16_t r;
  asm volatile("ld.global.nc.b16 %0, [%1];" : "=h"(r) : "l"(p));
  return r;
}
__device__ __forceinline__ uint4 ldg128(const void* p) {
  uint4 r;
  asm volatile("ld.global.nc.v4.b32 {%0,%1,%2,%3}, [%4];" : "=r"(r.x), "=r"(r.y), "=r"(r.z), "=r"(r.w) : "l"(p));
  return r;
}
__device__ __forceinline__ void l2_prefetch(const void* p, uint32_t bytes) {
  asm volatile("cp.async.bulk.prefetch.L2.global [%0], %1;" ::"l"(p), "r"(bytes) : "memory");
}
__device__ __forceinline__ float rcp_hw(float x) {
  float r;
  asm("rcp.approx.ftz.f32 %0, %1;" : "=f"(r) : "f"(x));
  return r;
}
__device__ __forceinline__ void warp_bulk_load(uint32_t sdst, const void* gsrc, uint32_t bytes, uint32_t bar) {
  asm volatile(
      "{\n.reg .pred p;\nelect.sync _|p, 0xffffffff;\n"
      "@p mbarrier.arrive.expect_tx.shared::cta.b64 _, [%3], %2;\n"
      "@p cp.async.bulk.shared::cluster.global.mbarrier::complete_tx::bytes [%0], [%1], %2, [%3];\n}\n"
      ::"r"(sdst), "l"(gsrc), "r"(bytes), "r"(bar) : "memory");
}
__device__ __forceinline__ void warp_tma3d(uint32_t dst, const CUtensorMap* tm, uint32_t bar, uint32_t bytes, int c1, int c2) {
  asm volatile(
      "{\n.reg .pred p;\nelect.sync _|p, 0xffffffff;\n"
      "@p mbarrier.arrive.expect_tx.shared::cta.b64 _, [%2], %3;\n"
      "@p cp.async.bulk.tensor.3d.shared::cluster.global.mbarrier::complete_tx::bytes [%0], [%1, {%6,%4,%5}], [%2];\n}\n"
      ::"r"(dst), "l"(tm), "r"(bar), "r"(bytes), "r"(c1), "r"(c2), "r"(0) : "memory");
}
__device__ __forceinline__ bool elect_one() {
  uint32_t r;
  asm volatile("{\n.reg .pred p;\nelect.sync _|p, 0xffffffff;\nselp.u32 %0, 1, 0, p;\n}\n" : "=r"(r));
  return r;
}
__device__ __forceinline__ void warp_arrive(uint32_t bar) {
  asm volatile("{\n.reg .pred p;\nelect.sync _|p, 0xffffffff;\n@p mbarrier.arrive.shared::cta.b64 _, [%0];\n}\n" ::"r"(bar) : "memory");
}
__device__ __forceinline__ uint32_t pack_trunc(float lo, float hi) {
  return __byte_perm(__float_as_uint(lo), __float_as_uint(hi), 0x7632);
}
__device__ __forceinline__ void add_partial(float (&y)[8], const uint32_t (&r)[4], uint32_t c0, bool first) {
#pragma unroll
  for (int e = 0; e < 4; e++) {
    const float lo = __uint_as_float(r[e] * 65536u + (e ? 0x8000u : c0)), hi = __uint_as_float(r[e]);
    y[2 * e] = first ? lo : y[2 * e] + lo;
    y[2 * e + 1] = first ? hi : y[2 * e + 1] + hi;
  }
}
__device__ __forceinline__ void spin_cycles(uint32_t n) {
  uint32_t t0, t;
  asm volatile("mov.u32 %0, %%clock;" : "=r"(t0));
  do { asm volatile("mov.u32 %0, %%clock;" : "=r"(t)); } while (t - t0 < n);
}
__device__ __forceinline__ void sts128(uint32_t a, uint32_t x, uint32_t y, uint32_t z, uint32_t w) {
  asm volatile("st.shared.v4.b32 [%0], {%1,%2,%3,%4};" ::"r"(a), "r"(x), "r"(y), "r"(z), "r"(w) : "memory");
}
__device__ __forceinline__ void lds128(uint32_t a, uint32_t (&r)[4]) {
  asm volatile("ld.shared.v4.b32 {%0,%1,%2,%3}, [%4];" : "=r"(r[0]), "=r"(r[1]), "=r"(r[2]), "=r"(r[3]) : "r"(a) : "memory");
}

__device__ __forceinline__ uint32_t lds32(uint32_t a) {
  uint32_t r;
  asm volatile("ld.shared.b32 %0, [%1];" : "=r"(r) : "r"(a) : "memory");
  return r;
}
__device__ __forceinline__ void store_out(__nv_bfloat16* out, uint32_t woff, uint32_t x2s, uint32_t gb0, uint32_t gb1,
                                          const float (&y)[8]) {
  const uint32_t gb[2] = {gb0, gb1};
  uint32_t xa[2][4];
  lds128(x2s, xa[0]);
  lds128(x2s + 2048, xa[1]);
  uint32_t* const oo = (uint32_t*)out + woff;
#pragma unroll
  for (int e = 0; e < 4; e++)
    oo[(e >> 1) * 4 + (e & 1) * 8 * 256] =
        pack_bf16(fmaf(bf_lo(gb[e >> 1]), y[2 * e], __uint_as_float(xa[e >> 1][(e & 1) * 2])),
                  fmaf(bf_hi(gb[e >> 1]), y[2 * e + 1], __uint_as_float(xa[e >> 1][(e & 1) * 2 + 1])));
}

constexpr int SK = 2048, WIN = 512;
constexpr int FF = 1792, FSL = 224;
constexpr int NTILES = 80;
constexpr int NSLOT = 4;
constexpr uint32_t SLOT = 32768;
constexpr uint32_t SM_PARK = 0;
constexpr uint32_t SM_RING = 3 * SLOT;
constexpr uint32_t SM_TAB = 7 * SLOT;
constexpr uint32_t SM_RED = SM_TAB + 2048;
constexpr uint32_t SM_BAR = SM_RED + 256;
constexpr uint32_t SM_WBAR = SM_BAR + 128;
constexpr uint32_t SM_SBAR = SM_WBAR + 256;
constexpr uint32_t BAR_SLAB = 64, BAR_UV = 72, BAR_X2 = 80, BAR_TAG = 88;
constexpr uint32_t SM_DBAR = SM_SBAR + 16;
constexpr uint32_t SM_TOTAL = SM_DBAR + 128;

struct Scratch {
  uint4 P[16 * 8 * 4 * 1024];
  uint4 G[16 * 8 * 32 * 32];
  uint4 mod1[8 * 256];
  uint4 mod2[512];
  uint4 uv[2 * 448];
  uint4 stat[16 * 8 * 8];
  uint32_t sent[16 * 8 * 8];
  uint32_t epoch;
};
__device__ Scratch g_scratch;

#define TS(i) do { } while (0)
#define TR(code)
#define CK_(v)
#define CKS(i, v)

#define TRU(code)

struct Params {
  const __nv_bfloat16* x;
  const __nv_bfloat16* c;
  const __nv_bfloat16* wmod;
  const __nv_bfloat16* wo;
  const __nv_bfloat16* w1;
  const __nv_bfloat16* w2;
  __nv_bfloat16* out;
  Scratch* s;
  uint32_t zero;
};

constexpr uint32_t HI128 = (1024 >> 4) | (1u << 30);
constexpr int LB_MN128 = (16384 >> 4) << 16;
constexpr int LB_K128 = 1 << 16;
constexpr int LB_W1 = (8192 >> 4) << 16;

template <int I> struct IC {
  __host__ __device__ constexpr operator int() const { return I; }
};
template <int I, int N, typename F> __device__ __forceinline__ void static_for(F&& f) {
  if constexpr (I < N) {
    f(IC<I>{});
    static_for<I + 1, N>(f);
  }
}

struct Ring {
  uint32_t base16, bars;
  __device__ __forceinline__ uint32_t wait_full(uint32_t slot, uint32_t parity) const {
    mbar_wait(bars + slot * 8, parity);
    return base16 + slot * (SLOT >> 4);
  }
  __device__ __forceinline__ void release(uint32_t slot) const {
    warp_arrive(bars + 32 + slot * 8);
  }
};

__device__ __forceinline__ float silu_c(uint32_t bits) {
  float x = bf_lo(bits);
  return round_bf16(x * rcp_hw(1.f + ex2(-1.4426950408889634f * x)));
}
__device__ __forceinline__ void pack8(uint32_t (&o)[4], const float* v) {
  o[0] = pack_bf16(v[0], v[1]); o[1] = pack_bf16(v[2], v[3]); o[2] = pack_bf16(v[4], v[5]); o[3] = pack_bf16(v[6], v[7]);
}

template <int TAG, int N>
__device__ __forceinline__ void issue_pkts(const uint4* p, int stride, uint32_t (*r)[4]) {
#pragma unroll
  for (int i = 0; i < N; i++) ld_pkt(p + i * stride, r[i]);
}
__device__ __forceinline__ void wait_sent(const uint32_t* p, uint32_t tag, uint32_t step) {
#pragma unroll 1
  for (int spins = 0; spins < SPIN_LIMIT; spins++) {
    uint32_t v;
    asm volatile("ld.relaxed.gpu.global.u32 %0, [%1];" : "=r"(v) : "l"(p) : "memory");
    if (__all_sync(0xffffffffu, v - (tag * 32 + step + 1) < 16u)) break;
  }
}
__device__ __forceinline__ void ld_mod(const uint4* p, uint32_t tag, uint32_t (&r)[4]) {
  int spins = 0;
  ld_pkt(p, r);
  while (r[2] != tag && ++spins < SPIN_LIMIT) ld_pkt(p, r);
}

#define EARLY_TILES 2
#define PF_WMOD 1
#define MOD1_DELAY 500
#define RED3_UNIT 3
#define NITEM2 24
#define FIN_DELAY0 800
#define FIN_DELAY1 0
#define G_DELAY 300

__device__ __forceinline__ float reduce8(float (&a)[8], int lane) {
  const bool h16 = lane & 16, h8 = lane & 8, h4 = lane & 4;
#pragma unroll
  for (int k = 0; k < 4; k++) a[k] = (h16 ? a[k + 4] : a[k]) + __shfl_xor_sync(0xffffffffu, h16 ? a[k] : a[k + 4], 16);
#pragma unroll
  for (int k = 0; k < 2; k++) a[k] = (h8 ? a[k + 2] : a[k]) + __shfl_xor_sync(0xffffffffu, h8 ? a[k] : a[k + 2], 8);
  const float r = (h4 ? a[1] : a[0]) + __shfl_xor_sync(0xffffffffu, h4 ? a[0] : a[1], 4);
  return r + __shfl_xor_sync(0xffffffffu, r, 2);
}
__device__ __forceinline__ void fma8(float (&a)[8], float s, uint32_t w0, uint32_t w1, uint32_t w2, uint32_t w3) {
  a[0] = fmaf(s, bf_lo(w0), a[0]); a[1] = fmaf(s, bf_hi(w0), a[1]);
  a[2] = fmaf(s, bf_lo(w1), a[2]); a[3] = fmaf(s, bf_hi(w1), a[3]);
  a[4] = fmaf(s, bf_lo(w2), a[4]); a[5] = fmaf(s, bf_hi(w2), a[5]);
  a[6] = fmaf(s, bf_lo(w3), a[6]); a[7] = fmaf(s, bf_hi(w3), a[7]);
}

enum { NB_TAB = 1, NB_WG0 = 2, NB_WG1 = 3, NB_HELP = 4, NB_INIT = 5, NB_PASS0 = 6, NB_GATHER = 7, NB_PARK = 8, NB_PROD = 9 };

__global__ void __launch_bounds__(512, 1)
adaln_block_kernel(const __grid_constant__ CUtensorMap tmWq, const __grid_constant__ CUtensorMap tmK,
                   const __grid_constant__ CUtensorMap tmV, const __grid_constant__ CUtensorMap tmWo,
                   const __grid_constant__ CUtensorMap tmW1, const __grid_constant__ CUtensorMap tmW2,
                   const __grid_constant__ CUtensorMap tmWm, const __grid_constant__ CUtensorMap tmX,
                   const Params p) {
  extern __shared__ __align__(1024) uint8_t smem_raw[];
  const uint32_t sb = smem_u32(smem_raw);
  const int tid = threadIdx.x, lane = tid & 31;
  const int warp = __shfl_sync(0xffffffffu, tid >> 5, 0);
  const int kp = blockIdx.x >> 1;
  const int bid = (kp < 4 ? kp : kp < 36 ? 4 + ((kp - 4) & 7) * 4 + ((kp - 4) >> 3) : 36 + ((kp - 36) % 7) * 4 + (kp - 36) / 7) * 2 +
                  (blockIdx.x & 1);
  const int j = bid & 7, rt = bid >> 3;
  const uint32_t bars = sb + SM_BAR;
  if (warp != 13) asm volatile("barrier.cluster.arrive.relaxed.aligned;" ::: "memory");

  if (warp >= 12) {
    asm volatile("setmaxnreg.dec.sync.aligned.u32 24;");
    if (warp == 13) {
      if (elect_one()) {
#pragma unroll
        for (int i = 0; i < 28; i++) mbar_init(sb + SM_WBAR + i * 8, i < 26 ? 1 : 4);
        mbar_init(sb + SM_SBAR, 8);
#pragma unroll
        for (int i = 0; i < 16; i++) mbar_init(sb + SM_DBAR + i * 8, 1);
        asm volatile("fence.mbarrier_init.release.cluster;" ::: "memory");
      }
      __syncwarp();
      asm volatile("barrier.cluster.arrive.relaxed.aligned;" ::: "memory");
      bar_arrive(NB_INIT, 192);
      mbar_wait(sb + SM_SBAR, 0);
      const uint32_t tag = *(volatile uint32_t*)(smem_raw + SM_BAR + BAR_TAG);
#pragma unroll 1
      for (int n = 0; n < 14; n++) {
        const uint32_t lb = sb + SM_WBAR + 192 + (n & 1) * 8;
        mbar_wait(lb + 16, ((n >> 1) & 1) ^ 1);
        wait_sent(&p.s->sent[(rt * 8 + j) * 8 + (lane & 6) + (n & 1)], tag, n >> 1);
        if (elect_one()) {
          mbar_expect(lb, n < 8 ? 8192 + 2048 : 8192);
#pragma unroll
          for (int m = 0; m < 4; m++)
            asm volatile("cp.async.bulk.shared::cluster.global.mbarrier::complete_tx::bytes [%0], [%1], 2048, [%2];"
                         ::"r"(sb + SM_PARK + ((n & 1) * 4 + m) * 4096 + 2048),
                           "l"(p.s->P + ((size_t)(rt * 8 + j) * 4 + m) * 1024 + (n & 7) * 128), "r"(lb) : "memory");
          if (n < 8) tma3d(sb + SM_PARK + SLOT + n * 4096, &tmX, lb, 0, rt * 128 + j * 16, n * 4);
        }
        __syncwarp();
      }
    } else if (warp == 14) {
      if (elect_one()) {
        asm volatile("prefetch.tensormap [%0];" ::"l"(&tmWq) : "memory");
        asm volatile("prefetch.tensormap [%0];" ::"l"(&tmK) : "memory");
        asm volatile("prefetch.tensormap [%0];" ::"l"(&tmV) : "memory");
        asm volatile("prefetch.tensormap [%0];" ::"l"(&tmWo) : "memory");
        asm volatile("prefetch.tensormap [%0];" ::"l"(&tmX) : "memory");
        asm volatile("prefetch.tensormap [%0];" ::"l"(&tmW1) : "memory");
        asm volatile("prefetch.tensormap [%0];" ::"l"(&tmW2) : "memory");
      }
    } else if (warp == 12) {
      if (elect_one()) {
        mbar_init(bars + BAR_SLAB, 1);
        asm volatile("fence.mbarrier_init.release.cluster;" ::: "memory");
        mbar_expect(bars + BAR_SLAB, 8192);
        tma3d(sb + SM_RING + 3 * SLOT, &tmWm, bars + BAR_SLAB, 0, 0, bid);
        tma3d(sb + SM_RING + 3 * SLOT + 4096, &tmWm, bars + BAR_SLAB, 0, 256, bid);
#pragma unroll
        for (int i = 0; i < 4; i++) { mbar_init(bars + i * 8, 1); mbar_init(bars + 32 + i * 8, 8); }
        mbar_init(bars + BAR_UV, 4);
        mbar_init(bars + BAR_X2, 1);
        asm volatile("fence.mbarrier_init.release.cluster;" ::: "memory");
      }
      __syncwarp();
      bar_arrive(NB_INIT, 192);
      mbar_wait(bars + BAR_SLAB, 0);
      uint32_t s = 0, ph = 1;
#pragma unroll 1
      for (int tt = 0; tt < NTILES; tt++) {
        const CUtensorMap* tm;
        int c1, c2;
        uint32_t bytes = SLOT;
        if (tt < 16) {
          tm = &tmWq; c1 = (tt & 3) * 128; c2 = (j * 4 + (((tt >> 2) + 1) & 3)) * 2;
        } else if (tt < 48) {
          const int u = tt - 16;
          const bool isK = (u == 0) || ((u & 1) && u != 31);
          const int n = isK ? ((u + 1) >> 1) : (u == 31 ? 15 : (u >> 1) - 1);
          tm = isK ? &tmK : &tmV; c1 = j * SK + (SK - WIN) + (n & 3) * 128; c2 = 0;
        } else if (tt < 64) {
          const int u = tt - 48;
          tm = &tmWo; c1 = j * 512 + (u & 1) * 256; c2 = (u >> 1) ^ (~j & 1);
        } else if (tt < 72) {
          tm = &tmW1; c1 = (tt - 64) * 64; c2 = (j * 7) >> 1;
        } else {
          tm = &tmW2; c1 = j * FSL; c2 = (tt - 72) ^ (~j & 1); bytes = 28672;
        }
        if (tt == EARLY_TILES) bar_sync(NB_PROD, 160);
        mbar_wait(bars + 32 + s * 8, ph);
        warp_tma3d(sb + SM_RING + s * SLOT, tm, bars + s * 8, bytes, c1, c2);
        if (++s == 4) { s = 0; ph ^= 1; }
      }
    }
  } else if (warp >= 8) {
    CK_(c0);
    asm volatile("setmaxnreg.dec.sync.aligned.u32 40;");
    const int t = tid - 256, hw = warp - 8, q = lane & 3;
    float* const red = (float*)(smem_raw + SM_RED);
    uint32_t tag;
    float a[8];
    {
      uint32_t cb[4];
#pragma unroll
      for (int i = 0; i < 4; i++) cb[i] = ldg16(p.c + t + 128 * i);
      asm volatile("ld.relaxed.gpu.global.u32 %0, [%1];" : "=r"(tag) : "l"(&p.s->epoch) : "memory");
      bar_sync(NB_INIT, 192);
      CK_(c2);
      tag += 1;
      float sc[4];
#pragma unroll
      for (int i = 0; i < 4; i++) sc[i] = silu_c(cb[i]);
#pragma unroll
      for (int k = 0; k < 8; k++) a[k] = 0.f;
      if (t == 0) *(uint32_t*)(smem_raw + SM_BAR + BAR_TAG) = tag;
      mbar_wait(bars + BAR_SLAB, 0);
      CK_(c3);
      bar_arrive(NB_GATHER, 384);
#pragma unroll
      for (int i = 0; i < 4; i++) {
        uint32_t w[4];
        lds128(sb + SM_RING + 3 * SLOT + (t + 128 * i) * 16, w);
        fma8(a, sc[i], w[0], w[1], w[2], w[3]);
      }
      float r = reduce8(a, lane);
      r += __shfl_xor_sync(0xffffffffu, r, 1);
      if (q == 0) red[hw * 8 + (lane >> 2)] = r;
      CK_(c4);
      bar_sync(NB_HELP, 128);
      CK_(c5);
      if (hw == 0) {
        const int cl = lane & 7;
        float v = round_bf16(red[cl] + red[8 + cl] + red[16 + cl] + red[24 + cl]);
        if (bid >= 64) v = 1.f + v;
        float vn = __shfl_down_sync(0xffffffffu, v, 1);
        uint32_t wd = pack_bf16(v, vn);
        uint32_t w0 = __shfl_sync(0xffffffffu, wd, (lane & 1) * 4);
        uint32_t w1 = __shfl_sync(0xffffffffu, wd, (lane & 1) * 4 + 2);
        if (lane < 16) st_pkt(&p.s->mod1[(lane >> 1) * 256 + bid * 2 + (lane & 1)], w0, w1, tag, 0);
      }
      uint32_t r0[4], r1[4];
      const uint4* src = &p.s->mod1[j * 256 + t];
      CK_(c6);
      spin_cycles(MOD1_DELAY);
      CK_(c7);
      int spins = 0;
      do {
        ld_pkt(src, r0);
        ld_pkt(src + 128, r1);
      } while ((r0[2] != tag || r1[2] != tag) && ++spins < SPIN_LIMIT);
      const int g = t >> 2, pp = q * 2;
      const uint32_t ad = sb + SM_TAB + (uint32_t)(g * 4 + (pp & 3)) * 16 + (pp >> 2) * 4;
      asm volatile("st.shared.b32 [%0], %1;" ::"r"(ad + 8), "r"(r0[0]) : "memory");
      asm volatile("st.shared.b32 [%0], %1;" ::"r"(ad + 24), "r"(r0[1]) : "memory");
      asm volatile("st.shared.b32 [%0], %1;" ::"r"(ad), "r"(r1[0]) : "memory");
      asm volatile("st.shared.b32 [%0], %1;" ::"r"(ad + 16), "r"(r1[1]) : "memory");
      bar_arrive(NB_TAB, 384);
      bar_arrive(NB_PROD, 160);
      CK_(c8);
      CKS(0, c0); CKS(2, c2); CKS(3, c3); CKS(4, c4); CKS(5, c5); CKS(6, c6); CKS(7, c7); CKS(8, c8);
    }
    bar_sync(NB_PASS0, 384);
    if (t < 8) l2_prefetch((const char*)p.wo + (size_t)bid * 32768 + t * 4096, 4096);
    else if (t < 12) l2_prefetch((const char*)p.w1 + (size_t)bid * 14336 + (t - 8) * 3584, 3584);
    else if (t < 16) l2_prefetch((const char*)p.w2 + (size_t)bid * 14336 + (t - 12) * 3584, 3584);
    {
#pragma unroll
      for (int k = 0; k < 8; k++) a[k] = 0.f;
#pragma unroll 1
      for (int b = 0; b < 4; b++) {
        const int row = b * 128 + (t >> 1);
        const __nv_bfloat16* wp = p.wmod + (size_t)row * 3072 + 1024 + bid * 16 + (t & 1) * 8;
        const uint4 w0 = ldg128(wp), w1 = ldg128(wp + 64 * 3072);
        const uint32_t c0 = ldg16(p.c + row), c1 = ldg16(p.c + row + 64);
        fma8(a, silu_c(c0), w0.x, w0.y, w0.z, w0.w);
        fma8(a, silu_c(c1), w1.x, w1.y, w1.z, w1.w);
      }
      const float r = reduce8(a, lane);
      if ((lane & 2) == 0) red[hw * 16 + (lane & 1) * 8 + (lane >> 2)] = r;
      bar_sync(NB_HELP, 128);
      if (hw == 0) {
        const int cl = lane & 15;
        float v = round_bf16(red[cl] + red[16 + cl] + red[32 + cl] + red[48 + cl]);
        if ((bid >> 5) == 2) v = 1.f + v;
        float vn = __shfl_down_sync(0xffffffffu, v, 1);
        uint32_t wd = pack_bf16(v, vn);
        uint32_t w0 = __shfl_sync(0xffffffffu, wd, q * 2);
        uint32_t w1 = __shfl_sync(0xffffffffu, wd, q * 2 + 8);
        const int vec = (0x2130 >> ((bid >> 5) * 4)) & 3;
        if (lane < 4) st_pkt(&p.s->mod2[((bid & 31) * 4 + vec) * 4 + lane], w0, w1, tag, 0);
      }
    }
    {
      const int isv = hw & 1, kh = hw >> 1;
      if (bid < 112) {
        const int kk = lane >> 1;
        uint32_t m0[4], m1[4];
        const uint4* mp = &p.s->mod2[(kh * 16 + (lane >> 2)) * 16 + (isv ? 12 : 4) + q];
        ld_mod(mp, tag, m0);
        ld_mod(mp + 128, tag, m1);
#pragma unroll
        for (int k = 0; k < 8; k++) a[k] = 0.f;
#pragma unroll 1
        for (int g0 = 0; g0 < 16; g0 += 2) {
          uint4 w[2];
#pragma unroll
          for (int i = 0; i < 2; i++) w[i] = ldg128(p.w1 + (size_t)((kh * 16 + g0 + i) * 16 + kk) * FF + bid * 16 + (lane & 1) * 8);
#pragma unroll
          for (int i = 0; i < 2; i++) {
            const int sl = ((g0 + i) & 7) * 4 + ((kk & 7) >> 1);
            const uint32_t wa = __shfl_sync(0xffffffffu, g0 < 8 ? m0[0] : m1[0], sl), wb = __shfl_sync(0xffffffffu, g0 < 8 ? m0[1] : m1[1], sl);
            const uint32_t mw = (kk & 8) ? wb : wa;
            fma8(a, (kk & 1) ? bf_hi(mw) : bf_lo(mw), w[i].x, w[i].y, w[i].z, w[i].w);
          }
        }
        float r = reduce8(a, lane);
        bar_sync(NB_HELP, 128);
        if (kh) red[isv * 32 + lane] = r;
        bar_sync(NB_HELP, 128);
        if (!kh) {
          r = (r + red[isv * 32 + lane]) * (isv ? 0.5f : 1.f);
          const float r1 = __shfl_down_sync(0xffffffffu, r, 4), r2 = __shfl_down_sync(0xffffffffu, r, 8),
                      r3 = __shfl_down_sync(0xffffffffu, r, 12);
          if ((lane & 14) == 0)
            st_pkt(&p.s->uv[isv * 448 + bid * 4 + (lane & 1) * 2 + (lane >> 4)], (__float_as_uint(r) & ~1u) | (tag & 1u),
                   __float_as_uint(r1), __float_as_uint(r2), __float_as_uint(r3));
        }
      }
      const int i = kh * 32 + lane;
      if (i < 56) {
        uint32_t m[4];
        int spins = 0;
        while (true) {
          ld_pkt(&p.s->uv[isv * 448 + j * 56 + i], m);
          if (!((m[0] ^ tag) & 1u) || ++spins >= SPIN_LIMIT) break;
          __nanosleep(200);
        }
        const int ip = (j & 1) ? (i < 8 ? i + 48 : i - 8) : i;
        const uint32_t ad = sb + SM_TAB + ip * 32 + isv * 8;
        asm volatile("st.shared.v2.b32 [%0], {%1,%2};" ::"r"(ad), "r"(m[0]), "r"(m[1]) : "memory");
        asm volatile("st.shared.v2.b32 [%0], {%1,%2};" ::"r"(ad + 16), "r"(m[2]), "r"(m[3]) : "memory");
      }
      __syncwarp();
      warp_arrive(bars + BAR_UV);
      TS(9);
    }
    {
      uint32_t mga[4], mg2[4], mgb[4];
      const uint4* mp = &p.s->mod2[((lane >> 2) * 4 + hw) * 16 + q];
      ld_mod(mp, tag, mga);
      ld_mod(mp + 4, tag, mg2);
      ld_mod(mp + 8, tag, mgb);
      if (lane >= 24) asm volatile("st.shared.v2.b32 [%0], {%1,%2};" ::"r"(sb + SM_TAB + 1792 + ((((lane >> 2) & 1) * 4 + hw) * 4 + q) * 8),
                                   "r"(mgb[0]), "r"(mgb[1]) : "memory");
      const uint32_t x2s = sb + SM_PARK + SLOT + hw * 512 + lane * 16;
      const uint4* const Pown = p.s->P + (size_t)(rt * 8 + j) * 4096 + hw * 32 + lane;
      float s0 = 0.f, s1 = 0.f, v0 = 0.f, v1 = 0.f;
      bar_sync(NB_PARK, 384);
      asm volatile("setmaxnreg.inc.sync.aligned.u32 56;");
#pragma unroll 1
      for (int n = 0; n < 14; n++) {
        const int cc = n & 7;
        const bool ex1 = n < 8;
        const uint32_t lb = sb + SM_WBAR + 192 + (n & 1) * 8;
        uint32_t r[4][4];
        float y[8];
        mbar_wait(lb, (n >> 1) & 1);
#pragma unroll
        for (int i = 0; i < 4; i++) lds128(sb + SM_PARK + ((n & 1) * 4 + i) * 4096 + 2048 + hw * 512 + lane * 16, r[i]);
        verify4_rt<16384>(Pown + cc * 128, r, ex1);
        warp_arrive(lb + 16);
#pragma unroll
        for (int i = 0; i < 4; i++) add_partial(y, r[i], ex1 ? 0u : 0x10000u, i == 0);
        const int src = cc * 4 + q;
        const uint32_t ma = __shfl_sync(0xffffffffu, ex1 ? mga[0] : mgb[0], src), mb = __shfl_sync(0xffffffffu, ex1 ? mga[1] : mgb[1], src);
        if (ex1) {
          uint32_t xr[4];
          asm volatile("ldmatrix.sync.aligned.m8n8.x4.shared.b16 {%0,%1,%2,%3}, [%4];"
                       : "=r"(xr[0]), "=r"(xr[1]), "=r"(xr[2]), "=r"(xr[3])
                       : "r"(sb + SM_PARK + SLOT + hw * 512 + cc * 4096 + (lane & 15) * 32 + (lane >> 4) * 16) : "memory");
          const uint32_t mc = __shfl_sync(0xffffffffu, mg2[0], src), md = __shfl_sync(0xffffffffu, mg2[1], src);
#pragma unroll
          for (int e = 0; e < 4; e++) {
            const uint32_t m = e < 2 ? ma : mb;
            const float u = fmaf(bf_lo(m), y[2 * e], bf_lo(xr[e])), v = fmaf(bf_hi(m), y[2 * e + 1], bf_hi(xr[e]));
            y[2 * e] = u; y[2 * e + 1] = v;
            if (e & 1) { s1 += u + v; v1 = fmaf(u, u, fmaf(v, v, v1)); }
            else { s0 += u + v; v0 = fmaf(u, u, fmaf(v, v, v0)); }
          }
          st_pkt(p.s->G + ((rt * 8 + j) * 32 + cc * 4 + hw) * 32 + lane, pack_tag<0>(y[0] * bf_lo(mc), y[1] * bf_hi(mc)),
                 pack_bf16(y[2] * bf_lo(mc), y[3] * bf_hi(mc)), pack_bf16(y[4] * bf_lo(md), y[5] * bf_hi(md)),
                 pack_bf16(y[6] * bf_lo(md), y[7] * bf_hi(md)));
          sts128(x2s + cc * 4096, __float_as_uint(y[0]), __float_as_uint(y[1]), __float_as_uint(y[2]), __float_as_uint(y[3]));
          sts128(x2s + cc * 4096 + 2048, __float_as_uint(y[4]), __float_as_uint(y[5]), __float_as_uint(y[6]), __float_as_uint(y[7]));
          if (n == 7) {
            const bool o1 = lane & 1, o2 = lane & 2;
            float c0 = (o1 ? v0 : s0) + __shfl_xor_sync(0xffffffffu, o1 ? s0 : v0, 1);
            float c1 = (o1 ? v1 : s1) + __shfl_xor_sync(0xffffffffu, o1 ? s1 : v1, 1);
            c0 = (o2 ? c1 : c0) + __shfl_xor_sync(0xffffffffu, o2 ? c0 : c1, 2);
            *(float*)(smem_raw + SM_PARK + 16384 + 2048 + hw * 512 + lane * 4) = c0;
            bar_sync(NB_HELP, 128);
            if (hw == 0) {
              const float* ps = (const float*)(smem_raw + SM_PARK + 16384 + 2048) + lane;
              const float m = (c0 + ps[128] + ps[256] + ps[384]) * (1.f / 512.f);
              const float mean = __shfl_sync(0xffffffffu, m, lane & ~1), sq = __shfl_sync(0xffffffffu, m, lane | 1);
              const float rs = 0.5f * rsqrtf(fmaxf(fmaf(-mean, mean, sq), 0.f) + 1e-5f), mr = -mean * rs;
              const float rs1 = __shfl_down_sync(0xffffffffu, rs, 2), mr1 = __shfl_down_sync(0xffffffffu, mr, 2);
              if (q == 0)
                st_pkt(&p.s->stat[(rt * 8 + j) * 8 + (lane >> 2)], (__float_as_uint(rs) & ~1u) | (tag & 1u), __float_as_uint(mr),
                       __float_as_uint(rs1), __float_as_uint(mr1));
              warp_arrive(bars + BAR_X2);
            }
          }
        } else {
          store_out(p.out, (uint32_t)(rt * 128 + 16 * j + (lane >> 2)) * 256 + (cc * 4 + hw) * 8 + q, x2s + cc * 4096, ma, mb, y);
        }
      }
    }
  } else {
    const int wg = warp >> 2;
    const int q = lane & 3, gq = lane >> 2;
    const Ring ring{((sb + SM_RING) & 0x3FFFF) >> 4, bars};
    const uint32_t xoff = (uint32_t)(rt * 128 + 16 * j + warp) * 256 + gq * 8 + q;
    const uint32_t ooff = ((uint32_t)(rt * 8 + j) * 32 + gq) * 32 + warp * 4 + q;
    const uint32_t wblk = sb + SM_PARK + warp * 4096, wprv = wblk + lane * 16;
    const uint32_t wbar = sb + SM_WBAR + warp * 24;
    const uint4* const Gw = p.s->G + (rt * 8 + warp) * 1024;

    {
      const uint32_t* xo = (const uint32_t*)p.x + xoff;
      uint32_t xr[4][4];
      CK_(d0);
#pragma unroll
      for (int c = 0; c < 4; c++) {
        xr[c][0] = ldg32(xo + c * 64);
        xr[c][1] = ldg32(xo + c * 64 + 8 * 256);
        xr[c][2] = ldg32(xo + c * 64 + 4);
        xr[c][3] = ldg32(xo + c * 64 + 4 + 8 * 256);
      }
      CK_(d1);
      fence_regs(xr);
      CK_(d2);
      float s0 = 0.f, s1 = 0.f, v0 = 0.f, v1 = 0.f;
#pragma unroll
      for (int c = 0; c < 4; c++) {
#pragma unroll
        for (int e = 0; e < 4; e++) {
          const float a = bf_lo(xr[c][e]), b = bf_hi(xr[c][e]);
          if (e & 1) { s1 += a + b; v1 = fmaf(a, a, fmaf(b, b, v1)); }
          else { s0 += a + b; v0 = fmaf(a, a, fmaf(b, b, v0)); }
        }
      }
#pragma unroll
      for (int o = 16; o > 0; o >>= 1) {
        s0 += __shfl_xor_sync(0xffffffffu, s0, o);
        s1 += __shfl_xor_sync(0xffffffffu, s1, o);
        v0 += __shfl_xor_sync(0xffffffffu, v0, o);
        v1 += __shfl_xor_sync(0xffffffffu, v1, o);
      }
      const float m0 = s0 * (1.f / 512.f), m1 = s1 * (1.f / 512.f);
      const float r0 = rsqrtf(fmaxf(fmaf(-m0, m0, v0 * (1.f / 512.f)), 0.f) + 1e-5f);
      const float r1 = rsqrtf(fmaxf(fmaf(-m1, m1, v1 * (1.f / 512.f)), 0.f) + 1e-5f);
#pragma unroll
      for (int c = 0; c < 4; c++) {
        st_pkt(p.s->G + ooff + c * 256,
               pack_tag<1>((bf_lo(xr[c][0]) - m0) * r0, (bf_hi(xr[c][0]) - m0) * r0),
               pack_bf16((bf_lo(xr[c][1]) - m1) * r1, (bf_hi(xr[c][1]) - m1) * r1),
               pack_bf16((bf_lo(xr[c][2]) - m0) * r0, (bf_hi(xr[c][2]) - m0) * r0),
               pack_bf16((bf_lo(xr[c][3]) - m1) * r1, (bf_hi(xr[c][3]) - m1) * r1));
      }
      CK_(d3);
      CKS(16, d0); CKS(17, d1); CKS(18, d2); CKS(19, d3);

    }
    asm volatile("setmaxnreg.inc.sync.aligned.u32 224;");
    uint32_t qf[8][4];
    {
      uint32_t h[32][4];
      float acc[64];
      const uint4* Gin = Gw + lane;
      asm volatile("barrier.cluster.wait.acquire.aligned;" ::: "memory");
      bar_sync(NB_GATHER, 384);
      if (G_DELAY) spin_cycles(G_DELAY);
#pragma unroll
      for (int c = 0; c < 3; c++) warp_bulk_load(wblk + c * SLOT, Gw + c * 256, 4096, wbar + c * 8);
#pragma unroll
      for (int c = 0; c < 4; c++) {
        mbar_wait(wbar + (c % 3) * 8, c / 3);
#pragma unroll
        for (int i = 0; i < 8; i++) lds128(wprv + (c % 3) * SLOT + i * 512, h[c * 8 + i]);
        verify8_tag1<512>(Gin + c * 256, h + c * 8);
        if (c == 0) {
          warp_bulk_load(wblk, Gw + 768, 4096, wbar);
          TS(1);
          bar_sync(NB_TAB, 384);
        }
#pragma unroll
        for (int i = 0; i < 8; i++) {
          uint32_t m[4];
          lds128(sb + SM_TAB + (uint32_t)((c * 8 + i) * 4 + q) * 16, m);
          uint32_t* hh = h[c * 8 + i];
          hh[0] = hfma2_bf16(hh[0], m[0], m[2]);
          hh[1] = hfma2_bf16(hh[1], m[0], m[2]);
          hh[2] = hfma2_bf16(hh[2], m[1], m[3]);
          hh[3] = hfma2_bf16(hh[3], m[1], m[3]);
        }
        fence_frags<8>(h + c * 8);
        const uint32_t b = ring.wait_full(c, 0);
        if (c > 0) { wg_wait<0>(); ring.release(c - 1); }
        if (c == 0) TS(2);
        wg_fence();
        static_for<0, 8>([&](auto K) { wgmma_rs_n128_tb1<LB_MN128 + K * 128, HI128>(acc, h[c * 8 + K], b, (c | K) != 0); });
        wg_commit();
      }
      bar_arrive(NB_PASS0, 384);
#pragma unroll 1
      for (int ps = 1; ps < 4; ps++) {
        wg_wait<0>();
        ring.release(3);
        fence_regs(acc);
#pragma unroll
        for (int i = 0; i < 8; i++) {
          uint32_t o[4];
          pack8(o, acc + 8 * i);
          sts128(wprv + (ps - 1) * SLOT + i * 512, o[0], o[1], o[2], o[3]);
        }
#pragma unroll
        for (int c = 0; c < 4; c += 2) {
          const uint32_t b = ring.wait_full(c, ps & 1);
          ring.wait_full(c + 1, ps & 1);
          if (c > 0) { wg_wait<0>(); ring.release(c - 1); }
          wg_fence();
          static_for<0, 8>([&](auto K) { wgmma_rs_n128_tb1<LB_MN128 + K * 128, HI128>(acc, h[c * 8 + K], b, (c | K) != 0); });
          wg_commit();
          static_for<0, 8>([&](auto K) { wgmma_rs_n128_tb1<LB_MN128 + 2048 + K * 128, HI128>(acc, h[c * 8 + 8 + K], b, 1); });
          wg_commit();
          wg_wait<1>();
          ring.release(c);
        }
      }
      wg_wait<0>();
      ring.release(3);
      fence_regs(acc);
#pragma unroll
      for (int i = 0; i < 8; i++) pack8(qf[i], acc + 8 * i);
    }
    fence_regs(qf);
    TS(3);

    uint32_t o[24][4];
    {
      float S[64], O[64];
      uint32_t P[8][4];
      const float cs = 0.08838834764831845f * 1.4426950408889634f;
      const int TAU = 0x41800000;
      float m0, m1, l0, l1;

      auto float_block_max = [&]() {
        float b0 = fmaxf(S[0], S[1]), b1 = fmaxf(S[2], S[3]);
#pragma unroll
        for (int i = 1; i < 16; i++) {
          b0 = fmaxf(b0, fmaxf(S[4 * i], S[4 * i + 1]));
          b1 = fmaxf(b1, fmaxf(S[4 * i + 2], S[4 * i + 3]));
        }
        b0 = fmaxf(b0, __shfl_xor_sync(0xffffffffu, b0, 1)); b1 = fmaxf(b1, __shfl_xor_sync(0xffffffffu, b1, 1));
        b0 = fmaxf(b0, __shfl_xor_sync(0xffffffffu, b0, 2)); b1 = fmaxf(b1, __shfl_xor_sync(0xffffffffu, b1, 2));
        m0 = b0 * cs; m1 = b1 * cs;
      };
      auto first_block_max = [&]() {
        int a0 = max(__float_as_int(S[0]), __float_as_int(S[1]));
        int a1 = max(__float_as_int(S[2]), __float_as_int(S[3]));
#pragma unroll
        for (int i = 1; i < 16; i++) {
          a0 = __vimax3_s32(a0, __float_as_int(S[4 * i]), __float_as_int(S[4 * i + 1]));
          a1 = __vimax3_s32(a1, __float_as_int(S[4 * i + 2]), __float_as_int(S[4 * i + 3]));
        }
        a0 = max(a0, __shfl_xor_sync(0xffffffffu, a0, 1)); a1 = max(a1, __shfl_xor_sync(0xffffffffu, a1, 1));
        a0 = max(a0, __shfl_xor_sync(0xffffffffu, a0, 2)); a1 = max(a1, __shfl_xor_sync(0xffffffffu, a1, 2));
        m0 = __int_as_float(a0) * cs; m1 = __int_as_float(a1) * cs;
        if (__any_sync(0xffffffffu, (a0 | a1) < 0)) float_block_max();
      };
      auto scale_sub = [&]() {
#pragma unroll
        for (int i = 0; i < 16; i++) {
          S[4 * i] = fmaf(S[4 * i], cs, -m0); S[4 * i + 1] = fmaf(S[4 * i + 1], cs, -m0);
          S[4 * i + 2] = fmaf(S[4 * i + 2], cs, -m1); S[4 * i + 3] = fmaf(S[4 * i + 3], cs, -m1);
        }
      };
      auto exps = [&](int i0, int i1) {
#pragma unroll
        for (int i = i0; i < i1; i++) {
          S[4 * i] = ex2(S[4 * i]); S[4 * i + 1] = ex2(S[4 * i + 1]);
          S[4 * i + 2] = ex2(S[4 * i + 2]); S[4 * i + 3] = ex2(S[4 * i + 3]);
          l0 += S[4 * i]; l1 += S[4 * i + 2]; l0 += S[4 * i + 1]; l1 += S[4 * i + 3];
        }
      };
      {
        const uint32_t b = ring.wait_full(0, 0);
        wg_fence();
        static_for<0, 8>([&](auto K) { wgmma_rs_n128_tb0<LB_K128 + (K >> 2) * 1024 + (K & 3) * 2, HI128>(S, qf[K], b, K != 0); });
        wg_commit();
        wg_wait<0>();
        fence_regs(S);
        ring.release(0);
        float_block_max();
        scale_sub();
        l0 = 0.f; l1 = 0.f;
        exps(0, 16);
#pragma unroll
        for (int i = 0; i < 8; i++) pack8(P[i], S + 8 * i);
      }
      fence_regs(P);
      if (wg == 1) bar_arrive(2, 256);
#pragma unroll 1
      for (int n = 1; n < 16; n++) {
        const uint32_t tk = 2 * n - 1, tv = 2 * n;
        const bool newhead = (n & 3) == 0;
        const uint32_t bk = ring.wait_full(tk & 3, (tk >> 2) & 1);
        const uint32_t bv = ring.wait_full(tv & 3, (tv >> 2) & 1);
        bar_sync(2 + wg, 256);
        wg_fence();
        static_for<0, 8>([&](auto K) { wgmma_rs_n128_tb0<LB_K128 + (K >> 2) * 1024 + (K & 3) * 2, HI128>(S, qf[K], bk, K != 0); });
        wg_commit();
        static_for<0, 8>([&](auto K) { wgmma_rs_n128_tb1<LB_MN128 + K * 128, HI128>(O, P[K], bv, K != 0 || (n & 3) != 1); });
        wg_commit();
        bar_arrive(2 + (wg ^ 1), 256);
        wg_wait<1>();
        fence_regs(S);
        ring.release(tk & 3);
        if ((n & 3) == 3 && n != 15) {
          fence_regs(qf);
#pragma unroll
          for (int i = 0; i < 8; i++) lds128(wprv + (n >> 2) * SLOT + i * 512, qf[i]);
        }
        float f0 = 1.f, f1 = 1.f;
        bool resc = newhead;
        if (newhead) {
          l0 += __shfl_xor_sync(0xffffffffu, l0, 1); l1 += __shfl_xor_sync(0xffffffffu, l1, 1);
          l0 += __shfl_xor_sync(0xffffffffu, l0, 2); l1 += __shfl_xor_sync(0xffffffffu, l1, 2);
          f0 = rcp_hw(l0); f1 = rcp_hw(l1);
          l0 = 0.f; l1 = 0.f;
          first_block_max();
          scale_sub();
        } else {
          scale_sub();
          int a0 = __vimax3_s32(__float_as_int(S[0]), __float_as_int(S[1]), __float_as_int(S[1]));
          int a1 = __vimax3_s32(__float_as_int(S[2]), __float_as_int(S[3]), __float_as_int(S[3]));
#pragma unroll
          for (int i = 1; i < 16; i++) {
            a0 = __vimax3_s32(a0, __float_as_int(S[4 * i]), __float_as_int(S[4 * i + 1]));
            a1 = __vimax3_s32(a1, __float_as_int(S[4 * i + 2]), __float_as_int(S[4 * i + 3]));
          }
          if (__any_sync(0xffffffffu, max(a0, a1) > TAU)) {
            a0 = max(a0, 0); a1 = max(a1, 0);
            a0 = max(a0, __shfl_xor_sync(0xffffffffu, a0, 1)); a1 = max(a1, __shfl_xor_sync(0xffffffffu, a1, 1));
            a0 = max(a0, __shfl_xor_sync(0xffffffffu, a0, 2)); a1 = max(a1, __shfl_xor_sync(0xffffffffu, a1, 2));
            const float d0 = __int_as_float(a0), d1 = __int_as_float(a1);
#pragma unroll
            for (int i = 0; i < 16; i++) { S[4 * i] -= d0; S[4 * i + 1] -= d0; S[4 * i + 2] -= d1; S[4 * i + 3] -= d1; }
            m0 += d0; m1 += d1;
            f0 = ex2(-d0); f1 = ex2(-d1);
            l0 *= f0; l1 *= f1;
            resc = true;
          }
        }
        exps(0, 4);
        wg_wait<0>();
        fence_regs(O);
        fence_regs(P);
        ring.release(tv & 3);
        if (resc) {
#pragma unroll
          for (int i = 0; i < 16; i++) {
            O[4 * i] *= f0; O[4 * i + 1] *= f0; O[4 * i + 2] *= f1; O[4 * i + 3] *= f1;
          }
          if (newhead) {
#pragma unroll
            for (int i = 0; i < 8; i++) {
              uint32_t o[4];
              pack8(o, O + 8 * i);
              sts128(wprv + ((n >> 2) - 1) * SLOT + i * 512, o[0], o[1], o[2], o[3]);
            }
          }
        }
        exps(4, 16);
#pragma unroll
        for (int i = 0; i < 8; i++) pack8(P[i], S + 8 * i);
        fence_regs(P);
        fence_regs(O);
      }
      {
        const uint32_t bv = ring.wait_full(3, 1);
        if (wg == 0) bar_sync(2, 256);
        wg_fence();
        static_for<0, 8>([&](auto K) { wgmma_rs_n128_tb1<LB_MN128 + K * 128, HI128>(O, P[K], bv, 1); });
        wg_commit();
#pragma unroll
        for (int i = 0; i < 16; i++) lds128(wprv + (i >> 3) * SLOT + (i & 7) * 512, o[i]);
        l0 += __shfl_xor_sync(0xffffffffu, l0, 1); l1 += __shfl_xor_sync(0xffffffffu, l1, 1);
        l0 += __shfl_xor_sync(0xffffffffu, l0, 2); l1 += __shfl_xor_sync(0xffffffffu, l1, 2);
        const float f0 = rcp_hw(l0), f1 = rcp_hw(l1);
        wg_wait<0>();
        fence_regs(O);
        ring.release(3);
#pragma unroll
        for (int i = 0; i < 8; i++) {
          qf[i][0] = pack_bf16(O[8 * i] * f0, O[8 * i + 1] * f0); qf[i][1] = pack_bf16(O[8 * i + 2] * f1, O[8 * i + 3] * f1);
          qf[i][2] = pack_bf16(O[8 * i + 4] * f0, O[8 * i + 5] * f0); qf[i][3] = pack_bf16(O[8 * i + 6] * f1, O[8 * i + 7] * f1);
        }
      }
    }
    fence_regs(qf);
    TS(4);
    asm volatile("setmaxnreg.dec.sync.aligned.u32 216;");
    bar_arrive(NB_PARK, 384);

    uint4* const Pout = p.s->P + ((size_t)(rt * 8 + warp) * 4 + (j >> 1)) * 1024 + (j & 1) * 128 + lane;
    const uint32_t tag = *(volatile uint32_t*)(smem_raw + SM_BAR + BAR_TAG);
    const uint32_t rbar = sb + SM_DBAR + warp * 16;
    uint32_t peer_land, peer_bar;
    asm("mapa.shared::cluster.u32 %0, %1, %2;" : "=r"(peer_land) : "r"(wprv), "r"(~j & 1));
    asm("mapa.shared::cluster.u32 %0, %1, %2;" : "=r"(peer_bar) : "r"(rbar), "r"(~j & 1));
    auto arm_and_ack = [&](uint32_t dep) {
      asm volatile(
          "{\n.reg .pred p;\nelect.sync _|p, 0xffffffff;\n"
          "@p mbarrier.arrive.expect_tx.shared::cta.b64 _, [%0], 2048;\n"
          "@p mbarrier.arrive.shared::cluster.b64 _, [%1];\n}\n" ::"r"(rbar), "r"(peer_bar + 8 + (dep & p.zero)) : "memory");
    };
    auto send_chunk = [&](float (&acc)[32], int pair) {
      mbar_wait(rbar + 8, pair & 1);
#pragma unroll
      for (int i = 0; i < 4; i++)
        asm volatile("st.async.weak.shared::cluster.mbarrier::complete_tx::bytes.v4.b32 [%0], {%1,%2,%3,%4}, [%5];"
                     ::"r"(peer_land + i * 512), "r"(pack_trunc(acc[8 * i], acc[8 * i + 1])), "r"(pack_trunc(acc[8 * i + 2], acc[8 * i + 3])),
                       "r"(pack_trunc(acc[8 * i + 4], acc[8 * i + 5])), "r"(pack_trunc(acc[8 * i + 6], acc[8 * i + 7])), "r"(peer_bar)
                     : "memory");
    };
    uint32_t pk[4][4];
    auto recv_chunk = [&](int pair) {
      mbar_wait(rbar, pair & 1);
#pragma unroll
      for (int i = 0; i < 4; i++) lds128(wprv + i * 512, pk[i]);
      if (pair < 7) arm_and_ack(pk[3][0]);
    };
    auto keep_chunk = [&](float (&acc)[32], int pair) {
      const uint32_t t1 = pair < 4;
#pragma unroll
      for (int i = 0; i < 4; i++) {
#pragma unroll
        for (int e = 0; e < 4; e++)
          pk[i][e] = pack_trunc(acc[8 * i + 2 * e] + __uint_as_float(pk[i][e] * 65536u + 0x8000u),
                                acc[8 * i + 2 * e + 1] + __uint_as_float(pk[i][e]));
        st_pkt(Pout + (pair & 3) * 256 + i * 32, (pk[i][0] & ~1u) | t1, pk[i][1], pk[i][2], pk[i][3]);
      }
      if (lane == 0)
        asm volatile("st.relaxed.gpu.global.u32 [%0], %1;" ::"l"(&p.s->sent[(rt * 8 + warp) * 8 + j]), "r"(tag * 32 + pair + 1) : "memory");
    };
    const uint4* const Gin = Gw + lane;
    auto g_issue = [&](int u) { warp_bulk_load(wblk + 2 * SLOT, Gw + u * 256, 4096, wbar); };

#pragma unroll
    for (int i = 16; i < 24; i++) lds128(wprv + 2 * SLOT + (i & 7) * 512, o[i]);
    fence_regs(o);
    arm_and_ack(o[23][0]);
    warp_arrive(sb + SM_SBAR);
#pragma unroll 1
    for (int cc = 0; cc < 8; cc++) {
      float acc[32];
      const uint32_t s0 = (cc & 1) * 2, b = ring.wait_full(s0, (cc >> 1) & 1);
      ring.wait_full(s0 + 1, (cc >> 1) & 1);
      wg_fence();
      static_for<0, 16>([&](auto K) { wgmma_rs_n64_tb1<K * 128, HI128>(acc, o[K], b, K != 0); });
      wg_commit();
      static_for<0, 16>([&](auto K) { wgmma_rs_n64_tb1<2048 + K * 128, HI128>(acc, K < 8 ? o[16 + (K & 7)] : qf[K & 7], b, 1); });
      wg_commit();
      wg_wait<1>();
      ring.release(s0);
      if (cc & 1) recv_chunk(cc >> 1);
      wg_wait<0>();
      TRU(4);
      ring.release(s0 + 1);
      fence_regs(acc);
      if (cc & 1) keep_chunk(acc, cc >> 1);
      else send_chunk(acc, cc >> 1);
      if (cc == 6) g_issue(0);
    }
    TS(5);

    uint32_t H[14][4];
    {
      float acca[96], accb[16];
      const uint4* const statp = &p.s->stat[(rt * 8 + warp) * 8];
#pragma unroll 1
      for (int u = 0; u < 4; u++) {
        uint32_t fa[8][4];
        const uint32_t s0 = (u & 1) * 2, b = ring.wait_full(s0, (u >> 1) & 1);
        ring.wait_full(s0 + 1, (u >> 1) & 1);
        mbar_wait(wbar, u & 1);
#pragma unroll
        for (int i = 0; i < 8; i++) lds128(wprv + 2 * SLOT + i * 512, fa[i]);
        verify8_tag0<512>(Gin + u * 256, fa);
        if (u < 2) g_issue(u + 1);
        const uint32_t ba = b + (j & 1) * 512, bb = b + ((j & 1) ? 4 : 1536);
        wg_fence();
        static_for<0, 4>([&](auto K) { wgmma_rs_n32_tb1<LB_W1 + K * 128, HI128>(accb, fa[K], bb, (u | K) != 0); });
        static_for<0, 4>([&](auto K) { wgmma_rs_n192_tb1<LB_W1 + K * 128, HI128>(acca, fa[K], ba, (u | K) != 0); });
        wg_commit();
        static_for<0, 4>([&](auto K) { wgmma_rs_n32_tb1<LB_W1 + 2048 + K * 128, HI128>(accb, fa[4 + K], bb, 1); });
        static_for<0, 4>([&](auto K) { wgmma_rs_n192_tb1<LB_W1 + 2048 + K * 128, HI128>(acca, fa[4 + K], ba, 1); });
        wg_commit();
        wg_wait<1>();
        ring.release(s0);
        if (u == 2) g_issue(3);
        if (u == 3) warp_bulk_load(wblk + 2 * SLOT, statp, 128, wbar + 16);
        wg_wait<0>();
        TRU(4);
        ring.release(s0 + 1);
      }
      fence_regs(acca);
      fence_regs(accb);
      TS(9);
      mbar_wait(bars + BAR_UV, 0);
      uint32_t xr[4];
      mbar_wait(wbar + 16, 1);
      lds128(wblk + 2 * SLOT + gq * 16, xr);
      {
        int spins = 0;
        while (((xr[0] ^ tag) & 1u) && ++spins < SPIN_LIMIT) ld_pkt(statp + gq, xr);
      }
      const float ra0 = __uint_as_float(xr[0]), rb0 = __uint_as_float(xr[1]), ra1 = __uint_as_float(xr[2]),
                  rb1 = __uint_as_float(xr[3]);
#pragma unroll
      for (int i = 0; i < 28; i++) {
        uint32_t m[4];
        lds128(sb + SM_TAB + (i * 4 + q) * 16, m);
        const float u0 = __uint_as_float(m[0]), u1 = __uint_as_float(m[1]), w0 = __uint_as_float(m[2]), w1 = __uint_as_float(m[3]);
        const float* acc = i < 24 ? acca + 4 * i : accb + 4 * (i - 24);
        const float z0 = fmaf(acc[0], ra0, fmaf(u0, rb0, w0)), z1 = fmaf(acc[1], ra0, fmaf(u1, rb0, w1));
        const float z2 = fmaf(acc[2], ra1, fmaf(u0, rb1, w0)), z3 = fmaf(acc[3], ra1, fmaf(u1, rb1, w1));
        H[i >> 1][(i & 1) * 2] = pack_bf16(fmaf(z0, tanh_hw(z0), z0), fmaf(z1, tanh_hw(z1), z1));
        H[i >> 1][(i & 1) * 2 + 1] = pack_bf16(fmaf(z2, tanh_hw(z2), z2), fmaf(z3, tanh_hw(z3), z3));
      }
    }
    fence_regs(H);
    TS(10);
    const int go = 24 + warp;
    {
      float accs[32], acck[32];
      auto ffn2 = [&](float (&acc)[32], uint32_t b) {
        const uint32_t ba = b + (j & 1) * 256, bb = b - (j & 1) * 1536;
        static_for<0, 14>([&](auto K) { wgmma_rs_n64_tb1<K * 128, HI128>(acc, H[K], K < 12 ? ba : bb, K != 0); });
        wg_commit();
      };
      {
        const uint32_t b = ring.wait_full(0, 0);
        wg_fence();
        ffn2(accs, b);
        wg_wait<0>();
        TRU(4);
        ring.release(0);
        fence_regs(accs);
        send_chunk(accs, 4);
      }
#pragma unroll 1
      for (int pc = 0; pc < 3; pc++) {
        const uint32_t tk = 2 * pc + 1, ts = tk + 1;
        const uint32_t bk = ring.wait_full(tk & 3, (tk >> 2) & 1), bs = ring.wait_full(ts & 3, (ts >> 2) & 1);
        wg_fence();
        ffn2(acck, bk);
        ffn2(accs, bs);
        wg_wait<1>();
        ring.release(tk & 3);
        recv_chunk(4 + pc);
        fence_regs(acck);
        keep_chunk(acck, 4 + pc);
        wg_wait<0>();
        TRU(4);
        ring.release(ts & 3);
        fence_regs(accs);
        send_chunk(accs, 5 + pc);
      }
      const uint32_t b = ring.wait_full(3, 1);
      wg_fence();
      ffn2(acck, b);
      recv_chunk(7);
      wg_wait<0>();
      fence_regs(acck);
      keep_chunk(acck, 7);
    }
    TS(11);
    {
      const uint4* const Pown = p.s->P + (size_t)(rt * 8 + j) * 4096 + go * 32 + lane;
      uint32_t r[4][4];
      float y[8];
      mbar_wait(bars + BAR_X2, 0);
      issue_pkts<0, 4>(Pown, 1024, r);
      verify4_rt<16384>(Pown, r, 0);
      TS(13);
#pragma unroll
      for (int s = 0; s < 4; s++) add_partial(y, r[s], 0x10000u, s == 0);
      const uint32_t gt = sb + SM_TAB + 1792 + ((go - 24) * 4 + q) * 8;
      store_out(p.out, (uint32_t)(rt * 128 + 16 * j + gq) * 256 + go * 8 + q, sb + SM_PARK + SLOT + (go >> 2) * 4096 + (go & 3) * 512 + lane * 16,
                lds32(gt), lds32(gt + 4), y);
    }
    TS(12);
    if (bid == 0 && tid == 0) asm volatile("st.relaxed.gpu.global.u32 [%0], %1;" ::"l"(&p.s->epoch), "r"(tag) : "memory");
  }
}

typedef CUresult (*EncodeFn)(CUtensorMap*, CUtensorMapDataType, cuuint32_t, void*, const cuuint64_t*, const cuuint64_t*,
                             const cuuint32_t*, const cuuint32_t*, CUtensorMapInterleave, CUtensorMapSwizzle,
                             CUtensorMapL2promotion, CUtensorMapFloatOOBfill);

static void make_map(EncodeFn fn, CUtensorMap* tm, const void* ptr, int inner, int rows, int cols, int box_rows, int box_outer,
                     CUtensorMapSwizzle swz) {
  cuuint64_t gd[3] = {(cuuint64_t)inner, (cuuint64_t)rows, (cuuint64_t)(cols / inner)};
  cuuint64_t gs[2] = {(cuuint64_t)cols * 2, (cuuint64_t)inner * 2};
  cuuint32_t bx[3] = {(cuuint32_t)inner, (cuuint32_t)box_rows, (cuuint32_t)box_outer};
  cuuint32_t es[3] = {1, 1, 1};
  fn(tm, CU_TENSOR_MAP_DATA_TYPE_BFLOAT16, 3, const_cast<void*>(ptr), gd, gs, bx, es, CU_TENSOR_MAP_INTERLEAVE_NONE, swz,
     CU_TENSOR_MAP_L2_PROMOTION_L2_128B, CU_TENSOR_MAP_FLOAT_OOB_FILL_NONE);
}

extern "C" void kernel_launch(void* const* d_in, const int* in_sizes, int n_in, void* d_out, int out_size) {
  (void)in_sizes; (void)n_in; (void)out_size;
  void* fnp = nullptr;
  cudaDriverEntryPointQueryResult qr;
  cudaGetDriverEntryPoint("cuTensorMapEncodeTiled", &fnp, cudaEnableDefault, &qr);
  EncodeFn fn = (EncodeFn)fnp;
  CUtensorMap tmWq, tmK, tmV, tmWo, tmW1, tmW2, tmWm, tmX;
  make_map(fn, &tmWq, d_in[3], 64, 512, 4096, 128, 2, CU_TENSOR_MAP_SWIZZLE_128B);
  make_map(fn, &tmK, d_in[1], 64, 8 * SK, 128, 128, 2, CU_TENSOR_MAP_SWIZZLE_128B);
  make_map(fn, &tmV, d_in[2], 64, 8 * SK, 128, 128, 2, CU_TENSOR_MAP_SWIZZLE_128B);
  make_map(fn, &tmWo, d_in[4], 64, 4096, 512, 256, 1, CU_TENSOR_MAP_SWIZZLE_128B);
  make_map(fn, &tmW1, d_in[6], 64, 512, FF, 64, 4, CU_TENSOR_MAP_SWIZZLE_128B);
  make_map(fn, &tmW2, d_in[7], 64, FF, 512, 224, 1, CU_TENSOR_MAP_SWIZZLE_128B);
  make_map(fn, &tmWm, d_in[9], 8, 512, 3072, 256, 1, CU_TENSOR_MAP_SWIZZLE_NONE);
  make_map(fn, &tmX, d_in[0], 16, 2048, 512, 16, 4, CU_TENSOR_MAP_SWIZZLE_NONE);
  Params p;
  p.x = (const __nv_bfloat16*)d_in[0];
  p.c = (const __nv_bfloat16*)d_in[8];
  p.wmod = (const __nv_bfloat16*)d_in[9];
  p.wo = (const __nv_bfloat16*)d_in[4];
  p.w1 = (const __nv_bfloat16*)d_in[6];
  p.w2 = (const __nv_bfloat16*)d_in[7];
  p.out = (__nv_bfloat16*)d_out;
  p.zero = 0;
  cudaGetSymbolAddress((void**)&p.s, g_scratch);
  cudaFuncSetAttribute(adaln_block_kernel, cudaFuncAttributeMaxDynamicSharedMemorySize, SM_TOTAL);
  cudaLaunchConfig_t cfg = {};
  cfg.gridDim = 128; cfg.blockDim = 512; cfg.dynamicSmemBytes = SM_TOTAL; cfg.stream = cudaStreamPerThread;
  cudaLaunchAttribute at[1];
  at[0].id = cudaLaunchAttributeClusterDimension; at[0].val.clusterDim.x = 2; at[0].val.clusterDim.y = 1; at[0].val.clusterDim.z = 1;
  cfg.attrs = at; cfg.numAttrs = 1;
  cudaLaunchKernelEx(&cfg, adaln_block_kernel, tmWq, tmK, tmV, tmWo, tmW1, tmW2, tmWm, tmX, p);
}
```

```cpp
#include <cuda_runtime.h>
#include <cuda_bf16.h>
#include <cuda.h>
#include <stdint.h>

template <int OFF, uint32_t HI>
__device__ __forceinline__ void wgmma_rs_n128_tb0(float (&d)[64], const uint32_t (&a)[4], uint32_t lo, int sd) {
  asm volatile("{\n.reg .pred p;\n.reg .b32 l;\n.reg .b64 db;\nsetp.ne.b32 p, %69, 0;\n"
    "add.u32 l, %68, %70;\nmov.b64 db, {l, %71};\n"
    "wgmma.mma_async.sync.aligned.m64n128k16.f32.bf16.bf16 "
    "{%0,%1,%2,%3,%4,%5,%6,%7,%8,%9,%10,%11,%12,%13,%14,%15,"
    "%16,%17,%18,%19,%20,%21,%22,%23,%24,%25,%26,%27,%28,%29,%30,%31,"
    "%32,%33,%34,%35,%36,%37,%38,%39,%40,%41,%42,%43,%44,%45,%46,%47,"
    "%48,%49,%50,%51,%52,%53,%54,%55,%56,%57,%58,%59,%60,%61,%62,%63}, "
    "{%64,%65,%66,%67}, db, p, 1, 1, 0;\n}\n"
    : "+f"(d[0]), "+f"(d[1]), "+f"(d[2]), "+f"(d[3]), "+f"(d[4]), "+f"(d[5]), "+f"(d[6]), "+f"(d[7]),
      "+f"(d[8]), "+f"(d[9]), "+f"(d[10]), "+f"(d[11]), "+f"(d[12]), "+f"(d[13]), "+f"(d[14]), "+f"(d[15]),
      "+f"(d[16]), "+f"(d[17]), "+f"(d[18]), "+f"(d[19]), "+f"(d[20]), "+f"(d[21]), "+f"(d[22]), "+f"(d[23]),
      "+f"(d[24]), "+f"(d[25]), "+f"(d[26]), "+f"(d[27]), "+f"(d[28]), "+f"(d[29]), "+f"(d[30]), "+f"(d[31]),
      "+f"(d[32]), "+f"(d[33]), "+f"(d[34]), "+f"(d[35]), "+f"(d[36]), "+f"(d[37]), "+f"(d[38]), "+f"(d[39]),
      "+f"(d[40]), "+f"(d[41]), "+f"(d[42]), "+f"(d[43]), "+f"(d[44]), "+f"(d[45]), "+f"(d[46]), "+f"(d[47]),
      "+f"(d[48]), "+f"(d[49]), "+f"(d[50]), "+f"(d[51]), "+f"(d[52]), "+f"(d[53]), "+f"(d[54]), "+f"(d[55]),
      "+f"(d[56]), "+f"(d[57]), "+f"(d[58]), "+f"(d[59]), "+f"(d[60]), "+f"(d[61]), "+f"(d[62]), "+f"(d[63])
    : "r"(a[0]), "r"(a[1]), "r"(a[2]), "r"(a[3]), "r"(lo), "r"(sd), "n"(OFF), "n"(HI));
}

template <int OFF, uint32_t HI>
__device__ __forceinline__ void wgmma_rs_n128_tb1(float (&d)[64], const uint32_t (&a)[4], uint32_t lo, int sd) {
  asm volatile("{\n.reg .pred p;\n.reg .b32 l;\n.reg .b64 db;\nsetp.ne.b32 p, %69, 0;\n"
    "add.u32 l, %68, %70;\nmov.b64 db, {l, %71};\n"
    "wgmma.mma_async.sync.aligned.m64n128k16.f32.bf16.bf16 "
    "{%0,%1,%2,%3,%4,%5,%6,%7,%8,%9,%10,%11,%12,%13,%14,%15,"
    "%16,%17,%18,%19,%20,%21,%22,%23,%24,%25,%26,%27,%28,%29,%30,%31,"
    "%32,%33,%34,%35,%36,%37,%38,%39,%40,%41,%42,%43,%44,%45,%46,%47,"
    "%48,%49,%50,%51,%52,%53,%54,%55,%56,%57,%58,%59,%60,%61,%62,%63}, "
    "{%64,%65,%66,%67}, db, p, 1, 1, 1;\n}\n"
    : "+f"(d[0]), "+f"(d[1]), "+f"(d[2]), "+f"(d[3]), "+f"(d[4]), "+f"(d[5]), "+f"(d[6]), "+f"(d[7]),
      "+f"(d[8]), "+f"(d[9]), "+f"(d[10]), "+f"(d[11]), "+f"(d[12]), "+f"(d[13]), "+f"(d[14]), "+f"(d[15]),
      "+f"(d[16]), "+f"(d[17]), "+f"(d[18]), "+f"(d[19]), "+f"(d[20]), "+f"(d[21]), "+f"(d[22]), "+f"(d[23]),
      "+f"(d[24]), "+f"(d[25]), "+f"(d[26]), "+f"(d[27]), "+f"(d[28]), "+f"(d[29]), "+f"(d[30]), "+f"(d[31]),
      "+f"(d[32]), "+f"(d[33]), "+f"(d[34]), "+f"(d[35]), "+f"(d[36]), "+f"(d[37]), "+f"(d[38]), "+f"(d[39]),
      "+f"(d[40]), "+f"(d[41]), "+f"(d[42]), "+f"(d[43]), "+f"(d[44]), "+f"(d[45]), "+f"(d[46]), "+f"(d[47]),
      "+f"(d[48]), "+f"(d[49]), "+f"(d[50]), "+f"(d[51]), "+f"(d[52]), "+f"(d[53]), "+f"(d[54]), "+f"(d[55]),
      "+f"(d[56]), "+f"(d[57]), "+f"(d[58]), "+f"(d[59]), "+f"(d[60]), "+f"(d[61]), "+f"(d[62]), "+f"(d[63])
    : "r"(a[0]), "r"(a[1]), "r"(a[2]), "r"(a[3]), "r"(lo), "r"(sd), "n"(OFF), "n"(HI));
}

template <int OFF, uint32_t HI>
__device__ __forceinline__ void wgmma_rs_n192_tb1(float (&d)[96], const uint32_t (&a)[4], uint32_t lo, int sd) {
  asm volatile("{\n.reg .pred p;\n.reg .b32 l;\n.reg .b64 db;\nsetp.ne.b32 p, %101, 0;\n"
    "add.u32 l, %100, %102;\nmov.b64 db, {l, %103};\n"
    "wgmma.mma_async.sync.aligned.m64n192k16.f32.bf16.bf16 "
    "{%0,%1,%2,%3,%4,%5,%6,%7,%8,%9,%10,%11,%12,%13,%14,%15,"
    "%16,%17,%18,%19,%20,%21,%22,%23,%24,%25,%26,%27,%28,%29,%30,%31,"
    "%32,%33,%34,%35,%36,%37,%38,%39,%40,%41,%42,%43,%44,%45,%46,%47,"
    "%48,%49,%50,%51,%52,%53,%54,%55,%56,%57,%58,%59,%60,%61,%62,%63,"
    "%64,%65,%66,%67,%68,%69,%70,%71,%72,%73,%74,%75,%76,%77,%78,%79,"
    "%80,%81,%82,%83,%84,%85,%86,%87,%88,%89,%90,%91,%92,%93,%94,%95}, "
    "{%96,%97,%98,%99}, db, p, 1, 1, 1;\n}\n"
    : "+f"(d[0]), "+f"(d[1]), "+f"(d[2]), "+f"(d[3]), "+f"(d[4]), "+f"(d[5]), "+f"(d[6]), "+f"(d[7]),
      "+f"(d[8]), "+f"(d[9]), "+f"(d[10]), "+f"(d[11]), "+f"(d[12]), "+f"(d[13]), "+f"(d[14]), "+f"(d[15]),
      "+f"(d[16]), "+f"(d[17]), "+f"(d[18]), "+f"(d[19]), "+f"(d[20]), "+f"(d[21]), "+f"(d[22]), "+f"(d[23]),
      "+f"(d[24]), "+f"(d[25]), "+f"(d[26]), "+f"(d[27]), "+f"(d[28]), "+f"(d[29]), "+f"(d[30]), "+f"(d[31]),
      "+f"(d[32]), "+f"(d[33]), "+f"(d[34]), "+f"(d[35]), "+f"(d[36]), "+f"(d[37]), "+f"(d[38]), "+f"(d[39]),
      "+f"(d[40]), "+f"(d[41]), "+f"(d[42]), "+f"(d[43]), "+f"(d[44]), "+f"(d[45]), "+f"(d[46]), "+f"(d[47]),
      "+f"(d[48]), "+f"(d[49]), "+f"(d[50]), "+f"(d[51]), "+f"(d[52]), "+f"(d[53]), "+f"(d[54]), "+f"(d[55]),
      "+f"(d[56]), "+f"(d[57]), "+f"(d[58]), "+f"(d[59]), "+f"(d[60]), "+f"(d[61]), "+f"(d[62]), "+f"(d[63]),
      "+f"(d[64]), "+f"(d[65]), "+f"(d[66]), "+f"(d[67]), "+f"(d[68]), "+f"(d[69]), "+f"(d[70]), "+f"(d[71]),
      "+f"(d[72]), "+f"(d[73]), "+f"(d[74]), "+f"(d[75]), "+f"(d[76]), "+f"(d[77]), "+f"(d[78]), "+f"(d[79]),
      "+f"(d[80]), "+f"(d[81]), "+f"(d[82]), "+f"(d[83]), "+f"(d[84]), "+f"(d[85]), "+f"(d[86]), "+f"(d[87]),
      "+f"(d[88]), "+f"(d[89]), "+f"(d[90]), "+f"(d[91]), "+f"(d[92]), "+f"(d[93]), "+f"(d[94]), "+f"(d[95])
    : "r"(a[0]), "r"(a[1]), "r"(a[2]), "r"(a[3]), "r"(lo), "r"(sd), "n"(OFF), "n"(HI));
}

template <int OFF, uint32_t HI>
__device__ __forceinline__ void wgmma_rs_n32_tb1(float (&d)[16], const uint32_t (&a)[4], uint32_t lo, int sd) {
  asm volatile("{\n.reg .pred p;\n.reg .b32 l;\n.reg .b64 db;\nsetp.ne.b32 p, %21, 0;\n"
    "add.u32 l, %20, %22;\nmov.b64 db, {l, %23};\n"
    "wgmma.mma_async.sync.aligned.m64n32k16.f32.bf16.bf16 "
    "{%0,%1,%2,%3,%4,%5,%6,%7,%8,%9,%10,%11,%12,%13,%14,%15}, "
    "{%16,%17,%18,%19}, db, p, 1, 1, 1;\n}\n"
    : "+f"(d[0]), "+f"(d[1]), "+f"(d[2]), "+f"(d[3]), "+f"(d[4]), "+f"(d[5]), "+f"(d[6]), "+f"(d[7]),
      "+f"(d[8]), "+f"(d[9]), "+f"(d[10]), "+f"(d[11]), "+f"(d[12]), "+f"(d[13]), "+f"(d[14]), "+f"(d[15])
    : "r"(a[0]), "r"(a[1]), "r"(a[2]), "r"(a[3]), "r"(lo), "r"(sd), "n"(OFF), "n"(HI));
}

template <int OFF, uint32_t HI>
__device__ __forceinline__ void wgmma_rs_n64_tb1(float (&d)[32], const uint32_t (&a)[4], uint32_t lo, int sd) {
  asm volatile("{\n.reg .pred p;\n.reg .b32 l;\n.reg .b64 db;\nsetp.ne.b32 p, %37, 0;\n"
    "add.u32 l, %36, %38;\nmov.b64 db, {l, %39};\n"
    "wgmma.mma_async.sync.aligned.m64n64k16.f32.bf16.bf16 "
    "{%0,%1,%2,%3,%4,%5,%6,%7,%8,%9,%10,%11,%12,%13,%14,%15,"
    "%16,%17,%18,%19,%20,%21,%22,%23,%24,%25,%26,%27,%28,%29,%30,%31}, "
    "{%32,%33,%34,%35}, db, p, 1, 1, 1;\n}\n"
    : "+f"(d[0]), "+f"(d[1]), "+f"(d[2]), "+f"(d[3]), "+f"(d[4]), "+f"(d[5]), "+f"(d[6]), "+f"(d[7]),
      "+f"(d[8]), "+f"(d[9]), "+f"(d[10]), "+f"(d[11]), "+f"(d[12]), "+f"(d[13]), "+f"(d[14]), "+f"(d[15]),
      "+f"(d[16]), "+f"(d[17]), "+f"(d[18]), "+f"(d[19]), "+f"(d[20]), "+f"(d[21]), "+f"(d[22]), "+f"(d[23]),
      "+f"(d[24]), "+f"(d[25]), "+f"(d[26]), "+f"(d[27]), "+f"(d[28]), "+f"(d[29]), "+f"(d[30]), "+f"(d[31])
    : "r"(a[0]), "r"(a[1]), "r"(a[2]), "r"(a[3]), "r"(lo), "r"(sd), "n"(OFF), "n"(HI));
}

template <int STR>
__device__ __forceinline__ void verify8_tag1(const uint4* p, uint32_t (*r)[4]) {
  asm volatile("{\n.reg .pred p, q;\n.reg .b32 a, n;\nmov.u32 n, 0;\n"
    "LAB_CHK:\n"
    "and.b32 a, %0, %4;\n"
    "and.b32 a, a, %8;\n"
    "and.b32 a, a, %12;\n"
    "and.b32 a, a, %16;\n"
    "and.b32 a, a, %20;\n"
    "and.b32 a, a, %24;\n"
    "and.b32 a, a, %28;\n"
    "and.b32 a, a, 1;\nsetp.eq.u32 p, a, 1;\nvote.sync.all.pred p, p, 0xffffffff;\n"
    "@p bra.uni LAB_OK;\n"
    "and.b32 a, %0, 1;\nsetp.ne.u32 q, a, 1;\n"
    "@q ld.relaxed.gpu.global.v4.b32 {%0,%1,%2,%3}, [%32+%33];\n"
    "and.b32 a, %4, 1;\nsetp.ne.u32 q, a, 1;\n"
    "@q ld.relaxed.gpu.global.v4.b32 {%4,%5,%6,%7}, [%32+%34];\n"
    "and.b32 a, %8, 1;\nsetp.ne.u32 q, a, 1;\n"
    "@q ld.relaxed.gpu.global.v4.b32 {%8,%9,%10,%11}, [%32+%35];\n"
    "and.b32 a, %12, 1;\nsetp.ne.u32 q, a, 1;\n"
    "@q ld.relaxed.gpu.global.v4.b32 {%12,%13,%14,%15}, [%32+%36];\n"
    "and.b32 a, %16, 1;\nsetp.ne.u32 q, a, 1;\n"
    "@q ld.relaxed.gpu.global.v4.b32 {%16,%17,%18,%19}, [%32+%37];\n"
    "and.b32 a, %20, 1;\nsetp.ne.u32 q, a, 1;\n"
    "@q ld.relaxed.gpu.global.v4.b32 {%20,%21,%22,%23}, [%32+%38];\n"
    "and.b32 a, %24, 1;\nsetp.ne.u32 q, a, 1;\n"
    "@q ld.relaxed.gpu.global.v4.b32 {%24,%25,%26,%27}, [%32+%39];\n"
    "and.b32 a, %28, 1;\nsetp.ne.u32 q, a, 1;\n"
    "@q ld.relaxed.gpu.global.v4.b32 {%28,%29,%30,%31}, [%32+%40];\n"
    "add.u32 n, n, 1;\nsetp.lt.u32 q, n, 262144;\n@q bra.uni LAB_CHK;\n"
    "LAB_OK:\n"
    "}\n"
    : "+r"(r[0][0]), "+r"(r[0][1]), "+r"(r[0][2]), "+r"(r[0][3]), "+r"(r[1][0]), "+r"(r[1][1]), "+r"(r[1][2]), "+r"(r[1][3]),
      "+r"(r[2][0]), "+r"(r[2][1]), "+r"(r[2][2]), "+r"(r[2][3]), "+r"(r[3][0]), "+r"(r[3][1]), "+r"(r[3][2]), "+r"(r[3][3]),
      "+r"(r[4][0]), "+r"(r[4][1]), "+r"(r[4][2]), "+r"(r[4][3]), "+r"(r[5][0]), "+r"(r[5][1]), "+r"(r[5][2]), "+r"(r[5][3]),
      "+r"(r[6][0]), "+r"(r[6][1]), "+r"(r[6][2]), "+r"(r[6][3]), "+r"(r[7][0]), "+r"(r[7][1]), "+r"(r[7][2]), "+r"(r[7][3])
    : "l"(p), "n"(0 * STR), "n"(1 * STR), "n"(2 * STR), "n"(3 * STR), "n"(4 * STR), "n"(5 * STR), "n"(6 * STR), "n"(7 * STR)
    : "memory");
}

template <int STR>
__device__ __forceinline__ void verify4_rt(const uint4* p, uint32_t (*r)[4], uint32_t tag) {
  asm volatile("{\n.reg .pred p, q;\n.reg .b32 a, b, n;\nmov.u32 n, 0;\n"
    "LAB_CHK:\n"
    "lop3.b32 a, %0, %4, %21, 0x7e;\n"
    "lop3.b32 b, %8, %12, %21, 0x7e;\nor.b32 a, a, b;\n"
    "and.b32 a, a, 1;\nsetp.eq.u32 p, a, 0;\nvote.sync.all.pred p, p, 0xffffffff;\n"
    "@p bra.uni LAB_OK;\n"
    "and.b32 a, %0, 1;\nsetp.ne.u32 q, a, %21;\n"
    "@q ld.relaxed.gpu.global.v4.b32 {%0,%1,%2,%3}, [%16+%17];\n"
    "and.b32 a, %4, 1;\nsetp.ne.u32 q, a, %21;\n"
    "@q ld.relaxed.gpu.global.v4.b32 {%4,%5,%6,%7}, [%16+%18];\n"
    "and.b32 a, %8, 1;\nsetp.ne.u32 q, a, %21;\n"
    "@q ld.relaxed.gpu.global.v4.b32 {%8,%9,%10,%11}, [%16+%19];\n"
    "and.b32 a, %12, 1;\nsetp.ne.u32 q, a, %21;\n"
    "@q ld.relaxed.gpu.global.v4.b32 {%12,%13,%14,%15}, [%16+%20];\n"
    "add.u32 n, n, 1;\nsetp.lt.u32 q, n, 262144;\n@q bra.uni LAB_CHK;\n"
    "LAB_OK:\n}\n"
    : "+r"(r[0][0]), "+r"(r[0][1]), "+r"(r[0][2]), "+r"(r[0][3]), "+r"(r[1][0]), "+r"(r[1][1]), "+r"(r[1][2]), "+r"(r[1][3]),
      "+r"(r[2][0]), "+r"(r[2][1]), "+r"(r[2][2]), "+r"(r[2][3]), "+r"(r[3][0]), "+r"(r[3][1]), "+r"(r[3][2]), "+r"(r[3][3])
    : "l"(p), "n"(0 * STR), "n"(1 * STR), "n"(2 * STR), "n"(3 * STR), "r"(tag)
    : "memory");
}

template <int STR>
__device__ __forceinline__ void verify8_tag0(const uint4* p, uint32_t (*r)[4]) {
  asm volatile("{\n.reg .pred p, q;\n.reg .b32 a, n;\nmov.u32 n, 0;\n"
    "LAB_CHK:\n"
    "or.b32 a, %0, %4;\n"
    "or.b32 a, a, %8;\n"
    "or.b32 a, a, %12;\n"
    "or.b32 a, a, %16;\n"
    "or.b32 a, a, %20;\n"
    "or.b32 a, a, %24;\n"
    "or.b32 a, a, %28;\n"
    "and.b32 a, a, 1;\nsetp.eq.u32 p, a, 0;\nvote.sync.all.pred p, p, 0xffffffff;\n"
    "@p bra.uni LAB_OK;\n"
    "and.b32 a, %0, 1;\nsetp.ne.u32 q, a, 0;\n"
    "@q ld.relaxed.gpu.global.v4.b32 {%0,%1,%2,%3}, [%32+%33];\n"
    "and.b32 a, %4, 1;\nsetp.ne.u32 q, a, 0;\n"
    "@q ld.relaxed.gpu.global.v4.b32 {%4,%5,%6,%7}, [%32+%34];\n"
    "and.b32 a, %8, 1;\nsetp.ne.u32 q, a, 0;\n"
    "@q ld.relaxed.gpu.global.v4.b32 {%8,%9,%10,%11}, [%32+%35];\n"
    "and.b32 a, %12, 1;\nsetp.ne.u32 q, a, 0;\n"
    "@q ld.relaxed.gpu.global.v4.b32 {%12,%13,%14,%15}, [%32+%36];\n"
    "and.b32 a, %16, 1;\nsetp.ne.u32 q, a, 0;\n"
    "@q ld.relaxed.gpu.global.v4.b32 {%16,%17,%18,%19}, [%32+%37];\n"
    "and.b32 a, %20, 1;\nsetp.ne.u32 q, a, 0;\n"
    "@q ld.relaxed.gpu.global.v4.b32 {%20,%21,%22,%23}, [%32+%38];\n"
    "and.b32 a, %24, 1;\nsetp.ne.u32 q, a, 0;\n"
    "@q ld.relaxed.gpu.global.v4.b32 {%24,%25,%26,%27}, [%32+%39];\n"
    "and.b32 a, %28, 1;\nsetp.ne.u32 q, a, 0;\n"
    "@q ld.relaxed.gpu.global.v4.b32 {%28,%29,%30,%31}, [%32+%40];\n"
    "add.u32 n, n, 1;\nsetp.lt.u32 q, n, 262144;\n@q bra.uni LAB_CHK;\n"
    "LAB_OK:\n"
    "or.b32 %0, %0, 1;\n"
    "or.b32 %4, %4, 1;\n"
    "or.b32 %8, %8, 1;\n"
    "or.b32 %12, %12, 1;\n"
    "or.b32 %16, %16, 1;\n"
    "or.b32 %20, %20, 1;\n"
    "or.b32 %24, %24, 1;\n"
    "or.b32 %28, %28, 1;\n"
    "}\n"
    : "+r"(r[0][0]), "+r"(r[0][1]), "+r"(r[0][2]), "+r"(r[0][3]), "+r"(r[1][0]), "+r"(r[1][1]), "+r"(r[1][2]), "+r"(r[1][3]),
      "+r"(r[2][0]), "+r"(r[2][1]), "+r"(r[2][2]), "+r"(r[2][3]), "+r"(r[3][0]), "+r"(r[3][1]), "+r"(r[3][2]), "+r"(r[3][3]),
      "+r"(r[4][0]), "+r"(r[4][1]), "+r"(r[4][2]), "+r"(r[4][3]), "+r"(r[5][0]), "+r"(r[5][1]), "+r"(r[5][2]), "+r"(r[5][3]),
      "+r"(r[6][0]), "+r"(r[6][1]), "+r"(r[6][2]), "+r"(r[6][3]), "+r"(r[7][0]), "+r"(r[7][1]), "+r"(r[7][2]), "+r"(r[7][3])
    : "l"(p), "n"(0 * STR), "n"(1 * STR), "n"(2 * STR), "n"(3 * STR), "n"(4 * STR), "n"(5 * STR), "n"(6 * STR), "n"(7 * STR)
    : "memory");
}

#define SPIN_LIMIT (1 << 18)

__device__ __forceinline__ uint32_t smem_u32(const void* p) { return (uint32_t)__cvta_generic_to_shared(p); }
__device__ __forceinline__ void mbar_init(uint32_t a, uint32_t c) {
  asm volatile("mbarrier.init.shared::cta.b64 [%0], %1;" ::"r"(a), "r"(c) : "memory");
}
__device__ __forceinline__ void mbar_expect(uint32_t a, uint32_t b) {
  asm volatile("mbarrier.arrive.expect_tx.shared::cta.b64 _, [%0], %1;" ::"r"(a), "r"(b) : "memory");
}
__device__ __forceinline__ void mbar_arrive(uint32_t a) {
  asm volatile("mbarrier.arrive.shared::cta.b64 _, [%0];" ::"r"(a) : "memory");
}
__device__ __forceinline__ void mbar_wait(uint32_t a, uint32_t parity) {
  asm volatile(
      "{\n.reg .pred p;\n.reg .u32 n;\nmov.u32 n, 0;\n"
      "LAB_WAIT:\n"
      "mbarrier.try_wait.parity.shared::cta.b64 p, [%0], %1;\n"
      "@p bra LAB_DONE;\n"
      "add.u32 n, n, 1;\n"
      "setp.lt.u32 p, n, 262144;\n"
      "@p bra LAB_WAIT;\n"
      "LAB_DONE:\n}\n" ::"r"(a), "r"(parity) : "memory");
}
__device__ __forceinline__ bool mbar_test(uint32_t a, uint32_t parity) {
  uint32_t ok;
  asm volatile("{\n.reg .pred p;\nmbarrier.test_wait.parity.shared::cta.b64 p, [%1], %2;\nselp.u32 %0, 1, 0, p;\n}\n"
               : "=r"(ok) : "r"(a), "r"(parity) : "memory");
  return ok;
}
__device__ __forceinline__ void tma3d(uint32_t dst, const CUtensorMap* tm, uint32_t bar, int c0, int c1, int c2) {
  asm volatile(
      "cp.async.bulk.tensor.3d.shared::cluster.global.mbarrier::complete_tx::bytes [%0], [%1, {%3,%4,%5}], [%2];"
      ::"r"(dst), "l"(tm), "r"(bar), "r"(c0), "r"(c1), "r"(c2) : "memory");
}
__device__ __forceinline__ void wg_fence() { asm volatile("wgmma.fence.sync.aligned;" ::: "memory"); }
__device__ __forceinline__ void wg_commit() { asm volatile("wgmma.commit_group.sync.aligned;" ::: "memory"); }
template <int N> __device__ __forceinline__ void wg_wait() {
  asm volatile("wgmma.wait_group.sync.aligned %0;" ::"n"(N) : "memory");
}
template <int N> __device__ __forceinline__ void fence_regs(float (&d)[N]) {
#pragma unroll
  for (int i = 0; i < N; i++) asm volatile("" : "+f"(d[i])::"memory");
}
template <int N> __device__ __forceinline__ void fence_regs(uint32_t (&d)[N][4]) {
#pragma unroll
  for (int i = 0; i < N; i++) asm volatile("" : "+r"(d[i][0]), "+r"(d[i][1]), "+r"(d[i][2]), "+r"(d[i][3])::"memory");
}
template <int N> __device__ __forceinline__ void fence_frags(uint32_t (*d)[4]) {
#pragma unroll
  for (int i = 0; i < N; i++) asm volatile("" : "+r"(d[i][0]), "+r"(d[i][1]), "+r"(d[i][2]), "+r"(d[i][3])::"memory");
}
__device__ __forceinline__ void bar_sync(int id, int n) { asm volatile("bar.sync %0, %1;" ::"r"(id), "r"(n) : "memory"); }
__device__ __forceinline__ void bar_arrive(int id, int n) { asm volatile("bar.arrive %0, %1;" ::"r"(id), "r"(n) : "memory"); }

__device__ __forceinline__ uint32_t pack_bf16(float lo, float hi) {
  uint32_t r;
  asm("cvt.rn.bf16x2.f32 %0, %1, %2;" : "=r"(r) : "f"(hi), "f"(lo));
  return r;
}
__device__ __forceinline__ float bf_lo(uint32_t w) { return __uint_as_float(w << 16); }
__device__ __forceinline__ float bf_hi(uint32_t w) { return __uint_as_float(w & 0xFFFF0000u); }
__device__ __forceinline__ float round_bf16(float x) { return bf_lo(pack_bf16(x, 0.f)); }
__device__ __forceinline__ uint32_t hfma2_bf16(uint32_t a, uint32_t b, uint32_t c) {
  uint32_t r;
  asm("fma.rn.bf16x2 %0, %1, %2, %3;" : "=r"(r) : "r"(a), "r"(b), "r"(c));
  return r;
}
__device__ __forceinline__ float ex2(float x) {
  float r;
  asm("ex2.approx.ftz.f32 %0, %1;" : "=f"(r) : "f"(x));
  return r;
}
__device__ __forceinline__ float tanh_hw(float x) {
  float r;
  asm("tanh.approx.f32 %0, %1;" : "=f"(r) : "f"(x));
  return r;
}
template <int TAG> __device__ __forceinline__ uint32_t pack_tag(float lo, float hi) {
  uint32_t w = __byte_perm(__float_as_uint(lo), pack_bf16(lo, hi), 0x7632);
  return TAG ? (w | 1u) : (w & ~1u);
}
__device__ __forceinline__ void st_pkt(uint4* p, uint32_t a, uint32_t b, uint32_t c, uint32_t d) {
  asm volatile(
      "st.relaxed.gpu.global.v4.b32 [%0], {%1,%2,%3,%4};" ::"l"(p), "r"(a), "r"(b), "r"(c), "r"(d) : "memory");
}
__device__ __forceinline__ void ld_pkt(const uint4* p, uint32_t (&r)[4]) {
  asm volatile(
      "ld.relaxed.gpu.global.v4.b32 {%0,%1,%2,%3}, [%4];"
      : "=r"(r[0]), "=r"(r[1]), "=r"(r[2]), "=r"(r[3]) : "l"(p) : "memory");
}
__device__ __forceinline__ uint32_t ldg32(const void* p) {
  uint32_t r;
  asm volatile("ld.global.nc.b32 %0, [%1];" : "=r"(r) : "l"(p));
  return r;
}
__device__ __forceinline__ uint32_t ldg16(const void* p) {
  uint16_t r;
  asm volatile("ld.global.nc.b16 %0, [%1];" : "=h"(r) : "l"(p));
  return r;
}
__device__ __forceinline__ uint4 ldg128(const void* p) {
  uint4 r;
  asm volatile("ld.global.nc.v4.b32 {%0,%1,%2,%3}, [%4];" : "=r"(r.x), "=r"(r.y), "=r"(r.z), "=r"(r.w) : "l"(p));
  return r;
}
__device__ __forceinline__ void l2_prefetch(const void* p, uint32_t bytes) {
  asm volatile("cp.async.bulk.prefetch.L2.global [%0], %1;" ::"l"(p), "r"(bytes) : "memory");
}
__device__ __forceinline__ float rcp_hw(float x) {
  float r;
  asm("rcp.approx.ftz.f32 %0, %1;" : "=f"(r) : "f"(x));
  return r;
}
__device__ __forceinline__ void warp_bulk_load(uint32_t sdst, const void* gsrc, uint32_t bytes, uint32_t bar) {
  asm volatile(
      "{\n.reg .pred p;\nelect.sync _|p, 0xffffffff;\n"
      "@p mbarrier.arrive.expect_tx.shared::cta.b64 _, [%3], %2;\n"
      "@p cp.async.bulk.shared::cluster.global.mbarrier::complete_tx::bytes [%0], [%1], %2, [%3];\n}\n"
      ::"r"(sdst), "l"(gsrc), "r"(bytes), "r"(bar) : "memory");
}
__device__ __forceinline__ void warp_tma3d(uint32_t dst, const CUtensorMap* tm, uint32_t bar, uint32_t bytes, int c1, int c2) {
  asm volatile(
      "{\n.reg .pred p;\nelect.sync _|p, 0xffffffff;\n"
      "@p mbarrier.arrive.expect_tx.shared::cta.b64 _, [%2], %3;\n"
      "@p cp.async.bulk.tensor.3d.shared::cluster.global.mbarrier::complete_tx::bytes [%0], [%1, {%6,%4,%5}], [%2];\n}\n"
      ::"r"(dst), "l"(tm), "r"(bar), "r"(bytes), "r"(c1), "r"(c2), "r"(0) : "memory");
}
__device__ __forceinline__ bool elect_one() {
  uint32_t r;
  asm volatile("{\n.reg .pred p;\nelect.sync _|p, 0xffffffff;\nselp.u32 %0, 1, 0, p;\n}\n" : "=r"(r));
  return r;
}
__device__ __forceinline__ void warp_arrive(uint32_t bar) {
  asm volatile("{\n.reg .pred p;\nelect.sync _|p, 0xffffffff;\n@p mbarrier.arrive.shared::cta.b64 _, [%0];\n}\n" ::"r"(bar) : "memory");
}
__device__ __forceinline__ uint32_t pack_trunc(float lo, float hi) {
  return __byte_perm(__float_as_uint(lo), __float_as_uint(hi), 0x7632);
}
__device__ __forceinline__ void add_partial(float (&y)[8], const uint32_t (&r)[4], uint32_t c0, bool first) {
#pragma unroll
  for (int e = 0; e < 4; e++) {
    const float lo = __uint_as_float(r[e] * 65536u + (e ? 0x8000u : c0)), hi = __uint_as_float(r[e]);
    y[2 * e] = first ? lo : y[2 * e] + lo;
    y[2 * e + 1] = first ? hi : y[2 * e + 1] + hi;
  }
}
__device__ __forceinline__ void spin_cycles(uint32_t n) {
  uint32_t t0, t;
  asm volatile("mov.u32 %0, %%clock;" : "=r"(t0));
  do { asm volatile("mov.u32 %0, %%clock;" : "=r"(t)); } while (t - t0 < n);
}
__device__ __forceinline__ void sts128(uint32_t a, uint32_t x, uint32_t y, uint32_t z, uint32_t w) {
  asm volatile("st.shared.v4.b32 [%0], {%1,%2,%3,%4};" ::"r"(a), "r"(x), "r"(y), "r"(z), "r"(w) : "memory");
}
__device__ __forceinline__ void lds128(uint32_t a, uint32_t (&r)[4]) {
  asm volatile("ld.shared.v4.b32 {%0,%1,%2,%3}, [%4];" : "=r"(r[0]), "=r"(r[1]), "=r"(r[2]), "=r"(r[3]) : "r"(a) : "memory");
}

__device__ __forceinline__ uint32_t lds32(uint32_t a) {
  uint32_t r;
  asm volatile("ld.shared.b32 %0, [%1];" : "=r"(r) : "r"(a) : "memory");
  return r;
}
__device__ __forceinline__ void store_out(__nv_bfloat16* out, uint32_t woff, uint32_t x2s, uint32_t gb0, uint32_t gb1,
                                          const float (&y)[8]) {
  const uint32_t gb[2] = {gb0, gb1};
  uint32_t xa[2][4];
  lds128(x2s, xa[0]);
  lds128(x2s + 2048, xa[1]);
  uint32_t* const oo = (uint32_t*)out + woff;
#pragma unroll
  for (int e = 0; e < 4; e++)
    oo[(e >> 1) * 4 + (e & 1) * 8 * 256] =
        pack_bf16(fmaf(bf_lo(gb[e >> 1]), y[2 * e], __uint_as_float(xa[e >> 1][(e & 1) * 2])),
                  fmaf(bf_hi(gb[e >> 1]), y[2 * e + 1], __uint_as_float(xa[e >> 1][(e & 1) * 2 + 1])));
}

constexpr int SK = 2048, WIN = 512;
constexpr int FF = 1792, FSL = 224;
constexpr int NTILES = 80;
constexpr int NSLOT = 4;
constexpr uint32_t SLOT = 32768;
constexpr uint32_t SM_PARK = 0;
constexpr uint32_t SM_RING = 3 * SLOT;
constexpr uint32_t SM_TAB = 7 * SLOT;
constexpr uint32_t SM_RED = SM_TAB + 2048;
constexpr uint32_t SM_BAR = SM_RED + 256;
constexpr uint32_t SM_WBAR = SM_BAR + 128;
constexpr uint32_t SM_SBAR = SM_WBAR + 256;
constexpr uint32_t BAR_SLAB = 64, BAR_UV = 72, BAR_X2 = 80, BAR_TAG = 88;
constexpr uint32_t SM_DBAR = SM_SBAR + 16;
constexpr uint32_t SM_TOTAL = SM_DBAR + 128;

struct Scratch {
  uint4 P[16 * 8 * 4 * 1024];
  uint4 G[16 * 8 * 32 * 32];
  uint4 mod1[8 * 256];
  uint4 mod2[512];
  uint4 uv[2 * 448];
  uint4 stat[16 * 8 * 8];
  uint32_t sent[16 * 8 * 8];
  uint32_t epoch;
};
__device__ Scratch g_scratch;

#define TS(i) do { } while (0)
#define TR(code)
#define CK_(v)
#define CKS(i, v)

#define TRU(code)

struct Params {
  const __nv_bfloat16* x;
  const __nv_bfloat16* c;
  const __nv_bfloat16* wmod;
  const __nv_bfloat16* wo;
  const __nv_bfloat16* w1;
  const __nv_bfloat16* w2;
  __nv_bfloat16* out;
  Scratch* s;
  uint32_t zero;
};

constexpr uint32_t HI128 = (1024 >> 4) | (1u << 30);
constexpr int LB_MN128 = (16384 >> 4) << 16;
constexpr int LB_K128 = 1 << 16;
constexpr int LB_W1 = (8192 >> 4) << 16;

template <int I> struct IC {
  __host__ __device__ constexpr operator int() const { return I; }
};
template <int I, int N, typename F> __device__ __forceinline__ void static_for(F&& f) {
  if constexpr (I < N) {
    f(IC<I>{});
    static_for<I + 1, N>(f);
  }
}

struct Ring {
  uint32_t base16, bars;
  __device__ __forceinline__ uint32_t wait_full(uint32_t slot, uint32_t parity) const {
    mbar_wait(bars + slot * 8, parity);
    return base16 + slot * (SLOT >> 4);
  }
  __device__ __forceinline__ void release(uint32_t slot) const {
    warp_arrive(bars + 32 + slot * 8);
  }
};

__device__ __forceinline__ float silu_c(uint32_t bits) {
  float x = bf_lo(bits);
  return round_bf16(x * rcp_hw(1.f + ex2(-1.4426950408889634f * x)));
}
__device__ __forceinline__ void pack8(uint32_t (&o)[4], const float* v) {
  o[0] = pack_bf16(v[0], v[1]); o[1] = pack_bf16(v[2], v[3]); o[2] = pack_bf16(v[4], v[5]); o[3] = pack_bf16(v[6], v[7]);
}

template <int TAG, int N>
__device__ __forceinline__ void issue_pkts(const uint4* p, int stride, uint32_t (*r)[4]) {
#pragma unroll
  for (int i = 0; i < N; i++) ld_pkt(p + i * stride, r[i]);
}
__device__ __forceinline__ void wait_sent(const uint32_t* p, uint32_t tag, uint32_t step) {
#pragma unroll 1
  for (int spins = 0; spins < SPIN_LIMIT; spins++) {
    uint32_t v;
    asm volatile("ld.relaxed.gpu.global.u32 %0, [%1];" : "=r"(v) : "l"(p) : "memory");
    if (__all_sync(0xffffffffu, v - (tag * 32 + step + 1) < 16u)) break;
  }
}
__device__ __forceinline__ void ld_mod(const uint4* p, uint32_t tag, uint32_t (&r)[4]) {
  int spins = 0;
  ld_pkt(p, r);
  while (r[2] != tag && ++spins < SPIN_LIMIT) ld_pkt(p, r);
}

#define EARLY_TILES 2
#define PF_WMOD 1
#define MOD1_DELAY 500
#define RED3_UNIT 3
#define NITEM2 24
#define FIN_DELAY0 800
#define FIN_DELAY1 0
#define FFN2_TURNS 1
#define G_DELAY 300

__device__ __forceinline__ float reduce8(float (&a)[8], int lane) {
  const bool h16 = lane & 16, h8 = lane & 8, h4 = lane & 4;
#pragma unroll
  for (int k = 0; k < 4; k++) a[k] = (h16 ? a[k + 4] : a[k]) + __shfl_xor_sync(0xffffffffu, h16 ? a[k] : a[k + 4], 16);
#pragma unroll
  for (int k = 0; k < 2; k++) a[k] = (h8 ? a[k + 2] : a[k]) + __shfl_xor_sync(0xffffffffu, h8 ? a[k] : a[k + 2], 8);
  const float r = (h4 ? a[1] : a[0]) + __shfl_xor_sync(0xffffffffu, h4 ? a[0] : a[1], 4);
  return r + __shfl_xor_sync(0xffffffffu, r, 2);
}
__device__ __forceinline__ void fma8(float (&a)[8], float s, uint32_t w0, uint32_t w1, uint32_t w2, uint32_t w3) {
  a[0] = fmaf(s, bf_lo(w0), a[0]); a[1] = fmaf(s, bf_hi(w0), a[1]);
  a[2] = fmaf(s, bf_lo(w1), a[2]); a[3] = fmaf(s, bf_hi(w1), a[3]);
  a[4] = fmaf(s, bf_lo(w2), a[4]); a[5] = fmaf(s, bf_hi(w2), a[5]);
  a[6] = fmaf(s, bf_lo(w3), a[6]); a[7] = fmaf(s, bf_hi(w3), a[7]);
}

enum { NB_TAB = 1, NB_WG0 = 2, NB_WG1 = 3, NB_HELP = 4, NB_INIT = 5, NB_PASS0 = 6, NB_GATHER = 7, NB_PARK = 8, NB_PROD = 9 };

__global__ void __launch_bounds__(512, 1)
adaln_block_kernel(const __grid_constant__ CUtensorMap tmWq, const __grid_constant__ CUtensorMap tmK,
                   const __grid_constant__ CUtensorMap tmV, const __grid_constant__ CUtensorMap tmWo,
                   const __grid_constant__ CUtensorMap tmW1, const __grid_constant__ CUtensorMap tmW2,
                   const __grid_constant__ CUtensorMap tmWm, const __grid_constant__ CUtensorMap tmX,
                   const Params p) {
  extern __shared__ __align__(1024) uint8_t smem_raw[];
  const uint32_t sb = smem_u32(smem_raw);
  const int tid = threadIdx.x, lane = tid & 31;
  const int warp = __shfl_sync(0xffffffffu, tid >> 5, 0);
  const int kp = blockIdx.x >> 1;
  const int bid = (kp < 4 ? kp : kp < 36 ? 4 + ((kp - 4) & 7) * 4 + ((kp - 4) >> 3) : 36 + ((kp - 36) % 7) * 4 + (kp - 36) / 7) * 2 +
                  (blockIdx.x & 1);
  const int j = bid & 7, rt = bid >> 3;
  const uint32_t bars = sb + SM_BAR;
  if (warp != 13) asm volatile("barrier.cluster.arrive.relaxed.aligned;" ::: "memory");

  if (warp >= 12) {
    asm volatile("setmaxnreg.dec.sync.aligned.u32 24;");
    if (warp == 13) {
      if (elect_one()) {
#pragma unroll
        for (int i = 0; i < 28; i++) mbar_init(sb + SM_WBAR + i * 8, i < 26 ? 1 : 4);
        mbar_init(sb + SM_SBAR, 8);
#pragma unroll
        for (int i = 0; i < 16; i++) mbar_init(sb + SM_DBAR + i * 8, 1);
        asm volatile("fence.mbarrier_init.release.cluster;" ::: "memory");
      }
      __syncwarp();
      asm volatile("barrier.cluster.arrive.relaxed.aligned;" ::: "memory");
      bar_arrive(NB_INIT, 192);
      mbar_wait(sb + SM_SBAR, 0);
      const uint32_t tag = *(volatile uint32_t*)(smem_raw + SM_BAR + BAR_TAG);
#pragma unroll 1
      for (int n = 0; n < 14; n++) {
        const uint32_t lb = sb + SM_WBAR + 192 + (n & 1) * 8;
        mbar_wait(lb + 16, ((n >> 1) & 1) ^ 1);
        wait_sent(&p.s->sent[(rt * 8 + j) * 8 + (lane & 6) + (n & 1)], tag, n >> 1);
        if (elect_one()) {
          mbar_expect(lb, n < 8 ? 8192 + 2048 : 8192);
#pragma unroll
          for (int m = 0; m < 4; m++)
            asm volatile("cp.async.bulk.shared::cluster.global.mbarrier::complete_tx::bytes [%0], [%1], 2048, [%2];"
                         ::"r"(sb + SM_PARK + ((n & 1) * 4 + m) * 4096 + 2048),
                           "l"(p.s->P + ((size_t)(rt * 8 + j) * 4 + m) * 1024 + (n & 7) * 128), "r"(lb) : "memory");
          if (n < 8) tma3d(sb + SM_PARK + SLOT + n * 4096, &tmX, lb, 0, rt * 128 + j * 16, n * 4);
        }
        __syncwarp();
      }
    } else if (warp == 14) {
      if (elect_one()) {
        asm volatile("prefetch.tensormap [%0];" ::"l"(&tmWq) : "memory");
        asm volatile("prefetch.tensormap [%0];" ::"l"(&tmK) : "memory");
        asm volatile("prefetch.tensormap [%0];" ::"l"(&tmV) : "memory");
        asm volatile("prefetch.tensormap [%0];" ::"l"(&tmWo) : "memory");
        asm volatile("prefetch.tensormap [%0];" ::"l"(&tmX) : "memory");
        asm volatile("prefetch.tensormap [%0];" ::"l"(&tmW1) : "memory");
        asm volatile("prefetch.tensormap [%0];" ::"l"(&tmW2) : "memory");
      }
    } else if (warp == 12) {
      if (elect_one()) {
        mbar_init(bars + BAR_SLAB, 1);
        asm volatile("fence.mbarrier_init.release.cluster;" ::: "memory");
        mbar_expect(bars + BAR_SLAB, 8192);
        tma3d(sb + SM_RING + 3 * SLOT, &tmWm, bars + BAR_SLAB, 0, 0, bid);
        tma3d(sb + SM_RING + 3 * SLOT + 4096, &tmWm, bars + BAR_SLAB, 0, 256, bid);
#pragma unroll
        for (int i = 0; i < 4; i++) { mbar_init(bars + i * 8, 1); mbar_init(bars + 32 + i * 8, 8); }
        mbar_init(bars + BAR_UV, 4);
        mbar_init(bars + BAR_X2, 1);
        asm volatile("fence.mbarrier_init.release.cluster;" ::: "memory");
      }
      __syncwarp();
      bar_arrive(NB_INIT, 192);
      mbar_wait(bars + BAR_SLAB, 0);
      uint32_t s = 0, ph = 1;
#pragma unroll 1
      for (int tt = 0; tt < NTILES; tt++) {
        const CUtensorMap* tm;
        int c1, c2;
        uint32_t bytes = SLOT;
        if (tt < 16) {
          tm = &tmWq; c1 = (tt & 3) * 128; c2 = (j * 4 + (((tt >> 2) + 1) & 3)) * 2;
        } else if (tt < 48) {
          const int u = tt - 16;
          const bool isK = (u == 0) || ((u & 1) && u != 31);
          const int n = isK ? ((u + 1) >> 1) : (u == 31 ? 15 : (u >> 1) - 1);
          tm = isK ? &tmK : &tmV; c1 = j * SK + (SK - WIN) + (n & 3) * 128; c2 = 0;
        } else if (tt < 64) {
          const int u = tt - 48;
          tm = &tmWo; c1 = j * 512 + (u & 1) * 256; c2 = (u >> 1) ^ (~j & 1);
        } else if (tt < 72) {
          tm = &tmW1; c1 = (tt - 64) * 64; c2 = (j * 7) >> 1;
        } else {
          tm = &tmW2; c1 = j * FSL; c2 = (tt - 72) ^ (~j & 1); bytes = 28672;
        }
        if (tt == EARLY_TILES) bar_sync(NB_PROD, 160);
        mbar_wait(bars + 32 + s * 8, ph);
        warp_tma3d(sb + SM_RING + s * SLOT, tm, bars + s * 8, bytes, c1, c2);
        if (++s == 4) { s = 0; ph ^= 1; }
      }
    }
  } else if (warp >= 8) {
    CK_(c0);
    asm volatile("setmaxnreg.dec.sync.aligned.u32 40;");
    const int t = tid - 256, hw = warp - 8, q = lane & 3;
    float* const red = (float*)(smem_raw + SM_RED);
    uint32_t tag;
    float a[8];
    {
      uint32_t cb[4];
#pragma unroll
      for (int i = 0; i < 4; i++) cb[i] = ldg16(p.c + t + 128 * i);
      asm volatile("ld.relaxed.gpu.global.u32 %0, [%1];" : "=r"(tag) : "l"(&p.s->epoch) : "memory");
      bar_sync(NB_INIT, 192);
      CK_(c2);
      tag += 1;
      float sc[4];
#pragma unroll
      for (int i = 0; i < 4; i++) sc[i] = silu_c(cb[i]);
#pragma unroll
      for (int k = 0; k < 8; k++) a[k] = 0.f;
      if (t == 0) *(uint32_t*)(smem_raw + SM_BAR + BAR_TAG) = tag;
      mbar_wait(bars + BAR_SLAB, 0);
      CK_(c3);
      bar_arrive(NB_GATHER, 384);
#pragma unroll
      for (int i = 0; i < 4; i++) {
        uint32_t w[4];
        lds128(sb + SM_RING + 3 * SLOT + (t + 128 * i) * 16, w);
        fma8(a, sc[i], w[0], w[1], w[2], w[3]);
      }
      float r = reduce8(a, lane);
      r += __shfl_xor_sync(0xffffffffu, r, 1);
      if (q == 0) red[hw * 8 + (lane >> 2)] = r;
      CK_(c4);
      bar_sync(NB_HELP, 128);
      CK_(c5);
      if (hw == 0) {
        const int cl = lane & 7;
        float v = round_bf16(red[cl] + red[8 + cl] + red[16 + cl] + red[24 + cl]);
        if (bid >= 64) v = 1.f + v;
        float vn = __shfl_down_sync(0xffffffffu, v, 1);
        uint32_t wd = pack_bf16(v, vn);
        uint32_t w0 = __shfl_sync(0xffffffffu, wd, (lane & 1) * 4);
        uint32_t w1 = __shfl_sync(0xffffffffu, wd, (lane & 1) * 4 + 2);
        if (lane < 16) st_pkt(&p.s->mod1[(lane >> 1) * 256 + bid * 2 + (lane & 1)], w0, w1, tag, 0);
      }
      uint32_t r0[4], r1[4];
      const uint4* src = &p.s->mod1[j * 256 + t];
      CK_(c6);
      spin_cycles(MOD1_DELAY);
      CK_(c7);
      int spins = 0;
      do {
        ld_pkt(src, r0);
        ld_pkt(src + 128, r1);
      } while ((r0[2] != tag || r1[2] != tag) && ++spins < SPIN_LIMIT);
      const int g = t >> 2, pp = q * 2;
      const uint32_t ad = sb + SM_TAB + (uint32_t)(g * 4 + (pp & 3)) * 16 + (pp >> 2) * 4;
      asm volatile("st.shared.b32 [%0], %1;" ::"r"(ad + 8), "r"(r0[0]) : "memory");
      asm volatile("st.shared.b32 [%0], %1;" ::"r"(ad + 24), "r"(r0[1]) : "memory");
      asm volatile("st.shared.b32 [%0], %1;" ::"r"(ad), "r"(r1[0]) : "memory");
      asm volatile("st.shared.b32 [%0], %1;" ::"r"(ad + 16), "r"(r1[1]) : "memory");
      bar_arrive(NB_TAB, 384);
      bar_arrive(NB_PROD, 160);
      CK_(c8);
      CKS(0, c0); CKS(2, c2); CKS(3, c3); CKS(4, c4); CKS(5, c5); CKS(6, c6); CKS(7, c7); CKS(8, c8);
    }
    bar_sync(NB_PASS0, 384);
    if (t < 8) l2_prefetch((const char*)p.wo + (size_t)bid * 32768 + t * 4096, 4096);
    else if (t < 12) l2_prefetch((const char*)p.w1 + (size_t)bid * 14336 + (t - 8) * 3584, 3584);
    else if (t < 16) l2_prefetch((const char*)p.w2 + (size_t)bid * 14336 + (t - 12) * 3584, 3584);
    {
#pragma unroll
      for (int k = 0; k < 8; k++) a[k] = 0.f;
#pragma unroll 1
      for (int b = 0; b < 4; b++) {
        const int row = b * 128 + (t >> 1);
        const __nv_bfloat16* wp = p.wmod + (size_t)row * 3072 + 1024 + bid * 16 + (t & 1) * 8;
        const uint4 w0 = ldg128(wp), w1 = ldg128(wp + 64 * 3072);
        const uint32_t c0 = ldg16(p.c + row), c1 = ldg16(p.c + row + 64);
        fma8(a, silu_c(c0), w0.x, w0.y, w0.z, w0.w);
        fma8(a, silu_c(c1), w1.x, w1.y, w1.z, w1.w);
      }
      const float r = reduce8(a, lane);
      if ((lane & 2) == 0) red[hw * 16 + (lane & 1) * 8 + (lane >> 2)] = r;
      bar_sync(NB_HELP, 128);
      if (hw == 0) {
        const int cl = lane & 15;
        float v = round_bf16(red[cl] + red[16 + cl] + red[32 + cl] + red[48 + cl]);
        if ((bid >> 5) == 2) v = 1.f + v;
        float vn = __shfl_down_sync(0xffffffffu, v, 1);
        uint32_t wd = pack_bf16(v, vn);
        uint32_t w0 = __shfl_sync(0xffffffffu, wd, q * 2);
        uint32_t w1 = __shfl_sync(0xffffffffu, wd, q * 2 + 8);
        const int vec = (0x2130 >> ((bid >> 5) * 4)) & 3;
        if (lane < 4) st_pkt(&p.s->mod2[((bid & 31) * 4 + vec) * 4 + lane], w0, w1, tag, 0);
      }
    }
    {
      const int isv = hw & 1, kh = hw >> 1;
      if (bid < 112) {
        const int kk = lane >> 1;
        uint32_t m0[4], m1[4];
        const uint4* mp = &p.s->mod2[(kh * 16 + (lane >> 2)) * 16 + (isv ? 12 : 4) + q];
        ld_mod(mp, tag, m0);
        ld_mod(mp + 128, tag, m1);
#pragma unroll
        for (int k = 0; k < 8; k++) a[k] = 0.f;
#pragma unroll 1
        for (int g0 = 0; g0 < 16; g0 += 2) {
          uint4 w[2];
#pragma unroll
          for (int i = 0; i < 2; i++) w[i] = ldg128(p.w1 + (size_t)((kh * 16 + g0 + i) * 16 + kk) * FF + bid * 16 + (lane & 1) * 8);
#pragma unroll
          for (int i = 0; i < 2; i++) {
            const int sl = ((g0 + i) & 7) * 4 + ((kk & 7) >> 1);
            const uint32_t wa = __shfl_sync(0xffffffffu, g0 < 8 ? m0[0] : m1[0], sl), wb = __shfl_sync(0xffffffffu, g0 < 8 ? m0[1] : m1[1], sl);
            const uint32_t mw = (kk & 8) ? wb : wa;
            fma8(a, (kk & 1) ? bf_hi(mw) : bf_lo(mw), w[i].x, w[i].y, w[i].z, w[i].w);
          }
        }
        float r = reduce8(a, lane);
        bar_sync(NB_HELP, 128);
        if (kh) red[isv * 32 + lane] = r;
        bar_sync(NB_HELP, 128);
        if (!kh) {
          r = (r + red[isv * 32 + lane]) * (isv ? 0.5f : 1.f);
          const float r1 = __shfl_down_sync(0xffffffffu, r, 4), r2 = __shfl_down_sync(0xffffffffu, r, 8),
                      r3 = __shfl_down_sync(0xffffffffu, r, 12);
          if ((lane & 14) == 0)
            st_pkt(&p.s->uv[isv * 448 + bid * 4 + (lane & 1) * 2 + (lane >> 4)], (__float_as_uint(r) & ~1u) | (tag & 1u),
                   __float_as_uint(r1), __float_as_uint(r2), __float_as_uint(r3));
        }
      }
      const int i = kh * 32 + lane;
      if (i < 56) {
        uint32_t m[4];
        int spins = 0;
        while (true) {
          ld_pkt(&p.s->uv[isv * 448 + j * 56 + i], m);
          if (!((m[0] ^ tag) & 1u) || ++spins >= SPIN_LIMIT) break;
          __nanosleep(200);
        }
        const int ip = (j & 1) ? (i < 8 ? i + 48 : i - 8) : i;
        const uint32_t ad = sb + SM_TAB + ip * 32 + isv * 8;
        asm volatile("st.shared.v2.b32 [%0], {%1,%2};" ::"r"(ad), "r"(m[0]), "r"(m[1]) : "memory");
        asm volatile("st.shared.v2.b32 [%0], {%1,%2};" ::"r"(ad + 16), "r"(m[2]), "r"(m[3]) : "memory");
      }
      __syncwarp();
      warp_arrive(bars + BAR_UV);
      TS(9);
    }
    {
      uint32_t mga[4], mg2[4], mgb[4];
      const uint4* mp = &p.s->mod2[((lane >> 2) * 4 + hw) * 16 + q];
      ld_mod(mp, tag, mga);
      ld_mod(mp + 4, tag, mg2);
      ld_mod(mp + 8, tag, mgb);
      if (lane >= 24) asm volatile("st.shared.v2.b32 [%0], {%1,%2};" ::"r"(sb + SM_TAB + 1792 + ((((lane >> 2) & 1) * 4 + hw) * 4 + q) * 8),
                                   "r"(mgb[0]), "r"(mgb[1]) : "memory");
      const uint32_t x2s = sb + SM_PARK + SLOT + hw * 512 + lane * 16;
      const uint4* const Pown = p.s->P + (size_t)(rt * 8 + j) * 4096 + hw * 32 + lane;
      float s0 = 0.f, s1 = 0.f, v0 = 0.f, v1 = 0.f;
      bar_sync(NB_PARK, 384);
      asm volatile("setmaxnreg.inc.sync.aligned.u32 56;");
#pragma unroll 1
      for (int n = 0; n < 14; n++) {
        const int cc = n & 7;
        const bool ex1 = n < 8;
        const uint32_t lb = sb + SM_WBAR + 192 + (n & 1) * 8;
        uint32_t r[4][4];
        float y[8];
        mbar_wait(lb, (n >> 1) & 1);
#pragma unroll
        for (int i = 0; i < 4; i++) lds128(sb + SM_PARK + ((n & 1) * 4 + i) * 4096 + 2048 + hw * 512 + lane * 16, r[i]);
        verify4_rt<16384>(Pown + cc * 128, r, ex1);
        warp_arrive(lb + 16);
#pragma unroll
        for (int i = 0; i < 4; i++) add_partial(y, r[i], ex1 ? 0u : 0x10000u, i == 0);
        const int src = cc * 4 + q;
        const uint32_t ma = __shfl_sync(0xffffffffu, ex1 ? mga[0] : mgb[0], src), mb = __shfl_sync(0xffffffffu, ex1 ? mga[1] : mgb[1], src);
        if (ex1) {
          uint32_t xr[4];
          asm volatile("ldmatrix.sync.aligned.m8n8.x4.shared.b16 {%0,%1,%2,%3}, [%4];"
                       : "=r"(xr[0]), "=r"(xr[1]), "=r"(xr[2]), "=r"(xr[3])
                       : "r"(sb + SM_PARK + SLOT + hw * 512 + cc * 4096 + (lane & 15) * 32 + (lane >> 4) * 16) : "memory");
          const uint32_t mc = __shfl_sync(0xffffffffu, mg2[0], src), md = __shfl_sync(0xffffffffu, mg2[1], src);
#pragma unroll
          for (int e = 0; e < 4; e++) {
            const uint32_t m = e < 2 ? ma : mb;
            const float u = fmaf(bf_lo(m), y[2 * e], bf_lo(xr[e])), v = fmaf(bf_hi(m), y[2 * e + 1], bf_hi(xr[e]));
            y[2 * e] = u; y[2 * e + 1] = v;
            if (e & 1) { s1 += u + v; v1 = fmaf(u, u, fmaf(v, v, v1)); }
            else { s0 += u + v; v0 = fmaf(u, u, fmaf(v, v, v0)); }
          }
          st_pkt(p.s->G + ((rt * 8 + j) * 32 + cc * 4 + hw) * 32 + lane, pack_tag<0>(y[0] * bf_lo(mc), y[1] * bf_hi(mc)),
                 pack_bf16(y[2] * bf_lo(mc), y[3] * bf_hi(mc)), pack_bf16(y[4] * bf_lo(md), y[5] * bf_hi(md)),
                 pack_bf16(y[6] * bf_lo(md), y[7] * bf_hi(md)));
          sts128(x2s + cc * 4096, __float_as_uint(y[0]), __float_as_uint(y[1]), __float_as_uint(y[2]), __float_as_uint(y[3]));
          sts128(x2s + cc * 4096 + 2048, __float_as_uint(y[4]), __float_as_uint(y[5]), __float_as_uint(y[6]), __float_as_uint(y[7]));
          if (n == 7) {
            const bool o1 = lane & 1, o2 = lane & 2;
            float c0 = (o1 ? v0 : s0) + __shfl_xor_sync(0xffffffffu, o1 ? s0 : v0, 1);
            float c1 = (o1 ? v1 : s1) + __shfl_xor_sync(0xffffffffu, o1 ? s1 : v1, 1);
            c0 = (o2 ? c1 : c0) + __shfl_xor_sync(0xffffffffu, o2 ? c0 : c1, 2);
            *(float*)(smem_raw + SM_PARK + 16384 + 2048 + hw * 512 + lane * 4) = c0;
            bar_sync(NB_HELP, 128);
            if (hw == 0) {
              const float* ps = (const float*)(smem_raw + SM_PARK + 16384 + 2048) + lane;
              const float m = (c0 + ps[128] + ps[256] + ps[384]) * (1.f / 512.f);
              const float mean = __shfl_sync(0xffffffffu, m, lane & ~1), sq = __shfl_sync(0xffffffffu, m, lane | 1);
              const float rs = 0.5f * rsqrtf(fmaxf(fmaf(-mean, mean, sq), 0.f) + 1e-5f), mr = -mean * rs;
              const float rs1 = __shfl_down_sync(0xffffffffu, rs, 2), mr1 = __shfl_down_sync(0xffffffffu, mr, 2);
              if (q == 0)
                st_pkt(&p.s->stat[(rt * 8 + j) * 8 + (lane >> 2)], (__float_as_uint(rs) & ~1u) | (tag & 1u), __float_as_uint(mr),
                       __float_as_uint(rs1), __float_as_uint(mr1));
              warp_arrive(bars + BAR_X2);
            }
          }
        } else {
          store_out(p.out, (uint32_t)(rt * 128 + 16 * j + (lane >> 2)) * 256 + (cc * 4 + hw) * 8 + q, x2s + cc * 4096, ma, mb, y);
        }
      }
    }
  } else {
    const int wg = warp >> 2;
    const int q = lane & 3, gq = lane >> 2;
    const Ring ring{((sb + SM_RING) & 0x3FFFF) >> 4, bars};
    const uint32_t xoff = (uint32_t)(rt * 128 + 16 * j + warp) * 256 + gq * 8 + q;
    const uint32_t ooff = ((uint32_t)(rt * 8 + j) * 32 + gq) * 32 + warp * 4 + q;
    const uint32_t wblk = sb + SM_PARK + warp * 4096, wprv = wblk + lane * 16;
    const uint32_t wbar = sb + SM_WBAR + warp * 24;
    const uint4* const Gw = p.s->G + (rt * 8 + warp) * 1024;

    {
      const uint32_t* xo = (const uint32_t*)p.x + xoff;
      uint32_t xr[4][4];
      CK_(d0);
#pragma unroll
      for (int c = 0; c < 4; c++) {
        xr[c][0] = ldg32(xo + c * 64);
        xr[c][1] = ldg32(xo + c * 64 + 8 * 256);
        xr[c][2] = ldg32(xo + c * 64 + 4);
        xr[c][3] = ldg32(xo + c * 64 + 4 + 8 * 256);
      }
      CK_(d1);
      fence_regs(xr);
      CK_(d2);
      float s0 = 0.f, s1 = 0.f, v0 = 0.f, v1 = 0.f;
#pragma unroll
      for (int c = 0; c < 4; c++) {
#pragma unroll
        for (int e = 0; e < 4; e++) {
          const float a = bf_lo(xr[c][e]), b = bf_hi(xr[c][e]);
          if (e & 1) { s1 += a + b; v1 = fmaf(a, a, fmaf(b, b, v1)); }
          else { s0 += a + b; v0 = fmaf(a, a, fmaf(b, b, v0)); }
        }
      }
#pragma unroll
      for (int o = 16; o > 0; o >>= 1) {
        s0 += __shfl_xor_sync(0xffffffffu, s0, o);
        s1 += __shfl_xor_sync(0xffffffffu, s1, o);
        v0 += __shfl_xor_sync(0xffffffffu, v0, o);
        v1 += __shfl_xor_sync(0xffffffffu, v1, o);
      }
      const float m0 = s0 * (1.f / 512.f), m1 = s1 * (1.f / 512.f);
      const float r0 = rsqrtf(fmaxf(fmaf(-m0, m0, v0 * (1.f / 512.f)), 0.f) + 1e-5f);
      const float r1 = rsqrtf(fmaxf(fmaf(-m1, m1, v1 * (1.f / 512.f)), 0.f) + 1e-5f);
#pragma unroll
      for (int c = 0; c < 4; c++) {
        st_pkt(p.s->G + ooff + c * 256,
               pack_tag<1>((bf_lo(xr[c][0]) - m0) * r0, (bf_hi(xr[c][0]) - m0) * r0),
               pack_bf16((bf_lo(xr[c][1]) - m1) * r1, (bf_hi(xr[c][1]) - m1) * r1),
               pack_bf16((bf_lo(xr[c][2]) - m0) * r0, (bf_hi(xr[c][2]) - m0) * r0),
               pack_bf16((bf_lo(xr[c][3]) - m1) * r1, (bf_hi(xr[c][3]) - m1) * r1));
      }
      CK_(d3);
      CKS(16, d0); CKS(17, d1); CKS(18, d2); CKS(19, d3);

    }
    asm volatile("setmaxnreg.inc.sync.aligned.u32 224;");
    auto my_turn = [&]() { bar_sync(NB_WG0 + wg, 256); };
    auto your_turn = [&]() { bar_arrive(NB_WG0 + (wg ^ 1), 256); };
    if (wg == 1) your_turn();
    uint32_t qf[8][4];
    {
      uint32_t h[32][4];
      float acc[64];
      const uint4* Gin = Gw + lane;
      asm volatile("barrier.cluster.wait.acquire.aligned;" ::: "memory");
      bar_sync(NB_GATHER, 384);
      if (G_DELAY) spin_cycles(G_DELAY);
#pragma unroll
      for (int c = 0; c < 3; c++) warp_bulk_load(wblk + c * SLOT, Gw + c * 256, 4096, wbar + c * 8);
#pragma unroll
      for (int c = 0; c < 4; c++) {
        mbar_wait(wbar + (c % 3) * 8, c / 3);
#pragma unroll
        for (int i = 0; i < 8; i++) lds128(wprv + (c % 3) * SLOT + i * 512, h[c * 8 + i]);
        verify8_tag1<512>(Gin + c * 256, h + c * 8);
        if (c == 0) {
          warp_bulk_load(wblk, Gw + 768, 4096, wbar);
          TS(1);
          bar_sync(NB_TAB, 384);
        }
#pragma unroll
        for (int i = 0; i < 8; i++) {
          uint32_t m[4];
          lds128(sb + SM_TAB + (uint32_t)((c * 8 + i) * 4 + q) * 16, m);
          uint32_t* hh = h[c * 8 + i];
          hh[0] = hfma2_bf16(hh[0], m[0], m[2]);
          hh[1] = hfma2_bf16(hh[1], m[0], m[2]);
          hh[2] = hfma2_bf16(hh[2], m[1], m[3]);
          hh[3] = hfma2_bf16(hh[3], m[1], m[3]);
        }
        fence_frags<8>(h + c * 8);
        const uint32_t b = ring.wait_full(c, 0);
        if (c > 0) { wg_wait<0>(); ring.release(c - 1); }
        if (c == 0) TS(2);
        my_turn();
        wg_fence();
        static_for<0, 8>([&](auto K) { wgmma_rs_n128_tb1<LB_MN128 + K * 128, HI128>(acc, h[c * 8 + K], b, (c | K) != 0); });
        wg_commit();
        your_turn();
      }
      bar_arrive(NB_PASS0, 384);
#pragma unroll 1
      for (int ps = 1; ps < 4; ps++) {
        wg_wait<0>();
        ring.release(3);
        fence_regs(acc);
#pragma unroll
        for (int i = 0; i < 8; i++) {
          uint32_t o[4];
          pack8(o, acc + 8 * i);
          sts128(wprv + (ps - 1) * SLOT + i * 512, o[0], o[1], o[2], o[3]);
        }
#pragma unroll
        for (int c = 0; c < 4; c += 2) {
          const uint32_t b = ring.wait_full(c, ps & 1);
          ring.wait_full(c + 1, ps & 1);
          if (c > 0) { wg_wait<0>(); ring.release(c - 1); }
          my_turn();
          wg_fence();
          static_for<0, 8>([&](auto K) { wgmma_rs_n128_tb1<LB_MN128 + K * 128, HI128>(acc, h[c * 8 + K], b, (c | K) != 0); });
          wg_commit();
          static_for<0, 8>([&](auto K) { wgmma_rs_n128_tb1<LB_MN128 + 2048 + K * 128, HI128>(acc, h[c * 8 + 8 + K], b, 1); });
          wg_commit();
          your_turn();
          wg_wait<1>();
          ring.release(c);
        }
      }
      wg_wait<0>();
      ring.release(3);
      fence_regs(acc);
#pragma unroll
      for (int i = 0; i < 8; i++) pack8(qf[i], acc + 8 * i);
    }
    fence_regs(qf);
    TS(3);

    uint32_t o[24][4];
    {
      float S[64], O[64];
      uint32_t P[8][4];
      const float cs = 0.08838834764831845f * 1.4426950408889634f;
      const int TAU = 0x41800000;
      float m0, m1, l0, l1;

      auto float_block_max = [&]() {
        float b0 = fmaxf(S[0], S[1]), b1 = fmaxf(S[2], S[3]);
#pragma unroll
        for (int i = 1; i < 16; i++) {
          b0 = fmaxf(b0, fmaxf(S[4 * i], S[4 * i + 1]));
          b1 = fmaxf(b1, fmaxf(S[4 * i + 2], S[4 * i + 3]));
        }
        b0 = fmaxf(b0, __shfl_xor_sync(0xffffffffu, b0, 1)); b1 = fmaxf(b1, __shfl_xor_sync(0xffffffffu, b1, 1));
        b0 = fmaxf(b0, __shfl_xor_sync(0xffffffffu, b0, 2)); b1 = fmaxf(b1, __shfl_xor_sync(0xffffffffu, b1, 2));
        m0 = b0 * cs; m1 = b1 * cs;
      };
      auto first_block_max = [&]() {
        int a0 = max(__float_as_int(S[0]), __float_as_int(S[1]));
        int a1 = max(__float_as_int(S[2]), __float_as_int(S[3]));
#pragma unroll
        for (int i = 1; i < 16; i++) {
          a0 = __vimax3_s32(a0, __float_as_int(S[4 * i]), __float_as_int(S[4 * i + 1]));
          a1 = __vimax3_s32(a1, __float_as_int(S[4 * i + 2]), __float_as_int(S[4 * i + 3]));
        }
        a0 = max(a0, __shfl_xor_sync(0xffffffffu, a0, 1)); a1 = max(a1, __shfl_xor_sync(0xffffffffu, a1, 1));
        a0 = max(a0, __shfl_xor_sync(0xffffffffu, a0, 2)); a1 = max(a1, __shfl_xor_sync(0xffffffffu, a1, 2));
        m0 = __int_as_float(a0) * cs; m1 = __int_as_float(a1) * cs;
        if (__any_sync(0xffffffffu, (a0 | a1) < 0)) float_block_max();
      };
      auto scale_sub = [&]() {
#pragma unroll
        for (int i = 0; i < 16; i++) {
          S[4 * i] = fmaf(S[4 * i], cs, -m0); S[4 * i + 1] = fmaf(S[4 * i + 1], cs, -m0);
          S[4 * i + 2] = fmaf(S[4 * i + 2], cs, -m1); S[4 * i + 3] = fmaf(S[4 * i + 3], cs, -m1);
        }
      };
      auto exps = [&](int i0, int i1) {
#pragma unroll
        for (int i = i0; i < i1; i++) {
          S[4 * i] = ex2(S[4 * i]); S[4 * i + 1] = ex2(S[4 * i + 1]);
          S[4 * i + 2] = ex2(S[4 * i + 2]); S[4 * i + 3] = ex2(S[4 * i + 3]);
          l0 += S[4 * i]; l1 += S[4 * i + 2]; l0 += S[4 * i + 1]; l1 += S[4 * i + 3];
        }
      };
      {
        const uint32_t b = ring.wait_full(0, 0);
        my_turn();
        wg_fence();
        static_for<0, 8>([&](auto K) { wgmma_rs_n128_tb0<LB_K128 + (K >> 2) * 1024 + (K & 3) * 2, HI128>(S, qf[K], b, K != 0); });
        wg_commit();
        your_turn();
        wg_wait<0>();
        fence_regs(S);
        ring.release(0);
        float_block_max();
        scale_sub();
        l0 = 0.f; l1 = 0.f;
        exps(0, 16);
#pragma unroll
        for (int i = 0; i < 8; i++) pack8(P[i], S + 8 * i);
      }
      fence_regs(P);
#pragma unroll 1
      for (int n = 1; n < 16; n++) {
        const uint32_t tk = 2 * n - 1, tv = 2 * n;
        const bool newhead = (n & 3) == 0;
        const uint32_t bk = ring.wait_full(tk & 3, (tk >> 2) & 1);
        const uint32_t bv = ring.wait_full(tv & 3, (tv >> 2) & 1);
        my_turn();
        wg_fence();
        static_for<0, 8>([&](auto K) { wgmma_rs_n128_tb0<LB_K128 + (K >> 2) * 1024 + (K & 3) * 2, HI128>(S, qf[K], bk, K != 0); });
        wg_commit();
        static_for<0, 8>([&](auto K) { wgmma_rs_n128_tb1<LB_MN128 + K * 128, HI128>(O, P[K], bv, K != 0 || (n & 3) != 1); });
        wg_commit();
        your_turn();
        wg_wait<1>();
        fence_regs(S);
        ring.release(tk & 3);
        if ((n & 3) == 3 && n != 15) {
          fence_regs(qf);
#pragma unroll
          for (int i = 0; i < 8; i++) lds128(wprv + (n >> 2) * SLOT + i * 512, qf[i]);
        }
        float f0 = 1.f, f1 = 1.f;
        bool resc = newhead;
        if (newhead) {
          l0 += __shfl_xor_sync(0xffffffffu, l0, 1); l1 += __shfl_xor_sync(0xffffffffu, l1, 1);
          l0 += __shfl_xor_sync(0xffffffffu, l0, 2); l1 += __shfl_xor_sync(0xffffffffu, l1, 2);
          f0 = rcp_hw(l0); f1 = rcp_hw(l1);
          l0 = 0.f; l1 = 0.f;
          first_block_max();
          scale_sub();
        } else {
          scale_sub();
          int a0 = __vimax3_s32(__float_as_int(S[0]), __float_as_int(S[1]), __float_as_int(S[1]));
          int a1 = __vimax3_s32(__float_as_int(S[2]), __float_as_int(S[3]), __float_as_int(S[3]));
#pragma unroll
          for (int i = 1; i < 16; i++) {
            a0 = __vimax3_s32(a0, __float_as_int(S[4 * i]), __float_as_int(S[4 * i + 1]));
            a1 = __vimax3_s32(a1, __float_as_int(S[4 * i + 2]), __float_as_int(S[4 * i + 3]));
          }
          if (__any_sync(0xffffffffu, max(a0, a1) > TAU)) {
            a0 = max(a0, 0); a1 = max(a1, 0);
            a0 = max(a0, __shfl_xor_sync(0xffffffffu, a0, 1)); a1 = max(a1, __shfl_xor_sync(0xffffffffu, a1, 1));
            a0 = max(a0, __shfl_xor_sync(0xffffffffu, a0, 2)); a1 = max(a1, __shfl_xor_sync(0xffffffffu, a1, 2));
            const float d0 = __int_as_float(a0), d1 = __int_as_float(a1);
#pragma unroll
            for (int i = 0; i < 16; i++) { S[4 * i] -= d0; S[4 * i + 1] -= d0; S[4 * i + 2] -= d1; S[4 * i + 3] -= d1; }
            m0 += d0; m1 += d1;
            f0 = ex2(-d0); f1 = ex2(-d1);
            l0 *= f0; l1 *= f1;
            resc = true;
          }
        }
        exps(0, 4);
        wg_wait<0>();
        fence_regs(O);
        fence_regs(P);
        ring.release(tv & 3);
        if (resc) {
#pragma unroll
          for (int i = 0; i < 16; i++) {
            O[4 * i] *= f0; O[4 * i + 1] *= f0; O[4 * i + 2] *= f1; O[4 * i + 3] *= f1;
          }
          if (newhead) {
#pragma unroll
            for (int i = 0; i < 8; i++) {
              uint32_t o[4];
              pack8(o, O + 8 * i);
              sts128(wprv + ((n >> 2) - 1) * SLOT + i * 512, o[0], o[1], o[2], o[3]);
            }
          }
        }
        exps(4, 16);
#pragma unroll
        for (int i = 0; i < 8; i++) pack8(P[i], S + 8 * i);
        fence_regs(P);
        fence_regs(O);
      }
      {
        const uint32_t bv = ring.wait_full(3, 1);
        my_turn();
        wg_fence();
        static_for<0, 8>([&](auto K) { wgmma_rs_n128_tb1<LB_MN128 + K * 128, HI128>(O, P[K], bv, 1); });
        wg_commit();
        your_turn();
#pragma unroll
        for (int i = 0; i < 16; i++) lds128(wprv + (i >> 3) * SLOT + (i & 7) * 512, o[i]);
        l0 += __shfl_xor_sync(0xffffffffu, l0, 1); l1 += __shfl_xor_sync(0xffffffffu, l1, 1);
        l0 += __shfl_xor_sync(0xffffffffu, l0, 2); l1 += __shfl_xor_sync(0xffffffffu, l1, 2);
        const float f0 = rcp_hw(l0), f1 = rcp_hw(l1);
        wg_wait<0>();
        fence_regs(O);
        ring.release(3);
#pragma unroll
        for (int i = 0; i < 8; i++) {
          qf[i][0] = pack_bf16(O[8 * i] * f0, O[8 * i + 1] * f0); qf[i][1] = pack_bf16(O[8 * i + 2] * f1, O[8 * i + 3] * f1);
          qf[i][2] = pack_bf16(O[8 * i + 4] * f0, O[8 * i + 5] * f0); qf[i][3] = pack_bf16(O[8 * i + 6] * f1, O[8 * i + 7] * f1);
        }
      }
    }
    fence_regs(qf);
    TS(4);
    asm volatile("setmaxnreg.dec.sync.aligned.u32 216;");
    bar_arrive(NB_PARK, 384);

    uint4* const Pout = p.s->P + ((size_t)(rt * 8 + warp) * 4 + (j >> 1)) * 1024 + (j & 1) * 128 + lane;
    const uint32_t tag = *(volatile uint32_t*)(smem_raw + SM_BAR + BAR_TAG);
    const uint32_t rbar = sb + SM_DBAR + warp * 16;
    uint32_t peer_land, peer_bar;
    asm("mapa.shared::cluster.u32 %0, %1, %2;" : "=r"(peer_land) : "r"(wprv), "r"(~j & 1));
    asm("mapa.shared::cluster.u32 %0, %1, %2;" : "=r"(peer_bar) : "r"(rbar), "r"(~j & 1));
    auto arm_and_ack = [&](uint32_t dep) {
      asm volatile(
          "{\n.reg .pred p;\nelect.sync _|p, 0xffffffff;\n"
          "@p mbarrier.arrive.expect_tx.shared::cta.b64 _, [%0], 2048;\n"
          "@p mbarrier.arrive.shared::cluster.b64 _, [%1];\n}\n" ::"r"(rbar), "r"(peer_bar + 8 + (dep & p.zero)) : "memory");
    };
    auto send_chunk = [&](float (&acc)[32], int pair) {
      mbar_wait(rbar + 8, pair & 1);
#pragma unroll
      for (int i = 0; i < 4; i++)
        asm volatile("st.async.weak.shared::cluster.mbarrier::complete_tx::bytes.v4.b32 [%0], {%1,%2,%3,%4}, [%5];"
                     ::"r"(peer_land + i * 512), "r"(pack_trunc(acc[8 * i], acc[8 * i + 1])), "r"(pack_trunc(acc[8 * i + 2], acc[8 * i + 3])),
                       "r"(pack_trunc(acc[8 * i + 4], acc[8 * i + 5])), "r"(pack_trunc(acc[8 * i + 6], acc[8 * i + 7])), "r"(peer_bar)
                     : "memory");
    };
    uint32_t pk[4][4];
    auto recv_chunk = [&](int pair) {
      mbar_wait(rbar, pair & 1);
#pragma unroll
      for (int i = 0; i < 4; i++) lds128(wprv + i * 512, pk[i]);
      if (pair < 7) arm_and_ack(pk[3][0]);
    };
    auto keep_chunk = [&](float (&acc)[32], int pair) {
      const uint32_t t1 = pair < 4;
#pragma unroll
      for (int i = 0; i < 4; i++) {
#pragma unroll
        for (int e = 0; e < 4; e++)
          pk[i][e] = pack_trunc(acc[8 * i + 2 * e] + __uint_as_float(pk[i][e] * 65536u + 0x8000u),
                                acc[8 * i + 2 * e + 1] + __uint_as_float(pk[i][e]));
        st_pkt(Pout + (pair & 3) * 256 + i * 32, (pk[i][0] & ~1u) | t1, pk[i][1], pk[i][2], pk[i][3]);
      }
      if (lane == 0)
        asm volatile("st.relaxed.gpu.global.u32 [%0], %1;" ::"l"(&p.s->sent[(rt * 8 + warp) * 8 + j]), "r"(tag * 32 + pair + 1) : "memory");
    };
    const uint4* const Gin = Gw + lane;
    auto g_issue = [&](int u) { warp_bulk_load(wblk + 2 * SLOT, Gw + u * 256, 4096, wbar); };

#pragma unroll
    for (int i = 16; i < 24; i++) lds128(wprv + 2 * SLOT + (i & 7) * 512, o[i]);
    fence_regs(o);
    arm_and_ack(o[23][0]);
    warp_arrive(sb + SM_SBAR);
#pragma unroll 1
    for (int cc = 0; cc < 8; cc++) {
      float acc[32];
      const uint32_t s0 = (cc & 1) * 2, b = ring.wait_full(s0, (cc >> 1) & 1);
      ring.wait_full(s0 + 1, (cc >> 1) & 1);
      my_turn();
      wg_fence();
      static_for<0, 16>([&](auto K) { wgmma_rs_n64_tb1<K * 128, HI128>(acc, o[K], b, K != 0); });
      wg_commit();
      static_for<0, 16>([&](auto K) { wgmma_rs_n64_tb1<2048 + K * 128, HI128>(acc, K < 8 ? o[16 + (K & 7)] : qf[K & 7], b, 1); });
      wg_commit();
      your_turn();
      wg_wait<1>();
      ring.release(s0);
      if (cc & 1) recv_chunk(cc >> 1);
      wg_wait<0>();
      TRU(4);
      ring.release(s0 + 1);
      fence_regs(acc);
      if (cc & 1) keep_chunk(acc, cc >> 1);
      else send_chunk(acc, cc >> 1);
      if (cc == 6) g_issue(0);
    }
    TS(5);

    uint32_t H[14][4];
    {
      float acca[96], accb[16];
      const uint4* const statp = &p.s->stat[(rt * 8 + warp) * 8];
#pragma unroll 1
      for (int u = 0; u < 4; u++) {
        uint32_t fa[8][4];
        const uint32_t s0 = (u & 1) * 2, b = ring.wait_full(s0, (u >> 1) & 1);
        ring.wait_full(s0 + 1, (u >> 1) & 1);
        mbar_wait(wbar, u & 1);
#pragma unroll
        for (int i = 0; i < 8; i++) lds128(wprv + 2 * SLOT + i * 512, fa[i]);
        verify8_tag0<512>(Gin + u * 256, fa);
        if (u < 2) g_issue(u + 1);
        const uint32_t ba = b + (j & 1) * 512, bb = b + ((j & 1) ? 4 : 1536);
        my_turn();
        wg_fence();
        static_for<0, 4>([&](auto K) { wgmma_rs_n32_tb1<LB_W1 + K * 128, HI128>(accb, fa[K], bb, (u | K) != 0); });
        static_for<0, 4>([&](auto K) { wgmma_rs_n192_tb1<LB_W1 + K * 128, HI128>(acca, fa[K], ba, (u | K) != 0); });
        wg_commit();
        static_for<0, 4>([&](auto K) { wgmma_rs_n32_tb1<LB_W1 + 2048 + K * 128, HI128>(accb, fa[4 + K], bb, 1); });
        static_for<0, 4>([&](auto K) { wgmma_rs_n192_tb1<LB_W1 + 2048 + K * 128, HI128>(acca, fa[4 + K], ba, 1); });
        wg_commit();
        if (FFN2_TURNS || u < 3 || wg == 0) your_turn();
        wg_wait<1>();
        ring.release(s0);
        if (u == 2) g_issue(3);
        if (u == 3) warp_bulk_load(wblk + 2 * SLOT, statp, 128, wbar + 16);
        wg_wait<0>();
        TRU(4);
        ring.release(s0 + 1);
      }
      fence_regs(acca);
      fence_regs(accb);
      TS(9);
      mbar_wait(bars + BAR_UV, 0);
      uint32_t xr[4];
      mbar_wait(wbar + 16, 1);
      lds128(wblk + 2 * SLOT + gq * 16, xr);
      {
        int spins = 0;
        while (((xr[0] ^ tag) & 1u) && ++spins < SPIN_LIMIT) ld_pkt(statp + gq, xr);
      }
      const float ra0 = __uint_as_float(xr[0]), rb0 = __uint_as_float(xr[1]), ra1 = __uint_as_float(xr[2]),
                  rb1 = __uint_as_float(xr[3]);
#pragma unroll
      for (int i = 0; i < 28; i++) {
        uint32_t m[4];
        lds128(sb + SM_TAB + (i * 4 + q) * 16, m);
        const float u0 = __uint_as_float(m[0]), u1 = __uint_as_float(m[1]), w0 = __uint_as_float(m[2]), w1 = __uint_as_float(m[3]);
        const float* acc = i < 24 ? acca + 4 * i : accb + 4 * (i - 24);
        const float z0 = fmaf(acc[0], ra0, fmaf(u0, rb0, w0)), z1 = fmaf(acc[1], ra0, fmaf(u1, rb0, w1));
        const float z2 = fmaf(acc[2], ra1, fmaf(u0, rb1, w0)), z3 = fmaf(acc[3], ra1, fmaf(u1, rb1, w1));
        H[i >> 1][(i & 1) * 2] = pack_bf16(fmaf(z0, tanh_hw(z0), z0), fmaf(z1, tanh_hw(z1), z1));
        H[i >> 1][(i & 1) * 2 + 1] = pack_bf16(fmaf(z2, tanh_hw(z2), z2), fmaf(z3, tanh_hw(z3), z3));
      }
    }
    fence_regs(H);
    TS(10);
    const int go = 24 + warp;
    {
      float accs[32], acck[32];
      auto ffn2 = [&](float (&acc)[32], uint32_t b) {
        const uint32_t ba = b + (j & 1) * 256, bb = b - (j & 1) * 1536;
        static_for<0, 14>([&](auto K) { wgmma_rs_n64_tb1<K * 128, HI128>(acc, H[K], K < 12 ? ba : bb, K != 0); });
        wg_commit();
      };
      {
        const uint32_t b = ring.wait_full(0, 0);
        if (FFN2_TURNS) my_turn();
        wg_fence();
        ffn2(accs, b);
        if (FFN2_TURNS) your_turn();
        wg_wait<0>();
        TRU(4);
        ring.release(0);
        fence_regs(accs);
        send_chunk(accs, 4);
      }
#pragma unroll 1
      for (int pc = 0; pc < 3; pc++) {
        const uint32_t tk = 2 * pc + 1, ts = tk + 1;
        const uint32_t bk = ring.wait_full(tk & 3, (tk >> 2) & 1), bs = ring.wait_full(ts & 3, (ts >> 2) & 1);
        if (FFN2_TURNS) my_turn();
        wg_fence();
        ffn2(acck, bk);
        ffn2(accs, bs);
        if (FFN2_TURNS) your_turn();
        wg_wait<1>();
        ring.release(tk & 3);
        recv_chunk(4 + pc);
        fence_regs(acck);
        keep_chunk(acck, 4 + pc);
        wg_wait<0>();
        TRU(4);
        ring.release(ts & 3);
        fence_regs(accs);
        send_chunk(accs, 5 + pc);
      }
      const uint32_t b = ring.wait_full(3, 1);
      if (FFN2_TURNS) my_turn();
      wg_fence();
      ffn2(acck, b);
      if (FFN2_TURNS && wg == 0) your_turn();
      recv_chunk(7);
      wg_wait<0>();
      fence_regs(acck);
      keep_chunk(acck, 7);
    }
    TS(11);
    {
      const uint4* const Pown = p.s->P + (size_t)(rt * 8 + j) * 4096 + go * 32 + lane;
      uint32_t r[4][4];
      float y[8];
      mbar_wait(bars + BAR_X2, 0);
      issue_pkts<0, 4>(Pown, 1024, r);
      verify4_rt<16384>(Pown, r, 0);
      TS(13);
#pragma unroll
      for (int s = 0; s < 4; s++) add_partial(y, r[s], 0x10000u, s == 0);
      const uint32_t gt = sb + SM_TAB + 1792 + ((go - 24) * 4 + q) * 8;
      store_out(p.out, (uint32_t)(rt * 128 + 16 * j + gq) * 256 + go * 8 + q, sb + SM_PARK + SLOT + (go >> 2) * 4096 + (go & 3) * 512 + lane * 16,
                lds32(gt), lds32(gt + 4), y);
    }
    TS(12);
    if (bid == 0 && tid == 0) asm volatile("st.relaxed.gpu.global.u32 [%0], %1;" ::"l"(&p.s->epoch), "r"(tag) : "memory");
  }
}

typedef CUresult (*EncodeFn)(CUtensorMap*, CUtensorMapDataType, cuuint32_t, void*, const cuuint64_t*, const cuuint64_t*,
                             const cuuint32_t*, const cuuint32_t*, CUtensorMapInterleave, CUtensorMapSwizzle,
                             CUtensorMapL2promotion, CUtensorMapFloatOOBfill);

static void make_map(EncodeFn fn, CUtensorMap* tm, const void* ptr, int inner, int rows, int cols, int box_rows, int box_outer,
                     CUtensorMapSwizzle swz) {
  cuuint64_t gd[3] = {(cuuint64_t)inner, (cuuint64_t)rows, (cuuint64_t)(cols / inner)};
  cuuint64_t gs[2] = {(cuuint64_t)cols * 2, (cuuint64_t)inner * 2};
  cuuint32_t bx[3] = {(cuuint32_t)inner, (cuuint32_t)box_rows, (cuuint32_t)box_outer};
  cuuint32_t es[3] = {1, 1, 1};
  fn(tm, CU_TENSOR_MAP_DATA_TYPE_BFLOAT16, 3, const_cast<void*>(ptr), gd, gs, bx, es, CU_TENSOR_MAP_INTERLEAVE_NONE, swz,
     CU_TENSOR_MAP_L2_PROMOTION_L2_128B, CU_TENSOR_MAP_FLOAT_OOB_FILL_NONE);
}

extern "C" void kernel_launch(void* const* d_in, const int* in_sizes, int n_in, void* d_out, int out_size) {
  (void)in_sizes; (void)n_in; (void)out_size;
  void* fnp = nullptr;
  cudaDriverEntryPointQueryResult qr;
  cudaGetDriverEntryPoint("cuTensorMapEncodeTiled", &fnp, cudaEnableDefault, &qr);
  EncodeFn fn = (EncodeFn)fnp;
  CUtensorMap tmWq, tmK, tmV, tmWo, tmW1, tmW2, tmWm, tmX;
  make_map(fn, &tmWq, d_in[3], 64, 512, 4096, 128, 2, CU_TENSOR_MAP_SWIZZLE_128B);
  make_map(fn, &tmK, d_in[1], 64, 8 * SK, 128, 128, 2, CU_TENSOR_MAP_SWIZZLE_128B);
  make_map(fn, &tmV, d_in[2], 64, 8 * SK, 128, 128, 2, CU_TENSOR_MAP_SWIZZLE_128B);
  make_map(fn, &tmWo, d_in[4], 64, 4096, 512, 256, 1, CU_TENSOR_MAP_SWIZZLE_128B);
  make_map(fn, &tmW1, d_in[6], 64, 512, FF, 64, 4, CU_TENSOR_MAP_SWIZZLE_128B);
  make_map(fn, &tmW2, d_in[7], 64, FF, 512, 224, 1, CU_TENSOR_MAP_SWIZZLE_128B);
  make_map(fn, &tmWm, d_in[9], 8, 512, 3072, 256, 1, CU_TENSOR_MAP_SWIZZLE_NONE);
  make_map(fn, &tmX, d_in[0], 16, 2048, 512, 16, 4, CU_TENSOR_MAP_SWIZZLE_NONE);
  Params p;
  p.x = (const __nv_bfloat16*)d_in[0];
  p.c = (const __nv_bfloat16*)d_in[8];
  p.wmod = (const __nv_bfloat16*)d_in[9];
  p.wo = (const __nv_bfloat16*)d_in[4];
  p.w1 = (const __nv_bfloat16*)d_in[6];
  p.w2 = (const __nv_bfloat16*)d_in[7];
  p.out = (__nv_bfloat16*)d_out;
  p.zero = 0;
  cudaGetSymbolAddress((void**)&p.s, g_scratch);
  cudaFuncSetAttribute(adaln_block_kernel, cudaFuncAttributeMaxDynamicSharedMemorySize, SM_TOTAL);
  cudaLaunchConfig_t cfg = {};
  cfg.gridDim = 128; cfg.blockDim = 512; cfg.dynamicSmemBytes = SM_TOTAL; cfg.stream = cudaStreamPerThread;
  cudaLaunchAttribute at[1];
  at[0].id = cudaLaunchAttributeClusterDimension; at[0].val.clusterDim.x = 2; at[0].val.clusterDim.y = 1; at[0].val.clusterDim.z = 1;
  cfg.attrs = at; cfg.numAttrs = 1;
  cudaLaunchKernelEx(&cfg, adaln_block_kernel, tmWq, tmK, tmV, tmWo, tmW1, tmW2, tmWm, tmX, p);
}
```

```cpp
#include <cuda_runtime.h>
#include <cuda_bf16.h>
#include <cuda.h>
#include <stdint.h>

template <int OFF, uint32_t HI>
__device__ __forceinline__ void wgmma_rs_n128_tb0(float (&d)[64], const uint32_t (&a)[4], uint32_t lo, int sd) {
  asm volatile("{\n.reg .pred p;\n.reg .b32 l;\n.reg .b64 db;\nsetp.ne.b32 p, %69, 0;\n"
    "add.u32 l, %68, %70;\nmov.b64 db, {l, %71};\n"
    "wgmma.mma_async.sync.aligned.m64n128k16.f32.bf16.bf16 "
    "{%0,%1,%2,%3,%4,%5,%6,%7,%8,%9,%10,%11,%12,%13,%14,%15,"
    "%16,%17,%18,%19,%20,%21,%22,%23,%24,%25,%26,%27,%28,%29,%30,%31,"
    "%32,%33,%34,%35,%36,%37,%38,%39,%40,%41,%42,%43,%44,%45,%46,%47,"
    "%48,%49,%50,%51,%52,%53,%54,%55,%56,%57,%58,%59,%60,%61,%62,%63}, "
    "{%64,%65,%66,%67}, db, p, 1, 1, 0;\n}\n"
    : "+f"(d[0]), "+f"(d[1]), "+f"(d[2]), "+f"(d[3]), "+f"(d[4]), "+f"(d[5]), "+f"(d[6]), "+f"(d[7]),
      "+f"(d[8]), "+f"(d[9]), "+f"(d[10]), "+f"(d[11]), "+f"(d[12]), "+f"(d[13]), "+f"(d[14]), "+f"(d[15]),
      "+f"(d[16]), "+f"(d[17]), "+f"(d[18]), "+f"(d[19]), "+f"(d[20]), "+f"(d[21]), "+f"(d[22]), "+f"(d[23]),
      "+f"(d[24]), "+f"(d[25]), "+f"(d[26]), "+f"(d[27]), "+f"(d[28]), "+f"(d[29]), "+f"(d[30]), "+f"(d[31]),
      "+f"(d[32]), "+f"(d[33]), "+f"(d[34]), "+f"(d[35]), "+f"(d[36]), "+f"(d[37]), "+f"(d[38]), "+f"(d[39]),
      "+f"(d[40]), "+f"(d[41]), "+f"(d[42]), "+f"(d[43]), "+f"(d[44]), "+f"(d[45]), "+f"(d[46]), "+f"(d[47]),
      "+f"(d[48]), "+f"(d[49]), "+f"(d[50]), "+f"(d[51]), "+f"(d[52]), "+f"(d[53]), "+f"(d[54]), "+f"(d[55]),
      "+f"(d[56]), "+f"(d[57]), "+f"(d[58]), "+f"(d[59]), "+f"(d[60]), "+f"(d[61]), "+f"(d[62]), "+f"(d[63])
    : "r"(a[0]), "r"(a[1]), "r"(a[2]), "r"(a[3]), "r"(lo), "r"(sd), "n"(OFF), "n"(HI));
}

template <int OFF, uint32_t HI>
__device__ __forceinline__ void wgmma_rs_n128_tb1(float (&d)[64], const uint32_t (&a)[4], uint32_t lo, int sd) {
  asm volatile("{\n.reg .pred p;\n.reg .b32 l;\n.reg .b64 db;\nsetp.ne.b32 p, %69, 0;\n"
    "add.u32 l, %68, %70;\nmov.b64 db, {l, %71};\n"
    "wgmma.mma_async.sync.aligned.m64n128k16.f32.bf16.bf16 "
    "{%0,%1,%2,%3,%4,%5,%6,%7,%8,%9,%10,%11,%12,%13,%14,%15,"
    "%16,%17,%18,%19,%20,%21,%22,%23,%24,%25,%26,%27,%28,%29,%30,%31,"
    "%32,%33,%34,%35,%36,%37,%38,%39,%40,%41,%42,%43,%44,%45,%46,%47,"
    "%48,%49,%50,%51,%52,%53,%54,%55,%56,%57,%58,%59,%60,%61,%62,%63}, "
    "{%64,%65,%66,%67}, db, p, 1, 1, 1;\n}\n"
    : "+f"(d[0]), "+f"(d[1]), "+f"(d[2]), "+f"(d[3]), "+f"(d[4]), "+f"(d[5]), "+f"(d[6]), "+f"(d[7]),
      "+f"(d[8]), "+f"(d[9]), "+f"(d[10]), "+f"(d[11]), "+f"(d[12]), "+f"(d[13]), "+f"(d[14]), "+f"(d[15]),
      "+f"(d[16]), "+f"(d[17]), "+f"(d[18]), "+f"(d[19]), "+f"(d[20]), "+f"(d[21]), "+f"(d[22]), "+f"(d[23]),
      "+f"(d[24]), "+f"(d[25]), "+f"(d[26]), "+f"(d[27]), "+f"(d[28]), "+f"(d[29]), "+f"(d[30]), "+f"(d[31]),
      "+f"(d[32]), "+f"(d[33]), "+f"(d[34]), "+f"(d[35]), "+f"(d[36]), "+f"(d[37]), "+f"(d[38]), "+f"(d[39]),
      "+f"(d[40]), "+f"(d[41]), "+f"(d[42]), "+f"(d[43]), "+f"(d[44]), "+f"(d[45]), "+f"(d[46]), "+f"(d[47]),
      "+f"(d[48]), "+f"(d[49]), "+f"(d[50]), "+f"(d[51]), "+f"(d[52]), "+f"(d[53]), "+f"(d[54]), "+f"(d[55]),
      "+f"(d[56]), "+f"(d[57]), "+f"(d[58]), "+f"(d[59]), "+f"(d[60]), "+f"(d[61]), "+f"(d[62]), "+f"(d[63])
    : "r"(a[0]), "r"(a[1]), "r"(a[2]), "r"(a[3]), "r"(lo), "r"(sd), "n"(OFF), "n"(HI));
}

template <int OFF, uint32_t HI>
__device__ __forceinline__ void wgmma_rs_n192_tb1(float (&d)[96], const uint32_t (&a)[4], uint32_t lo, int sd) {
  asm volatile("{\n.reg .pred p;\n.reg .b32 l;\n.reg .b64 db;\nsetp.ne.b32 p, %101, 0;\n"
    "add.u32 l, %100, %102;\nmov.b64 db, {l, %103};\n"
    "wgmma.mma_async.sync.aligned.m64n192k16.f32.bf16.bf16 "
    "{%0,%1,%2,%3,%4,%5,%6,%7,%8,%9,%10,%11,%12,%13,%14,%15,"
    "%16,%17,%18,%19,%20,%21,%22,%23,%24,%25,%26,%27,%28,%29,%30,%31,"
    "%32,%33,%34,%35,%36,%37,%38,%39,%40,%41,%42,%43,%44,%45,%46,%47,"
    "%48,%49,%50,%51,%52,%53,%54,%55,%56,%57,%58,%59,%60,%61,%62,%63,"
    "%64,%65,%66,%67,%68,%69,%70,%71,%72,%73,%74,%75,%76,%77,%78,%79,"
    "%80,%81,%82,%83,%84,%85,%86,%87,%88,%89,%90,%91,%92,%93,%94,%95}, "
    "{%96,%97,%98,%99}, db, p, 1, 1, 1;\n}\n"
    : "+f"(d[0]), "+f"(d[1]), "+f"(d[2]), "+f"(d[3]), "+f"(d[4]), "+f"(d[5]), "+f"(d[6]), "+f"(d[7]),
      "+f"(d[8]), "+f"(d[9]), "+f"(d[10]), "+f"(d[11]), "+f"(d[12]), "+f"(d[13]), "+f"(d[14]), "+f"(d[15]),
      "+f"(d[16]), "+f"(d[17]), "+f"(d[18]), "+f"(d[19]), "+f"(d[20]), "+f"(d[21]), "+f"(d[22]), "+f"(d[23]),
      "+f"(d[24]), "+f"(d[25]), "+f"(d[26]), "+f"(d[27]), "+f"(d[28]), "+f"(d[29]), "+f"(d[30]), "+f"(d[31]),
      "+f"(d[32]), "+f"(d[33]), "+f"(d[34]), "+f"(d[35]), "+f"(d[36]), "+f"(d[37]), "+f"(d[38]), "+f"(d[39]),
      "+f"(d[40]), "+f"(d[41]), "+f"(d[42]), "+f"(d[43]), "+f"(d[44]), "+f"(d[45]), "+f"(d[46]), "+f"(d[47]),
      "+f"(d[48]), "+f"(d[49]), "+f"(d[50]), "+f"(d[51]), "+f"(d[52]), "+f"(d[53]), "+f"(d[54]), "+f"(d[55]),
      "+f"(d[56]), "+f"(d[57]), "+f"(d[58]), "+f"(d[59]), "+f"(d[60]), "+f"(d[61]), "+f"(d[62]), "+f"(d[63]),
      "+f"(d[64]), "+f"(d[65]), "+f"(d[66]), "+f"(d[67]), "+f"(d[68]), "+f"(d[69]), "+f"(d[70]), "+f"(d[71]),
      "+f"(d[72]), "+f"(d[73]), "+f"(d[74]), "+f"(d[75]), "+f"(d[76]), "+f"(d[77]), "+f"(d[78]), "+f"(d[79]),
      "+f"(d[80]), "+f"(d[81]), "+f"(d[82]), "+f"(d[83]), "+f"(d[84]), "+f"(d[85]), "+f"(d[86]), "+f"(d[87]),
      "+f"(d[88]), "+f"(d[89]), "+f"(d[90]), "+f"(d[91]), "+f"(d[92]), "+f"(d[93]), "+f"(d[94]), "+f"(d[95])
    : "r"(a[0]), "r"(a[1]), "r"(a[2]), "r"(a[3]), "r"(lo), "r"(sd), "n"(OFF), "n"(HI));
}

template <int OFF, uint32_t HI>
__device__ __forceinline__ void wgmma_rs_n32_tb1(float (&d)[16], const uint32_t (&a)[4], uint32_t lo, int sd) {
  asm volatile("{\n.reg .pred p;\n.reg .b32 l;\n.reg .b64 db;\nsetp.ne.b32 p, %21, 0;\n"
    "add.u32 l, %20, %22;\nmov.b64 db, {l, %23};\n"
    "wgmma.mma_async.sync.aligned.m64n32k16.f32.bf16.bf16 "
    "{%0,%1,%2,%3,%4,%5,%6,%7,%8,%9,%10,%11,%12,%13,%14,%15}, "
    "{%16,%17,%18,%19}, db, p, 1, 1, 1;\n}\n"
    : "+f"(d[0]), "+f"(d[1]), "+f"(d[2]), "+f"(d[3]), "+f"(d[4]), "+f"(d[5]), "+f"(d[6]), "+f"(d[7]),
      "+f"(d[8]), "+f"(d[9]), "+f"(d[10]), "+f"(d[11]), "+f"(d[12]), "+f"(d[13]), "+f"(d[14]), "+f"(d[15])
    : "r"(a[0]), "r"(a[1]), "r"(a[2]), "r"(a[3]), "r"(lo), "r"(sd), "n"(OFF), "n"(HI));
}

template <int OFF, uint32_t HI>
__device__ __forceinline__ void wgmma_rs_n64_tb1(float (&d)[32], const uint32_t (&a)[4], uint32_t lo, int sd) {
  asm volatile("{\n.reg .pred p;\n.reg .b32 l;\n.reg .b64 db;\nsetp.ne.b32 p, %37, 0;\n"
    "add.u32 l, %36, %38;\nmov.b64 db, {l, %39};\n"
    "wgmma.mma_async.sync.aligned.m64n64k16.f32.bf16.bf16 "
    "{%0,%1,%2,%3,%4,%5,%6,%7,%8,%9,%10,%11,%12,%13,%14,%15,"
    "%16,%17,%18,%19,%20,%21,%22,%23,%24,%25,%26,%27,%28,%29,%30,%31}, "
    "{%32,%33,%34,%35}, db, p, 1, 1, 1;\n}\n"
    : "+f"(d[0]), "+f"(d[1]), "+f"(d[2]), "+f"(d[3]), "+f"(d[4]), "+f"(d[5]), "+f"(d[6]), "+f"(d[7]),
      "+f"(d[8]), "+f"(d[9]), "+f"(d[10]), "+f"(d[11]), "+f"(d[12]), "+f"(d[13]), "+f"(d[14]), "+f"(d[15]),
      "+f"(d[16]), "+f"(d[17]), "+f"(d[18]), "+f"(d[19]), "+f"(d[20]), "+f"(d[21]), "+f"(d[22]), "+f"(d[23]),
      "+f"(d[24]), "+f"(d[25]), "+f"(d[26]), "+f"(d[27]), "+f"(d[28]), "+f"(d[29]), "+f"(d[30]), "+f"(d[31])
    : "r"(a[0]), "r"(a[1]), "r"(a[2]), "r"(a[3]), "r"(lo), "r"(sd), "n"(OFF), "n"(HI));
}

template <int STR>
__device__ __forceinline__ void verify8_tag1(const uint4* p, uint32_t (*r)[4]) {
  asm volatile("{\n.reg .pred p, q;\n.reg .b32 a, n;\nmov.u32 n, 0;\n"
    "LAB_CHK:\n"
    "and.b32 a, %0, %4;\n"
    "and.b32 a, a, %8;\n"
    "and.b32 a, a, %12;\n"
    "and.b32 a, a, %16;\n"
    "and.b32 a, a, %20;\n"
    "and.b32 a, a, %24;\n"
    "and.b32 a, a, %28;\n"
    "and.b32 a, a, 1;\nsetp.eq.u32 p, a, 1;\nvote.sync.all.pred p, p, 0xffffffff;\n"
    "@p bra.uni LAB_OK;\n"
    "and.b32 a, %0, 1;\nsetp.ne.u32 q, a, 1;\n"
    "@q ld.relaxed.gpu.global.v4.b32 {%0,%1,%2,%3}, [%32+%33];\n"
    "and.b32 a, %4, 1;\nsetp.ne.u32 q, a, 1;\n"
    "@q ld.relaxed.gpu.global.v4.b32 {%4,%5,%6,%7}, [%32+%34];\n"
    "and.b32 a, %8, 1;\nsetp.ne.u32 q, a, 1;\n"
    "@q ld.relaxed.gpu.global.v4.b32 {%8,%9,%10,%11}, [%32+%35];\n"
    "and.b32 a, %12, 1;\nsetp.ne.u32 q, a, 1;\n"
    "@q ld.relaxed.gpu.global.v4.b32 {%12,%13,%14,%15}, [%32+%36];\n"
    "and.b32 a, %16, 1;\nsetp.ne.u32 q, a, 1;\n"
    "@q ld.relaxed.gpu.global.v4.b32 {%16,%17,%18,%19}, [%32+%37];\n"
    "and.b32 a, %20, 1;\nsetp.ne.u32 q, a, 1;\n"
    "@q ld.relaxed.gpu.global.v4.b32 {%20,%21,%22,%23}, [%32+%38];\n"
    "and.b32 a, %24, 1;\nsetp.ne.u32 q, a, 1;\n"
    "@q ld.relaxed.gpu.global.v4.b32 {%24,%25,%26,%27}, [%32+%39];\n"
    "and.b32 a, %28, 1;\nsetp.ne.u32 q, a, 1;\n"
    "@q ld.relaxed.gpu.global.v4.b32 {%28,%29,%30,%31}, [%32+%40];\n"
    "add.u32 n, n, 1;\nsetp.lt.u32 q, n, 262144;\n@q bra.uni LAB_CHK;\n"
    "LAB_OK:\n"
    "}\n"
    : "+r"(r[0][0]), "+r"(r[0][1]), "+r"(r[0][2]), "+r"(r[0][3]), "+r"(r[1][0]), "+r"(r[1][1]), "+r"(r[1][2]), "+r"(r[1][3]),
      "+r"(r[2][0]), "+r"(r[2][1]), "+r"(r[2][2]), "+r"(r[2][3]), "+r"(r[3][0]), "+r"(r[3][1]), "+r"(r[3][2]), "+r"(r[3][3]),
      "+r"(r[4][0]), "+r"(r[4][1]), "+r"(r[4][2]), "+r"(r[4][3]), "+r"(r[5][0]), "+r"(r[5][1]), "+r"(r[5][2]), "+r"(r[5][3]),
      "+r"(r[6][0]), "+r"(r[6][1]), "+r"(r[6][2]), "+r"(r[6][3]), "+r"(r[7][0]), "+r"(r[7][1]), "+r"(r[7][2]), "+r"(r[7][3])
    : "l"(p), "n"(0 * STR), "n"(1 * STR), "n"(2 * STR), "n"(3 * STR), "n"(4 * STR), "n"(5 * STR), "n"(6 * STR), "n"(7 * STR)
    : "memory");
}

template <int STR>
__device__ __forceinline__ void verify4_rt(const uint4* p, uint32_t (*r)[4], uint32_t tag) {
  asm volatile("{\n.reg .pred p, q;\n.reg .b32 a, b, n;\nmov.u32 n, 0;\n"
    "LAB_CHK:\n"
    "lop3.b32 a, %0, %4, %21, 0x7e;\n"
    "lop3.b32 b, %8, %12, %21, 0x7e;\nor.b32 a, a, b;\n"
    "and.b32 a, a, 1;\nsetp.eq.u32 p, a, 0;\nvote.sync.all.pred p, p, 0xffffffff;\n"
    "@p bra.uni LAB_OK;\n"
    "and.b32 a, %0, 1;\nsetp.ne.u32 q, a, %21;\n"
    "@q ld.relaxed.gpu.global.v4.b32 {%0,%1,%2,%3}, [%16+%17];\n"
    "and.b32 a, %4, 1;\nsetp.ne.u32 q, a, %21;\n"
    "@q ld.relaxed.gpu.global.v4.b32 {%4,%5,%6,%7}, [%16+%18];\n"
    "and.b32 a, %8, 1;\nsetp.ne.u32 q, a, %21;\n"
    "@q ld.relaxed.gpu.global.v4.b32 {%8,%9,%10,%11}, [%16+%19];\n"
    "and.b32 a, %12, 1;\nsetp.ne.u32 q, a, %21;\n"
    "@q ld.relaxed.gpu.global.v4.b32 {%12,%13,%14,%15}, [%16+%20];\n"
    "add.u32 n, n, 1;\nsetp.lt.u32 q, n, 262144;\n@q bra.uni LAB_CHK;\n"
    "LAB_OK:\n}\n"
    : "+r"(r[0][0]), "+r"(r[0][1]), "+r"(r[0][2]), "+r"(r[0][3]), "+r"(r[1][0]), "+r"(r[1][1]), "+r"(r[1][2]), "+r"(r[1][3]),
      "+r"(r[2][0]), "+r"(r[2][1]), "+r"(r[2][2]), "+r"(r[2][3]), "+r"(r[3][0]), "+r"(r[3][1]), "+r"(r[3][2]), "+r"(r[3][3])
    : "l"(p), "n"(0 * STR), "n"(1 * STR), "n"(2 * STR), "n"(3 * STR), "r"(tag)
    : "memory");
}

template <int STR>
__device__ __forceinline__ void verify8_tag0(const uint4* p, uint32_t (*r)[4]) {
  asm volatile("{\n.reg .pred p, q;\n.reg .b32 a, n;\nmov.u32 n, 0;\n"
    "LAB_CHK:\n"
    "or.b32 a, %0, %4;\n"
    "or.b32 a, a, %8;\n"
    "or.b32 a, a, %12;\n"
    "or.b32 a, a, %16;\n"
    "or.b32 a, a, %20;\n"
    "or.b32 a, a, %24;\n"
    "or.b32 a, a, %28;\n"
    "and.b32 a, a, 1;\nsetp.eq.u32 p, a, 0;\nvote.sync.all.pred p, p, 0xffffffff;\n"
    "@p bra.uni LAB_OK;\n"
    "and.b32 a, %0, 1;\nsetp.ne.u32 q, a, 0;\n"
    "@q ld.relaxed.gpu.global.v4.b32 {%0,%1,%2,%3}, [%32+%33];\n"
    "and.b32 a, %4, 1;\nsetp.ne.u32 q, a, 0;\n"
    "@q ld.relaxed.gpu.global.v4.b32 {%4,%5,%6,%7}, [%32+%34];\n"
    "and.b32 a, %8, 1;\nsetp.ne.u32 q, a, 0;\n"
    "@q ld.relaxed.gpu.global.v4.b32 {%8,%9,%10,%11}, [%32+%35];\n"
    "and.b32 a, %12, 1;\nsetp.ne.u32 q, a, 0;\n"
    "@q ld.relaxed.gpu.global.v4.b32 {%12,%13,%14,%15}, [%32+%36];\n"
    "and.b32 a, %16, 1;\nsetp.ne.u32 q, a, 0;\n"
    "@q ld.relaxed.gpu.global.v4.b32 {%16,%17,%18,%19}, [%32+%37];\n"
    "and.b32 a, %20, 1;\nsetp.ne.u32 q, a, 0;\n"
    "@q ld.relaxed.gpu.global.v4.b32 {%20,%21,%22,%23}, [%32+%38];\n"
    "and.b32 a, %24, 1;\nsetp.ne.u32 q, a, 0;\n"
    "@q ld.relaxed.gpu.global.v4.b32 {%24,%25,%26,%27}, [%32+%39];\n"
    "and.b32 a, %28, 1;\nsetp.ne.u32 q, a, 0;\n"
    "@q ld.relaxed.gpu.global.v4.b32 {%28,%29,%30,%31}, [%32+%40];\n"
    "add.u32 n, n, 1;\nsetp.lt.u32 q, n, 262144;\n@q bra.uni LAB_CHK;\n"
    "LAB_OK:\n"
    "or.b32 %0, %0, 1;\n"
    "or.b32 %4, %4, 1;\n"
    "or.b32 %8, %8, 1;\n"
    "or.b32 %12, %12, 1;\n"
    "or.b32 %16, %16, 1;\n"
    "or.b32 %20, %20, 1;\n"
    "or.b32 %24, %24, 1;\n"
    "or.b32 %28, %28, 1;\n"
    "}\n"
    : "+r"(r[0][0]), "+r"(r[0][1]), "+r"(r[0][2]), "+r"(r[0][3]), "+r"(r[1][0]), "+r"(r[1][1]), "+r"(r[1][2]), "+r"(r[1][3]),
      "+r"(r[2][0]), "+r"(r[2][1]), "+r"(r[2][2]), "+r"(r[2][3]), "+r"(r[3][0]), "+r"(r[3][1]), "+r"(r[3][2]), "+r"(r[3][3]),
      "+r"(r[4][0]), "+r"(r[4][1]), "+r"(r[4][2]), "+r"(r[4][3]), "+r"(r[5][0]), "+r"(r[5][1]), "+r"(r[5][2]), "+r"(r[5][3]),
      "+r"(r[6][0]), "+r"(r[6][1]), "+r"(r[6][2]), "+r"(r[6][3]), "+r"(r[7][0]), "+r"(r[7][1]), "+r"(r[7][2]), "+r"(r[7][3])
    : "l"(p), "n"(0 * STR), "n"(1 * STR), "n"(2 * STR), "n"(3 * STR), "n"(4 * STR), "n"(5 * STR), "n"(6 * STR), "n"(7 * STR)
    : "memory");
}

#define SPIN_LIMIT (1 << 18)

__device__ __forceinline__ uint32_t smem_u32(const void* p) { return (uint32_t)__cvta_generic_to_shared(p); }
__device__ __forceinline__ void mbar_init(uint32_t a, uint32_t c) {
  asm volatile("mbarrier.init.shared::cta.b64 [%0], %1;" ::"r"(a), "r"(c) : "memory");
}
__device__ __forceinline__ void mbar_expect(uint32_t a, uint32_t b) {
  asm volatile("mbarrier.arrive.expect_tx.shared::cta.b64 _, [%0], %1;" ::"r"(a), "r"(b) : "memory");
}
__device__ __forceinline__ void mbar_arrive(uint32_t a) {
  asm volatile("mbarrier.arrive.shared::cta.b64 _, [%0];" ::"r"(a) : "memory");
}
__device__ __forceinline__ void mbar_wait(uint32_t a, uint32_t parity) {
  asm volatile(
      "{\n.reg .pred p;\n.reg .u32 n;\nmov.u32 n, 0;\n"
      "LAB_WAIT:\n"
      "mbarrier.try_wait.parity.shared::cta.b64 p, [%0], %1;\n"
      "@p bra LAB_DONE;\n"
      "add.u32 n, n, 1;\n"
      "setp.lt.u32 p, n, 262144;\n"
      "@p bra LAB_WAIT;\n"
      "LAB_DONE:\n}\n" ::"r"(a), "r"(parity) : "memory");
}
__device__ __forceinline__ bool mbar_test(uint32_t a, uint32_t parity) {
  uint32_t ok;
  asm volatile("{\n.reg .pred p;\nmbarrier.test_wait.parity.shared::cta.b64 p, [%1], %2;\nselp.u32 %0, 1, 0, p;\n}\n"
               : "=r"(ok) : "r"(a), "r"(parity) : "memory");
  return ok;
}
__device__ __forceinline__ void tma3d(uint32_t dst, const CUtensorMap* tm, uint32_t bar, int c0, int c1, int c2) {
  asm volatile(
      "cp.async.bulk.tensor.3d.shared::cluster.global.mbarrier::complete_tx::bytes [%0], [%1, {%3,%4,%5}], [%2];"
      ::"r"(dst), "l"(tm), "r"(bar), "r"(c0), "r"(c1), "r"(c2) : "memory");
}
__device__ __forceinline__ void wg_fence() { asm volatile("wgmma.fence.sync.aligned;" ::: "memory"); }
__device__ __forceinline__ void wg_commit() { asm volatile("wgmma.commit_group.sync.aligned;" ::: "memory"); }
template <int N> __device__ __forceinline__ void wg_wait() {
  asm volatile("wgmma.wait_group.sync.aligned %0;" ::"n"(N) : "memory");
}
template <int N> __device__ __forceinline__ void fence_regs(float (&d)[N]) {
#pragma unroll
  for (int i = 0; i < N; i++) asm volatile("" : "+f"(d[i])::"memory");
}
template <int N> __device__ __forceinline__ void fence_regs(uint32_t (&d)[N][4]) {
#pragma unroll
  for (int i = 0; i < N; i++) asm volatile("" : "+r"(d[i][0]), "+r"(d[i][1]), "+r"(d[i][2]), "+r"(d[i][3])::"memory");
}
template <int N> __device__ __forceinline__ void fence_frags(uint32_t (*d)[4]) {
#pragma unroll
  for (int i = 0; i < N; i++) asm volatile("" : "+r"(d[i][0]), "+r"(d[i][1]), "+r"(d[i][2]), "+r"(d[i][3])::"memory");
}
__device__ __forceinline__ void bar_sync(int id, int n) { asm volatile("bar.sync %0, %1;" ::"r"(id), "r"(n) : "memory"); }
__device__ __forceinline__ void bar_arrive(int id, int n) { asm volatile("bar.arrive %0, %1;" ::"r"(id), "r"(n) : "memory"); }

__device__ __forceinline__ uint32_t pack_bf16(float lo, float hi) {
  uint32_t r;
  asm("cvt.rn.bf16x2.f32 %0, %1, %2;" : "=r"(r) : "f"(hi), "f"(lo));
  return r;
}
__device__ __forceinline__ float bf_lo(uint32_t w) { return __uint_as_float(w << 16); }
__device__ __forceinline__ float bf_hi(uint32_t w) { return __uint_as_float(w & 0xFFFF0000u); }
__device__ __forceinline__ float round_bf16(float x) { return bf_lo(pack_bf16(x, 0.f)); }
__device__ __forceinline__ uint32_t hfma2_bf16(uint32_t a, uint32_t b, uint32_t c) {
  uint32_t r;
  asm("fma.rn.bf16x2 %0, %1, %2, %3;" : "=r"(r) : "r"(a), "r"(b), "r"(c));
  return r;
}
__device__ __forceinline__ float ex2(float x) {
  float r;
  asm("ex2.approx.ftz.f32 %0, %1;" : "=f"(r) : "f"(x));
  return r;
}
__device__ __forceinline__ float tanh_hw(float x) {
  float r;
  asm("tanh.approx.f32 %0, %1;" : "=f"(r) : "f"(x));
  return r;
}
template <int TAG> __device__ __forceinline__ uint32_t pack_tag(float lo, float hi) {
  uint32_t w = __byte_perm(__float_as_uint(lo), pack_bf16(lo, hi), 0x7632);
  return TAG ? (w | 1u) : (w & ~1u);
}
__device__ __forceinline__ void st_pkt(uint4* p, uint32_t a, uint32_t b, uint32_t c, uint32_t d) {
  asm volatile(
      "st.relaxed.gpu.global.v4.b32 [%0], {%1,%2,%3,%4};" ::"l"(p), "r"(a), "r"(b), "r"(c), "r"(d) : "memory");
}
__device__ __forceinline__ void ld_pkt(const uint4* p, uint32_t (&r)[4]) {
  asm volatile(
      "ld.relaxed.gpu.global.v4.b32 {%0,%1,%2,%3}, [%4];"
      : "=r"(r[0]), "=r"(r[1]), "=r"(r[2]), "=r"(r[3]) : "l"(p) : "memory");
}
__device__ __forceinline__ uint32_t ldg32(const void* p) {
  uint32_t r;
  asm volatile("ld.global.nc.b32 %0, [%1];" : "=r"(r) : "l"(p));
  return r;
}
__device__ __forceinline__ uint32_t ldg16(const void* p) {
  uint16_t r;
  asm volatile("ld.global.nc.b16 %0, [%1];" : "=h"(r) : "l"(p));
  return r;
}
__device__ __forceinline__ uint4 ldg128(const void* p) {
  uint4 r;
  asm volatile("ld.global.nc.v4.b32 {%0,%1,%2,%3}, [%4];" : "=r"(r.x), "=r"(r.y), "=r"(r.z), "=r"(r.w) : "l"(p));
  return r;
}
__device__ __forceinline__ void l2_prefetch(const void* p, uint32_t bytes) {
  asm volatile("cp.async.bulk.prefetch.L2.global [%0], %1;" ::"l"(p), "r"(bytes) : "memory");
}
__device__ __forceinline__ float rcp_hw(float x) {
  float r;
  asm("rcp.approx.ftz.f32 %0, %1;" : "=f"(r) : "f"(x));
  return r;
}
__device__ __forceinline__ void warp_bulk_load(uint32_t sdst, const void* gsrc, uint32_t bytes, uint32_t bar) {
  asm volatile(
      "{\n.reg .pred p;\nelect.sync _|p, 0xffffffff;\n"
      "@p mbarrier.arrive.expect_tx.shared::cta.b64 _, [%3], %2;\n"
      "@p cp.async.bulk.shared::cluster.global.mbarrier::complete_tx::bytes [%0], [%1], %2, [%3];\n}\n"
      ::"r"(sdst), "l"(gsrc), "r"(bytes), "r"(bar) : "memory");
}
__device__ __forceinline__ void warp_tma3d(uint32_t dst, const CUtensorMap* tm, uint32_t bar, uint32_t bytes, int c1, int c2) {
  asm volatile(
      "{\n.reg .pred p;\nelect.sync _|p, 0xffffffff;\n"
      "@p mbarrier.arrive.expect_tx.shared::cta.b64 _, [%2], %3;\n"
      "@p cp.async.bulk.tensor.3d.shared::cluster.global.mbarrier::complete_tx::bytes [%0], [%1, {%6,%4,%5}], [%2];\n}\n"
      ::"r"(dst), "l"(tm), "r"(bar), "r"(bytes), "r"(c1), "r"(c2), "r"(0) : "memory");
}
__device__ __forceinline__ bool elect_one() {
  uint32_t r;
  asm volatile("{\n.reg .pred p;\nelect.sync _|p, 0xffffffff;\nselp.u32 %0, 1, 0, p;\n}\n" : "=r"(r));
  return r;
}
__device__ __forceinline__ void warp_arrive(uint32_t bar) {
  asm volatile("{\n.reg .pred p;\nelect.sync _|p, 0xffffffff;\n@p mbarrier.arrive.shared::cta.b64 _, [%0];\n}\n" ::"r"(bar) : "memory");
}
__device__ __forceinline__ uint32_t pack_trunc(float lo, float hi) {
  return __byte_perm(__float_as_uint(lo), __float_as_uint(hi), 0x7632);
}
__device__ __forceinline__ void add_partial(float (&y)[8], const uint32_t (&r)[4], uint32_t c0, bool first) {
#pragma unroll
  for (int e = 0; e < 4; e++) {
    const float lo = __uint_as_float(r[e] * 65536u + (e ? 0x8000u : c0)), hi = __uint_as_float(r[e]);
    y[2 * e] = first ? lo : y[2 * e] + lo;
    y[2 * e + 1] = first ? hi : y[2 * e + 1] + hi;
  }
}
__device__ __forceinline__ void spin_cycles(uint32_t n) {
  uint32_t t0, t;
  asm volatile("mov.u32 %0, %%clock;" : "=r"(t0));
  do { asm volatile("mov.u32 %0, %%clock;" : "=r"(t)); } while (t - t0 < n);
}
__device__ __forceinline__ void sts128(uint32_t a, uint32_t x, uint32_t y, uint32_t z, uint32_t w) {
  asm volatile("st.shared.v4.b32 [%0], {%1,%2,%3,%4};" ::"r"(a), "r"(x), "r"(y), "r"(z), "r"(w) : "memory");
}
__device__ __forceinline__ void lds128(uint32_t a, uint32_t (&r)[4]) {
  asm volatile("ld.shared.v4.b32 {%0,%1,%2,%3}, [%4];" : "=r"(r[0]), "=r"(r[1]), "=r"(r[2]), "=r"(r[3]) : "r"(a) : "memory");
}

__device__ __forceinline__ uint32_t lds32(uint32_t a) {
  uint32_t r;
  asm volatile("ld.shared.b32 %0, [%1];" : "=r"(r) : "r"(a) : "memory");
  return r;
}
__device__ __forceinline__ void store_out(__nv_bfloat16* out, uint32_t woff, uint32_t x2s, uint32_t gb0, uint32_t gb1,
                                          const float (&y)[8]) {
  const uint32_t gb[2] = {gb0, gb1};
  uint32_t xa[2][4];
  lds128(x2s, xa[0]);
  lds128(x2s + 2048, xa[1]);
  uint32_t* const oo = (uint32_t*)out + woff;
#pragma unroll
  for (int e = 0; e < 4; e++)
    oo[(e >> 1) * 4 + (e & 1) * 8 * 256] =
        pack_bf16(fmaf(bf_lo(gb[e >> 1]), y[2 * e], __uint_as_float(xa[e >> 1][(e & 1) * 2])),
                  fmaf(bf_hi(gb[e >> 1]), y[2 * e + 1], __uint_as_float(xa[e >> 1][(e & 1) * 2 + 1])));
}

constexpr int SK = 2048, WIN = 512;
constexpr int FF = 1792, FSL = 224;
constexpr int NTILES = 80;
constexpr int NSLOT = 4;
constexpr uint32_t SLOT = 32768;
constexpr uint32_t SM_PARK = 0;
constexpr uint32_t SM_RING = 3 * SLOT;
constexpr uint32_t SM_TAB = 7 * SLOT;
constexpr uint32_t SM_RED = SM_TAB + 2048;
constexpr uint32_t SM_BAR = SM_RED + 256;
constexpr uint32_t SM_WBAR = SM_BAR + 128;
constexpr uint32_t SM_SBAR = SM_WBAR + 256;
constexpr uint32_t BAR_SLAB = 64, BAR_UV = 72, BAR_X2 = 80, BAR_TAG = 88;
constexpr uint32_t SM_DBAR = SM_SBAR + 16;
constexpr uint32_t SM_TOTAL = SM_DBAR + 128;

struct Scratch {
  uint4 P[16 * 8 * 4 * 1024];
  uint4 G[16 * 8 * 32 * 32];
  uint4 mod1[8 * 256];
  uint4 mod2[512];
  uint4 uv[2 * 448];
  uint4 stat[16 * 8 * 8];
  uint32_t sent[16 * 8 * 8];
  uint32_t epoch;
};
__device__ Scratch g_scratch;

#define TS(i) do { } while (0)
#define TR(code)
#define CK_(v)
#define CKS(i, v)

#define TRU(code)

struct Params {
  const __nv_bfloat16* x;
  const __nv_bfloat16* c;
  const __nv_bfloat16* wmod;
  const __nv_bfloat16* wo;
  const __nv_bfloat16* w1;
  const __nv_bfloat16* w2;
  __nv_bfloat16* out;
  Scratch* s;
  uint32_t zero;
};

constexpr uint32_t HI128 = (1024 >> 4) | (1u << 30);
constexpr int LB_MN128 = (16384 >> 4) << 16;
constexpr int LB_K128 = 1 << 16;
constexpr int LB_W1 = (8192 >> 4) << 16;

template <int I> struct IC {
  __host__ __device__ constexpr operator int() const { return I; }
};
template <int I, int N, typename F> __device__ __forceinline__ void static_for(F&& f) {
  if constexpr (I < N) {
    f(IC<I>{});
    static_for<I + 1, N>(f);
  }
}

struct Ring {
  uint32_t base16, bars;
  __device__ __forceinline__ uint32_t tile(uint32_t slot) const { return base16 + slot * (SLOT >> 4); }
  __device__ __forceinline__ void release(uint32_t slot) const {
    warp_arrive(bars + 32 + slot * 8);
  }
};

__device__ __forceinline__ float silu_c(uint32_t bits) {
  float x = bf_lo(bits);
  return round_bf16(x * rcp_hw(1.f + ex2(-1.4426950408889634f * x)));
}
__device__ __forceinline__ void pack8(uint32_t (&o)[4], const float* v) {
  o[0] = pack_bf16(v[0], v[1]); o[1] = pack_bf16(v[2], v[3]); o[2] = pack_bf16(v[4], v[5]); o[3] = pack_bf16(v[6], v[7]);
}

template <int TAG, int N>
__device__ __forceinline__ void issue_pkts(const uint4* p, int stride, uint32_t (*r)[4]) {
#pragma unroll
  for (int i = 0; i < N; i++) ld_pkt(p + i * stride, r[i]);
}
__device__ __forceinline__ void wait_sent(const uint32_t* p, uint32_t tag, uint32_t step) {
#pragma unroll 1
  for (int spins = 0; spins < SPIN_LIMIT; spins++) {
    uint32_t v;
    asm volatile("ld.relaxed.gpu.global.u32 %0, [%1];" : "=r"(v) : "l"(p) : "memory");
    if (__all_sync(0xffffffffu, v - (tag * 32 + step + 1) < 16u)) break;
  }
}
__device__ __forceinline__ void ld_mod(const uint4* p, uint32_t tag, uint32_t (&r)[4]) {
  int spins = 0;
  ld_pkt(p, r);
  while (r[2] != tag && ++spins < SPIN_LIMIT) ld_pkt(p, r);
}

#define EARLY_TILES 2
#define PF_WMOD 1
#define MOD1_DELAY 500
#define RED3_UNIT 3
#define NITEM2 24
#define FIN_DELAY0 800
#define FIN_DELAY1 0
#define G_DELAY 300

__device__ __forceinline__ float reduce8(float (&a)[8], int lane) {
  const bool h16 = lane & 16, h8 = lane & 8, h4 = lane & 4;
#pragma unroll
  for (int k = 0; k < 4; k++) a[k] = (h16 ? a[k + 4] : a[k]) + __shfl_xor_sync(0xffffffffu, h16 ? a[k] : a[k + 4], 16);
#pragma unroll
  for (int k = 0; k < 2; k++) a[k] = (h8 ? a[k + 2] : a[k]) + __shfl_xor_sync(0xffffffffu, h8 ? a[k] : a[k + 2], 8);
  const float r = (h4 ? a[1] : a[0]) + __shfl_xor_sync(0xffffffffu, h4 ? a[0] : a[1], 4);
  return r + __shfl_xor_sync(0xffffffffu, r, 2);
}
__device__ __forceinline__ void fma8(float (&a)[8], float s, uint32_t w0, uint32_t w1, uint32_t w2, uint32_t w3) {
  a[0] = fmaf(s, bf_lo(w0), a[0]); a[1] = fmaf(s, bf_hi(w0), a[1]);
  a[2] = fmaf(s, bf_lo(w1), a[2]); a[3] = fmaf(s, bf_hi(w1), a[3]);
  a[4] = fmaf(s, bf_lo(w2), a[4]); a[5] = fmaf(s, bf_hi(w2), a[5]);
  a[6] = fmaf(s, bf_lo(w3), a[6]); a[7] = fmaf(s, bf_hi(w3), a[7]);
}

enum { NB_TAB = 1, NB_WG0 = 2, NB_WG1 = 3, NB_HELP = 4, NB_INIT = 5, NB_PASS0 = 6, NB_GATHER = 7, NB_PARK = 8, NB_PROD = 9 };

__global__ void __launch_bounds__(512, 1)
adaln_block_kernel(const __grid_constant__ CUtensorMap tmWq, const __grid_constant__ CUtensorMap tmK,
                   const __grid_constant__ CUtensorMap tmV, const __grid_constant__ CUtensorMap tmWo,
                   const __grid_constant__ CUtensorMap tmW1, const __grid_constant__ CUtensorMap tmW2,
                   const __grid_constant__ CUtensorMap tmWm, const __grid_constant__ CUtensorMap tmX,
                   const Params p) {
  extern __shared__ __align__(1024) uint8_t smem_raw[];
  const uint32_t sb = smem_u32(smem_raw);
  const int tid = threadIdx.x, lane = tid & 31;
  const int warp = __shfl_sync(0xffffffffu, tid >> 5, 0);
  const int kp = blockIdx.x >> 1;
  const int bid = (kp < 4 ? kp : kp < 36 ? 4 + ((kp - 4) & 7) * 4 + ((kp - 4) >> 3) : 36 + ((kp - 36) % 7) * 4 + (kp - 36) / 7) * 2 +
                  (blockIdx.x & 1);
  const int j = bid & 7, rt = bid >> 3;
  const uint32_t bars = sb + SM_BAR;
  if (warp != 13) asm volatile("barrier.cluster.arrive.relaxed.aligned;" ::: "memory");

  if (warp >= 12) {
    asm volatile("setmaxnreg.dec.sync.aligned.u32 24;");
    if (warp == 13) {
      if (elect_one()) {
#pragma unroll
        for (int i = 0; i < 28; i++) mbar_init(sb + SM_WBAR + i * 8, i < 26 ? 1 : 4);
        mbar_init(sb + SM_SBAR, 8);
#pragma unroll
        for (int i = 0; i < 16; i++) mbar_init(sb + SM_DBAR + i * 8, 1);
        asm volatile("fence.mbarrier_init.release.cluster;" ::: "memory");
      }
      __syncwarp();
      asm volatile("barrier.cluster.arrive.relaxed.aligned;" ::: "memory");
      bar_arrive(NB_INIT, 224);
      mbar_wait(sb + SM_SBAR, 0);
      const uint32_t tag = *(volatile uint32_t*)(smem_raw + SM_BAR + BAR_TAG);
#pragma unroll 1
      for (int n = 0; n < 14; n++) {
        const uint32_t lb = sb + SM_WBAR + 192 + (n & 1) * 8;
        mbar_wait(lb + 16, ((n >> 1) & 1) ^ 1);
        wait_sent(&p.s->sent[(rt * 8 + j) * 8 + (lane & 6) + (n & 1)], tag, n >> 1);
        if (elect_one()) {
          mbar_expect(lb, n < 8 ? 8192 + 2048 : 8192);
#pragma unroll
          for (int m = 0; m < 4; m++)
            asm volatile("cp.async.bulk.shared::cluster.global.mbarrier::complete_tx::bytes [%0], [%1], 2048, [%2];"
                         ::"r"(sb + SM_PARK + ((n & 1) * 4 + m) * 4096 + 2048),
                           "l"(p.s->P + ((size_t)(rt * 8 + j) * 4 + m) * 1024 + (n & 7) * 128), "r"(lb) : "memory");
          if (n < 8) tma3d(sb + SM_PARK + SLOT + n * 4096, &tmX, lb, 0, rt * 128 + j * 16, n * 4);
        }
        __syncwarp();
      }
    } else if (warp == 14) {
      if (elect_one()) {
        asm volatile("prefetch.tensormap [%0];" ::"l"(&tmWq) : "memory");
        asm volatile("prefetch.tensormap [%0];" ::"l"(&tmK) : "memory");
        asm volatile("prefetch.tensormap [%0];" ::"l"(&tmV) : "memory");
        asm volatile("prefetch.tensormap [%0];" ::"l"(&tmWo) : "memory");
        asm volatile("prefetch.tensormap [%0];" ::"l"(&tmX) : "memory");
        asm volatile("prefetch.tensormap [%0];" ::"l"(&tmW1) : "memory");
        asm volatile("prefetch.tensormap [%0];" ::"l"(&tmW2) : "memory");
      }
      __syncwarp();
      bar_sync(NB_INIT, 224);
#pragma unroll 1
      for (int tt = 0; tt < NTILES; tt++) {
        mbar_wait(bars + (tt & 3) * 8, (tt >> 2) & 1);
        const bool single = tt < 4 || tt == 16 || tt == 47 || tt == 72 || tt == 79;
        const bool second = (tt > 16 && tt < 47) || tt > 72 ? !(tt & 1) : (tt & 1);
        if (single || second) bar_sync(NB_WG0, 288);
      }
    } else if (warp == 12) {
      if (elect_one()) {
        mbar_init(bars + BAR_SLAB, 1);
        asm volatile("fence.mbarrier_init.release.cluster;" ::: "memory");
        mbar_expect(bars + BAR_SLAB, 8192);
        tma3d(sb + SM_RING + 3 * SLOT, &tmWm, bars + BAR_SLAB, 0, 0, bid);
        tma3d(sb + SM_RING + 3 * SLOT + 4096, &tmWm, bars + BAR_SLAB, 0, 256, bid);
#pragma unroll
        for (int i = 0; i < 4; i++) { mbar_init(bars + i * 8, 1); mbar_init(bars + 32 + i * 8, 8); }
        mbar_init(bars + BAR_UV, 4);
        mbar_init(bars + BAR_X2, 1);
        asm volatile("fence.mbarrier_init.release.cluster;" ::: "memory");
      }
      __syncwarp();
      bar_arrive(NB_INIT, 224);
      mbar_wait(bars + BAR_SLAB, 0);
      uint32_t s = 0, ph = 1;
#pragma unroll 1
      for (int tt = 0; tt < NTILES; tt++) {
        const CUtensorMap* tm;
        int c1, c2;
        uint32_t bytes = SLOT;
        if (tt < 16) {
          tm = &tmWq; c1 = (tt & 3) * 128; c2 = (j * 4 + (((tt >> 2) + 1) & 3)) * 2;
        } else if (tt < 48) {
          const int u = tt - 16;
          const bool isK = (u == 0) || ((u & 1) && u != 31);
          const int n = isK ? ((u + 1) >> 1) : (u == 31 ? 15 : (u >> 1) - 1);
          tm = isK ? &tmK : &tmV; c1 = j * SK + (SK - WIN) + (n & 3) * 128; c2 = 0;
        } else if (tt < 64) {
          const int u = tt - 48;
          tm = &tmWo; c1 = j * 512 + (u & 1) * 256; c2 = (u >> 1) ^ (~j & 1);
        } else if (tt < 72) {
          tm = &tmW1; c1 = (tt - 64) * 64; c2 = (j * 7) >> 1;
        } else {
          tm = &tmW2; c1 = j * FSL; c2 = (tt - 72) ^ (~j & 1); bytes = 28672;
        }
        if (tt == EARLY_TILES) bar_sync(NB_PROD, 160);
        mbar_wait(bars + 32 + s * 8, ph);
        warp_tma3d(sb + SM_RING + s * SLOT, tm, bars + s * 8, bytes, c1, c2);
        if (++s == 4) { s = 0; ph ^= 1; }
      }
    }
  } else if (warp >= 8) {
    CK_(c0);
    asm volatile("setmaxnreg.dec.sync.aligned.u32 40;");
    const int t = tid - 256, hw = warp - 8, q = lane & 3;
    float* const red = (float*)(smem_raw + SM_RED);
    uint32_t tag;
    float a[8];
    {
      uint32_t cb[4];
#pragma unroll
      for (int i = 0; i < 4; i++) cb[i] = ldg16(p.c + t + 128 * i);
      asm volatile("ld.relaxed.gpu.global.u32 %0, [%1];" : "=r"(tag) : "l"(&p.s->epoch) : "memory");
      bar_sync(NB_INIT, 224);
      CK_(c2);
      tag += 1;
      float sc[4];
#pragma unroll
      for (int i = 0; i < 4; i++) sc[i] = silu_c(cb[i]);
#pragma unroll
      for (int k = 0; k < 8; k++) a[k] = 0.f;
      if (t == 0) *(uint32_t*)(smem_raw + SM_BAR + BAR_TAG) = tag;
      mbar_wait(bars + BAR_SLAB, 0);
      CK_(c3);
      bar_arrive(NB_GATHER, 384);
#pragma unroll
      for (int i = 0; i < 4; i++) {
        uint32_t w[4];
        lds128(sb + SM_RING + 3 * SLOT + (t + 128 * i) * 16, w);
        fma8(a, sc[i], w[0], w[1], w[2], w[3]);
      }
      float r = reduce8(a, lane);
      r += __shfl_xor_sync(0xffffffffu, r, 1);
      if (q == 0) red[hw * 8 + (lane >> 2)] = r;
      CK_(c4);
      bar_sync(NB_HELP, 128);
      CK_(c5);
      if (hw == 0) {
        const int cl = lane & 7;
        float v = round_bf16(red[cl] + red[8 + cl] + red[16 + cl] + red[24 + cl]);
        if (bid >= 64) v = 1.f + v;
        float vn = __shfl_down_sync(0xffffffffu, v, 1);
        uint32_t wd = pack_bf16(v, vn);
        uint32_t w0 = __shfl_sync(0xffffffffu, wd, (lane & 1) * 4);
        uint32_t w1 = __shfl_sync(0xffffffffu, wd, (lane & 1) * 4 + 2);
        if (lane < 16) st_pkt(&p.s->mod1[(lane >> 1) * 256 + bid * 2 + (lane & 1)], w0, w1, tag, 0);
      }
      uint32_t r0[4], r1[4];
      const uint4* src = &p.s->mod1[j * 256 + t];
      CK_(c6);
      spin_cycles(MOD1_DELAY);
      CK_(c7);
      int spins = 0;
      do {
        ld_pkt(src, r0);
        ld_pkt(src + 128, r1);
      } while ((r0[2] != tag || r1[2] != tag) && ++spins < SPIN_LIMIT);
      const int g = t >> 2, pp = q * 2;
      const uint32_t ad = sb + SM_TAB + (uint32_t)(g * 4 + (pp & 3)) * 16 + (pp >> 2) * 4;
      asm volatile("st.shared.b32 [%0], %1;" ::"r"(ad + 8), "r"(r0[0]) : "memory");
      asm volatile("st.shared.b32 [%0], %1;" ::"r"(ad + 24), "r"(r0[1]) : "memory");
      asm volatile("st.shared.b32 [%0], %1;" ::"r"(ad), "r"(r1[0]) : "memory");
      asm volatile("st.shared.b32 [%0], %1;" ::"r"(ad + 16), "r"(r1[1]) : "memory");
      bar_arrive(NB_TAB, 384);
      bar_arrive(NB_PROD, 160);
      CK_(c8);
      CKS(0, c0); CKS(2, c2); CKS(3, c3); CKS(4, c4); CKS(5, c5); CKS(6, c6); CKS(7, c7); CKS(8, c8);
    }
    bar_sync(NB_PASS0, 384);
    if (t < 8) l2_prefetch((const char*)p.wo + (size_t)bid * 32768 + t * 4096, 4096);
    else if (t < 12) l2_prefetch((const char*)p.w1 + (size_t)bid * 14336 + (t - 8) * 3584, 3584);
    else if (t < 16) l2_prefetch((const char*)p.w2 + (size_t)bid * 14336 + (t - 12) * 3584, 3584);
    {
#pragma unroll
      for (int k = 0; k < 8; k++) a[k] = 0.f;
#pragma unroll 1
      for (int b = 0; b < 4; b++) {
        const int row = b * 128 + (t >> 1);
        const __nv_bfloat16* wp = p.wmod + (size_t)row * 3072 + 1024 + bid * 16 + (t & 1) * 8;
        const uint4 w0 = ldg128(wp), w1 = ldg128(wp + 64 * 3072);
        const uint32_t c0 = ldg16(p.c + row), c1 = ldg16(p.c + row + 64);
        fma8(a, silu_c(c0), w0.x, w0.y, w0.z, w0.w);
        fma8(a, silu_c(c1), w1.x, w1.y, w1.z, w1.w);
      }
      const float r = reduce8(a, lane);
      if ((lane & 2) == 0) red[hw * 16 + (lane & 1) * 8 + (lane >> 2)] = r;
      bar_sync(NB_HELP, 128);
      if (hw == 0) {
        const int cl = lane & 15;
        float v = round_bf16(red[cl] + red[16 + cl] + red[32 + cl] + red[48 + cl]);
        if ((bid >> 5) == 2) v = 1.f + v;
        float vn = __shfl_down_sync(0xffffffffu, v, 1);
        uint32_t wd = pack_bf16(v, vn);
        uint32_t w0 = __shfl_sync(0xffffffffu, wd, q * 2);
        uint32_t w1 = __shfl_sync(0xffffffffu, wd, q * 2 + 8);
        const int vec = (0x2130 >> ((bid >> 5) * 4)) & 3;
        if (lane < 4) st_pkt(&p.s->mod2[((bid & 31) * 4 + vec) * 4 + lane], w0, w1, tag, 0);
      }
    }
    {
      const int isv = hw & 1, kh = hw >> 1;
      if (bid < 112) {
        const int kk = lane >> 1;
        uint32_t m0[4], m1[4];
        const uint4* mp = &p.s->mod2[(kh * 16 + (lane >> 2)) * 16 + (isv ? 12 : 4) + q];
        ld_mod(mp, tag, m0);
        ld_mod(mp + 128, tag, m1);
#pragma unroll
        for (int k = 0; k < 8; k++) a[k] = 0.f;
#pragma unroll 1
        for (int g0 = 0; g0 < 16; g0 += 2) {
          uint4 w[2];
#pragma unroll
          for (int i = 0; i < 2; i++) w[i] = ldg128(p.w1 + (size_t)((kh * 16 + g0 + i) * 16 + kk) * FF + bid * 16 + (lane & 1) * 8);
#pragma unroll
          for (int i = 0; i < 2; i++) {
            const int sl = ((g0 + i) & 7) * 4 + ((kk & 7) >> 1);
            const uint32_t wa = __shfl_sync(0xffffffffu, g0 < 8 ? m0[0] : m1[0], sl), wb = __shfl_sync(0xffffffffu, g0 < 8 ? m0[1] : m1[1], sl);
            const uint32_t mw = (kk & 8) ? wb : wa;
            fma8(a, (kk & 1) ? bf_hi(mw) : bf_lo(mw), w[i].x, w[i].y, w[i].z, w[i].w);
          }
        }
        float r = reduce8(a, lane);
        bar_sync(NB_HELP, 128);
        if (kh) red[isv * 32 + lane] = r;
        bar_sync(NB_HELP, 128);
        if (!kh) {
          r = (r + red[isv * 32 + lane]) * (isv ? 0.5f : 1.f);
          const float r1 = __shfl_down_sync(0xffffffffu, r, 4), r2 = __shfl_down_sync(0xffffffffu, r, 8),
                      r3 = __shfl_down_sync(0xffffffffu, r, 12);
          if ((lane & 14) == 0)
            st_pkt(&p.s->uv[isv * 448 + bid * 4 + (lane & 1) * 2 + (lane >> 4)], (__float_as_uint(r) & ~1u) | (tag & 1u),
                   __float_as_uint(r1), __float_as_uint(r2), __float_as_uint(r3));
        }
      }
      const int i = kh * 32 + lane;
      if (i < 56) {
        uint32_t m[4];
        int spins = 0;
        while (true) {
          ld_pkt(&p.s->uv[isv * 448 + j * 56 + i], m);
          if (!((m[0] ^ tag) & 1u) || ++spins >= SPIN_LIMIT) break;
          __nanosleep(200);
        }
        const int ip = (j & 1) ? (i < 8 ? i + 48 : i - 8) : i;
        const uint32_t ad = sb + SM_TAB + ip * 32 + isv * 8;
        asm volatile("st.shared.v2.b32 [%0], {%1,%2};" ::"r"(ad), "r"(m[0]), "r"(m[1]) : "memory");
        asm volatile("st.shared.v2.b32 [%0], {%1,%2};" ::"r"(ad + 16), "r"(m[2]), "r"(m[3]) : "memory");
      }
      __syncwarp();
      warp_arrive(bars + BAR_UV);
      TS(9);
    }
    {
      uint32_t mga[4], mg2[4], mgb[4];
      const uint4* mp = &p.s->mod2[((lane >> 2) * 4 + hw) * 16 + q];
      ld_mod(mp, tag, mga);
      ld_mod(mp + 4, tag, mg2);
      ld_mod(mp + 8, tag, mgb);
      if (lane >= 24) asm volatile("st.shared.v2.b32 [%0], {%1,%2};" ::"r"(sb + SM_TAB + 1792 + ((((lane >> 2) & 1) * 4 + hw) * 4 + q) * 8),
                                   "r"(mgb[0]), "r"(mgb[1]) : "memory");
      const uint32_t x2s = sb + SM_PARK + SLOT + hw * 512 + lane * 16;
      const uint4* const Pown = p.s->P + (size_t)(rt * 8 + j) * 4096 + hw * 32 + lane;
      float s0 = 0.f, s1 = 0.f, v0 = 0.f, v1 = 0.f;
      bar_sync(NB_PARK, 384);
      asm volatile("setmaxnreg.inc.sync.aligned.u32 56;");
#pragma unroll 1
      for (int n = 0; n < 14; n++) {
        const int cc = n & 7;
        const bool ex1 = n < 8;
        const uint32_t lb = sb + SM_WBAR + 192 + (n & 1) * 8;
        uint32_t r[4][4];
        float y[8];
        mbar_wait(lb, (n >> 1) & 1);
#pragma unroll
        for (int i = 0; i < 4; i++) lds128(sb + SM_PARK + ((n & 1) * 4 + i) * 4096 + 2048 + hw * 512 + lane * 16, r[i]);
        verify4_rt<16384>(Pown + cc * 128, r, ex1);
        warp_arrive(lb + 16);
#pragma unroll
        for (int i = 0; i < 4; i++) add_partial(y, r[i], ex1 ? 0u : 0x10000u, i == 0);
        const int src = cc * 4 + q;
        const uint32_t ma = __shfl_sync(0xffffffffu, ex1 ? mga[0] : mgb[0], src), mb = __shfl_sync(0xffffffffu, ex1 ? mga[1] : mgb[1], src);
        if (ex1) {
          uint32_t xr[4];
          asm volatile("ldmatrix.sync.aligned.m8n8.x4.shared.b16 {%0,%1,%2,%3}, [%4];"
                       : "=r"(xr[0]), "=r"(xr[1]), "=r"(xr[2]), "=r"(xr[3])
                       : "r"(sb + SM_PARK + SLOT + hw * 512 + cc * 4096 + (lane & 15) * 32 + (lane >> 4) * 16) : "memory");
          const uint32_t mc = __shfl_sync(0xffffffffu, mg2[0], src), md = __shfl_sync(0xffffffffu, mg2[1], src);
#pragma unroll
          for (int e = 0; e < 4; e++) {
            const uint32_t m = e < 2 ? ma : mb;
            const float u = fmaf(bf_lo(m), y[2 * e], bf_lo(xr[e])), v = fmaf(bf_hi(m), y[2 * e + 1], bf_hi(xr[e]));
            y[2 * e] = u; y[2 * e + 1] = v;
            if (e & 1) { s1 += u + v; v1 = fmaf(u, u, fmaf(v, v, v1)); }
            else { s0 += u + v; v0 = fmaf(u, u, fmaf(v, v, v0)); }
          }
          st_pkt(p.s->G + ((rt * 8 + j) * 32 + cc * 4 + hw) * 32 + lane, pack_tag<0>(y[0] * bf_lo(mc), y[1] * bf_hi(mc)),
                 pack_bf16(y[2] * bf_lo(mc), y[3] * bf_hi(mc)), pack_bf16(y[4] * bf_lo(md), y[5] * bf_hi(md)),
                 pack_bf16(y[6] * bf_lo(md), y[7] * bf_hi(md)));
          sts128(x2s + cc * 4096, __float_as_uint(y[0]), __float_as_uint(y[1]), __float_as_uint(y[2]), __float_as_uint(y[3]));
          sts128(x2s + cc * 4096 + 2048, __float_as_uint(y[4]), __float_as_uint(y[5]), __float_as_uint(y[6]), __float_as_uint(y[7]));
          if (n == 7) {
            const bool o1 = lane & 1, o2 = lane & 2;
            float c0 = (o1 ? v0 : s0) + __shfl_xor_sync(0xffffffffu, o1 ? s0 : v0, 1);
            float c1 = (o1 ? v1 : s1) + __shfl_xor_sync(0xffffffffu, o1 ? s1 : v1, 1);
            c0 = (o2 ? c1 : c0) + __shfl_xor_sync(0xffffffffu, o2 ? c0 : c1, 2);
            *(float*)(smem_raw + SM_PARK + 16384 + 2048 + hw * 512 + lane * 4) = c0;
            bar_sync(NB_HELP, 128);
            if (hw == 0) {
              const float* ps = (const float*)(smem_raw + SM_PARK + 16384 + 2048) + lane;
              const float m = (c0 + ps[128] + ps[256] + ps[384]) * (1.f / 512.f);
              const float mean = __shfl_sync(0xffffffffu, m, lane & ~1), sq = __shfl_sync(0xffffffffu, m, lane | 1);
              const float rs = 0.5f * rsqrtf(fmaxf(fmaf(-mean, mean, sq), 0.f) + 1e-5f), mr = -mean * rs;
              const float rs1 = __shfl_down_sync(0xffffffffu, rs, 2), mr1 = __shfl_down_sync(0xffffffffu, mr, 2);
              if (q == 0)
                st_pkt(&p.s->stat[(rt * 8 + j) * 8 + (lane >> 2)], (__float_as_uint(rs) & ~1u) | (tag & 1u), __float_as_uint(mr),
                       __float_as_uint(rs1), __float_as_uint(mr1));
              warp_arrive(bars + BAR_X2);
            }
          }
        } else {
          store_out(p.out, (uint32_t)(rt * 128 + 16 * j + (lane >> 2)) * 256 + (cc * 4 + hw) * 8 + q, x2s + cc * 4096, ma, mb, y);
        }
      }
    }
  } else {
    const int wg = warp >> 2;
    const int q = lane & 3, gq = lane >> 2;
    const Ring ring{((sb + SM_RING) & 0x3FFFF) >> 4, bars};
    const uint32_t xoff = (uint32_t)(rt * 128 + 16 * j + warp) * 256 + gq * 8 + q;
    const uint32_t ooff = ((uint32_t)(rt * 8 + j) * 32 + gq) * 32 + warp * 4 + q;
    const uint32_t wblk = sb + SM_PARK + warp * 4096, wprv = wblk + lane * 16;
    const uint32_t wbar = sb + SM_WBAR + warp * 24;
    const uint4* const Gw = p.s->G + (rt * 8 + warp) * 1024;

    {
      const uint32_t* xo = (const uint32_t*)p.x + xoff;
      uint32_t xr[4][4];
      CK_(d0);
#pragma unroll
      for (int c = 0; c < 4; c++) {
        xr[c][0] = ldg32(xo + c * 64);
        xr[c][1] = ldg32(xo + c * 64 + 8 * 256);
        xr[c][2] = ldg32(xo + c * 64 + 4);
        xr[c][3] = ldg32(xo + c * 64 + 4 + 8 * 256);
      }
      CK_(d1);
      fence_regs(xr);
      CK_(d2);
      float s0 = 0.f, s1 = 0.f, v0 = 0.f, v1 = 0.f;
#pragma unroll
      for (int c = 0; c < 4; c++) {
#pragma unroll
        for (int e = 0; e < 4; e++) {
          const float a = bf_lo(xr[c][e]), b = bf_hi(xr[c][e]);
          if (e & 1) { s1 += a + b; v1 = fmaf(a, a, fmaf(b, b, v1)); }
          else { s0 += a + b; v0 = fmaf(a, a, fmaf(b, b, v0)); }
        }
      }
#pragma unroll
      for (int o = 16; o > 0; o >>= 1) {
        s0 += __shfl_xor_sync(0xffffffffu, s0, o);
        s1 += __shfl_xor_sync(0xffffffffu, s1, o);
        v0 += __shfl_xor_sync(0xffffffffu, v0, o);
        v1 += __shfl_xor_sync(0xffffffffu, v1, o);
      }
      const float m0 = s0 * (1.f / 512.f), m1 = s1 * (1.f / 512.f);
      const float r0 = rsqrtf(fmaxf(fmaf(-m0, m0, v0 * (1.f / 512.f)), 0.f) + 1e-5f);
      const float r1 = rsqrtf(fmaxf(fmaf(-m1, m1, v1 * (1.f / 512.f)), 0.f) + 1e-5f);
#pragma unroll
      for (int c = 0; c < 4; c++) {
        st_pkt(p.s->G + ooff + c * 256,
               pack_tag<1>((bf_lo(xr[c][0]) - m0) * r0, (bf_hi(xr[c][0]) - m0) * r0),
               pack_bf16((bf_lo(xr[c][1]) - m1) * r1, (bf_hi(xr[c][1]) - m1) * r1),
               pack_bf16((bf_lo(xr[c][2]) - m0) * r0, (bf_hi(xr[c][2]) - m0) * r0),
               pack_bf16((bf_lo(xr[c][3]) - m1) * r1, (bf_hi(xr[c][3]) - m1) * r1));
      }
      CK_(d3);
      CKS(16, d0); CKS(17, d1); CKS(18, d2); CKS(19, d3);

    }
    asm volatile("setmaxnreg.inc.sync.aligned.u32 224;");
    auto my_turn = [&]() { bar_sync(NB_WG0 + wg, 288 - wg * 32); };
    auto your_turn = [&]() { bar_arrive(NB_WG0 + (wg ^ 1), 256 + wg * 32); };
    if (wg == 1) your_turn();
    uint32_t qf[8][4];
    {
      uint32_t h[32][4];
      float acc[64];
      const uint4* Gin = Gw + lane;
      asm volatile("barrier.cluster.wait.acquire.aligned;" ::: "memory");
      bar_sync(NB_GATHER, 384);
      if (G_DELAY) spin_cycles(G_DELAY);
#pragma unroll
      for (int c = 0; c < 3; c++) warp_bulk_load(wblk + c * SLOT, Gw + c * 256, 4096, wbar + c * 8);
#pragma unroll
      for (int c = 0; c < 4; c++) {
        mbar_wait(wbar + (c % 3) * 8, c / 3);
#pragma unroll
        for (int i = 0; i < 8; i++) lds128(wprv + (c % 3) * SLOT + i * 512, h[c * 8 + i]);
        verify8_tag1<512>(Gin + c * 256, h + c * 8);
        if (c == 0) {
          warp_bulk_load(wblk, Gw + 768, 4096, wbar);
          TS(1);
          bar_sync(NB_TAB, 384);
        }
#pragma unroll
        for (int i = 0; i < 8; i++) {
          uint32_t m[4];
          lds128(sb + SM_TAB + (uint32_t)((c * 8 + i) * 4 + q) * 16, m);
          uint32_t* hh = h[c * 8 + i];
          hh[0] = hfma2_bf16(hh[0], m[0], m[2]);
          hh[1] = hfma2_bf16(hh[1], m[0], m[2]);
          hh[2] = hfma2_bf16(hh[2], m[1], m[3]);
          hh[3] = hfma2_bf16(hh[3], m[1], m[3]);
        }
        fence_frags<8>(h + c * 8);
        const uint32_t b = ring.tile(c);
        if (c > 0) { wg_wait<0>(); ring.release(c - 1); }
        if (c == 0) TS(2);
        my_turn();
        wg_fence();
        static_for<0, 8>([&](auto K) { wgmma_rs_n128_tb1<LB_MN128 + K * 128, HI128>(acc, h[c * 8 + K], b, (c | K) != 0); });
        wg_commit();
        your_turn();
      }
      bar_arrive(NB_PASS0, 384);
#pragma unroll 1
      for (int ps = 1; ps < 4; ps++) {
        wg_wait<0>();
        ring.release(3);
        fence_regs(acc);
#pragma unroll
        for (int i = 0; i < 8; i++) {
          uint32_t o[4];
          pack8(o, acc + 8 * i);
          sts128(wprv + (ps - 1) * SLOT + i * 512, o[0], o[1], o[2], o[3]);
        }
#pragma unroll
        for (int c = 0; c < 4; c += 2) {
          const uint32_t b = ring.tile(c);
          if (c > 0) { wg_wait<0>(); ring.release(c - 1); }
          my_turn();
          wg_fence();
          static_for<0, 8>([&](auto K) { wgmma_rs_n128_tb1<LB_MN128 + K * 128, HI128>(acc, h[c * 8 + K], b, (c | K) != 0); });
          wg_commit();
          static_for<0, 8>([&](auto K) { wgmma_rs_n128_tb1<LB_MN128 + 2048 + K * 128, HI128>(acc, h[c * 8 + 8 + K], b, 1); });
          wg_commit();
          your_turn();
          wg_wait<1>();
          ring.release(c);
        }
      }
      wg_wait<0>();
      ring.release(3);
      fence_regs(acc);
#pragma unroll
      for (int i = 0; i < 8; i++) pack8(qf[i], acc + 8 * i);
    }
    fence_regs(qf);
    TS(3);

    uint32_t o[24][4];
    {
      float S[64], O[64];
      uint32_t P[8][4];
      const float cs = 0.08838834764831845f * 1.4426950408889634f;
      const int TAU = 0x41800000;
      float m0, m1, l0, l1;

      auto float_block_max = [&]() {
        float b0 = fmaxf(S[0], S[1]), b1 = fmaxf(S[2], S[3]);
#pragma unroll
        for (int i = 1; i < 16; i++) {
          b0 = fmaxf(b0, fmaxf(S[4 * i], S[4 * i + 1]));
          b1 = fmaxf(b1, fmaxf(S[4 * i + 2], S[4 * i + 3]));
        }
        b0 = fmaxf(b0, __shfl_xor_sync(0xffffffffu, b0, 1)); b1 = fmaxf(b1, __shfl_xor_sync(0xffffffffu, b1, 1));
        b0 = fmaxf(b0, __shfl_xor_sync(0xffffffffu, b0, 2)); b1 = fmaxf(b1, __shfl_xor_sync(0xffffffffu, b1, 2));
        m0 = b0 * cs; m1 = b1 * cs;
      };
      auto first_block_max = [&]() {
        int a0 = max(__float_as_int(S[0]), __float_as_int(S[1]));
        int a1 = max(__float_as_int(S[2]), __float_as_int(S[3]));
#pragma unroll
        for (int i = 1; i < 16; i++) {
          a0 = __vimax3_s32(a0, __float_as_int(S[4 * i]), __float_as_int(S[4 * i + 1]));
          a1 = __vimax3_s32(a1, __float_as_int(S[4 * i + 2]), __float_as_int(S[4 * i + 3]));
        }
        a0 = max(a0, __shfl_xor_sync(0xffffffffu, a0, 1)); a1 = max(a1, __shfl_xor_sync(0xffffffffu, a1, 1));
        a0 = max(a0, __shfl_xor_sync(0xffffffffu, a0, 2)); a1 = max(a1, __shfl_xor_sync(0xffffffffu, a1, 2));
        m0 = __int_as_float(a0) * cs; m1 = __int_as_float(a1) * cs;
        if (__any_sync(0xffffffffu, (a0 | a1) < 0)) float_block_max();
      };
      auto scale_sub = [&]() {
#pragma unroll
        for (int i = 0; i < 16; i++) {
          S[4 * i] = fmaf(S[4 * i], cs, -m0); S[4 * i + 1] = fmaf(S[4 * i + 1], cs, -m0);
          S[4 * i + 2] = fmaf(S[4 * i + 2], cs, -m1); S[4 * i + 3] = fmaf(S[4 * i + 3], cs, -m1);
        }
      };
      auto exps = [&](int i0, int i1) {
#pragma unroll
        for (int i = i0; i < i1; i++) {
          S[4 * i] = ex2(S[4 * i]); S[4 * i + 1] = ex2(S[4 * i + 1]);
          S[4 * i + 2] = ex2(S[4 * i + 2]); S[4 * i + 3] = ex2(S[4 * i + 3]);
          l0 += S[4 * i]; l1 += S[4 * i + 2]; l0 += S[4 * i + 1]; l1 += S[4 * i + 3];
        }
      };
      {
        const uint32_t b = ring.tile(0);
        my_turn();
        wg_fence();
        static_for<0, 8>([&](auto K) { wgmma_rs_n128_tb0<LB_K128 + (K >> 2) * 1024 + (K & 3) * 2, HI128>(S, qf[K], b, K != 0); });
        wg_commit();
        your_turn();
        wg_wait<0>();
        fence_regs(S);
        ring.release(0);
        float_block_max();
        scale_sub();
        l0 = 0.f; l1 = 0.f;
        exps(0, 16);
#pragma unroll
        for (int i = 0; i < 8; i++) pack8(P[i], S + 8 * i);
      }
      fence_regs(P);
#pragma unroll 1
      for (int n = 1; n < 16; n++) {
        const uint32_t tk = 2 * n - 1, tv = 2 * n;
        const bool newhead = (n & 3) == 0;
        const uint32_t bk = ring.tile(tk & 3);
        const uint32_t bv = ring.tile(tv & 3);
        my_turn();
        wg_fence();
        static_for<0, 8>([&](auto K) { wgmma_rs_n128_tb0<LB_K128 + (K >> 2) * 1024 + (K & 3) * 2, HI128>(S, qf[K], bk, K != 0); });
        wg_commit();
        static_for<0, 8>([&](auto K) { wgmma_rs_n128_tb1<LB_MN128 + K * 128, HI128>(O, P[K], bv, K != 0 || (n & 3) != 1); });
        wg_commit();
        your_turn();
        wg_wait<1>();
        fence_regs(S);
        ring.release(tk & 3);
        if ((n & 3) == 3 && n != 15) {
          fence_regs(qf);
#pragma unroll
          for (int i = 0; i < 8; i++) lds128(wprv + (n >> 2) * SLOT + i * 512, qf[i]);
        }
        float f0 = 1.f, f1 = 1.f;
        bool resc = newhead;
        if (newhead) {
          l0 += __shfl_xor_sync(0xffffffffu, l0, 1); l1 += __shfl_xor_sync(0xffffffffu, l1, 1);
          l0 += __shfl_xor_sync(0xffffffffu, l0, 2); l1 += __shfl_xor_sync(0xffffffffu, l1, 2);
          f0 = rcp_hw(l0); f1 = rcp_hw(l1);
          l0 = 0.f; l1 = 0.f;
          first_block_max();
          scale_sub();
        } else {
          scale_sub();
          int a0 = __vimax3_s32(__float_as_int(S[0]), __float_as_int(S[1]), __float_as_int(S[1]));
          int a1 = __vimax3_s32(__float_as_int(S[2]), __float_as_int(S[3]), __float_as_int(S[3]));
#pragma unroll
          for (int i = 1; i < 16; i++) {
            a0 = __vimax3_s32(a0, __float_as_int(S[4 * i]), __float_as_int(S[4 * i + 1]));
            a1 = __vimax3_s32(a1, __float_as_int(S[4 * i + 2]), __float_as_int(S[4 * i + 3]));
          }
          if (__any_sync(0xffffffffu, max(a0, a1) > TAU)) {
            a0 = max(a0, 0); a1 = max(a1, 0);
            a0 = max(a0, __shfl_xor_sync(0xffffffffu, a0, 1)); a1 = max(a1, __shfl_xor_sync(0xffffffffu, a1, 1));
            a0 = max(a0, __shfl_xor_sync(0xffffffffu, a0, 2)); a1 = max(a1, __shfl_xor_sync(0xffffffffu, a1, 2));
            const float d0 = __int_as_float(a0), d1 = __int_as_float(a1);
#pragma unroll
            for (int i = 0; i < 16; i++) { S[4 * i] -= d0; S[4 * i + 1] -= d0; S[4 * i + 2] -= d1; S[4 * i + 3] -= d1; }
            m0 += d0; m1 += d1;
            f0 = ex2(-d0); f1 = ex2(-d1);
            l0 *= f0; l1 *= f1;
            resc = true;
          }
        }
        exps(0, 4);
        wg_wait<0>();
        fence_regs(O);
        fence_regs(P);
        ring.release(tv & 3);
        if (resc) {
#pragma unroll
          for (int i = 0; i < 16; i++) {
            O[4 * i] *= f0; O[4 * i + 1] *= f0; O[4 * i + 2] *= f1; O[4 * i + 3] *= f1;
          }
          if (newhead) {
#pragma unroll
            for (int i = 0; i < 8; i++) {
              uint32_t o[4];
              pack8(o, O + 8 * i);
              sts128(wprv + ((n >> 2) - 1) * SLOT + i * 512, o[0], o[1], o[2], o[3]);
            }
          }
        }
        exps(4, 16);
#pragma unroll
        for (int i = 0; i < 8; i++) pack8(P[i], S + 8 * i);
        fence_regs(P);
        fence_regs(O);
      }
      {
        const uint32_t bv = ring.tile(3);
        my_turn();
        wg_fence();
        static_for<0, 8>([&](auto K) { wgmma_rs_n128_tb1<LB_MN128 + K * 128, HI128>(O, P[K], bv, 1); });
        wg_commit();
        your_turn();
#pragma unroll
        for (int i = 0; i < 16; i++) lds128(wprv + (i >> 3) * SLOT + (i & 7) * 512, o[i]);
        l0 += __shfl_xor_sync(0xffffffffu, l0, 1); l1 += __shfl_xor_sync(0xffffffffu, l1, 1);
        l0 += __shfl_xor_sync(0xffffffffu, l0, 2); l1 += __shfl_xor_sync(0xffffffffu, l1, 2);
        const float f0 = rcp_hw(l0), f1 = rcp_hw(l1);
        wg_wait<0>();
        fence_regs(O);
        ring.release(3);
#pragma unroll
        for (int i = 0; i < 8; i++) {
          qf[i][0] = pack_bf16(O[8 * i] * f0, O[8 * i + 1] * f0); qf[i][1] = pack_bf16(O[8 * i + 2] * f1, O[8 * i + 3] * f1);
          qf[i][2] = pack_bf16(O[8 * i + 4] * f0, O[8 * i + 5] * f0); qf[i][3] = pack_bf16(O[8 * i + 6] * f1, O[8 * i + 7] * f1);
        }
      }
    }
    fence_regs(qf);
    TS(4);
    asm volatile("setmaxnreg.dec.sync.aligned.u32 216;");
    bar_arrive(NB_PARK, 384);

    uint4* const Pout = p.s->P + ((size_t)(rt * 8 + warp) * 4 + (j >> 1)) * 1024 + (j & 1) * 128 + lane;
    const uint32_t tag = *(volatile uint32_t*)(smem_raw + SM_BAR + BAR_TAG);
    const uint32_t rbar = sb + SM_DBAR + warp * 16;
    uint32_t peer_land, peer_bar;
    asm("mapa.shared::cluster.u32 %0, %1, %2;" : "=r"(peer_land) : "r"(wprv), "r"(~j & 1));
    asm("mapa.shared::cluster.u32 %0, %1, %2;" : "=r"(peer_bar) : "r"(rbar), "r"(~j & 1));
    auto arm_and_ack = [&](uint32_t dep) {
      asm volatile(
          "{\n.reg .pred p;\nelect.sync _|p, 0xffffffff;\n"
          "@p mbarrier.arrive.expect_tx.shared::cta.b64 _, [%0], 2048;\n"
          "@p mbarrier.arrive.shared::cluster.b64 _, [%1];\n}\n" ::"r"(rbar), "r"(peer_bar + 8 + (dep & p.zero)) : "memory");
    };
    auto send_chunk = [&](float (&acc)[32], int pair) {
      mbar_wait(rbar + 8, pair & 1);
#pragma unroll
      for (int i = 0; i < 4; i++)
        asm volatile("st.async.weak.shared::cluster.mbarrier::complete_tx::bytes.v4.b32 [%0], {%1,%2,%3,%4}, [%5];"
                     ::"r"(peer_land + i * 512), "r"(pack_trunc(acc[8 * i], acc[8 * i + 1])), "r"(pack_trunc(acc[8 * i + 2], acc[8 * i + 3])),
                       "r"(pack_trunc(acc[8 * i + 4], acc[8 * i + 5])), "r"(pack_trunc(acc[8 * i + 6], acc[8 * i + 7])), "r"(peer_bar)
                     : "memory");
    };
    uint32_t pk[4][4];
    auto recv_chunk = [&](int pair) {
      mbar_wait(rbar, pair & 1);
#pragma unroll
      for (int i = 0; i < 4; i++) lds128(wprv + i * 512, pk[i]);
      if (pair < 7) arm_and_ack(pk[3][0]);
    };
    auto keep_chunk = [&](float (&acc)[32], int pair) {
      const uint32_t t1 = pair < 4;
#pragma unroll
      for (int i = 0; i < 4; i++) {
#pragma unroll
        for (int e = 0; e < 4; e++)
          pk[i][e] = pack_trunc(acc[8 * i + 2 * e] + __uint_as_float(pk[i][e] * 65536u + 0x8000u),
                                acc[8 * i + 2 * e + 1] + __uint_as_float(pk[i][e]));
        st_pkt(Pout + (pair & 3) * 256 + i * 32, (pk[i][0] & ~1u) | t1, pk[i][1], pk[i][2], pk[i][3]);
      }
      if (lane == 0)
        asm volatile("st.relaxed.gpu.global.u32 [%0], %1;" ::"l"(&p.s->sent[(rt * 8 + warp) * 8 + j]), "r"(tag * 32 + pair + 1) : "memory");
    };
    const uint4* const Gin = Gw + lane;
    auto g_issue = [&](int u) { warp_bulk_load(wblk + 2 * SLOT, Gw + u * 256, 4096, wbar); };

#pragma unroll
    for (int i = 16; i < 24; i++) lds128(wprv + 2 * SLOT + (i & 7) * 512, o[i]);
    fence_regs(o);
    arm_and_ack(o[23][0]);
    warp_arrive(sb + SM_SBAR);
#pragma unroll 1
    for (int cc = 0; cc < 8; cc++) {
      float acc[32];
      const uint32_t s0 = (cc & 1) * 2, b = ring.tile(s0);
      my_turn();
      wg_fence();
      static_for<0, 16>([&](auto K) { wgmma_rs_n64_tb1<K * 128, HI128>(acc, o[K], b, K != 0); });
      wg_commit();
      static_for<0, 16>([&](auto K) { wgmma_rs_n64_tb1<2048 + K * 128, HI128>(acc, K < 8 ? o[16 + (K & 7)] : qf[K & 7], b, 1); });
      wg_commit();
      your_turn();
      wg_wait<1>();
      ring.release(s0);
      if (cc & 1) recv_chunk(cc >> 1);
      wg_wait<0>();
      TRU(4);
      ring.release(s0 + 1);
      fence_regs(acc);
      if (cc & 1) keep_chunk(acc, cc >> 1);
      else send_chunk(acc, cc >> 1);
      if (cc == 6) g_issue(0);
    }
    TS(5);

    uint32_t H[14][4];
    {
      float acca[96], accb[16];
      const uint4* const statp = &p.s->stat[(rt * 8 + warp) * 8];
#pragma unroll 1
      for (int u = 0; u < 4; u++) {
        uint32_t fa[8][4];
        const uint32_t s0 = (u & 1) * 2, b = ring.tile(s0);
        mbar_wait(wbar, u & 1);
#pragma unroll
        for (int i = 0; i < 8; i++) lds128(wprv + 2 * SLOT + i * 512, fa[i]);
        verify8_tag0<512>(Gin + u * 256, fa);
        if (u < 2) g_issue(u + 1);
        const uint32_t ba = b + (j & 1) * 512, bb = b + ((j & 1) ? 4 : 1536);
        my_turn();
        wg_fence();
        static_for<0, 4>([&](auto K) { wgmma_rs_n32_tb1<LB_W1 + K * 128, HI128>(accb, fa[K], bb, (u | K) != 0); });
        static_for<0, 4>([&](auto K) { wgmma_rs_n192_tb1<LB_W1 + K * 128, HI128>(acca, fa[K], ba, (u | K) != 0); });
        wg_commit();
        static_for<0, 4>([&](auto K) { wgmma_rs_n32_tb1<LB_W1 + 2048 + K * 128, HI128>(accb, fa[4 + K], bb, 1); });
        static_for<0, 4>([&](auto K) { wgmma_rs_n192_tb1<LB_W1 + 2048 + K * 128, HI128>(acca, fa[4 + K], ba, 1); });
        wg_commit();
        your_turn();
        wg_wait<1>();
        ring.release(s0);
        if (u == 2) g_issue(3);
        if (u == 3) warp_bulk_load(wblk + 2 * SLOT, statp, 128, wbar + 16);
        wg_wait<0>();
        TRU(4);
        ring.release(s0 + 1);
      }
      fence_regs(acca);
      fence_regs(accb);
      TS(9);
      mbar_wait(bars + BAR_UV, 0);
      uint32_t xr[4];
      mbar_wait(wbar + 16, 1);
      lds128(wblk + 2 * SLOT + gq * 16, xr);
      {
        int spins = 0;
        while (((xr[0] ^ tag) & 1u) && ++spins < SPIN_LIMIT) ld_pkt(statp + gq, xr);
      }
      const float ra0 = __uint_as_float(xr[0]), rb0 = __uint_as_float(xr[1]), ra1 = __uint_as_float(xr[2]),
                  rb1 = __uint_as_float(xr[3]);
#pragma unroll
      for (int i = 0; i < 28; i++) {
        uint32_t m[4];
        lds128(sb + SM_TAB + (i * 4 + q) * 16, m);
        const float u0 = __uint_as_float(m[0]), u1 = __uint_as_float(m[1]), w0 = __uint_as_float(m[2]), w1 = __uint_as_float(m[3]);
        const float* acc = i < 24 ? acca + 4 * i : accb + 4 * (i - 24);
        const float z0 = fmaf(acc[0], ra0, fmaf(u0, rb0, w0)), z1 = fmaf(acc[1], ra0, fmaf(u1, rb0, w1));
        const float z2 = fmaf(acc[2], ra1, fmaf(u0, rb1, w0)), z3 = fmaf(acc[3], ra1, fmaf(u1, rb1, w1));
        H[i >> 1][(i & 1) * 2] = pack_bf16(fmaf(z0, tanh_hw(z0), z0), fmaf(z1, tanh_hw(z1), z1));
        H[i >> 1][(i & 1) * 2 + 1] = pack_bf16(fmaf(z2, tanh_hw(z2), z2), fmaf(z3, tanh_hw(z3), z3));
      }
    }
    fence_regs(H);
    TS(10);
    const int go = 24 + warp;
    {
      float accs[32], acck[32];
      auto ffn2 = [&](float (&acc)[32], uint32_t b) {
        const uint32_t ba = b + (j & 1) * 256, bb = b - (j & 1) * 1536;
        static_for<0, 14>([&](auto K) { wgmma_rs_n64_tb1<K * 128, HI128>(acc, H[K], K < 12 ? ba : bb, K != 0); });
        wg_commit();
      };
      {
        const uint32_t b = ring.tile(0);
        my_turn();
        wg_fence();
        ffn2(accs, b);
        your_turn();
        wg_wait<0>();
        TRU(4);
        ring.release(0);
        fence_regs(accs);
        send_chunk(accs, 4);
      }
#pragma unroll 1
      for (int pc = 0; pc < 3; pc++) {
        const uint32_t tk = 2 * pc + 1, ts = tk + 1;
        const uint32_t bk = ring.tile(tk & 3), bs = ring.tile(ts & 3);
        my_turn();
        wg_fence();
        ffn2(acck, bk);
        ffn2(accs, bs);
        your_turn();
        wg_wait<1>();
        ring.release(tk & 3);
        recv_chunk(4 + pc);
        fence_regs(acck);
        keep_chunk(acck, 4 + pc);
        wg_wait<0>();
        TRU(4);
        ring.release(ts & 3);
        fence_regs(accs);
        send_chunk(accs, 5 + pc);
      }
      const uint32_t b = ring.tile(3);
      my_turn();
      wg_fence();
      ffn2(acck, b);
      if (wg == 0) your_turn();
      recv_chunk(7);
      wg_wait<0>();
      fence_regs(acck);
      keep_chunk(acck, 7);
    }
    TS(11);
    {
      const uint4* const Pown = p.s->P + (size_t)(rt * 8 + j) * 4096 + go * 32 + lane;
      uint32_t r[4][4];
      float y[8];
      mbar_wait(bars + BAR_X2, 0);
      issue_pkts<0, 4>(Pown, 1024, r);
      verify4_rt<16384>(Pown, r, 0);
      TS(13);
#pragma unroll
      for (int s = 0; s < 4; s++) add_partial(y, r[s], 0x10000u, s == 0);
      const uint32_t gt = sb + SM_TAB + 1792 + ((go - 24) * 4 + q) * 8;
      store_out(p.out, (uint32_t)(rt * 128 + 16 * j + gq) * 256 + go * 8 + q, sb + SM_PARK + SLOT + (go >> 2) * 4096 + (go & 3) * 512 + lane * 16,
                lds32(gt), lds32(gt + 4), y);
    }
    TS(12);
    if (bid == 0 && tid == 0) asm volatile("st.relaxed.gpu.global.u32 [%0], %1;" ::"l"(&p.s->epoch), "r"(tag) : "memory");
  }
}

typedef CUresult (*EncodeFn)(CUtensorMap*, CUtensorMapDataType, cuuint32_t, void*, const cuuint64_t*, const cuuint64_t*,
                             const cuuint32_t*, const cuuint32_t*, CUtensorMapInterleave, CUtensorMapSwizzle,
                             CUtensorMapL2promotion, CUtensorMapFloatOOBfill);

static void make_map(EncodeFn fn, CUtensorMap* tm, const void* ptr, int inner, int rows, int cols, int box_rows, int box_outer,
                     CUtensorMapSwizzle swz) {
  cuuint64_t gd[3] = {(cuuint64_t)inner, (cuuint64_t)rows, (cuuint64_t)(cols / inner)};
  cuuint64_t gs[2] = {(cuuint64_t)cols * 2, (cuuint64_t)inner * 2};
  cuuint32_t bx[3] = {(cuuint32_t)inner, (cuuint32_t)box_rows, (cuuint32_t)box_outer};
  cuuint32_t es[3] = {1, 1, 1};
  fn(tm, CU_TENSOR_MAP_DATA_TYPE_BFLOAT16, 3, const_cast<void*>(ptr), gd, gs, bx, es, CU_TENSOR_MAP_INTERLEAVE_NONE, swz,
     CU_TENSOR_MAP_L2_PROMOTION_L2_128B, CU_TENSOR_MAP_FLOAT_OOB_FILL_NONE);
}

extern "C" void kernel_launch(void* const* d_in, const int* in_sizes, int n_in, void* d_out, int out_size) {
  (void)in_sizes; (void)n_in; (void)out_size;
  void* fnp = nullptr;
  cudaDriverEntryPointQueryResult qr;
  cudaGetDriverEntryPoint("cuTensorMapEncodeTiled", &fnp, cudaEnableDefault, &qr);
  EncodeFn fn = (EncodeFn)fnp;
  CUtensorMap tmWq, tmK, tmV, tmWo, tmW1, tmW2, tmWm, tmX;
  make_map(fn, &tmWq, d_in[3], 64, 512, 4096, 128, 2, CU_TENSOR_MAP_SWIZZLE_128B);
  make_map(fn, &tmK, d_in[1], 64, 8 * SK, 128, 128, 2, CU_TENSOR_MAP_SWIZZLE_128B);
  make_map(fn, &tmV, d_in[2], 64, 8 * SK, 128, 128, 2, CU_TENSOR_MAP_SWIZZLE_128B);
  make_map(fn, &tmWo, d_in[4], 64, 4096, 512, 256, 1, CU_TENSOR_MAP_SWIZZLE_128B);
  make_map(fn, &tmW1, d_in[6], 64, 512, FF, 64, 4, CU_TENSOR_MAP_SWIZZLE_128B);
  make_map(fn, &tmW2, d_in[7], 64, FF, 512, 224, 1, CU_TENSOR_MAP_SWIZZLE_128B);
  make_map(fn, &tmWm, d_in[9], 8, 512, 3072, 256, 1, CU_TENSOR_MAP_SWIZZLE_NONE);
  make_map(fn, &tmX, d_in[0], 16, 2048, 512, 16, 4, CU_TENSOR_MAP_SWIZZLE_NONE);
  Params p;
  p.x = (const __nv_bfloat16*)d_in[0];
  p.c = (const __nv_bfloat16*)d_in[8];
  p.wmod = (const __nv_bfloat16*)d_in[9];
  p.wo = (const __nv_bfloat16*)d_in[4];
  p.w1 = (const __nv_bfloat16*)d_in[6];
  p.w2 = (const __nv_bfloat16*)d_in[7];
  p.out = (__nv_bfloat16*)d_out;
  p.zero = 0;
  cudaGetSymbolAddress((void**)&p.s, g_scratch);
  cudaFuncSetAttribute(adaln_block_kernel, cudaFuncAttributeMaxDynamicSharedMemorySize, SM_TOTAL);
  cudaLaunchConfig_t cfg = {};
  cfg.gridDim = 128; cfg.blockDim = 512; cfg.dynamicSmemBytes = SM_TOTAL; cfg.stream = cudaStreamPerThread;
  cudaLaunchAttribute at[1];
  at[0].id = cudaLaunchAttributeClusterDimension; at[0].val.clusterDim.x = 2; at[0].val.clusterDim.y = 1; at[0].val.clusterDim.z = 1;
  cfg.attrs = at; cfg.numAttrs = 1;
  cudaLaunchKernelEx(&cfg, adaln_block_kernel, tmWq, tmK, tmV, tmWo, tmW1, tmW2, tmWm, tmX, p);
}
```

```cpp
#include <cuda_runtime.h>
#include <cuda_bf16.h>
#include <cuda.h>
#include <stdint.h>

template <int OFF, uint32_t HI>
__device__ __forceinline__ void wgmma_rs_n128_tb0(float (&d)[64], const uint32_t (&a)[4], uint32_t lo, int sd) {
  asm volatile("{\n.reg .pred p;\n.reg .b32 l;\n.reg .b64 db;\nsetp.ne.b32 p, %69, 0;\n"
    "add.u32 l, %68, %70;\nmov.b64 db, {l, %71};\n"
    "wgmma.mma_async.sync.aligned.m64n128k16.f32.bf16.bf16 "
    "{%0,%1,%2,%3,%4,%5,%6,%7,%8,%9,%10,%11,%12,%13,%14,%15,"
    "%16,%17,%18,%19,%20,%21,%22,%23,%24,%25,%26,%27,%28,%29,%30,%31,"
    "%32,%33,%34,%35,%36,%37,%38,%39,%40,%41,%42,%43,%44,%45,%46,%47,"
    "%48,%49,%50,%51,%52,%53,%54,%55,%56,%57,%58,%59,%60,%61,%62,%63}, "
    "{%64,%65,%66,%67}, db, p, 1, 1, 0;\n}\n"
    : "+f"(d[0]), "+f"(d[1]), "+f"(d[2]), "+f"(d[3]), "+f"(d[4]), "+f"(d[5]), "+f"(d[6]), "+f"(d[7]),
      "+f"(d[8]), "+f"(d[9]), "+f"(d[10]), "+f"(d[11]), "+f"(d[12]), "+f"(d[13]), "+f"(d[14]), "+f"(d[15]),
      "+f"(d[16]), "+f"(d[17]), "+f"(d[18]), "+f"(d[19]), "+f"(d[20]), "+f"(d[21]), "+f"(d[22]), "+f"(d[23]),
      "+f"(d[24]), "+f"(d[25]), "+f"(d[26]), "+f"(d[27]), "+f"(d[28]), "+f"(d[29]), "+f"(d[30]), "+f"(d[31]),
      "+f"(d[32]), "+f"(d[33]), "+f"(d[34]), "+f"(d[35]), "+f"(d[36]), "+f"(d[37]), "+f"(d[38]), "+f"(d[39]),
      "+f"(d[40]), "+f"(d[41]), "+f"(d[42]), "+f"(d[43]), "+f"(d[44]), "+f"(d[45]), "+f"(d[46]), "+f"(d[47]),
      "+f"(d[48]), "+f"(d[49]), "+f"(d[50]), "+f"(d[51]), "+f"(d[52]), "+f"(d[53]), "+f"(d[54]), "+f"(d[55]),
      "+f"(d[56]), "+f"(d[57]), "+f"(d[58]), "+f"(d[59]), "+f"(d[60]), "+f"(d[61]), "+f"(d[62]), "+f"(d[63])
    : "r"(a[0]), "r"(a[1]), "r"(a[2]), "r"(a[3]), "r"(lo), "r"(sd), "n"(OFF), "n"(HI));
}

template <int OFF, uint32_t HI>
__device__ __forceinline__ void wgmma_rs_n128_tb1(float (&d)[64], const uint32_t (&a)[4], uint32_t lo, int sd) {
  asm volatile("{\n.reg .pred p;\n.reg .b32 l;\n.reg .b64 db;\nsetp.ne.b32 p, %69, 0;\n"
    "add.u32 l, %68, %70;\nmov.b64 db, {l, %71};\n"
    "wgmma.mma_async.sync.aligned.m64n128k16.f32.bf16.bf16 "
    "{%0,%1,%2,%3,%4,%5,%6,%7,%8,%9,%10,%11,%12,%13,%14,%15,"
    "%16,%17,%18,%19,%20,%21,%22,%23,%24,%25,%26,%27,%28,%29,%30,%31,"
    "%32,%33,%34,%35,%36,%37,%38,%39,%40,%41,%42,%43,%44,%45,%46,%47,"
    "%48,%49,%50,%51,%52,%53,%54,%55,%56,%57,%58,%59,%60,%61,%62,%63}, "
    "{%64,%65,%66,%67}, db, p, 1, 1, 1;\n}\n"
    : "+f"(d[0]), "+f"(d[1]), "+f"(d[2]), "+f"(d[3]), "+f"(d[4]), "+f"(d[5]), "+f"(d[6]), "+f"(d[7]),
      "+f"(d[8]), "+f"(d[9]), "+f"(d[10]), "+f"(d[11]), "+f"(d[12]), "+f"(d[13]), "+f"(d[14]), "+f"(d[15]),
      "+f"(d[16]), "+f"(d[17]), "+f"(d[18]), "+f"(d[19]), "+f"(d[20]), "+f"(d[21]), "+f"(d[22]), "+f"(d[23]),
      "+f"(d[24]), "+f"(d[25]), "+f"(d[26]), "+f"(d[27]), "+f"(d[28]), "+f"(d[29]), "+f"(d[30]), "+f"(d[31]),
      "+f"(d[32]), "+f"(d[33]), "+f"(d[34]), "+f"(d[35]), "+f"(d[36]), "+f"(d[37]), "+f"(d[38]), "+f"(d[39]),
      "+f"(d[40]), "+f"(d[41]), "+f"(d[42]), "+f"(d[43]), "+f"(d[44]), "+f"(d[45]), "+f"(d[46]), "+f"(d[47]),
      "+f"(d[48]), "+f"(d[49]), "+f"(d[50]), "+f"(d[51]), "+f"(d[52]), "+f"(d[53]), "+f"(d[54]), "+f"(d[55]),
      "+f"(d[56]), "+f"(d[57]), "+f"(d[58]), "+f"(d[59]), "+f"(d[60]), "+f"(d[61]), "+f"(d[62]), "+f"(d[63])
    : "r"(a[0]), "r"(a[1]), "r"(a[2]), "r"(a[3]), "r"(lo), "r"(sd), "n"(OFF), "n"(HI));
}

template <int OFF, uint32_t HI>
__device__ __forceinline__ void wgmma_rs_n192_tb1(float (&d)[96], const uint32_t (&a)[4], uint32_t lo, int sd) {
  asm volatile("{\n.reg .pred p;\n.reg .b32 l;\n.reg .b64 db;\nsetp.ne.b32 p, %101, 0;\n"
    "add.u32 l, %100, %102;\nmov.b64 db, {l, %103};\n"
    "wgmma.mma_async.sync.aligned.m64n192k16.f32.bf16.bf16 "
    "{%0,%1,%2,%3,%4,%5,%6,%7,%8,%9,%10,%11,%12,%13,%14,%15,"
    "%16,%17,%18,%19,%20,%21,%22,%23,%24,%25,%26,%27,%28,%29,%30,%31,"
    "%32,%33,%34,%35,%36,%37,%38,%39,%40,%41,%42,%43,%44,%45,%46,%47,"
    "%48,%49,%50,%51,%52,%53,%54,%55,%56,%57,%58,%59,%60,%61,%62,%63,"
    "%64,%65,%66,%67,%68,%69,%70,%71,%72,%73,%74,%75,%76,%77,%78,%79,"
    "%80,%81,%82,%83,%84,%85,%86,%87,%88,%89,%90,%91,%92,%93,%94,%95}, "
    "{%96,%97,%98,%99}, db, p, 1, 1, 1;\n}\n"
    : "+f"(d[0]), "+f"(d[1]), "+f"(d[2]), "+f"(d[3]), "+f"(d[4]), "+f"(d[5]), "+f"(d[6]), "+f"(d[7]),
      "+f"(d[8]), "+f"(d[9]), "+f"(d[10]), "+f"(d[11]), "+f"(d[12]), "+f"(d[13]), "+f"(d[14]), "+f"(d[15]),
      "+f"(d[16]), "+f"(d[17]), "+f"(d[18]), "+f"(d[19]), "+f"(d[20]), "+f"(d[21]), "+f"(d[22]), "+f"(d[23]),
      "+f"(d[24]), "+f"(d[25]), "+f"(d[26]), "+f"(d[27]), "+f"(d[28]), "+f"(d[29]), "+f"(d[30]), "+f"(d[31]),
      "+f"(d[32]), "+f"(d[33]), "+f"(d[34]), "+f"(d[35]), "+f"(d[36]), "+f"(d[37]), "+f"(d[38]), "+f"(d[39]),
      "+f"(d[40]), "+f"(d[41]), "+f"(d[42]), "+f"(d[43]), "+f"(d[44]), "+f"(d[45]), "+f"(d[46]), "+f"(d[47]),
      "+f"(d[48]), "+f"(d[49]), "+f"(d[50]), "+f"(d[51]), "+f"(d[52]), "+f"(d[53]), "+f"(d[54]), "+f"(d[55]),
      "+f"(d[56]), "+f"(d[57]), "+f"(d[58]), "+f"(d[59]), "+f"(d[60]), "+f"(d[61]), "+f"(d[62]), "+f"(d[63]),
      "+f"(d[64]), "+f"(d[65]), "+f"(d[66]), "+f"(d[67]), "+f"(d[68]), "+f"(d[69]), "+f"(d[70]), "+f"(d[71]),
      "+f"(d[72]), "+f"(d[73]), "+f"(d[74]), "+f"(d[75]), "+f"(d[76]), "+f"(d[77]), "+f"(d[78]), "+f"(d[79]),
      "+f"(d[80]), "+f"(d[81]), "+f"(d[82]), "+f"(d[83]), "+f"(d[84]), "+f"(d[85]), "+f"(d[86]), "+f"(d[87]),
      "+f"(d[88]), "+f"(d[89]), "+f"(d[90]), "+f"(d[91]), "+f"(d[92]), "+f"(d[93]), "+f"(d[94]), "+f"(d[95])
    : "r"(a[0]), "r"(a[1]), "r"(a[2]), "r"(a[3]), "r"(lo), "r"(sd), "n"(OFF), "n"(HI));
}

template <int OFF, uint32_t HI>
__device__ __forceinline__ void wgmma_rs_n32_tb1(float (&d)[16], const uint32_t (&a)[4], uint32_t lo, int sd) {
  asm volatile("{\n.reg .pred p;\n.reg .b32 l;\n.reg .b64 db;\nsetp.ne.b32 p, %21, 0;\n"
    "add.u32 l, %20, %22;\nmov.b64 db, {l, %23};\n"
    "wgmma.mma_async.sync.aligned.m64n32k16.f32.bf16.bf16 "
    "{%0,%1,%2,%3,%4,%5,%6,%7,%8,%9,%10,%11,%12,%13,%14,%15}, "
    "{%16,%17,%18,%19}, db, p, 1, 1, 1;\n}\n"
    : "+f"(d[0]), "+f"(d[1]), "+f"(d[2]), "+f"(d[3]), "+f"(d[4]), "+f"(d[5]), "+f"(d[6]), "+f"(d[7]),
      "+f"(d[8]), "+f"(d[9]), "+f"(d[10]), "+f"(d[11]), "+f"(d[12]), "+f"(d[13]), "+f"(d[14]), "+f"(d[15])
    : "r"(a[0]), "r"(a[1]), "r"(a[2]), "r"(a[3]), "r"(lo), "r"(sd), "n"(OFF), "n"(HI));
}

template <int OFF, uint32_t HI>
__device__ __forceinline__ void wgmma_rs_n64_tb1(float (&d)[32], const uint32_t (&a)[4], uint32_t lo, int sd) {
  asm volatile("{\n.reg .pred p;\n.reg .b32 l;\n.reg .b64 db;\nsetp.ne.b32 p, %37, 0;\n"
    "add.u32 l, %36, %38;\nmov.b64 db, {l, %39};\n"
    "wgmma.mma_async.sync.aligned.m64n64k16.f32.bf16.bf16 "
    "{%0,%1,%2,%3,%4,%5,%6,%7,%8,%9,%10,%11,%12,%13,%14,%15,"
    "%16,%17,%18,%19,%20,%21,%22,%23,%24,%25,%26,%27,%28,%29,%30,%31}, "
    "{%32,%33,%34,%35}, db, p, 1, 1, 1;\n}\n"
    : "+f"(d[0]), "+f"(d[1]), "+f"(d[2]), "+f"(d[3]), "+f"(d[4]), "+f"(d[5]), "+f"(d[6]), "+f"(d[7]),
      "+f"(d[8]), "+f"(d[9]), "+f"(d[10]), "+f"(d[11]), "+f"(d[12]), "+f"(d[13]), "+f"(d[14]), "+f"(d[15]),
      "+f"(d[16]), "+f"(d[17]), "+f"(d[18]), "+f"(d[19]), "+f"(d[20]), "+f"(d[21]), "+f"(d[22]), "+f"(d[23]),
      "+f"(d[24]), "+f"(d[25]), "+f"(d[26]), "+f"(d[27]), "+f"(d[28]), "+f"(d[29]), "+f"(d[30]), "+f"(d[31])
    : "r"(a[0]), "r"(a[1]), "r"(a[2]), "r"(a[3]), "r"(lo), "r"(sd), "n"(OFF), "n"(HI));
}

template <int STR>
__device__ __forceinline__ void verify8_tag1(const uint4* p, uint32_t (*r)[4]) {
  asm volatile("{\n.reg .pred p, q;\n.reg .b32 a, n;\nmov.u32 n, 0;\n"
    "LAB_CHK:\n"
    "and.b32 a, %0, %4;\n"
    "and.b32 a, a, %8;\n"
    "and.b32 a, a, %12;\n"
    "and.b32 a, a, %16;\n"
    "and.b32 a, a, %20;\n"
    "and.b32 a, a, %24;\n"
    "and.b32 a, a, %28;\n"
    "and.b32 a, a, 1;\nsetp.eq.u32 p, a, 1;\nvote.sync.all.pred p, p, 0xffffffff;\n"
    "@p bra.uni LAB_OK;\n"
    "and.b32 a, %0, 1;\nsetp.ne.u32 q, a, 1;\n"
    "@q ld.relaxed.gpu.global.v4.b32 {%0,%1,%2,%3}, [%32+%33];\n"
    "and.b32 a, %4, 1;\nsetp.ne.u32 q, a, 1;\n"
    "@q ld.relaxed.gpu.global.v4.b32 {%4,%5,%6,%7}, [%32+%34];\n"
    "and.b32 a, %8, 1;\nsetp.ne.u32 q, a, 1;\n"
    "@q ld.relaxed.gpu.global.v4.b32 {%8,%9,%10,%11}, [%32+%35];\n"
    "and.b32 a, %12, 1;\nsetp.ne.u32 q, a, 1;\n"
    "@q ld.relaxed.gpu.global.v4.b32 {%12,%13,%14,%15}, [%32+%36];\n"
    "and.b32 a, %16, 1;\nsetp.ne.u32 q, a, 1;\n"
    "@q ld.relaxed.gpu.global.v4.b32 {%16,%17,%18,%19}, [%32+%37];\n"
    "and.b32 a, %20, 1;\nsetp.ne.u32 q, a, 1;\n"
    "@q ld.relaxed.gpu.global.v4.b32 {%20,%21,%22,%23}, [%32+%38];\n"
    "and.b32 a, %24, 1;\nsetp.ne.u32 q, a, 1;\n"
    "@q ld.relaxed.gpu.global.v4.b32 {%24,%25,%26,%27}, [%32+%39];\n"
    "and.b32 a, %28, 1;\nsetp.ne.u32 q, a, 1;\n"
    "@q ld.relaxed.gpu.global.v4.b32 {%28,%29,%30,%31}, [%32+%40];\n"
    "add.u32 n, n, 1;\nsetp.lt.u32 q, n, 262144;\n@q bra.uni LAB_CHK;\n"
    "LAB_OK:\n"
    "}\n"
    : "+r"(r[0][0]), "+r"(r[0][1]), "+r"(r[0][2]), "+r"(r[0][3]), "+r"(r[1][0]), "+r"(r[1][1]), "+r"(r[1][2]), "+r"(r[1][3]),
      "+r"(r[2][0]), "+r"(r[2][1]), "+r"(r[2][2]), "+r"(r[2][3]), "+r"(r[3][0]), "+r"(r[3][1]), "+r"(r[3][2]), "+r"(r[3][3]),
      "+r"(r[4][0]), "+r"(r[4][1]), "+r"(r[4][2]), "+r"(r[4][3]), "+r"(r[5][0]), "+r"(r[5][1]), "+r"(r[5][2]), "+r"(r[5][3]),
      "+r"(r[6][0]), "+r"(r[6][1]), "+r"(r[6][2]), "+r"(r[6][3]), "+r"(r[7][0]), "+r"(r[7][1]), "+r"(r[7][2]), "+r"(r[7][3])
    : "l"(p), "n"(0 * STR), "n"(1 * STR), "n"(2 * STR), "n"(3 * STR), "n"(4 * STR), "n"(5 * STR), "n"(6 * STR), "n"(7 * STR)
    : "memory");
}

template <int STR>
__device__ __forceinline__ void verify4_rt(const uint4* p, uint32_t (*r)[4], uint32_t tag) {
  asm volatile("{\n.reg .pred p, q;\n.reg .b32 a, b, n;\nmov.u32 n, 0;\n"
    "LAB_CHK:\n"
    "lop3.b32 a, %0, %4, %21, 0x7e;\n"
    "lop3.b32 b, %8, %12, %21, 0x7e;\nor.b32 a, a, b;\n"
    "and.b32 a, a, 1;\nsetp.eq.u32 p, a, 0;\nvote.sync.all.pred p, p, 0xffffffff;\n"
    "@p bra.uni LAB_OK;\n"
    "and.b32 a, %0, 1;\nsetp.ne.u32 q, a, %21;\n"
    "@q ld.relaxed.gpu.global.v4.b32 {%0,%1,%2,%3}, [%16+%17];\n"
    "and.b32 a, %4, 1;\nsetp.ne.u32 q, a, %21;\n"
    "@q ld.relaxed.gpu.global.v4.b32 {%4,%5,%6,%7}, [%16+%18];\n"
    "and.b32 a, %8, 1;\nsetp.ne.u32 q, a, %21;\n"
    "@q ld.relaxed.gpu.global.v4.b32 {%8,%9,%10,%11}, [%16+%19];\n"
    "and.b32 a, %12, 1;\nsetp.ne.u32 q, a, %21;\n"
    "@q ld.relaxed.gpu.global.v4.b32 {%12,%13,%14,%15}, [%16+%20];\n"
    "add.u32 n, n, 1;\nsetp.lt.u32 q, n, 262144;\n@q bra.uni LAB_CHK;\n"
    "LAB_OK:\n}\n"
    : "+r"(r[0][0]), "+r"(r[0][1]), "+r"(r[0][2]), "+r"(r[0][3]), "+r"(r[1][0]), "+r"(r[1][1]), "+r"(r[1][2]), "+r"(r[1][3]),
      "+r"(r[2][0]), "+r"(r[2][1]), "+r"(r[2][2]), "+r"(r[2][3]), "+r"(r[3][0]), "+r"(r[3][1]), "+r"(r[3][2]), "+r"(r[3][3])
    : "l"(p), "n"(0 * STR), "n"(1 * STR), "n"(2 * STR), "n"(3 * STR), "r"(tag)
    : "memory");
}

template <int STR>
__device__ __forceinline__ void verify8_tag0(const uint4* p, uint32_t (*r)[4]) {
  asm volatile("{\n.reg .pred p, q;\n.reg .b32 a, n;\nmov.u32 n, 0;\n"
    "LAB_CHK:\n"
    "or.b32 a, %0, %4;\n"
    "or.b32 a, a, %8;\n"
    "or.b32 a, a, %12;\n"
    "or.b32 a, a, %16;\n"
    "or.b32 a, a, %20;\n"
    "or.b32 a, a, %24;\n"
    "or.b32 a, a, %28;\n"
    "and.b32 a, a, 1;\nsetp.eq.u32 p, a, 0;\nvote.sync.all.pred p, p, 0xffffffff;\n"
    "@p bra.uni LAB_OK;\n"
    "and.b32 a, %0, 1;\nsetp.ne.u32 q, a, 0;\n"
    "@q ld.relaxed.gpu.global.v4.b32 {%0,%1,%2,%3}, [%32+%33];\n"
    "and.b32 a, %4, 1;\nsetp.ne.u32 q, a, 0;\n"
    "@q ld.relaxed.gpu.global.v4.b32 {%4,%5,%6,%7}, [%32+%34];\n"
    "and.b32 a, %8, 1;\nsetp.ne.u32 q, a, 0;\n"
    "@q ld.relaxed.gpu.global.v4.b32 {%8,%9,%10,%11}, [%32+%35];\n"
    "and.b32 a, %12, 1;\nsetp.ne.u32 q, a, 0;\n"
    "@q ld.relaxed.gpu.global.v4.b32 {%12,%13,%14,%15}, [%32+%36];\n"
    "and.b32 a, %16, 1;\nsetp.ne.u32 q, a, 0;\n"
    "@q ld.relaxed.gpu.global.v4.b32 {%16,%17,%18,%19}, [%32+%37];\n"
    "and.b32 a, %20, 1;\nsetp.ne.u32 q, a, 0;\n"
    "@q ld.relaxed.gpu.global.v4.b32 {%20,%21,%22,%23}, [%32+%38];\n"
    "and.b32 a, %24, 1;\nsetp.ne.u32 q, a, 0;\n"
    "@q ld.relaxed.gpu.global.v4.b32 {%24,%25,%26,%27}, [%32+%39];\n"
    "and.b32 a, %28, 1;\nsetp.ne.u32 q, a, 0;\n"
    "@q ld.relaxed.gpu.global.v4.b32 {%28,%29,%30,%31}, [%32+%40];\n"
    "add.u32 n, n, 1;\nsetp.lt.u32 q, n, 262144;\n@q bra.uni LAB_CHK;\n"
    "LAB_OK:\n"
    "or.b32 %0, %0, 1;\n"
    "or.b32 %4, %4, 1;\n"
    "or.b32 %8, %8, 1;\n"
    "or.b32 %12, %12, 1;\n"
    "or.b32 %16, %16, 1;\n"
    "or.b32 %20, %20, 1;\n"
    "or.b32 %24, %24, 1;\n"
    "or.b32 %28, %28, 1;\n"
    "}\n"
    : "+r"(r[0][0]), "+r"(r[0][1]), "+r"(r[0][2]), "+r"(r[0][3]), "+r"(r[1][0]), "+r"(r[1][1]), "+r"(r[1][2]), "+r"(r[1][3]),
      "+r"(r[2][0]), "+r"(r[2][1]), "+r"(r[2][2]), "+r"(r[2][3]), "+r"(r[3][0]), "+r"(r[3][1]), "+r"(r[3][2]), "+r"(r[3][3]),
      "+r"(r[4][0]), "+r"(r[4][1]), "+r"(r[4][2]), "+r"(r[4][3]), "+r"(r[5][0]), "+r"(r[5][1]), "+r"(r[5][2]), "+r"(r[5][3]),
      "+r"(r[6][0]), "+r"(r[6][1]), "+r"(r[6][2]), "+r"(r[6][3]), "+r"(r[7][0]), "+r"(r[7][1]), "+r"(r[7][2]), "+r"(r[7][3])
    : "l"(p), "n"(0 * STR), "n"(1 * STR), "n"(2 * STR), "n"(3 * STR), "n"(4 * STR), "n"(5 * STR), "n"(6 * STR), "n"(7 * STR)
    : "memory");
}

#define SPIN_LIMIT (1 << 18)

__device__ __forceinline__ uint32_t smem_u32(const void* p) { return (uint32_t)__cvta_generic_to_shared(p); }
__device__ __forceinline__ void mbar_init(uint32_t a, uint32_t c) {
  asm volatile("mbarrier.init.shared::cta.b64 [%0], %1;" ::"r"(a), "r"(c) : "memory");
}
__device__ __forceinline__ void mbar_expect(uint32_t a, uint32_t b) {
  asm volatile("mbarrier.arrive.expect_tx.shared::cta.b64 _, [%0], %1;" ::"r"(a), "r"(b) : "memory");
}
__device__ __forceinline__ void mbar_arrive(uint32_t a) {
  asm volatile("mbarrier.arrive.shared::cta.b64 _, [%0];" ::"r"(a) : "memory");
}
__device__ __forceinline__ void mbar_wait(uint32_t a, uint32_t parity) {
  asm volatile(
      "{\n.reg .pred p;\n.reg .u32 n;\nmov.u32 n, 0;\n"
      "LAB_WAIT:\n"
      "mbarrier.try_wait.parity.shared::cta.b64 p, [%0], %1;\n"
      "@p bra LAB_DONE;\n"
      "add.u32 n, n, 1;\n"
      "setp.lt.u32 p, n, 262144;\n"
      "@p bra LAB_WAIT;\n"
      "LAB_DONE:\n}\n" ::"r"(a), "r"(parity) : "memory");
}
__device__ __forceinline__ bool mbar_test(uint32_t a, uint32_t parity) {
  uint32_t ok;
  asm volatile("{\n.reg .pred p;\nmbarrier.test_wait.parity.shared::cta.b64 p, [%1], %2;\nselp.u32 %0, 1, 0, p;\n}\n"
               : "=r"(ok) : "r"(a), "r"(parity) : "memory");
  return ok;
}
__device__ __forceinline__ void tma3d(uint32_t dst, const CUtensorMap* tm, uint32_t bar, int c0, int c1, int c2) {
  asm volatile(
      "cp.async.bulk.tensor.3d.shared::cluster.global.mbarrier::complete_tx::bytes [%0], [%1, {%3,%4,%5}], [%2];"
      ::"r"(dst), "l"(tm), "r"(bar), "r"(c0), "r"(c1), "r"(c2) : "memory");
}
__device__ __forceinline__ void wg_fence() { asm volatile("wgmma.fence.sync.aligned;" ::: "memory"); }
__device__ __forceinline__ void wg_commit() { asm volatile("wgmma.commit_group.sync.aligned;" ::: "memory"); }
template <int N> __device__ __forceinline__ void wg_wait() {
  asm volatile("wgmma.wait_group.sync.aligned %0;" ::"n"(N) : "memory");
}
template <int N> __device__ __forceinline__ void fence_regs(float (&d)[N]) {
#pragma unroll
  for (int i = 0; i < N; i++) asm volatile("" : "+f"(d[i])::"memory");
}
template <int N> __device__ __forceinline__ void fence_regs(uint32_t (&d)[N][4]) {
#pragma unroll
  for (int i = 0; i < N; i++) asm volatile("" : "+r"(d[i][0]), "+r"(d[i][1]), "+r"(d[i][2]), "+r"(d[i][3])::"memory");
}
template <int N> __device__ __forceinline__ void fence_frags(uint32_t (*d)[4]) {
#pragma unroll
  for (int i = 0; i < N; i++) asm volatile("" : "+r"(d[i][0]), "+r"(d[i][1]), "+r"(d[i][2]), "+r"(d[i][3])::"memory");
}
__device__ __forceinline__ void bar_sync(int id, int n) { asm volatile("bar.sync %0, %1;" ::"r"(id), "r"(n) : "memory"); }
__device__ __forceinline__ void bar_arrive(int id, int n) { asm volatile("bar.arrive %0, %1;" ::"r"(id), "r"(n) : "memory"); }

__device__ __forceinline__ uint32_t pack_bf16(float lo, float hi) {
  uint32_t r;
  asm("cvt.rn.bf16x2.f32 %0, %1, %2;" : "=r"(r) : "f"(hi), "f"(lo));
  return r;
}
__device__ __forceinline__ float bf_lo(uint32_t w) { return __uint_as_float(w << 16); }
__device__ __forceinline__ float bf_hi(uint32_t w) { return __uint_as_float(w & 0xFFFF0000u); }
__device__ __forceinline__ float round_bf16(float x) { return bf_lo(pack_bf16(x, 0.f)); }
__device__ __forceinline__ uint32_t hfma2_bf16(uint32_t a, uint32_t b, uint32_t c) {
  uint32_t r;
  asm("fma.rn.bf16x2 %0, %1, %2, %3;" : "=r"(r) : "r"(a), "r"(b), "r"(c));
  return r;
}
__device__ __forceinline__ float ex2(float x) {
  float r;
  asm("ex2.approx.ftz.f32 %0, %1;" : "=f"(r) : "f"(x));
  return r;
}
__device__ __forceinline__ float tanh_hw(float x) {
  float r;
  asm("tanh.approx.f32 %0, %1;" : "=f"(r) : "f"(x));
  return r;
}
template <int TAG> __device__ __forceinline__ uint32_t pack_tag(float lo, float hi) {
  uint32_t w = __byte_perm(__float_as_uint(lo), pack_bf16(lo, hi), 0x7632);
  return TAG ? (w | 1u) : (w & ~1u);
}
__device__ __forceinline__ void st_pkt(uint4* p, uint32_t a, uint32_t b, uint32_t c, uint32_t d) {
  asm volatile(
      "st.relaxed.gpu.global.v4.b32 [%0], {%1,%2,%3,%4};" ::"l"(p), "r"(a), "r"(b), "r"(c), "r"(d) : "memory");
}
__device__ __forceinline__ void ld_pkt(const uint4* p, uint32_t (&r)[4]) {
  asm volatile(
      "ld.relaxed.gpu.global.v4.b32 {%0,%1,%2,%3}, [%4];"
      : "=r"(r[0]), "=r"(r[1]), "=r"(r[2]), "=r"(r[3]) : "l"(p) : "memory");
}
__device__ __forceinline__ uint32_t ldg32(const void* p) {
  uint32_t r;
  asm volatile("ld.global.nc.b32 %0, [%1];" : "=r"(r) : "l"(p));
  return r;
}
__device__ __forceinline__ uint32_t ldg16(const void* p) {
  uint16_t r;
  asm volatile("ld.global.nc.b16 %0, [%1];" : "=h"(r) : "l"(p));
  return r;
}
__device__ __forceinline__ uint4 ldg128(const void* p) {
  uint4 r;
  asm volatile("ld.global.nc.v4.b32 {%0,%1,%2,%3}, [%4];" : "=r"(r.x), "=r"(r.y), "=r"(r.z), "=r"(r.w) : "l"(p));
  return r;
}
__device__ __forceinline__ void l2_prefetch(const void* p, uint32_t bytes) {
  asm volatile("cp.async.bulk.prefetch.L2.global [%0], %1;" ::"l"(p), "r"(bytes) : "memory");
}
__device__ __forceinline__ float rcp_hw(float x) {
  float r;
  asm("rcp.approx.ftz.f32 %0, %1;" : "=f"(r) : "f"(x));
  return r;
}
__device__ __forceinline__ void warp_bulk_load(uint32_t sdst, const void* gsrc, uint32_t bytes, uint32_t bar) {
  asm volatile(
      "{\n.reg .pred p;\nelect.sync _|p, 0xffffffff;\n"
      "@p mbarrier.arrive.expect_tx.shared::cta.b64 _, [%3], %2;\n"
      "@p cp.async.bulk.shared::cluster.global.mbarrier::complete_tx::bytes [%0], [%1], %2, [%3];\n}\n"
      ::"r"(sdst), "l"(gsrc), "r"(bytes), "r"(bar) : "memory");
}
__device__ __forceinline__ void warp_tma3d(uint32_t dst, const CUtensorMap* tm, uint32_t bar, uint32_t bytes, int c1, int c2) {
  asm volatile(
      "{\n.reg .pred p;\nelect.sync _|p, 0xffffffff;\n"
      "@p mbarrier.arrive.expect_tx.shared::cta.b64 _, [%2], %3;\n"
      "@p cp.async.bulk.tensor.3d.shared::cluster.global.mbarrier::complete_tx::bytes [%0], [%1, {%6,%4,%5}], [%2];\n}\n"
      ::"r"(dst), "l"(tm), "r"(bar), "r"(bytes), "r"(c1), "r"(c2), "r"(0) : "memory");
}
__device__ __forceinline__ bool elect_one() {
  uint32_t r;
  asm volatile("{\n.reg .pred p;\nelect.sync _|p, 0xffffffff;\nselp.u32 %0, 1, 0, p;\n}\n" : "=r"(r));
  return r;
}
__device__ __forceinline__ void warp_arrive(uint32_t bar) {
  asm volatile("{\n.reg .pred p;\nelect.sync _|p, 0xffffffff;\n@p mbarrier.arrive.shared::cta.b64 _, [%0];\n}\n" ::"r"(bar) : "memory");
}
__device__ __forceinline__ uint32_t pack_trunc(float lo, float hi) {
  return __byte_perm(__float_as_uint(lo), __float_as_uint(hi), 0x7632);
}
__device__ __forceinline__ void add_partial(float (&y)[8], const uint32_t (&r)[4], uint32_t c0, bool first) {
#pragma unroll
  for (int e = 0; e < 4; e++) {
    const float lo = __uint_as_float(r[e] * 65536u + (e ? 0x8000u : c0)), hi = __uint_as_float(r[e]);
    y[2 * e] = first ? lo : y[2 * e] + lo;
    y[2 * e + 1] = first ? hi : y[2 * e + 1] + hi;
  }
}
__device__ __forceinline__ void spin_cycles(uint32_t n) {
  uint32_t t0, t;
  asm volatile("mov.u32 %0, %%clock;" : "=r"(t0));
  do { asm volatile("mov.u32 %0, %%clock;" : "=r"(t)); } while (t - t0 < n);
}
__device__ __forceinline__ void sts128(uint32_t a, uint32_t x, uint32_t y, uint32_t z, uint32_t w) {
  asm volatile("st.shared.v4.b32 [%0], {%1,%2,%3,%4};" ::"r"(a), "r"(x), "r"(y), "r"(z), "r"(w) : "memory");
}
__device__ __forceinline__ void lds128(uint32_t a, uint32_t (&r)[4]) {
  asm volatile("ld.shared.v4.b32 {%0,%1,%2,%3}, [%4];" : "=r"(r[0]), "=r"(r[1]), "=r"(r[2]), "=r"(r[3]) : "r"(a) : "memory");
}

__device__ __forceinline__ uint32_t lds32(uint32_t a) {
  uint32_t r;
  asm volatile("ld.shared.b32 %0, [%1];" : "=r"(r) : "r"(a) : "memory");
  return r;
}
__device__ __forceinline__ void store_out(__nv_bfloat16* out, uint32_t woff, uint32_t x2s, uint32_t gb0, uint32_t gb1,
                                          const float (&y)[8]) {
  const uint32_t gb[2] = {gb0, gb1};
  uint32_t xa[2][4];
  lds128(x2s, xa[0]);
  lds128(x2s + 2048, xa[1]);
  uint32_t* const oo = (uint32_t*)out + woff;
#pragma unroll
  for (int e = 0; e < 4; e++)
    oo[(e >> 1) * 4 + (e & 1) * 8 * 256] =
        pack_bf16(fmaf(bf_lo(gb[e >> 1]), y[2 * e], __uint_as_float(xa[e >> 1][(e & 1) * 2])),
                  fmaf(bf_hi(gb[e >> 1]), y[2 * e + 1], __uint_as_float(xa[e >> 1][(e & 1) * 2 + 1])));
}

constexpr int SK = 2048, WIN = 512;
constexpr int FF = 1792, FSL = 224;
constexpr int NTILES = 80;
constexpr int NSLOT = 4;
constexpr uint32_t SLOT = 32768;
constexpr uint32_t SM_PARK = 0;
constexpr uint32_t SM_RING = 3 * SLOT;
constexpr uint32_t SM_TAB = 7 * SLOT;
constexpr uint32_t SM_RED = SM_TAB + 2048;
constexpr uint32_t SM_BAR = SM_RED + 256;
constexpr uint32_t SM_WBAR = SM_BAR + 128;
constexpr uint32_t SM_SBAR = SM_WBAR + 256;
constexpr uint32_t BAR_SLAB = 64, BAR_UV = 72, BAR_X2 = 80, BAR_TAG = 88;
constexpr uint32_t SM_DBAR = SM_SBAR + 16;
constexpr uint32_t SM_TOTAL = SM_DBAR + 128;

struct Scratch {
  uint4 P[16 * 8 * 4 * 1024];
  uint4 G[16 * 8 * 32 * 32];
  uint4 mod1[8 * 256];
  uint4 mod2[512];
  uint4 uv[2 * 448];
  uint4 stat[16 * 8 * 8];
  uint32_t sent[16 * 8 * 8];
  uint32_t epoch;
};
__device__ Scratch g_scratch;

#define TS(i) do { } while (0)
#define TR(code)
#define CK_(v)
#define CKS(i, v)

#define TRU(code)

struct Params {
  const __nv_bfloat16* x;
  const __nv_bfloat16* c;
  const __nv_bfloat16* wmod;
  const __nv_bfloat16* wo;
  const __nv_bfloat16* w1;
  const __nv_bfloat16* w2;
  __nv_bfloat16* out;
  Scratch* s;
  uint32_t zero;
};

constexpr uint32_t HI128 = (1024 >> 4) | (1u << 30);
constexpr int LB_MN128 = (16384 >> 4) << 16;
constexpr int LB_K128 = 1 << 16;
constexpr int LB_W1 = (8192 >> 4) << 16;

template <int I> struct IC {
  __host__ __device__ constexpr operator int() const { return I; }
};
template <int I, int N, typename F> __device__ __forceinline__ void static_for(F&& f) {
  if constexpr (I < N) {
    f(IC<I>{});
    static_for<I + 1, N>(f);
  }
}

struct Ring {
  uint32_t base16, bars;
  __device__ __forceinline__ uint32_t tile(uint32_t slot) const { return base16 + slot * (SLOT >> 4); }
  __device__ __forceinline__ void release(uint32_t slot) const {
    warp_arrive(bars + 32 + slot * 8);
  }
};

__device__ __forceinline__ float silu_c(uint32_t bits) {
  float x = bf_lo(bits);
  return round_bf16(x * rcp_hw(1.f + ex2(-1.4426950408889634f * x)));
}
__device__ __forceinline__ void pack8(uint32_t (&o)[4], const float* v) {
  o[0] = pack_bf16(v[0], v[1]); o[1] = pack_bf16(v[2], v[3]); o[2] = pack_bf16(v[4], v[5]); o[3] = pack_bf16(v[6], v[7]);
}

template <int TAG, int N>
__device__ __forceinline__ void issue_pkts(const uint4* p, int stride, uint32_t (*r)[4]) {
#pragma unroll
  for (int i = 0; i < N; i++) ld_pkt(p + i * stride, r[i]);
}
__device__ __forceinline__ void wait_sent(const uint32_t* p, uint32_t tag, uint32_t step) {
#pragma unroll 1
  for (int spins = 0; spins < SPIN_LIMIT; spins++) {
    uint32_t v;
    asm volatile("ld.relaxed.gpu.global.u32 %0, [%1];" : "=r"(v) : "l"(p) : "memory");
    if (__all_sync(0xffffffffu, v - (tag * 32 + step + 1) < 16u)) break;
  }
}
__device__ __forceinline__ void ld_mod(const uint4* p, uint32_t tag, uint32_t (&r)[4]) {
  int spins = 0;
  ld_pkt(p, r);
  while (r[2] != tag && ++spins < SPIN_LIMIT) ld_pkt(p, r);
}

#define EARLY_TILES 2
#define PF_WMOD 1
#define MOD1_DELAY 500
#define RED3_UNIT 3
#define NITEM2 24
#define FIN_DELAY0 800
#define FIN_DELAY1 0
#define PRE_EXP 4
#define G_DELAY 300

__device__ __forceinline__ float reduce8(float (&a)[8], int lane) {
  const bool h16 = lane & 16, h8 = lane & 8, h4 = lane & 4;
#pragma unroll
  for (int k = 0; k < 4; k++) a[k] = (h16 ? a[k + 4] : a[k]) + __shfl_xor_sync(0xffffffffu, h16 ? a[k] : a[k + 4], 16);
#pragma unroll
  for (int k = 0; k < 2; k++) a[k] = (h8 ? a[k + 2] : a[k]) + __shfl_xor_sync(0xffffffffu, h8 ? a[k] : a[k + 2], 8);
  const float r = (h4 ? a[1] : a[0]) + __shfl_xor_sync(0xffffffffu, h4 ? a[0] : a[1], 4);
  return r + __shfl_xor_sync(0xffffffffu, r, 2);
}
__device__ __forceinline__ void fma8(float (&a)[8], float s, uint32_t w0, uint32_t w1, uint32_t w2, uint32_t w3) {
  a[0] = fmaf(s, bf_lo(w0), a[0]); a[1] = fmaf(s, bf_hi(w0), a[1]);
  a[2] = fmaf(s, bf_lo(w1), a[2]); a[3] = fmaf(s, bf_hi(w1), a[3]);
  a[4] = fmaf(s, bf_lo(w2), a[4]); a[5] = fmaf(s, bf_hi(w2), a[5]);
  a[6] = fmaf(s, bf_lo(w3), a[6]); a[7] = fmaf(s, bf_hi(w3), a[7]);
}

enum { NB_TAB = 1, NB_WG0 = 2, NB_WG1 = 3, NB_HELP = 4, NB_INIT = 5, NB_PASS0 = 6, NB_GATHER = 7, NB_PARK = 8, NB_PROD = 9 };

__global__ void __launch_bounds__(512, 1)
adaln_block_kernel(const __grid_constant__ CUtensorMap tmWq, const __grid_constant__ CUtensorMap tmK,
                   const __grid_constant__ CUtensorMap tmV, const __grid_constant__ CUtensorMap tmWo,
                   const __grid_constant__ CUtensorMap tmW1, const __grid_constant__ CUtensorMap tmW2,
                   const __grid_constant__ CUtensorMap tmWm, const __grid_constant__ CUtensorMap tmX,
                   const Params p) {
  extern __shared__ __align__(1024) uint8_t smem_raw[];
  const uint32_t sb = smem_u32(smem_raw);
  const int tid = threadIdx.x, lane = tid & 31;
  const int warp = __shfl_sync(0xffffffffu, tid >> 5, 0);
  const int kp = blockIdx.x >> 1;
  const int bid = (kp < 4 ? kp : kp < 36 ? 4 + ((kp - 4) & 7) * 4 + ((kp - 4) >> 3) : 36 + ((kp - 36) % 7) * 4 + (kp - 36) / 7) * 2 +
                  (blockIdx.x & 1);
  const int j = bid & 7, rt = bid >> 3;
  const uint32_t bars = sb + SM_BAR;
  if (warp != 13) asm volatile("barrier.cluster.arrive.relaxed.aligned;" ::: "memory");

  if (warp >= 12) {
    asm volatile("setmaxnreg.dec.sync.aligned.u32 24;");
    if (warp == 13) {
      if (elect_one()) {
#pragma unroll
        for (int i = 0; i < 28; i++) mbar_init(sb + SM_WBAR + i * 8, i < 26 ? 1 : 4);
        mbar_init(sb + SM_SBAR, 8);
#pragma unroll
        for (int i = 0; i < 16; i++) mbar_init(sb + SM_DBAR + i * 8, 1);
        asm volatile("fence.mbarrier_init.release.cluster;" ::: "memory");
      }
      __syncwarp();
      asm volatile("barrier.cluster.arrive.relaxed.aligned;" ::: "memory");
      bar_arrive(NB_INIT, 224);
      mbar_wait(sb + SM_SBAR, 0);
      const uint32_t tag = *(volatile uint32_t*)(smem_raw + SM_BAR + BAR_TAG);
#pragma unroll 1
      for (int n = 0; n < 14; n++) {
        const uint32_t lb = sb + SM_WBAR + 192 + (n & 1) * 8;
        mbar_wait(lb + 16, ((n >> 1) & 1) ^ 1);
        wait_sent(&p.s->sent[(rt * 8 + j) * 8 + (lane & 6) + (n & 1)], tag, n >> 1);
        if (elect_one()) {
          mbar_expect(lb, n < 8 ? 8192 + 2048 : 8192);
#pragma unroll
          for (int m = 0; m < 4; m++)
            asm volatile("cp.async.bulk.shared::cluster.global.mbarrier::complete_tx::bytes [%0], [%1], 2048, [%2];"
                         ::"r"(sb + SM_PARK + ((n & 1) * 4 + m) * 4096 + 2048),
                           "l"(p.s->P + ((size_t)(rt * 8 + j) * 4 + m) * 1024 + (n & 7) * 128), "r"(lb) : "memory");
          if (n < 8) tma3d(sb + SM_PARK + SLOT + n * 4096, &tmX, lb, 0, rt * 128 + j * 16, n * 4);
        }
        __syncwarp();
      }
    } else if (warp == 14) {
      if (elect_one()) {
        asm volatile("prefetch.tensormap [%0];" ::"l"(&tmWq) : "memory");
        asm volatile("prefetch.tensormap [%0];" ::"l"(&tmK) : "memory");
        asm volatile("prefetch.tensormap [%0];" ::"l"(&tmV) : "memory");
        asm volatile("prefetch.tensormap [%0];" ::"l"(&tmWo) : "memory");
        asm volatile("prefetch.tensormap [%0];" ::"l"(&tmX) : "memory");
        asm volatile("prefetch.tensormap [%0];" ::"l"(&tmW1) : "memory");
        asm volatile("prefetch.tensormap [%0];" ::"l"(&tmW2) : "memory");
      }
      __syncwarp();
      bar_sync(NB_INIT, 224);
#pragma unroll 1
      for (int tt = 0; tt < NTILES; tt++) {
        mbar_wait(bars + (tt & 3) * 8, (tt >> 2) & 1);
        const bool single = tt < 4 || tt == 16 || tt == 47 || tt == 72 || tt == 79;
        const bool second = (tt > 16 && tt < 47) || tt > 72 ? !(tt & 1) : (tt & 1);
        if (single || second) bar_sync(NB_WG0, 288);
      }
    } else if (warp == 12) {
      if (elect_one()) {
        mbar_init(bars + BAR_SLAB, 1);
        asm volatile("fence.mbarrier_init.release.cluster;" ::: "memory");
        mbar_expect(bars + BAR_SLAB, 8192);
        tma3d(sb + SM_RING + 3 * SLOT, &tmWm, bars + BAR_SLAB, 0, 0, bid);
        tma3d(sb + SM_RING + 3 * SLOT + 4096, &tmWm, bars + BAR_SLAB, 0, 256, bid);
#pragma unroll
        for (int i = 0; i < 4; i++) { mbar_init(bars + i * 8, 1); mbar_init(bars + 32 + i * 8, 8); }
        mbar_init(bars + BAR_UV, 4);
        mbar_init(bars + BAR_X2, 1);
        asm volatile("fence.mbarrier_init.release.cluster;" ::: "memory");
      }
      __syncwarp();
      bar_arrive(NB_INIT, 224);
      mbar_wait(bars + BAR_SLAB, 0);
      uint32_t s = 0, ph = 1;
#pragma unroll 1
      for (int tt = 0; tt < NTILES; tt++) {
        const CUtensorMap* tm;
        int c1, c2;
        uint32_t bytes = SLOT;
        if (tt < 16) {
          tm = &tmWq; c1 = (tt & 3) * 128; c2 = (j * 4 + (((tt >> 2) + 1) & 3)) * 2;
        } else if (tt < 48) {
          const int u = tt - 16;
          const bool isK = (u == 0) || ((u & 1) && u != 31);
          const int n = isK ? ((u + 1) >> 1) : (u == 31 ? 15 : (u >> 1) - 1);
          tm = isK ? &tmK : &tmV; c1 = j * SK + (SK - WIN) + (n & 3) * 128; c2 = 0;
        } else if (tt < 64) {
          const int u = tt - 48;
          tm = &tmWo; c1 = j * 512 + (u & 1) * 256; c2 = (u >> 1) ^ (~j & 1);
        } else if (tt < 72) {
          tm = &tmW1; c1 = (tt - 64) * 64; c2 = (j * 7) >> 1;
        } else {
          tm = &tmW2; c1 = j * FSL; c2 = (tt - 72) ^ (~j & 1); bytes = 28672;
        }
        if (tt == EARLY_TILES) bar_sync(NB_PROD, 160);
        mbar_wait(bars + 32 + s * 8, ph);
        warp_tma3d(sb + SM_RING + s * SLOT, tm, bars + s * 8, bytes, c1, c2);
        if (++s == 4) { s = 0; ph ^= 1; }
      }
    }
  } else if (warp >= 8) {
    CK_(c0);
    asm volatile("setmaxnreg.dec.sync.aligned.u32 40;");
    const int t = tid - 256, hw = warp - 8, q = lane & 3;
    float* const red = (float*)(smem_raw + SM_RED);
    uint32_t tag;
    float a[8];
    {
      uint32_t cb[4];
#pragma unroll
      for (int i = 0; i < 4; i++) cb[i] = ldg16(p.c + t + 128 * i);
      asm volatile("ld.relaxed.gpu.global.u32 %0, [%1];" : "=r"(tag) : "l"(&p.s->epoch) : "memory");
      bar_sync(NB_INIT, 224);
      CK_(c2);
      tag += 1;
      float sc[4];
#pragma unroll
      for (int i = 0; i < 4; i++) sc[i] = silu_c(cb[i]);
#pragma unroll
      for (int k = 0; k < 8; k++) a[k] = 0.f;
      if (t == 0) *(uint32_t*)(smem_raw + SM_BAR + BAR_TAG) = tag;
      mbar_wait(bars + BAR_SLAB, 0);
      CK_(c3);
      bar_arrive(NB_GATHER, 384);
#pragma unroll
      for (int i = 0; i < 4; i++) {
        uint32_t w[4];
        lds128(sb + SM_RING + 3 * SLOT + (t + 128 * i) * 16, w);
        fma8(a, sc[i], w[0], w[1], w[2], w[3]);
      }
      float r = reduce8(a, lane);
      r += __shfl_xor_sync(0xffffffffu, r, 1);
      if (q == 0) red[hw * 8 + (lane >> 2)] = r;
      CK_(c4);
      bar_sync(NB_HELP, 128);
      CK_(c5);
      if (hw == 0) {
        const int cl = lane & 7;
        float v = round_bf16(red[cl] + red[8 + cl] + red[16 + cl] + red[24 + cl]);
        if (bid >= 64) v = 1.f + v;
        float vn = __shfl_down_sync(0xffffffffu, v, 1);
        uint32_t wd = pack_bf16(v, vn);
        uint32_t w0 = __shfl_sync(0xffffffffu, wd, (lane & 1) * 4);
        uint32_t w1 = __shfl_sync(0xffffffffu, wd, (lane & 1) * 4 + 2);
        if (lane < 16) st_pkt(&p.s->mod1[(lane >> 1) * 256 + bid * 2 + (lane & 1)], w0, w1, tag, 0);
      }
      uint32_t r0[4], r1[4];
      const uint4* src = &p.s->mod1[j * 256 + t];
      CK_(c6);
      spin_cycles(MOD1_DELAY);
      CK_(c7);
      int spins = 0;
      do {
        ld_pkt(src, r0);
        ld_pkt(src + 128, r1);
      } while ((r0[2] != tag || r1[2] != tag) && ++spins < SPIN_LIMIT);
      const int g = t >> 2, pp = q * 2;
      const uint32_t ad = sb + SM_TAB + (uint32_t)(g * 4 + (pp & 3)) * 16 + (pp >> 2) * 4;
      asm volatile("st.shared.b32 [%0], %1;" ::"r"(ad + 8), "r"(r0[0]) : "memory");
      asm volatile("st.shared.b32 [%0], %1;" ::"r"(ad + 24), "r"(r0[1]) : "memory");
      asm volatile("st.shared.b32 [%0], %1;" ::"r"(ad), "r"(r1[0]) : "memory");
      asm volatile("st.shared.b32 [%0], %1;" ::"r"(ad + 16), "r"(r1[1]) : "memory");
      bar_arrive(NB_TAB, 384);
      bar_arrive(NB_PROD, 160);
      CK_(c8);
      CKS(0, c0); CKS(2, c2); CKS(3, c3); CKS(4, c4); CKS(5, c5); CKS(6, c6); CKS(7, c7); CKS(8, c8);
    }
    bar_sync(NB_PASS0, 384);
    if (t < 8) l2_prefetch((const char*)p.wo + (size_t)bid * 32768 + t * 4096, 4096);
    else if (t < 12) l2_prefetch((const char*)p.w1 + (size_t)bid * 14336 + (t - 8) * 3584, 3584);
    else if (t < 16) l2_prefetch((const char*)p.w2 + (size_t)bid * 14336 + (t - 12) * 3584, 3584);
    {
#pragma unroll
      for (int k = 0; k < 8; k++) a[k] = 0.f;
#pragma unroll 1
      for (int b = 0; b < 4; b++) {
        const int row = b * 128 + (t >> 1);
        const __nv_bfloat16* wp = p.wmod + (size_t)row * 3072 + 1024 + bid * 16 + (t & 1) * 8;
        const uint4 w0 = ldg128(wp), w1 = ldg128(wp + 64 * 3072);
        const uint32_t c0 = ldg16(p.c + row), c1 = ldg16(p.c + row + 64);
        fma8(a, silu_c(c0), w0.x, w0.y, w0.z, w0.w);
        fma8(a, silu_c(c1), w1.x, w1.y, w1.z, w1.w);
      }
      const float r = reduce8(a, lane);
      if ((lane & 2) == 0) red[hw * 16 + (lane & 1) * 8 + (lane >> 2)] = r;
      bar_sync(NB_HELP, 128);
      if (hw == 0) {
        const int cl = lane & 15;
        float v = round_bf16(red[cl] + red[16 + cl] + red[32 + cl] + red[48 + cl]);
        if ((bid >> 5) == 2) v = 1.f + v;
        float vn = __shfl_down_sync(0xffffffffu, v, 1);
        uint32_t wd = pack_bf16(v, vn);
        uint32_t w0 = __shfl_sync(0xffffffffu, wd, q * 2);
        uint32_t w1 = __shfl_sync(0xffffffffu, wd, q * 2 + 8);
        const int vec = (0x2130 >> ((bid >> 5) * 4)) & 3;
        if (lane < 4) st_pkt(&p.s->mod2[((bid & 31) * 4 + vec) * 4 + lane], w0, w1, tag, 0);
      }
    }
    {
      const int isv = hw & 1, kh = hw >> 1;
      if (bid < 112) {
        const int kk = lane >> 1;
        uint32_t m0[4], m1[4];
        const uint4* mp = &p.s->mod2[(kh * 16 + (lane >> 2)) * 16 + (isv ? 12 : 4) + q];
        ld_mod(mp, tag, m0);
        ld_mod(mp + 128, tag, m1);
#pragma unroll
        for (int k = 0; k < 8; k++) a[k] = 0.f;
#pragma unroll 1
        for (int g0 = 0; g0 < 16; g0 += 2) {
          uint4 w[2];
#pragma unroll
          for (int i = 0; i < 2; i++) w[i] = ldg128(p.w1 + (size_t)((kh * 16 + g0 + i) * 16 + kk) * FF + bid * 16 + (lane & 1) * 8);
#pragma unroll
          for (int i = 0; i < 2; i++) {
            const int sl = ((g0 + i) & 7) * 4 + ((kk & 7) >> 1);
            const uint32_t wa = __shfl_sync(0xffffffffu, g0 < 8 ? m0[0] : m1[0], sl), wb = __shfl_sync(0xffffffffu, g0 < 8 ? m0[1] : m1[1], sl);
            const uint32_t mw = (kk & 8) ? wb : wa;
            fma8(a, (kk & 1) ? bf_hi(mw) : bf_lo(mw), w[i].x, w[i].y, w[i].z, w[i].w);
          }
        }
        float r = reduce8(a, lane);
        bar_sync(NB_HELP, 128);
        if (kh) red[isv * 32 + lane] = r;
        bar_sync(NB_HELP, 128);
        if (!kh) {
          r = (r + red[isv * 32 + lane]) * (isv ? 0.5f : 1.f);
          const float r1 = __shfl_down_sync(0xffffffffu, r, 4), r2 = __shfl_down_sync(0xffffffffu, r, 8),
                      r3 = __shfl_down_sync(0xffffffffu, r, 12);
          if ((lane & 14) == 0)
            st_pkt(&p.s->uv[isv * 448 + bid * 4 + (lane & 1) * 2 + (lane >> 4)], (__float_as_uint(r) & ~1u) | (tag & 1u),
                   __float_as_uint(r1), __float_as_uint(r2), __float_as_uint(r3));
        }
      }
      const int i = kh * 32 + lane;
      if (i < 56) {
        uint32_t m[4];
        int spins = 0;
        while (true) {
          ld_pkt(&p.s->uv[isv * 448 + j * 56 + i], m);
          if (!((m[0] ^ tag) & 1u) || ++spins >= SPIN_LIMIT) break;
          __nanosleep(200);
        }
        const int ip = (j & 1) ? (i < 8 ? i + 48 : i - 8) : i;
        const uint32_t ad = sb + SM_TAB + ip * 32 + isv * 8;
        asm volatile("st.shared.v2.b32 [%0], {%1,%2};" ::"r"(ad), "r"(m[0]), "r"(m[1]) : "memory");
        asm volatile("st.shared.v2.b32 [%0], {%1,%2};" ::"r"(ad + 16), "r"(m[2]), "r"(m[3]) : "memory");
      }
      __syncwarp();
      warp_arrive(bars + BAR_UV);
      TS(9);
    }
    {
      uint32_t mga[4], mg2[4], mgb[4];
      const uint4* mp = &p.s->mod2[((lane >> 2) * 4 + hw) * 16 + q];
      ld_mod(mp, tag, mga);
      ld_mod(mp + 4, tag, mg2);
      ld_mod(mp + 8, tag, mgb);
      if (lane >= 24) asm volatile("st.shared.v2.b32 [%0], {%1,%2};" ::"r"(sb + SM_TAB + 1792 + ((((lane >> 2) & 1) * 4 + hw) * 4 + q) * 8),
                                   "r"(mgb[0]), "r"(mgb[1]) : "memory");
      const uint32_t x2s = sb + SM_PARK + SLOT + hw * 512 + lane * 16;
      const uint4* const Pown = p.s->P + (size_t)(rt * 8 + j) * 4096 + hw * 32 + lane;
      float s0 = 0.f, s1 = 0.f, v0 = 0.f, v1 = 0.f;
      bar_sync(NB_PARK, 384);
      asm volatile("setmaxnreg.inc.sync.aligned.u32 56;");
#pragma unroll 1
      for (int n = 0; n < 14; n++) {
        const int cc = n & 7;
        const bool ex1 = n < 8;
        const uint32_t lb = sb + SM_WBAR + 192 + (n & 1) * 8;
        uint32_t r[4][4];
        float y[8];
        mbar_wait(lb, (n >> 1) & 1);
#pragma unroll
        for (int i = 0; i < 4; i++) lds128(sb + SM_PARK + ((n & 1) * 4 + i) * 4096 + 2048 + hw * 512 + lane * 16, r[i]);
        verify4_rt<16384>(Pown + cc * 128, r, ex1);
        warp_arrive(lb + 16);
#pragma unroll
        for (int i = 0; i < 4; i++) add_partial(y, r[i], ex1 ? 0u : 0x10000u, i == 0);
        const int src = cc * 4 + q;
        const uint32_t ma = __shfl_sync(0xffffffffu, ex1 ? mga[0] : mgb[0], src), mb = __shfl_sync(0xffffffffu, ex1 ? mga[1] : mgb[1], src);
        if (ex1) {
          uint32_t xr[4];
          asm volatile("ldmatrix.sync.aligned.m8n8.x4.shared.b16 {%0,%1,%2,%3}, [%4];"
                       : "=r"(xr[0]), "=r"(xr[1]), "=r"(xr[2]), "=r"(xr[3])
                       : "r"(sb + SM_PARK + SLOT + hw * 512 + cc * 4096 + (lane & 15) * 32 + (lane >> 4) * 16) : "memory");
          const uint32_t mc = __shfl_sync(0xffffffffu, mg2[0], src), md = __shfl_sync(0xffffffffu, mg2[1], src);
#pragma unroll
          for (int e = 0; e < 4; e++) {
            const uint32_t m = e < 2 ? ma : mb;
            const float u = fmaf(bf_lo(m), y[2 * e], bf_lo(xr[e])), v = fmaf(bf_hi(m), y[2 * e + 1], bf_hi(xr[e]));
            y[2 * e] = u; y[2 * e + 1] = v;
            if (e & 1) { s1 += u + v; v1 = fmaf(u, u, fmaf(v, v, v1)); }
            else { s0 += u + v; v0 = fmaf(u, u, fmaf(v, v, v0)); }
          }
          st_pkt(p.s->G + ((rt * 8 + j) * 32 + cc * 4 + hw) * 32 + lane, pack_tag<0>(y[0] * bf_lo(mc), y[1] * bf_hi(mc)),
                 pack_bf16(y[2] * bf_lo(mc), y[3] * bf_hi(mc)), pack_bf16(y[4] * bf_lo(md), y[5] * bf_hi(md)),
                 pack_bf16(y[6] * bf_lo(md), y[7] * bf_hi(md)));
          sts128(x2s + cc * 4096, __float_as_uint(y[0]), __float_as_uint(y[1]), __float_as_uint(y[2]), __float_as_uint(y[3]));
          sts128(x2s + cc * 4096 + 2048, __float_as_uint(y[4]), __float_as_uint(y[5]), __float_as_uint(y[6]), __float_as_uint(y[7]));
          if (n == 7) {
            const bool o1 = lane & 1, o2 = lane & 2;
            float c0 = (o1 ? v0 : s0) + __shfl_xor_sync(0xffffffffu, o1 ? s0 : v0, 1);
            float c1 = (o1 ? v1 : s1) + __shfl_xor_sync(0xffffffffu, o1 ? s1 : v1, 1);
            c0 = (o2 ? c1 : c0) + __shfl_xor_sync(0xffffffffu, o2 ? c0 : c1, 2);
            *(float*)(smem_raw + SM_PARK + 16384 + 2048 + hw * 512 + lane * 4) = c0;
            bar_sync(NB_HELP, 128);
            if (hw == 0) {
              const float* ps = (const float*)(smem_raw + SM_PARK + 16384 + 2048) + lane;
              const float m = (c0 + ps[128] + ps[256] + ps[384]) * (1.f / 512.f);
              const float mean = __shfl_sync(0xffffffffu, m, lane & ~1), sq = __shfl_sync(0xffffffffu, m, lane | 1);
              const float rs = 0.5f * rsqrtf(fmaxf(fmaf(-mean, mean, sq), 0.f) + 1e-5f), mr = -mean * rs;
              const float rs1 = __shfl_down_sync(0xffffffffu, rs, 2), mr1 = __shfl_down_sync(0xffffffffu, mr, 2);
              if (q == 0)
                st_pkt(&p.s->stat[(rt * 8 + j) * 8 + (lane >> 2)], (__float_as_uint(rs) & ~1u) | (tag & 1u), __float_as_uint(mr),
                       __float_as_uint(rs1), __float_as_uint(mr1));
              warp_arrive(bars + BAR_X2);
            }
          }
        } else {
          store_out(p.out, (uint32_t)(rt * 128 + 16 * j + (lane >> 2)) * 256 + (cc * 4 + hw) * 8 + q, x2s + cc * 4096, ma, mb, y);
        }
      }
    }
  } else {
    const int wg = warp >> 2;
    const int q = lane & 3, gq = lane >> 2;
    const Ring ring{((sb + SM_RING) & 0x3FFFF) >> 4, bars};
    const uint32_t xoff = (uint32_t)(rt * 128 + 16 * j + warp) * 256 + gq * 8 + q;
    const uint32_t ooff = ((uint32_t)(rt * 8 + j) * 32 + gq) * 32 + warp * 4 + q;
    const uint32_t wblk = sb + SM_PARK + warp * 4096, wprv = wblk + lane * 16;
    const uint32_t wbar = sb + SM_WBAR + warp * 24;
    const uint4* const Gw = p.s->G + (rt * 8 + warp) * 1024;

    {
      const uint32_t* xo = (const uint32_t*)p.x + xoff;
      uint32_t xr[4][4];
      CK_(d0);
#pragma unroll
      for (int c = 0; c < 4; c++) {
        xr[c][0] = ldg32(xo + c * 64);
        xr[c][1] = ldg32(xo + c * 64 + 8 * 256);
        xr[c][2] = ldg32(xo + c * 64 + 4);
        xr[c][3] = ldg32(xo + c * 64 + 4 + 8 * 256);
      }
      CK_(d1);
      fence_regs(xr);
      CK_(d2);
      float s0 = 0.f, s1 = 0.f, v0 = 0.f, v1 = 0.f;
#pragma unroll
      for (int c = 0; c < 4; c++) {
#pragma unroll
        for (int e = 0; e < 4; e++) {
          const float a = bf_lo(xr[c][e]), b = bf_hi(xr[c][e]);
          if (e & 1) { s1 += a + b; v1 = fmaf(a, a, fmaf(b, b, v1)); }
          else { s0 += a + b; v0 = fmaf(a, a, fmaf(b, b, v0)); }
        }
      }
#pragma unroll
      for (int o = 16; o > 0; o >>= 1) {
        s0 += __shfl_xor_sync(0xffffffffu, s0, o);
        s1 += __shfl_xor_sync(0xffffffffu, s1, o);
        v0 += __shfl_xor_sync(0xffffffffu, v0, o);
        v1 += __shfl_xor_sync(0xffffffffu, v1, o);
      }
      const float m0 = s0 * (1.f / 512.f), m1 = s1 * (1.f / 512.f);
      const float r0 = rsqrtf(fmaxf(fmaf(-m0, m0, v0 * (1.f / 512.f)), 0.f) + 1e-5f);
      const float r1 = rsqrtf(fmaxf(fmaf(-m1, m1, v1 * (1.f / 512.f)), 0.f) + 1e-5f);
#pragma unroll
      for (int c = 0; c < 4; c++) {
        st_pkt(p.s->G + ooff + c * 256,
               pack_tag<1>((bf_lo(xr[c][0]) - m0) * r0, (bf_hi(xr[c][0]) - m0) * r0),
               pack_bf16((bf_lo(xr[c][1]) - m1) * r1, (bf_hi(xr[c][1]) - m1) * r1),
               pack_bf16((bf_lo(xr[c][2]) - m0) * r0, (bf_hi(xr[c][2]) - m0) * r0),
               pack_bf16((bf_lo(xr[c][3]) - m1) * r1, (bf_hi(xr[c][3]) - m1) * r1));
      }
      CK_(d3);
      CKS(16, d0); CKS(17, d1); CKS(18, d2); CKS(19, d3);

    }
    asm volatile("setmaxnreg.inc.sync.aligned.u32 224;");
    auto my_turn = [&]() {
      asm volatile("{\n.reg .pred p;\nsetp.ne.u32 p, %0, 0;\n@p bar.sync 3, 256;\n@!p bar.sync 2, 288;\n}\n" ::"r"(wg) : "memory");
    };
    auto your_turn = [&]() {
      asm volatile("{\n.reg .pred p;\nsetp.ne.u32 p, %0, 0;\n@p bar.arrive 2, 288;\n@!p bar.arrive 3, 256;\n}\n" ::"r"(wg) : "memory");
    };
    if (wg == 1) your_turn();
    uint32_t qf[8][4];
    {
      uint32_t h[32][4];
      float acc[64];
      const uint4* Gin = Gw + lane;
      asm volatile("barrier.cluster.wait.acquire.aligned;" ::: "memory");
      bar_sync(NB_GATHER, 384);
      if (G_DELAY) spin_cycles(G_DELAY);
#pragma unroll
      for (int c = 0; c < 3; c++) warp_bulk_load(wblk + c * SLOT, Gw + c * 256, 4096, wbar + c * 8);
#pragma unroll
      for (int c = 0; c < 4; c++) {
        mbar_wait(wbar + (c % 3) * 8, c / 3);
#pragma unroll
        for (int i = 0; i < 8; i++) lds128(wprv + (c % 3) * SLOT + i * 512, h[c * 8 + i]);
        verify8_tag1<512>(Gin + c * 256, h + c * 8);
        if (c == 0) {
          warp_bulk_load(wblk, Gw + 768, 4096, wbar);
          TS(1);
          bar_sync(NB_TAB, 384);
        }
#pragma unroll
        for (int i = 0; i < 8; i++) {
          uint32_t m[4];
          lds128(sb + SM_TAB + (uint32_t)((c * 8 + i) * 4 + q) * 16, m);
          uint32_t* hh = h[c * 8 + i];
          hh[0] = hfma2_bf16(hh[0], m[0], m[2]);
          hh[1] = hfma2_bf16(hh[1], m[0], m[2]);
          hh[2] = hfma2_bf16(hh[2], m[1], m[3]);
          hh[3] = hfma2_bf16(hh[3], m[1], m[3]);
        }
        fence_frags<8>(h + c * 8);
        const uint32_t b = ring.tile(c);
        if (c > 0) { wg_wait<0>(); ring.release(c - 1); }
        if (c == 0) TS(2);
        my_turn();
        wg_fence();
        static_for<0, 8>([&](auto K) { wgmma_rs_n128_tb1<LB_MN128 + K * 128, HI128>(acc, h[c * 8 + K], b, (c | K) != 0); });
        wg_commit();
        your_turn();
      }
      bar_arrive(NB_PASS0, 384);
#pragma unroll 1
      for (int ps = 1; ps < 4; ps++) {
        wg_wait<0>();
        ring.release(3);
        fence_regs(acc);
#pragma unroll
        for (int i = 0; i < 8; i++) {
          uint32_t o[4];
          pack8(o, acc + 8 * i);
          sts128(wprv + (ps - 1) * SLOT + i * 512, o[0], o[1], o[2], o[3]);
        }
#pragma unroll
        for (int c = 0; c < 4; c += 2) {
          const uint32_t b = ring.tile(c);
          if (c > 0) { wg_wait<0>(); ring.release(c - 1); }
          my_turn();
          wg_fence();
          static_for<0, 8>([&](auto K) { wgmma_rs_n128_tb1<LB_MN128 + K * 128, HI128>(acc, h[c * 8 + K], b, (c | K) != 0); });
          wg_commit();
          static_for<0, 8>([&](auto K) { wgmma_rs_n128_tb1<LB_MN128 + 2048 + K * 128, HI128>(acc, h[c * 8 + 8 + K], b, 1); });
          wg_commit();
          your_turn();
          wg_wait<1>();
          ring.release(c);
        }
      }
      wg_wait<0>();
      ring.release(3);
      fence_regs(acc);
#pragma unroll
      for (int i = 0; i < 8; i++) pack8(qf[i], acc + 8 * i);
    }
    fence_regs(qf);
    TS(3);

    uint32_t o[24][4];
    {
      float S[64], O[64];
      uint32_t P[8][4];
      const float cs = 0.08838834764831845f * 1.4426950408889634f;
      const float TAU = 16.f;
      float m0, m1, l0, l1;

      auto float_block_max = [&]() {
        float b0 = fmaxf(S[0], S[1]), b1 = fmaxf(S[2], S[3]);
#pragma unroll
        for (int i = 1; i < 16; i++) {
          b0 = fmaxf(b0, fmaxf(S[4 * i], S[4 * i + 1]));
          b1 = fmaxf(b1, fmaxf(S[4 * i + 2], S[4 * i + 3]));
        }
        b0 = fmaxf(b0, __shfl_xor_sync(0xffffffffu, b0, 1)); b1 = fmaxf(b1, __shfl_xor_sync(0xffffffffu, b1, 1));
        b0 = fmaxf(b0, __shfl_xor_sync(0xffffffffu, b0, 2)); b1 = fmaxf(b1, __shfl_xor_sync(0xffffffffu, b1, 2));
        m0 = b0 * cs; m1 = b1 * cs;
      };
      auto first_block_max = [&]() {
        int a0 = max(__float_as_int(S[0]), __float_as_int(S[1]));
        int a1 = max(__float_as_int(S[2]), __float_as_int(S[3]));
#pragma unroll
        for (int i = 1; i < 16; i++) {
          a0 = __vimax3_s32(a0, __float_as_int(S[4 * i]), __float_as_int(S[4 * i + 1]));
          a1 = __vimax3_s32(a1, __float_as_int(S[4 * i + 2]), __float_as_int(S[4 * i + 3]));
        }
        a0 = max(a0, __shfl_xor_sync(0xffffffffu, a0, 1)); a1 = max(a1, __shfl_xor_sync(0xffffffffu, a1, 1));
        a0 = max(a0, __shfl_xor_sync(0xffffffffu, a0, 2)); a1 = max(a1, __shfl_xor_sync(0xffffffffu, a1, 2));
        m0 = __int_as_float(a0) * cs; m1 = __int_as_float(a1) * cs;
        if (__any_sync(0xffffffffu, (a0 | a1) < 0)) float_block_max();
      };
      auto exps = [&](int i0, int i1) {
#pragma unroll
        for (int i = i0; i < i1; i++) {
          S[4 * i] = ex2(fmaf(S[4 * i], cs, -m0)); S[4 * i + 1] = ex2(fmaf(S[4 * i + 1], cs, -m0));
          S[4 * i + 2] = ex2(fmaf(S[4 * i + 2], cs, -m1)); S[4 * i + 3] = ex2(fmaf(S[4 * i + 3], cs, -m1));
          l0 += S[4 * i]; l1 += S[4 * i + 2]; l0 += S[4 * i + 1]; l1 += S[4 * i + 3];
        }
      };
      auto softmax8 = [&](int i) {
        exps(2 * i, 2 * i + 2);
        pack8(P[i], S + 8 * i);
      };
      {
        const uint32_t b = ring.tile(0);
        my_turn();
        wg_fence();
        static_for<0, 8>([&](auto K) { wgmma_rs_n128_tb0<LB_K128 + (K >> 2) * 1024 + (K & 3) * 2, HI128>(S, qf[K], b, K != 0); });
        wg_commit();
        your_turn();
        wg_wait<0>();
        fence_regs(S);
        ring.release(0);
        float_block_max();
        l0 = 0.f; l1 = 0.f;
        exps(0, 16);
#pragma unroll
        for (int i = 0; i < 8; i++) pack8(P[i], S + 8 * i);
      }
      fence_regs(P);
#pragma unroll 1
      for (int n = 1; n < 16; n++) {
        const uint32_t tk = 2 * n - 1, tv = 2 * n;
        const bool newhead = (n & 3) == 0;
        const uint32_t bk = ring.tile(tk & 3);
        const uint32_t bv = ring.tile(tv & 3);
        my_turn();
        wg_fence();
        static_for<0, 8>([&](auto K) { wgmma_rs_n128_tb0<LB_K128 + (K >> 2) * 1024 + (K & 3) * 2, HI128>(S, qf[K], bk, K != 0); });
        wg_commit();
        static_for<0, 8>([&](auto K) { wgmma_rs_n128_tb1<LB_MN128 + K * 128, HI128>(O, P[K], bv, K != 0 || (n & 3) != 1); });
        wg_commit();
        your_turn();
        wg_wait<1>();
        fence_regs(S);
        ring.release(tk & 3);
        if ((n & 3) == 3 && n != 15) {
          fence_regs(qf);
#pragma unroll
          for (int i = 0; i < 8; i++) lds128(wprv + (n >> 2) * SLOT + i * 512, qf[i]);
        }
        if (newhead) {
          l0 += __shfl_xor_sync(0xffffffffu, l0, 1); l1 += __shfl_xor_sync(0xffffffffu, l1, 1);
          l0 += __shfl_xor_sync(0xffffffffu, l0, 2); l1 += __shfl_xor_sync(0xffffffffu, l1, 2);
          const float f0 = rcp_hw(l0), f1 = rcp_hw(l1);
          l0 = 0.f; l1 = 0.f;
          first_block_max();
          wg_wait<0>();
          fence_regs(O);
          fence_regs(P);
          ring.release(tv & 3);
#pragma unroll
          for (int i = 0; i < 8; i++) {
            softmax8(i);
            sts128(wprv + ((n >> 2) - 1) * SLOT + i * 512, pack_bf16(O[8 * i] * f0, O[8 * i + 1] * f0),
                   pack_bf16(O[8 * i + 2] * f1, O[8 * i + 3] * f1), pack_bf16(O[8 * i + 4] * f0, O[8 * i + 5] * f0),
                   pack_bf16(O[8 * i + 6] * f1, O[8 * i + 7] * f1));
          }
        } else {
          int a0 = max(__float_as_int(S[0]), __float_as_int(S[1]));
          int a1 = max(__float_as_int(S[2]), __float_as_int(S[3]));
#pragma unroll
          for (int i = 1; i < 16; i++) {
            a0 = __vimax3_s32(a0, __float_as_int(S[4 * i]), __float_as_int(S[4 * i + 1]));
            a1 = __vimax3_s32(a1, __float_as_int(S[4 * i + 2]), __float_as_int(S[4 * i + 3]));
          }
          const bool unsafe = fmaf(__int_as_float(max(a0, 0)), cs, -m0) > TAU || fmaf(__int_as_float(max(a1, 0)), cs, -m1) > TAU;
          if (__any_sync(0xffffffffu, unsafe)) {
            const float p0 = m0, p1 = m1;
            float_block_max();
            m0 = fmaxf(m0, p0); m1 = fmaxf(m1, p1);
            const float f0 = ex2(p0 - m0), f1 = ex2(p1 - m1);
            l0 *= f0; l1 *= f1;
            wg_wait<0>();
            fence_regs(O);
#pragma unroll
            for (int i = 0; i < 16; i++) {
              O[4 * i] *= f0; O[4 * i + 1] *= f0; O[4 * i + 2] *= f1; O[4 * i + 3] *= f1;
            }
          }
          exps(0, PRE_EXP);
          if (p.zero) exps(0, 1);
          wg_wait<0>();
          fence_regs(O);
          fence_regs(P);
          ring.release(tv & 3);
          exps(PRE_EXP, 16);
#pragma unroll
          for (int i = 0; i < 8; i++) pack8(P[i], S + 8 * i);
        }
        fence_regs(P);
        fence_regs(O);
      }
      {
        const uint32_t bv = ring.tile(3);
        my_turn();
        wg_fence();
        static_for<0, 8>([&](auto K) { wgmma_rs_n128_tb1<LB_MN128 + K * 128, HI128>(O, P[K], bv, 1); });
        wg_commit();
        your_turn();
#pragma unroll
        for (int i = 0; i < 16; i++) lds128(wprv + (i >> 3) * SLOT + (i & 7) * 512, o[i]);
        l0 += __shfl_xor_sync(0xffffffffu, l0, 1); l1 += __shfl_xor_sync(0xffffffffu, l1, 1);
        l0 += __shfl_xor_sync(0xffffffffu, l0, 2); l1 += __shfl_xor_sync(0xffffffffu, l1, 2);
        const float f0 = rcp_hw(l0), f1 = rcp_hw(l1);
        wg_wait<0>();
        fence_regs(O);
        ring.release(3);
#pragma unroll
        for (int i = 0; i < 8; i++) {
          qf[i][0] = pack_bf16(O[8 * i] * f0, O[8 * i + 1] * f0); qf[i][1] = pack_bf16(O[8 * i + 2] * f1, O[8 * i + 3] * f1);
          qf[i][2] = pack_bf16(O[8 * i + 4] * f0, O[8 * i + 5] * f0); qf[i][3] = pack_bf16(O[8 * i + 6] * f1, O[8 * i + 7] * f1);
        }
      }
    }
    fence_regs(qf);
    TS(4);
    asm volatile("setmaxnreg.dec.sync.aligned.u32 216;");
    bar_arrive(NB_PARK, 384);

    uint4* const Pout = p.s->P + ((size_t)(rt * 8 + warp) * 4 + (j >> 1)) * 1024 + (j & 1) * 128 + lane;
    const uint32_t tag = *(volatile uint32_t*)(smem_raw + SM_BAR + BAR_TAG);
    const uint32_t rbar = sb + SM_DBAR + warp * 16;
    uint32_t peer_land, peer_bar;
    asm("mapa.shared::cluster.u32 %0, %1, %2;" : "=r"(peer_land) : "r"(wprv), "r"(~j & 1));
    asm("mapa.shared::cluster.u32 %0, %1, %2;" : "=r"(peer_bar) : "r"(rbar), "r"(~j & 1));
    auto arm_and_ack = [&](uint32_t dep) {
      asm volatile(
          "{\n.reg .pred p;\nelect.sync _|p, 0xffffffff;\n"
          "@p mbarrier.arrive.expect_tx.shared::cta.b64 _, [%0], 2048;\n"
          "@p mbarrier.arrive.shared::cluster.b64 _, [%1];\n}\n" ::"r"(rbar), "r"(peer_bar + 8 + (dep & p.zero)) : "memory");
    };
    auto send_chunk = [&](float (&acc)[32], int pair) {
      mbar_wait(rbar + 8, pair & 1);
#pragma unroll
      for (int i = 0; i < 4; i++)
        asm volatile("st.async.weak.shared::cluster.mbarrier::complete_tx::bytes.v4.b32 [%0], {%1,%2,%3,%4}, [%5];"
                     ::"r"(peer_land + i * 512), "r"(pack_trunc(acc[8 * i], acc[8 * i + 1])), "r"(pack_trunc(acc[8 * i + 2], acc[8 * i + 3])),
                       "r"(pack_trunc(acc[8 * i + 4], acc[8 * i + 5])), "r"(pack_trunc(acc[8 * i + 6], acc[8 * i + 7])), "r"(peer_bar)
                     : "memory");
    };
    uint32_t pk[4][4];
    auto recv_chunk = [&](int pair) {
      mbar_wait(rbar, pair & 1);
#pragma unroll
      for (int i = 0; i < 4; i++) lds128(wprv + i * 512, pk[i]);
      if (pair < 7) arm_and_ack(pk[3][0]);
    };
    auto keep_chunk = [&](float (&acc)[32], int pair) {
      const uint32_t t1 = pair < 4;
#pragma unroll
      for (int i = 0; i < 4; i++) {
#pragma unroll
        for (int e = 0; e < 4; e++)
          pk[i][e] = pack_trunc(acc[8 * i + 2 * e] + __uint_as_float(pk[i][e] * 65536u + 0x8000u),
                                acc[8 * i + 2 * e + 1] + __uint_as_float(pk[i][e]));
        st_pkt(Pout + (pair & 3) * 256 + i * 32, (pk[i][0] & ~1u) | t1, pk[i][1], pk[i][2], pk[i][3]);
      }
      if (lane == 0)
        asm volatile("st.relaxed.gpu.global.u32 [%0], %1;" ::"l"(&p.s->sent[(rt * 8 + warp) * 8 + j]), "r"(tag * 32 + pair + 1) : "memory");
    };
    const uint4* const Gin = Gw + lane;
    auto g_issue = [&](int u) { warp_bulk_load(wblk + 2 * SLOT, Gw + u * 256, 4096, wbar); };

#pragma unroll
    for (int i = 16; i < 24; i++) lds128(wprv + 2 * SLOT + (i & 7) * 512, o[i]);
    fence_regs(o);
    arm_and_ack(o[23][0]);
    warp_arrive(sb + SM_SBAR);
#pragma unroll 1
    for (int cc = 0; cc < 8; cc++) {
      float acc[32];
      const uint32_t s0 = (cc & 1) * 2, b = ring.tile(s0);
      my_turn();
      wg_fence();
      static_for<0, 16>([&](auto K) { wgmma_rs_n64_tb1<K * 128, HI128>(acc, o[K], b, K != 0); });
      wg_commit();
      static_for<0, 16>([&](auto K) { wgmma_rs_n64_tb1<2048 + K * 128, HI128>(acc, K < 8 ? o[16 + (K & 7)] : qf[K & 7], b, 1); });
      wg_commit();
      your_turn();
      wg_wait<1>();
      ring.release(s0);
      if (cc & 1) recv_chunk(cc >> 1);
      wg_wait<0>();
      TRU(4);
      ring.release(s0 + 1);
      fence_regs(acc);
      if (cc & 1) keep_chunk(acc, cc >> 1);
      else send_chunk(acc, cc >> 1);
      if (cc == 6) g_issue(0);
    }
    TS(5);

    uint32_t H[14][4];
    {
      float acca[96], accb[16];
      const uint4* const statp = &p.s->stat[(rt * 8 + warp) * 8];
#pragma unroll 1
      for (int u = 0; u < 4; u++) {
        uint32_t fa[8][4];
        const uint32_t s0 = (u & 1) * 2, b = ring.tile(s0);
        mbar_wait(wbar, u & 1);
#pragma unroll
        for (int i = 0; i < 8; i++) lds128(wprv + 2 * SLOT + i * 512, fa[i]);
        verify8_tag0<512>(Gin + u * 256, fa);
        if (u < 2) g_issue(u + 1);
        const uint32_t ba = b + (j & 1) * 512, bb = b + ((j & 1) ? 4 : 1536);
        my_turn();
        wg_fence();
        static_for<0, 4>([&](auto K) { wgmma_rs_n32_tb1<LB_W1 + K * 128, HI128>(accb, fa[K], bb, (u | K) != 0); });
        static_for<0, 4>([&](auto K) { wgmma_rs_n192_tb1<LB_W1 + K * 128, HI128>(acca, fa[K], ba, (u | K) != 0); });
        wg_commit();
        static_for<0, 4>([&](auto K) { wgmma_rs_n32_tb1<LB_W1 + 2048 + K * 128, HI128>(accb, fa[4 + K], bb, 1); });
        static_for<0, 4>([&](auto K) { wgmma_rs_n192_tb1<LB_W1 + 2048 + K * 128, HI128>(acca, fa[4 + K], ba, 1); });
        wg_commit();
        your_turn();
        wg_wait<1>();
        ring.release(s0);
        if (u == 2) g_issue(3);
        if (u == 3) warp_bulk_load(wblk + 2 * SLOT, statp, 128, wbar + 16);
        wg_wait<0>();
        TRU(4);
        ring.release(s0 + 1);
      }
      fence_regs(acca);
      fence_regs(accb);
      TS(9);
      mbar_wait(bars + BAR_UV, 0);
      uint32_t xr[4];
      mbar_wait(wbar + 16, 1);
      lds128(wblk + 2 * SLOT + gq * 16, xr);
      {
        int spins = 0;
        while (((xr[0] ^ tag) & 1u) && ++spins < SPIN_LIMIT) ld_pkt(statp + gq, xr);
      }
      const float ra0 = __uint_as_float(xr[0]), rb0 = __uint_as_float(xr[1]), ra1 = __uint_as_float(xr[2]),
                  rb1 = __uint_as_float(xr[3]);
#pragma unroll
      for (int i = 0; i < 28; i++) {
        uint32_t m[4];
        lds128(sb + SM_TAB + (i * 4 + q) * 16, m);
        const float u0 = __uint_as_float(m[0]), u1 = __uint_as_float(m[1]), w0 = __uint_as_float(m[2]), w1 = __uint_as_float(m[3]);
        const float* acc = i < 24 ? acca + 4 * i : accb + 4 * (i - 24);
        const float z0 = fmaf(acc[0], ra0, fmaf(u0, rb0, w0)), z1 = fmaf(acc[1], ra0, fmaf(u1, rb0, w1));
        const float z2 = fmaf(acc[2], ra1, fmaf(u0, rb1, w0)), z3 = fmaf(acc[3], ra1, fmaf(u1, rb1, w1));
        H[i >> 1][(i & 1) * 2] = pack_bf16(fmaf(z0, tanh_hw(z0), z0), fmaf(z1, tanh_hw(z1), z1));
        H[i >> 1][(i & 1) * 2 + 1] = pack_bf16(fmaf(z2, tanh_hw(z2), z2), fmaf(z3, tanh_hw(z3), z3));
      }
    }
    fence_regs(H);
    TS(10);
    const int go = 24 + warp;
    {
      float accs[32], acck[32];
      auto ffn2 = [&](float (&acc)[32], uint32_t b) {
        const uint32_t ba = b + (j & 1) * 256, bb = b - (j & 1) * 1536;
        static_for<0, 14>([&](auto K) { wgmma_rs_n64_tb1<K * 128, HI128>(acc, H[K], K < 12 ? ba : bb, K != 0); });
        wg_commit();
      };
      {
        const uint32_t b = ring.tile(0);
        my_turn();
        wg_fence();
        ffn2(accs, b);
        your_turn();
        wg_wait<0>();
        TRU(4);
        ring.release(0);
        fence_regs(accs);
        send_chunk(accs, 4);
      }
#pragma unroll 1
      for (int pc = 0; pc < 3; pc++) {
        const uint32_t tk = 2 * pc + 1, ts = tk + 1;
        const uint32_t bk = ring.tile(tk & 3), bs = ring.tile(ts & 3);
        my_turn();
        wg_fence();
        ffn2(acck, bk);
        ffn2(accs, bs);
        your_turn();
        wg_wait<1>();
        ring.release(tk & 3);
        recv_chunk(4 + pc);
        fence_regs(acck);
        keep_chunk(acck, 4 + pc);
        wg_wait<0>();
        TRU(4);
        ring.release(ts & 3);
        fence_regs(accs);
        send_chunk(accs, 5 + pc);
      }
      const uint32_t b = ring.tile(3);
      my_turn();
      wg_fence();
      ffn2(acck, b);
      if (wg == 0) your_turn();
      recv_chunk(7);
      wg_wait<0>();
      fence_regs(acck);
      keep_chunk(acck, 7);
    }
    TS(11);
    {
      const uint4* const Pown = p.s->P + (size_t)(rt * 8 + j) * 4096 + go * 32 + lane;
      uint32_t r[4][4];
      float y[8];
      mbar_wait(bars + BAR_X2, 0);
      issue_pkts<0, 4>(Pown, 1024, r);
      verify4_rt<16384>(Pown, r, 0);
      TS(13);
#pragma unroll
      for (int s = 0; s < 4; s++) add_partial(y, r[s], 0x10000u, s == 0);
      const uint32_t gt = sb + SM_TAB + 1792 + ((go - 24) * 4 + q) * 8;
      store_out(p.out, (uint32_t)(rt * 128 + 16 * j + gq) * 256 + go * 8 + q, sb + SM_PARK + SLOT + (go >> 2) * 4096 + (go & 3) * 512 + lane * 16,
                lds32(gt), lds32(gt + 4), y);
    }
    TS(12);
    if (bid == 0 && tid == 0) asm volatile("st.relaxed.gpu.global.u32 [%0], %1;" ::"l"(&p.s->epoch), "r"(tag) : "memory");
  }
}

typedef CUresult (*EncodeFn)(CUtensorMap*, CUtensorMapDataType, cuuint32_t, void*, const cuuint64_t*, const cuuint64_t*,
                             const cuuint32_t*, const cuuint32_t*, CUtensorMapInterleave, CUtensorMapSwizzle,
                             CUtensorMapL2promotion, CUtensorMapFloatOOBfill);

static void make_map(EncodeFn fn, CUtensorMap* tm, const void* ptr, int inner, int rows, int cols, int box_rows, int box_outer,
                     CUtensorMapSwizzle swz) {
  cuuint64_t gd[3] = {(cuuint64_t)inner, (cuuint64_t)rows, (cuuint64_t)(cols / inner)};
  cuuint64_t gs[2] = {(cuuint64_t)cols * 2, (cuuint64_t)inner * 2};
  cuuint32_t bx[3] = {(cuuint32_t)inner, (cuuint32_t)box_rows, (cuuint32_t)box_outer};
  cuuint32_t es[3] = {1, 1, 1};
  fn(tm, CU_TENSOR_MAP_DATA_TYPE_BFLOAT16, 3, const_cast<void*>(ptr), gd, gs, bx, es, CU_TENSOR_MAP_INTERLEAVE_NONE, swz,
     CU_TENSOR_MAP_L2_PROMOTION_L2_128B, CU_TENSOR_MAP_FLOAT_OOB_FILL_NONE);
}

extern "C" void kernel_launch(void* const* d_in, const int* in_sizes, int n_in, void* d_out, int out_size) {
  (void)in_sizes; (void)n_in; (void)out_size;
  void* fnp = nullptr;
  cudaDriverEntryPointQueryResult qr;
  cudaGetDriverEntryPoint("cuTensorMapEncodeTiled", &fnp, cudaEnableDefault, &qr);
  EncodeFn fn = (EncodeFn)fnp;
  CUtensorMap tmWq, tmK, tmV, tmWo, tmW1, tmW2, tmWm, tmX;
  make_map(fn, &tmWq, d_in[3], 64, 512, 4096, 128, 2, CU_TENSOR_MAP_SWIZZLE_128B);
  make_map(fn, &tmK, d_in[1], 64, 8 * SK, 128, 128, 2, CU_TENSOR_MAP_SWIZZLE_128B);
  make_map(fn, &tmV, d_in[2], 64, 8 * SK, 128, 128, 2, CU_TENSOR_MAP_SWIZZLE_128B);
  make_map(fn, &tmWo, d_in[4], 64, 4096, 512, 256, 1, CU_TENSOR_MAP_SWIZZLE_128B);
  make_map(fn, &tmW1, d_in[6], 64, 512, FF, 64, 4, CU_TENSOR_MAP_SWIZZLE_128B);
  make_map(fn, &tmW2, d_in[7], 64, FF, 512, 224, 1, CU_TENSOR_MAP_SWIZZLE_128B);
  make_map(fn, &tmWm, d_in[9], 8, 512, 3072, 256, 1, CU_TENSOR_MAP_SWIZZLE_NONE);
  make_map(fn, &tmX, d_in[0], 16, 2048, 512, 16, 4, CU_TENSOR_MAP_SWIZZLE_NONE);
  Params p;
  p.x = (const __nv_bfloat16*)d_in[0];
  p.c = (const __nv_bfloat16*)d_in[8];
  p.wmod = (const __nv_bfloat16*)d_in[9];
  p.wo = (const __nv_bfloat16*)d_in[4];
  p.w1 = (const __nv_bfloat16*)d_in[6];
  p.w2 = (const __nv_bfloat16*)d_in[7];
  p.out = (__nv_bfloat16*)d_out;
  p.zero = 0;
  cudaGetSymbolAddress((void**)&p.s, g_scratch);
  cudaFuncSetAttribute(adaln_block_kernel, cudaFuncAttributeMaxDynamicSharedMemorySize, SM_TOTAL);
  cudaLaunchConfig_t cfg = {};
  cfg.gridDim = 128; cfg.blockDim = 512; cfg.dynamicSmemBytes = SM_TOTAL; cfg.stream = cudaStreamPerThread;
  cudaLaunchAttribute at[1];
  at[0].id = cudaLaunchAttributeClusterDimension; at[0].val.clusterDim.x = 2; at[0].val.clusterDim.y = 1; at[0].val.clusterDim.z = 1;
  cfg.attrs = at; cfg.numAttrs = 1;
  cudaLaunchKernelEx(&cfg, adaln_block_kernel, tmWq, tmK, tmV, tmWo, tmW1, tmW2, tmWm, tmX, p);
}
```

```cpp
#include <cuda_runtime.h>
#include <cuda_bf16.h>
#include <cuda.h>
#include <stdint.h>

template <int OFF, uint32_t HI>
__device__ __forceinline__ void wgmma_rs_n128_tb0(float (&d)[64], const uint32_t (&a)[4], uint32_t lo, int sd) {
  asm volatile("{\n.reg .pred p;\n.reg .b32 l;\n.reg .b64 db;\nsetp.ne.b32 p, %69, 0;\n"
    "add.u32 l, %68, %70;\nmov.b64 db, {l, %71};\n"
    "wgmma.mma_async.sync.aligned.m64n128k16.f32.bf16.bf16 "
    "{%0,%1,%2,%3,%4,%5,%6,%7,%8,%9,%10,%11,%12,%13,%14,%15,"
    "%16,%17,%18,%19,%20,%21,%22,%23,%24,%25,%26,%27,%28,%29,%30,%31,"
    "%32,%33,%34,%35,%36,%37,%38,%39,%40,%41,%42,%43,%44,%45,%46,%47,"
    "%48,%49,%50,%51,%52,%53,%54,%55,%56,%57,%58,%59,%60,%61,%62,%63}, "
    "{%64,%65,%66,%67}, db, p, 1, 1, 0;\n}\n"
    : "+f"(d[0]), "+f"(d[1]), "+f"(d[2]), "+f"(d[3]), "+f"(d[4]), "+f"(d[5]), "+f"(d[6]), "+f"(d[7]),
      "+f"(d[8]), "+f"(d[9]), "+f"(d[10]), "+f"(d[11]), "+f"(d[12]), "+f"(d[13]), "+f"(d[14]), "+f"(d[15]),
      "+f"(d[16]), "+f"(d[17]), "+f"(d[18]), "+f"(d[19]), "+f"(d[20]), "+f"(d[21]), "+f"(d[22]), "+f"(d[23]),
      "+f"(d[24]), "+f"(d[25]), "+f"(d[26]), "+f"(d[27]), "+f"(d[28]), "+f"(d[29]), "+f"(d[30]), "+f"(d[31]),
      "+f"(d[32]), "+f"(d[33]), "+f"(d[34]), "+f"(d[35]), "+f"(d[36]), "+f"(d[37]), "+f"(d[38]), "+f"(d[39]),
      "+f"(d[40]), "+f"(d[41]), "+f"(d[42]), "+f"(d[43]), "+f"(d[44]), "+f"(d[45]), "+f"(d[46]), "+f"(d[47]),
      "+f"(d[48]), "+f"(d[49]), "+f"(d[50]), "+f"(d[51]), "+f"(d[52]), "+f"(d[53]), "+f"(d[54]), "+f"(d[55]),
      "+f"(d[56]), "+f"(d[57]), "+f"(d[58]), "+f"(d[59]), "+f"(d[60]), "+f"(d[61]), "+f"(d[62]), "+f"(d[63])
    : "r"(a[0]), "r"(a[1]), "r"(a[2]), "r"(a[3]), "r"(lo), "r"(sd), "n"(OFF), "n"(HI));
}

template <int OFF, uint32_t HI>
__device__ __forceinline__ void wgmma_rs_n128_tb1(float (&d)[64], const uint32_t (&a)[4], uint32_t lo, int sd) {
  asm volatile("{\n.reg .pred p;\n.reg .b32 l;\n.reg .b64 db;\nsetp.ne.b32 p, %69, 0;\n"
    "add.u32 l, %68, %70;\nmov.b64 db, {l, %71};\n"
    "wgmma.mma_async.sync.aligned.m64n128k16.f32.bf16.bf16 "
    "{%0,%1,%2,%3,%4,%5,%6,%7,%8,%9,%10,%11,%12,%13,%14,%15,"
    "%16,%17,%18,%19,%20,%21,%22,%23,%24,%25,%26,%27,%28,%29,%30,%31,"
    "%32,%33,%34,%35,%36,%37,%38,%39,%40,%41,%42,%43,%44,%45,%46,%47,"
    "%48,%49,%50,%51,%52,%53,%54,%55,%56,%57,%58,%59,%60,%61,%62,%63}, "
    "{%64,%65,%66,%67}, db, p, 1, 1, 1;\n}\n"
    : "+f"(d[0]), "+f"(d[1]), "+f"(d[2]), "+f"(d[3]), "+f"(d[4]), "+f"(d[5]), "+f"(d[6]), "+f"(d[7]),
      "+f"(d[8]), "+f"(d[9]), "+f"(d[10]), "+f"(d[11]), "+f"(d[12]), "+f"(d[13]), "+f"(d[14]), "+f"(d[15]),
      "+f"(d[16]), "+f"(d[17]), "+f"(d[18]), "+f"(d[19]), "+f"(d[20]), "+f"(d[21]), "+f"(d[22]), "+f"(d[23]),
      "+f"(d[24]), "+f"(d[25]), "+f"(d[26]), "+f"(d[27]), "+f"(d[28]), "+f"(d[29]), "+f"(d[30]), "+f"(d[31]),
      "+f"(d[32]), "+f"(d[33]), "+f"(d[34]), "+f"(d[35]), "+f"(d[36]), "+f"(d[37]), "+f"(d[38]), "+f"(d[39]),
      "+f"(d[40]), "+f"(d[41]), "+f"(d[42]), "+f"(d[43]), "+f"(d[44]), "+f"(d[45]), "+f"(d[46]), "+f"(d[47]),
      "+f"(d[48]), "+f"(d[49]), "+f"(d[50]), "+f"(d[51]), "+f"(d[52]), "+f"(d[53]), "+f"(d[54]), "+f"(d[55]),
      "+f"(d[56]), "+f"(d[57]), "+f"(d[58]), "+f"(d[59]), "+f"(d[60]), "+f"(d[61]), "+f"(d[62]), "+f"(d[63])
    : "r"(a[0]), "r"(a[1]), "r"(a[2]), "r"(a[3]), "r"(lo), "r"(sd), "n"(OFF), "n"(HI));
}

template <int OFF, uint32_t HI>
__device__ __forceinline__ void wgmma_rs_n192_tb1(float (&d)[96], const uint32_t (&a)[4], uint32_t lo, int sd) {
  asm volatile("{\n.reg .pred p;\n.reg .b32 l;\n.reg .b64 db;\nsetp.ne.b32 p, %101, 0;\n"
    "add.u32 l, %100, %102;\nmov.b64 db, {l, %103};\n"
    "wgmma.mma_async.sync.aligned.m64n192k16.f32.bf16.bf16 "
    "{%0,%1,%2,%3,%4,%5,%6,%7,%8,%9,%10,%11,%12,%13,%14,%15,"
    "%16,%17,%18,%19,%20,%21,%22,%23,%24,%25,%26,%27,%28,%29,%30,%31,"
    "%32,%33,%34,%35,%36,%37,%38,%39,%40,%41,%42,%43,%44,%45,%46,%47,"
    "%48,%49,%50,%51,%52,%53,%54,%55,%56,%57,%58,%59,%60,%61,%62,%63,"
    "%64,%65,%66,%67,%68,%69,%70,%71,%72,%73,%74,%75,%76,%77,%78,%79,"
    "%80,%81,%82,%83,%84,%85,%86,%87,%88,%89,%90,%91,%92,%93,%94,%95}, "
    "{%96,%97,%98,%99}, db, p, 1, 1, 1;\n}\n"
    : "+f"(d[0]), "+f"(d[1]), "+f"(d[2]), "+f"(d[3]), "+f"(d[4]), "+f"(d[5]), "+f"(d[6]), "+f"(d[7]),
      "+f"(d[8]), "+f"(d[9]), "+f"(d[10]), "+f"(d[11]), "+f"(d[12]), "+f"(d[13]), "+f"(d[14]), "+f"(d[15]),
      "+f"(d[16]), "+f"(d[17]), "+f"(d[18]), "+f"(d[19]), "+f"(d[20]), "+f"(d[21]), "+f"(d[22]), "+f"(d[23]),
      "+f"(d[24]), "+f"(d[25]), "+f"(d[26]), "+f"(d[27]), "+f"(d[28]), "+f"(d[29]), "+f"(d[30]), "+f"(d[31]),
      "+f"(d[32]), "+f"(d[33]), "+f"(d[34]), "+f"(d[35]), "+f"(d[36]), "+f"(d[37]), "+f"(d[38]), "+f"(d[39]),
      "+f"(d[40]), "+f"(d[41]), "+f"(d[42]), "+f"(d[43]), "+f"(d[44]), "+f"(d[45]), "+f"(d[46]), "+f"(d[47]),
      "+f"(d[48]), "+f"(d[49]), "+f"(d[50]), "+f"(d[51]), "+f"(d[52]), "+f"(d[53]), "+f"(d[54]), "+f"(d[55]),
      "+f"(d[56]), "+f"(d[57]), "+f"(d[58]), "+f"(d[59]), "+f"(d[60]), "+f"(d[61]), "+f"(d[62]), "+f"(d[63]),
      "+f"(d[64]), "+f"(d[65]), "+f"(d[66]), "+f"(d[67]), "+f"(d[68]), "+f"(d[69]), "+f"(d[70]), "+f"(d[71]),
      "+f"(d[72]), "+f"(d[73]), "+f"(d[74]), "+f"(d[75]), "+f"(d[76]), "+f"(d[77]), "+f"(d[78]), "+f"(d[79]),
      "+f"(d[80]), "+f"(d[81]), "+f"(d[82]), "+f"(d[83]), "+f"(d[84]), "+f"(d[85]), "+f"(d[86]), "+f"(d[87]),
      "+f"(d[88]), "+f"(d[89]), "+f"(d[90]), "+f"(d[91]), "+f"(d[92]), "+f"(d[93]), "+f"(d[94]), "+f"(d[95])
    : "r"(a[0]), "r"(a[1]), "r"(a[2]), "r"(a[3]), "r"(lo), "r"(sd), "n"(OFF), "n"(HI));
}

template <int OFF, uint32_t HI>
__device__ __forceinline__ void wgmma_rs_n32_tb1(float (&d)[16], const uint32_t (&a)[4], uint32_t lo, int sd) {
  asm volatile("{\n.reg .pred p;\n.reg .b32 l;\n.reg .b64 db;\nsetp.ne.b32 p, %21, 0;\n"
    "add.u32 l, %20, %22;\nmov.b64 db, {l, %23};\n"
    "wgmma.mma_async.sync.aligned.m64n32k16.f32.bf16.bf16 "
    "{%0,%1,%2,%3,%4,%5,%6,%7,%8,%9,%10,%11,%12,%13,%14,%15}, "
    "{%16,%17,%18,%19}, db, p, 1, 1, 1;\n}\n"
    : "+f"(d[0]), "+f"(d[1]), "+f"(d[2]), "+f"(d[3]), "+f"(d[4]), "+f"(d[5]), "+f"(d[6]), "+f"(d[7]),
      "+f"(d[8]), "+f"(d[9]), "+f"(d[10]), "+f"(d[11]), "+f"(d[12]), "+f"(d[13]), "+f"(d[14]), "+f"(d[15])
    : "r"(a[0]), "r"(a[1]), "r"(a[2]), "r"(a[3]), "r"(lo), "r"(sd), "n"(OFF), "n"(HI));
}

template <int OFF, uint32_t HI>
__device__ __forceinline__ void wgmma_rs_n64_tb1(float (&d)[32], const uint32_t (&a)[4], uint32_t lo, int sd) {
  asm volatile("{\n.reg .pred p;\n.reg .b32 l;\n.reg .b64 db;\nsetp.ne.b32 p, %37, 0;\n"
    "add.u32 l, %36, %38;\nmov.b64 db, {l, %39};\n"
    "wgmma.mma_async.sync.aligned.m64n64k16.f32.bf16.bf16 "
    "{%0,%1,%2,%3,%4,%5,%6,%7,%8,%9,%10,%11,%12,%13,%14,%15,"
    "%16,%17,%18,%19,%20,%21,%22,%23,%24,%25,%26,%27,%28,%29,%30,%31}, "
    "{%32,%33,%34,%35}, db, p, 1, 1, 1;\n}\n"
    : "+f"(d[0]), "+f"(d[1]), "+f"(d[2]), "+f"(d[3]), "+f"(d[4]), "+f"(d[5]), "+f"(d[6]), "+f"(d[7]),
      "+f"(d[8]), "+f"(d[9]), "+f"(d[10]), "+f"(d[11]), "+f"(d[12]), "+f"(d[13]), "+f"(d[14]), "+f"(d[15]),
      "+f"(d[16]), "+f"(d[17]), "+f"(d[18]), "+f"(d[19]), "+f"(d[20]), "+f"(d[21]), "+f"(d[22]), "+f"(d[23]),
      "+f"(d[24]), "+f"(d[25]), "+f"(d[26]), "+f"(d[27]), "+f"(d[28]), "+f"(d[29]), "+f"(d[30]), "+f"(d[31])
    : "r"(a[0]), "r"(a[1]), "r"(a[2]), "r"(a[3]), "r"(lo), "r"(sd), "n"(OFF), "n"(HI));
}

template <int STR>
__device__ __forceinline__ void verify8_tag1(const uint4* p, uint32_t (*r)[4]) {
  asm volatile("{\n.reg .pred p, q;\n.reg .b32 a, n;\nmov.u32 n, 0;\n"
    "LAB_CHK:\n"
    "and.b32 a, %0, %4;\n"
    "and.b32 a, a, %8;\n"
    "and.b32 a, a, %12;\n"
    "and.b32 a, a, %16;\n"
    "and.b32 a, a, %20;\n"
    "and.b32 a, a, %24;\n"
    "and.b32 a, a, %28;\n"
    "and.b32 a, a, 1;\nsetp.eq.u32 p, a, 1;\nvote.sync.all.pred p, p, 0xffffffff;\n"
    "@p bra.uni LAB_OK;\n"
    "and.b32 a, %0, 1;\nsetp.ne.u32 q, a, 1;\n"
    "@q ld.relaxed.gpu.global.v4.b32 {%0,%1,%2,%3}, [%32+%33];\n"
    "and.b32 a, %4, 1;\nsetp.ne.u32 q, a, 1;\n"
    "@q ld.relaxed.gpu.global.v4.b32 {%4,%5,%6,%7}, [%32+%34];\n"
    "and.b32 a, %8, 1;\nsetp.ne.u32 q, a, 1;\n"
    "@q ld.relaxed.gpu.global.v4.b32 {%8,%9,%10,%11}, [%32+%35];\n"
    "and.b32 a, %12, 1;\nsetp.ne.u32 q, a, 1;\n"
    "@q ld.relaxed.gpu.global.v4.b32 {%12,%13,%14,%15}, [%32+%36];\n"
    "and.b32 a, %16, 1;\nsetp.ne.u32 q, a, 1;\n"
    "@q ld.relaxed.gpu.global.v4.b32 {%16,%17,%18,%19}, [%32+%37];\n"
    "and.b32 a, %20, 1;\nsetp.ne.u32 q, a, 1;\n"
    "@q ld.relaxed.gpu.global.v4.b32 {%20,%21,%22,%23}, [%32+%38];\n"
    "and.b32 a, %24, 1;\nsetp.ne.u32 q, a, 1;\n"
    "@q ld.relaxed.gpu.global.v4.b32 {%24,%25,%26,%27}, [%32+%39];\n"
    "and.b32 a, %28, 1;\nsetp.ne.u32 q, a, 1;\n"
    "@q ld.relaxed.gpu.global.v4.b32 {%28,%29,%30,%31}, [%32+%40];\n"
    "add.u32 n, n, 1;\nsetp.lt.u32 q, n, 262144;\n@q bra.uni LAB_CHK;\n"
    "LAB_OK:\n"
    "}\n"
    : "+r"(r[0][0]), "+r"(r[0][1]), "+r"(r[0][2]), "+r"(r[0][3]), "+r"(r[1][0]), "+r"(r[1][1]), "+r"(r[1][2]), "+r"(r[1][3]),
      "+r"(r[2][0]), "+r"(r[2][1]), "+r"(r[2][2]), "+r"(r[2][3]), "+r"(r[3][0]), "+r"(r[3][1]), "+r"(r[3][2]), "+r"(r[3][3]),
      "+r"(r[4][0]), "+r"(r[4][1]), "+r"(r[4][2]), "+r"(r[4][3]), "+r"(r[5][0]), "+r"(r[5][1]), "+r"(r[5][2]), "+r"(r[5][3]),
      "+r"(r[6][0]), "+r"(r[6][1]), "+r"(r[6][2]), "+r"(r[6][3]), "+r"(r[7][0]), "+r"(r[7][1]), "+r"(r[7][2]), "+r"(r[7][3])
    : "l"(p), "n"(0 * STR), "n"(1 * STR), "n"(2 * STR), "n"(3 * STR), "n"(4 * STR), "n"(5 * STR), "n"(6 * STR), "n"(7 * STR)
    : "memory");
}

template <int STR>
__device__ __forceinline__ void verify4_rt(const uint4* p, uint32_t (*r)[4], uint32_t tag) {
  asm volatile("{\n.reg .pred p, q;\n.reg .b32 a, b, n;\nmov.u32 n, 0;\n"
    "LAB_CHK:\n"
    "lop3.b32 a, %0, %4, %21, 0x7e;\n"
    "lop3.b32 b, %8, %12, %21, 0x7e;\nor.b32 a, a, b;\n"
    "and.b32 a, a, 1;\nsetp.eq.u32 p, a, 0;\nvote.sync.all.pred p, p, 0xffffffff;\n"
    "@p bra.uni LAB_OK;\n"
    "and.b32 a, %0, 1;\nsetp.ne.u32 q, a, %21;\n"
    "@q ld.relaxed.gpu.global.v4.b32 {%0,%1,%2,%3}, [%16+%17];\n"
    "and.b32 a, %4, 1;\nsetp.ne.u32 q, a, %21;\n"
    "@q ld.relaxed.gpu.global.v4.b32 {%4,%5,%6,%7}, [%16+%18];\n"
    "and.b32 a, %8, 1;\nsetp.ne.u32 q, a, %21;\n"
    "@q ld.relaxed.gpu.global.v4.b32 {%8,%9,%10,%11}, [%16+%19];\n"
    "and.b32 a, %12, 1;\nsetp.ne.u32 q, a, %21;\n"
    "@q ld.relaxed.gpu.global.v4.b32 {%12,%13,%14,%15}, [%16+%20];\n"
    "add.u32 n, n, 1;\nsetp.lt.u32 q, n, 262144;\n@q bra.uni LAB_CHK;\n"
    "LAB_OK:\n}\n"
    : "+r"(r[0][0]), "+r"(r[0][1]), "+r"(r[0][2]), "+r"(r[0][3]), "+r"(r[1][0]), "+r"(r[1][1]), "+r"(r[1][2]), "+r"(r[1][3]),
      "+r"(r[2][0]), "+r"(r[2][1]), "+r"(r[2][2]), "+r"(r[2][3]), "+r"(r[3][0]), "+r"(r[3][1]), "+r"(r[3][2]), "+r"(r[3][3])
    : "l"(p), "n"(0 * STR), "n"(1 * STR), "n"(2 * STR), "n"(3 * STR), "r"(tag)
    : "memory");
}

template <int STR>
__device__ __forceinline__ void verify8_tag0(const uint4* p, uint32_t (*r)[4]) {
  asm volatile("{\n.reg .pred p, q;\n.reg .b32 a, n;\nmov.u32 n, 0;\n"
    "LAB_CHK:\n"
    "or.b32 a, %0, %4;\n"
    "or.b32 a, a, %8;\n"
    "or.b32 a, a, %12;\n"
    "or.b32 a, a, %16;\n"
    "or.b32 a, a, %20;\n"
    "or.b32 a, a, %24;\n"
    "or.b32 a, a, %28;\n"
    "and.b32 a, a, 1;\nsetp.eq.u32 p, a, 0;\nvote.sync.all.pred p, p, 0xffffffff;\n"
    "@p bra.uni LAB_OK;\n"
    "and.b32 a, %0, 1;\nsetp.ne.u32 q, a, 0;\n"
    "@q ld.relaxed.gpu.global.v4.b32 {%0,%1,%2,%3}, [%32+%33];\n"
    "and.b32 a, %4, 1;\nsetp.ne.u32 q, a, 0;\n"
    "@q ld.relaxed.gpu.global.v4.b32 {%4,%5,%6,%7}, [%32+%34];\n"
    "and.b32 a, %8, 1;\nsetp.ne.u32 q, a, 0;\n"
    "@q ld.relaxed.gpu.global.v4.b32 {%8,%9,%10,%11}, [%32+%35];\n"
    "and.b32 a, %12, 1;\nsetp.ne.u32 q, a, 0;\n"
    "@q ld.relaxed.gpu.global.v4.b32 {%12,%13,%14,%15}, [%32+%36];\n"
    "and.b32 a, %16, 1;\nsetp.ne.u32 q, a, 0;\n"
    "@q ld.relaxed.gpu.global.v4.b32 {%16,%17,%18,%19}, [%32+%37];\n"
    "and.b32 a, %20, 1;\nsetp.ne.u32 q, a, 0;\n"
    "@q ld.relaxed.gpu.global.v4.b32 {%20,%21,%22,%23}, [%32+%38];\n"
    "and.b32 a, %24, 1;\nsetp.ne.u32 q, a, 0;\n"
    "@q ld.relaxed.gpu.global.v4.b32 {%24,%25,%26,%27}, [%32+%39];\n"
    "and.b32 a, %28, 1;\nsetp.ne.u32 q, a, 0;\n"
    "@q ld.relaxed.gpu.global.v4.b32 {%28,%29,%30,%31}, [%32+%40];\n"
    "add.u32 n, n, 1;\nsetp.lt.u32 q, n, 262144;\n@q bra.uni LAB_CHK;\n"
    "LAB_OK:\n"
    "or.b32 %0, %0, 1;\n"
    "or.b32 %4, %4, 1;\n"
    "or.b32 %8, %8, 1;\n"
    "or.b32 %12, %12, 1;\n"
    "or.b32 %16, %16, 1;\n"
    "or.b32 %20, %20, 1;\n"
    "or.b32 %24, %24, 1;\n"
    "or.b32 %28, %28, 1;\n"
    "}\n"
    : "+r"(r[0][0]), "+r"(r[0][1]), "+r"(r[0][2]), "+r"(r[0][3]), "+r"(r[1][0]), "+r"(r[1][1]), "+r"(r[1][2]), "+r"(r[1][3]),
      "+r"(r[2][0]), "+r"(r[2][1]), "+r"(r[2][2]), "+r"(r[2][3]), "+r"(r[3][0]), "+r"(r[3][1]), "+r"(r[3][2]), "+r"(r[3][3]),
      "+r"(r[4][0]), "+r"(r[4][1]), "+r"(r[4][2]), "+r"(r[4][3]), "+r"(r[5][0]), "+r"(r[5][1]), "+r"(r[5][2]), "+r"(r[5][3]),
      "+r"(r[6][0]), "+r"(r[6][1]), "+r"(r[6][2]), "+r"(r[6][3]), "+r"(r[7][0]), "+r"(r[7][1]), "+r"(r[7][2]), "+r"(r[7][3])
    : "l"(p), "n"(0 * STR), "n"(1 * STR), "n"(2 * STR), "n"(3 * STR), "n"(4 * STR), "n"(5 * STR), "n"(6 * STR), "n"(7 * STR)
    : "memory");
}

#define SPIN_LIMIT (1 << 18)

__device__ __forceinline__ uint32_t smem_u32(const void* p) { return (uint32_t)__cvta_generic_to_shared(p); }
__device__ __forceinline__ void mbar_init(uint32_t a, uint32_t c) {
  asm volatile("mbarrier.init.shared::cta.b64 [%0], %1;" ::"r"(a), "r"(c) : "memory");
}
__device__ __forceinline__ void mbar_expect(uint32_t a, uint32_t b) {
  asm volatile("mbarrier.arrive.expect_tx.shared::cta.b64 _, [%0], %1;" ::"r"(a), "r"(b) : "memory");
}
__device__ __forceinline__ void mbar_arrive(uint32_t a) {
  asm volatile("mbarrier.arrive.shared::cta.b64 _, [%0];" ::"r"(a) : "memory");
}
__device__ __forceinline__ void mbar_wait(uint32_t a, uint32_t parity) {
  asm volatile(
      "{\n.reg .pred p;\n.reg .u32 n;\nmov.u32 n, 0;\n"
      "LAB_WAIT:\n"
      "mbarrier.try_wait.parity.shared::cta.b64 p, [%0], %1;\n"
      "@p bra LAB_DONE;\n"
      "add.u32 n, n, 1;\n"
      "setp.lt.u32 p, n, 262144;\n"
      "@p bra LAB_WAIT;\n"
      "LAB_DONE:\n}\n" ::"r"(a), "r"(parity) : "memory");
}
__device__ __forceinline__ bool mbar_test(uint32_t a, uint32_t parity) {
  uint32_t ok;
  asm volatile("{\n.reg .pred p;\nmbarrier.test_wait.parity.shared::cta.b64 p, [%1], %2;\nselp.u32 %0, 1, 0, p;\n}\n"
               : "=r"(ok) : "r"(a), "r"(parity) : "memory");
  return ok;
}
__device__ __forceinline__ void tma3d(uint32_t dst, const CUtensorMap* tm, uint32_t bar, int c0, int c1, int c2) {
  asm volatile(
      "cp.async.bulk.tensor.3d.shared::cluster.global.mbarrier::complete_tx::bytes [%0], [%1, {%3,%4,%5}], [%2];"
      ::"r"(dst), "l"(tm), "r"(bar), "r"(c0), "r"(c1), "r"(c2) : "memory");
}
__device__ __forceinline__ void wg_fence() { asm volatile("wgmma.fence.sync.aligned;" ::: "memory"); }
__device__ __forceinline__ void wg_commit() { asm volatile("wgmma.commit_group.sync.aligned;" ::: "memory"); }
template <int N> __device__ __forceinline__ void wg_wait() {
  asm volatile("wgmma.wait_group.sync.aligned %0;" ::"n"(N) : "memory");
}
template <int N> __device__ __forceinline__ void fence_regs(float (&d)[N]) {
#pragma unroll
  for (int i = 0; i < N; i++) asm volatile("" : "+f"(d[i])::"memory");
}
template <int N> __device__ __forceinline__ void fence_regs(uint32_t (&d)[N][4]) {
#pragma unroll
  for (int i = 0; i < N; i++) asm volatile("" : "+r"(d[i][0]), "+r"(d[i][1]), "+r"(d[i][2]), "+r"(d[i][3])::"memory");
}
template <int N> __device__ __forceinline__ void fence_frags(uint32_t (*d)[4]) {
#pragma unroll
  for (int i = 0; i < N; i++) asm volatile("" : "+r"(d[i][0]), "+r"(d[i][1]), "+r"(d[i][2]), "+r"(d[i][3])::"memory");
}
__device__ __forceinline__ void bar_sync(int id, int n) { asm volatile("bar.sync %0, %1;" ::"r"(id), "r"(n) : "memory"); }
__device__ __forceinline__ void bar_arrive(int id, int n) { asm volatile("bar.arrive %0, %1;" ::"r"(id), "r"(n) : "memory"); }

__device__ __forceinline__ uint32_t pack_bf16(float lo, float hi) {
  uint32_t r;
  asm("cvt.rn.bf16x2.f32 %0, %1, %2;" : "=r"(r) : "f"(hi), "f"(lo));
  return r;
}
__device__ __forceinline__ float bf_lo(uint32_t w) { return __uint_as_float(w << 16); }
__device__ __forceinline__ float bf_hi(uint32_t w) { return __uint_as_float(w & 0xFFFF0000u); }
__device__ __forceinline__ float round_bf16(float x) { return bf_lo(pack_bf16(x, 0.f)); }
__device__ __forceinline__ uint32_t hfma2_bf16(uint32_t a, uint32_t b, uint32_t c) {
  uint32_t r;
  asm("fma.rn.bf16x2 %0, %1, %2, %3;" : "=r"(r) : "r"(a), "r"(b), "r"(c));
  return r;
}
__device__ __forceinline__ float ex2(float x) {
  float r;
  asm("ex2.approx.ftz.f32 %0, %1;" : "=f"(r) : "f"(x));
  return r;
}
__device__ __forceinline__ float tanh_hw(float x) {
  float r;
  asm("tanh.approx.f32 %0, %1;" : "=f"(r) : "f"(x));
  return r;
}
template <int TAG> __device__ __forceinline__ uint32_t pack_tag(float lo, float hi) {
  uint32_t w = __byte_perm(__float_as_uint(lo), pack_bf16(lo, hi), 0x7632);
  return TAG ? (w | 1u) : (w & ~1u);
}
__device__ __forceinline__ void st_pkt(uint4* p, uint32_t a, uint32_t b, uint32_t c, uint32_t d) {
  asm volatile(
      "st.relaxed.gpu.global.v4.b32 [%0], {%1,%2,%3,%4};" ::"l"(p), "r"(a), "r"(b), "r"(c), "r"(d) : "memory");
}
__device__ __forceinline__ void ld_pkt(const uint4* p, uint32_t (&r)[4]) {
  asm volatile(
      "ld.relaxed.gpu.global.v4.b32 {%0,%1,%2,%3}, [%4];"
      : "=r"(r[0]), "=r"(r[1]), "=r"(r[2]), "=r"(r[3]) : "l"(p) : "memory");
}
__device__ __forceinline__ uint32_t ldg32(const void* p) {
  uint32_t r;
  asm volatile("ld.global.nc.b32 %0, [%1];" : "=r"(r) : "l"(p));
  return r;
}
__device__ __forceinline__ uint32_t ldg16(const void* p) {
  uint16_t r;
  asm volatile("ld.global.nc.b16 %0, [%1];" : "=h"(r) : "l"(p));
  return r;
}
__device__ __forceinline__ uint4 ldg128(const void* p) {
  uint4 r;
  asm volatile("ld.global.nc.v4.b32 {%0,%1,%2,%3}, [%4];" : "=r"(r.x), "=r"(r.y), "=r"(r.z), "=r"(r.w) : "l"(p));
  return r;
}
__device__ __forceinline__ void l2_prefetch(const void* p, uint32_t bytes) {
  asm volatile("cp.async.bulk.prefetch.L2.global [%0], %1;" ::"l"(p), "r"(bytes) : "memory");
}
__device__ __forceinline__ float rcp_hw(float x) {
  float r;
  asm("rcp.approx.ftz.f32 %0, %1;" : "=f"(r) : "f"(x));
  return r;
}
__device__ __forceinline__ void warp_bulk_load(uint32_t sdst, const void* gsrc, uint32_t bytes, uint32_t bar) {
  asm volatile(
      "{\n.reg .pred p;\nelect.sync _|p, 0xffffffff;\n"
      "@p mbarrier.arrive.expect_tx.shared::cta.b64 _, [%3], %2;\n"
      "@p cp.async.bulk.shared::cluster.global.mbarrier::complete_tx::bytes [%0], [%1], %2, [%3];\n}\n"
      ::"r"(sdst), "l"(gsrc), "r"(bytes), "r"(bar) : "memory");
}
__device__ __forceinline__ void warp_tma3d(uint32_t dst, const CUtensorMap* tm, uint32_t bar, uint32_t bytes, int c1, int c2) {
  asm volatile(
      "{\n.reg .pred p;\nelect.sync _|p, 0xffffffff;\n"
      "@p mbarrier.arrive.expect_tx.shared::cta.b64 _, [%2], %3;\n"
      "@p cp.async.bulk.tensor.3d.shared::cluster.global.mbarrier::complete_tx::bytes [%0], [%1, {%6,%4,%5}], [%2];\n}\n"
      ::"r"(dst), "l"(tm), "r"(bar), "r"(bytes), "r"(c1), "r"(c2), "r"(0) : "memory");
}
__device__ __forceinline__ bool elect_one() {
  uint32_t r;
  asm volatile("{\n.reg .pred p;\nelect.sync _|p, 0xffffffff;\nselp.u32 %0, 1, 0, p;\n}\n" : "=r"(r));
  return r;
}
__device__ __forceinline__ void warp_arrive(uint32_t bar) {
  asm volatile("{\n.reg .pred p;\nelect.sync _|p, 0xffffffff;\n@p mbarrier.arrive.shared::cta.b64 _, [%0];\n}\n" ::"r"(bar) : "memory");
}
__device__ __forceinline__ uint32_t pack_trunc(float lo, float hi) {
  return __byte_perm(__float_as_uint(lo), __float_as_uint(hi), 0x7632);
}
__device__ __forceinline__ void add_partial(float (&y)[8], const uint32_t (&r)[4], uint32_t c0, bool first) {
#pragma unroll
  for (int e = 0; e < 4; e++) {
    const float lo = __uint_as_float(r[e] * 65536u + (e ? 0x8000u : c0)), hi = __uint_as_float(r[e]);
    y[2 * e] = first ? lo : y[2 * e] + lo;
    y[2 * e + 1] = first ? hi : y[2 * e + 1] + hi;
  }
}
__device__ __forceinline__ void spin_cycles(uint32_t n) {
  uint32_t t0, t;
  asm volatile("mov.u32 %0, %%clock;" : "=r"(t0));
  do { asm volatile("mov.u32 %0, %%clock;" : "=r"(t)); } while (t - t0 < n);
}
__device__ __forceinline__ void sts128(uint32_t a, uint32_t x, uint32_t y, uint32_t z, uint32_t w) {
  asm volatile("st.shared.v4.b32 [%0], {%1,%2,%3,%4};" ::"r"(a), "r"(x), "r"(y), "r"(z), "r"(w) : "memory");
}
__device__ __forceinline__ void lds128(uint32_t a, uint32_t (&r)[4]) {
  asm volatile("ld.shared.v4.b32 {%0,%1,%2,%3}, [%4];" : "=r"(r[0]), "=r"(r[1]), "=r"(r[2]), "=r"(r[3]) : "r"(a) : "memory");
}

__device__ __forceinline__ uint32_t lds32(uint32_t a) {
  uint32_t r;
  asm volatile("ld.shared.b32 %0, [%1];" : "=r"(r) : "r"(a) : "memory");
  return r;
}
__device__ __forceinline__ void store_out(__nv_bfloat16* out, uint32_t woff, uint32_t x2s, uint32_t gb0, uint32_t gb1,
                                          const float (&y)[8]) {
  const uint32_t gb[2] = {gb0, gb1};
  uint32_t xa[2][4];
  lds128(x2s, xa[0]);
  lds128(x2s + 2048, xa[1]);
  uint32_t* const oo = (uint32_t*)out + woff;
#pragma unroll
  for (int e = 0; e < 4; e++)
    oo[(e >> 1) * 4 + (e & 1) * 8 * 256] =
        pack_bf16(fmaf(bf_lo(gb[e >> 1]), y[2 * e], __uint_as_float(xa[e >> 1][(e & 1) * 2])),
                  fmaf(bf_hi(gb[e >> 1]), y[2 * e + 1], __uint_as_float(xa[e >> 1][(e & 1) * 2 + 1])));
}

constexpr int SK = 2048, WIN = 512;
constexpr int FF = 1792, FSL = 224;
constexpr int NTILES = 80;
constexpr int NSLOT = 4;
constexpr uint32_t SLOT = 32768;
constexpr uint32_t SM_PARK = 0;
constexpr uint32_t SM_RING = 3 * SLOT;
constexpr uint32_t SM_TAB = 7 * SLOT;
constexpr uint32_t SM_RED = SM_TAB + 2048;
constexpr uint32_t SM_BAR = SM_RED + 256;
constexpr uint32_t SM_WBAR = SM_BAR + 128;
constexpr uint32_t SM_SBAR = SM_WBAR + 256;
constexpr uint32_t BAR_SLAB = 64, BAR_UV = 72, BAR_X2 = 80, BAR_TAG = 88;
constexpr uint32_t SM_DBAR = SM_SBAR + 16;
constexpr uint32_t SM_TOTAL = SM_DBAR + 128;

struct Scratch {
  uint4 P[16 * 8 * 4 * 1024];
  uint4 G[16 * 8 * 32 * 32];
  uint4 mod1[8 * 256];
  uint4 mod2[512];
  uint4 uv[2 * 448];
  uint4 stat[16 * 8 * 8];
  uint32_t sent[16 * 8 * 8];
  uint32_t epoch;
};
__device__ Scratch g_scratch;

#define TS(i) do { } while (0)
#define TR(code)
#define CK_(v)
#define CKS(i, v)

#define TRU(code)

struct Params {
  const __nv_bfloat16* x;
  const __nv_bfloat16* c;
  const __nv_bfloat16* wmod;
  const __nv_bfloat16* wo;
  const __nv_bfloat16* w1;
  const __nv_bfloat16* w2;
  __nv_bfloat16* out;
  Scratch* s;
  uint32_t zero;
};

constexpr uint32_t HI128 = (1024 >> 4) | (1u << 30);
constexpr int LB_MN128 = (16384 >> 4) << 16;
constexpr int LB_K128 = 1 << 16;
constexpr int LB_W1 = (8192 >> 4) << 16;

template <int I> struct IC {
  __host__ __device__ constexpr operator int() const { return I; }
};
template <int I, int N, typename F> __device__ __forceinline__ void static_for(F&& f) {
  if constexpr (I < N) {
    f(IC<I>{});
    static_for<I + 1, N>(f);
  }
}

struct Ring {
  uint32_t base16, bars;
  __device__ __forceinline__ uint32_t tile(uint32_t slot) const { return base16 + slot * (SLOT >> 4); }
  __device__ __forceinline__ void release(uint32_t slot) const {
    warp_arrive(bars + 32 + slot * 8);
  }
};

__device__ __forceinline__ float silu_c(uint32_t bits) {
  float x = bf_lo(bits);
  return round_bf16(x * rcp_hw(1.f + ex2(-1.4426950408889634f * x)));
}
__device__ __forceinline__ void pack8(uint32_t (&o)[4], const float* v) {
  o[0] = pack_bf16(v[0], v[1]); o[1] = pack_bf16(v[2], v[3]); o[2] = pack_bf16(v[4], v[5]); o[3] = pack_bf16(v[6], v[7]);
}

template <int TAG, int N>
__device__ __forceinline__ void issue_pkts(const uint4* p, int stride, uint32_t (*r)[4]) {
#pragma unroll
  for (int i = 0; i < N; i++) ld_pkt(p + i * stride, r[i]);
}
__device__ __forceinline__ void wait_sent(const uint32_t* p, uint32_t tag, uint32_t step) {
#pragma unroll 1
  for (int spins = 0; spins < SPIN_LIMIT; spins++) {
    uint32_t v;
    asm volatile("ld.relaxed.gpu.global.u32 %0, [%1];" : "=r"(v) : "l"(p) : "memory");
    if (__all_sync(0xffffffffu, v - (tag * 32 + step + 1) < 16u)) break;
  }
}
__device__ __forceinline__ void ld_mod(const uint4* p, uint32_t tag, uint32_t (&r)[4]) {
  int spins = 0;
  ld_pkt(p, r);
  while (r[2] != tag && ++spins < SPIN_LIMIT) ld_pkt(p, r);
}

#define EARLY_TILES 2
#define PF_WMOD 1
#define MOD1_DELAY 500
#define RED3_UNIT 3
#define NITEM2 24
#define FIN_DELAY0 800
#define FIN_DELAY1 0
#define PRE_EXP 4
#define G_DELAY 300

__device__ __forceinline__ float reduce8(float (&a)[8], int lane) {
  const bool h16 = lane & 16, h8 = lane & 8, h4 = lane & 4;
#pragma unroll
  for (int k = 0; k < 4; k++) a[k] = (h16 ? a[k + 4] : a[k]) + __shfl_xor_sync(0xffffffffu, h16 ? a[k] : a[k + 4], 16);
#pragma unroll
  for (int k = 0; k < 2; k++) a[k] = (h8 ? a[k + 2] : a[k]) + __shfl_xor_sync(0xffffffffu, h8 ? a[k] : a[k + 2], 8);
  const float r = (h4 ? a[1] : a[0]) + __shfl_xor_sync(0xffffffffu, h4 ? a[0] : a[1], 4);
  return r + __shfl_xor_sync(0xffffffffu, r, 2);
}
__device__ __forceinline__ void fma8(float (&a)[8], float s, uint32_t w0, uint32_t w1, uint32_t w2, uint32_t w3) {
  a[0] = fmaf(s, bf_lo(w0), a[0]); a[1] = fmaf(s, bf_hi(w0), a[1]);
  a[2] = fmaf(s, bf_lo(w1), a[2]); a[3] = fmaf(s, bf_hi(w1), a[3]);
  a[4] = fmaf(s, bf_lo(w2), a[4]); a[5] = fmaf(s, bf_hi(w2), a[5]);
  a[6] = fmaf(s, bf_lo(w3), a[6]); a[7] = fmaf(s, bf_hi(w3), a[7]);
}

enum { NB_TAB = 1, NB_WG0 = 2, NB_WG1 = 3, NB_HELP = 4, NB_INIT = 5, NB_PASS0 = 6, NB_GATHER = 7, NB_PARK = 8, NB_PROD = 9 };

__global__ void __launch_bounds__(512, 1)
adaln_block_kernel(const __grid_constant__ CUtensorMap tmWq, const __grid_constant__ CUtensorMap tmK,
                   const __grid_constant__ CUtensorMap tmV, const __grid_constant__ CUtensorMap tmWo,
                   const __grid_constant__ CUtensorMap tmW1, const __grid_constant__ CUtensorMap tmW2,
                   const __grid_constant__ CUtensorMap tmWm, const __grid_constant__ CUtensorMap tmX,
                   const Params p) {
  extern __shared__ __align__(1024) uint8_t smem_raw[];
  const uint32_t sb = smem_u32(smem_raw);
  const int tid = threadIdx.x, lane = tid & 31;
  const int warp = __shfl_sync(0xffffffffu, tid >> 5, 0);
  const int kp = blockIdx.x >> 1;
  const int bid = (kp < 4 ? kp : kp < 36 ? 4 + ((kp - 4) & 7) * 4 + ((kp - 4) >> 3) : 36 + ((kp - 36) % 7) * 4 + (kp - 36) / 7) * 2 +
                  (blockIdx.x & 1);
  const int j = bid & 7, rt = bid >> 3;
  const uint32_t bars = sb + SM_BAR;
  if (warp != 13) asm volatile("barrier.cluster.arrive.relaxed.aligned;" ::: "memory");

  if (warp >= 12) {
    asm volatile("setmaxnreg.dec.sync.aligned.u32 24;");
    if (warp == 13) {
      if (elect_one()) {
#pragma unroll
        for (int i = 0; i < 28; i++) mbar_init(sb + SM_WBAR + i * 8, i < 26 ? 1 : 4);
        mbar_init(sb + SM_SBAR, 8);
#pragma unroll
        for (int i = 0; i < 16; i++) mbar_init(sb + SM_DBAR + i * 8, 1);
        asm volatile("fence.mbarrier_init.release.cluster;" ::: "memory");
      }
      __syncwarp();
      asm volatile("barrier.cluster.arrive.relaxed.aligned;" ::: "memory");
      bar_arrive(NB_INIT, 224);
      mbar_wait(sb + SM_SBAR, 0);
      const uint32_t tag = *(volatile uint32_t*)(smem_raw + SM_BAR + BAR_TAG);
#pragma unroll 1
      for (int n = 0; n < 14; n++) {
        const uint32_t lb = sb + SM_WBAR + 192 + (n & 1) * 8;
        mbar_wait(lb + 16, ((n >> 1) & 1) ^ 1);
        wait_sent(&p.s->sent[(rt * 8 + j) * 8 + (lane & 6) + (n & 1)], tag, n >> 1);
        if (elect_one()) {
          mbar_expect(lb, n < 8 ? 8192 + 2048 : 8192);
#pragma unroll
          for (int m = 0; m < 4; m++)
            asm volatile("cp.async.bulk.shared::cluster.global.mbarrier::complete_tx::bytes [%0], [%1], 2048, [%2];"
                         ::"r"(sb + SM_PARK + ((n & 1) * 4 + m) * 4096 + 2048),
                           "l"(p.s->P + ((size_t)(rt * 8 + j) * 4 + m) * 1024 + (n & 7) * 128), "r"(lb) : "memory");
          if (n < 8) tma3d(sb + SM_PARK + SLOT + n * 4096, &tmX, lb, 0, rt * 128 + j * 16, n * 4);
        }
        __syncwarp();
      }
    } else if (warp == 14) {
      if (elect_one()) {
        asm volatile("prefetch.tensormap [%0];" ::"l"(&tmWq) : "memory");
        asm volatile("prefetch.tensormap [%0];" ::"l"(&tmK) : "memory");
        asm volatile("prefetch.tensormap [%0];" ::"l"(&tmV) : "memory");
        asm volatile("prefetch.tensormap [%0];" ::"l"(&tmWo) : "memory");
        asm volatile("prefetch.tensormap [%0];" ::"l"(&tmX) : "memory");
        asm volatile("prefetch.tensormap [%0];" ::"l"(&tmW1) : "memory");
        asm volatile("prefetch.tensormap [%0];" ::"l"(&tmW2) : "memory");
      }
      __syncwarp();
      bar_sync(NB_INIT, 224);
#pragma unroll 1
      for (int tt = 0; tt < NTILES; tt++) {
        mbar_wait(bars + (tt & 3) * 8, (tt >> 2) & 1);
        const bool single = tt < 4 || tt == 14 || tt == 47 || tt == 72 || tt == 79;
        const bool second = (tt > 14 && tt < 47) || tt > 72 ? !(tt & 1) : (tt & 1);
        if (single || second) bar_sync(NB_WG0, 288);
      }
    } else if (warp == 12) {
      if (elect_one()) {
        mbar_init(bars + BAR_SLAB, 1);
        asm volatile("fence.mbarrier_init.release.cluster;" ::: "memory");
        mbar_expect(bars + BAR_SLAB, 8192);
        tma3d(sb + SM_RING + 3 * SLOT, &tmWm, bars + BAR_SLAB, 0, 0, bid);
        tma3d(sb + SM_RING + 3 * SLOT + 4096, &tmWm, bars + BAR_SLAB, 0, 256, bid);
#pragma unroll
        for (int i = 0; i < 4; i++) { mbar_init(bars + i * 8, 1); mbar_init(bars + 32 + i * 8, 8); }
        mbar_init(bars + BAR_UV, 4);
        mbar_init(bars + BAR_X2, 1);
        asm volatile("fence.mbarrier_init.release.cluster;" ::: "memory");
      }
      __syncwarp();
      bar_arrive(NB_INIT, 224);
      mbar_wait(bars + BAR_SLAB, 0);
      uint32_t s = 0, ph = 1;
#pragma unroll 1
      for (int tt = 0; tt < NTILES; tt++) {
        const CUtensorMap* tm;
        int c1, c2;
        uint32_t bytes = SLOT;
        if (tt < 15 || tt == 16) {
          const int u = min(tt, 15);
          tm = &tmWq; c1 = (u & 3) * 128; c2 = (j * 4 + (u >> 2)) * 2;
        } else if (tt < 48) {
          const bool isK = (tt & 1) && tt != 47;
          const int n = isK ? (tt - 15) >> 1 : (tt - 17) >> 1;
          tm = isK ? &tmK : &tmV; c1 = j * SK + (SK - WIN) + (n & 3) * 128; c2 = 0;
        } else if (tt < 64) {
          const int u = tt - 48;
          tm = &tmWo; c1 = j * 512 + (u & 1) * 256; c2 = (u >> 1) ^ (~j & 1);
        } else if (tt < 72) {
          tm = &tmW1; c1 = (tt - 64) * 64; c2 = (j * 7) >> 1;
        } else {
          tm = &tmW2; c1 = j * FSL; c2 = (tt - 72) ^ (~j & 1); bytes = 28672;
        }
        if (tt == EARLY_TILES) bar_sync(NB_PROD, 160);
        mbar_wait(bars + 32 + s * 8, ph);
        warp_tma3d(sb + SM_RING + s * SLOT, tm, bars + s * 8, bytes, c1, c2);
        if (++s == 4) { s = 0; ph ^= 1; }
      }
    }
  } else if (warp >= 8) {
    CK_(c0);
    asm volatile("setmaxnreg.dec.sync.aligned.u32 40;");
    const int t = tid - 256, hw = warp - 8, q = lane & 3;
    float* const red = (float*)(smem_raw + SM_RED);
    uint32_t tag;
    float a[8];
    {
      uint32_t cb[4];
#pragma unroll
      for (int i = 0; i < 4; i++) cb[i] = ldg16(p.c + t + 128 * i);
      asm volatile("ld.relaxed.gpu.global.u32 %0, [%1];" : "=r"(tag) : "l"(&p.s->epoch) : "memory");
      bar_sync(NB_INIT, 224);
      CK_(c2);
      tag += 1;
      float sc[4];
#pragma unroll
      for (int i = 0; i < 4; i++) sc[i] = silu_c(cb[i]);
#pragma unroll
      for (int k = 0; k < 8; k++) a[k] = 0.f;
      if (t == 0) *(uint32_t*)(smem_raw + SM_BAR + BAR_TAG) = tag;
      mbar_wait(bars + BAR_SLAB, 0);
      CK_(c3);
      bar_arrive(NB_GATHER, 384);
#pragma unroll
      for (int i = 0; i < 4; i++) {
        uint32_t w[4];
        lds128(sb + SM_RING + 3 * SLOT + (t + 128 * i) * 16, w);
        fma8(a, sc[i], w[0], w[1], w[2], w[3]);
      }
      float r = reduce8(a, lane);
      r += __shfl_xor_sync(0xffffffffu, r, 1);
      if (q == 0) red[hw * 8 + (lane >> 2)] = r;
      CK_(c4);
      bar_sync(NB_HELP, 128);
      CK_(c5);
      if (hw == 0) {
        const int cl = lane & 7;
        float v = round_bf16(red[cl] + red[8 + cl] + red[16 + cl] + red[24 + cl]);
        if (bid >= 64) v = 1.f + v;
        float vn = __shfl_down_sync(0xffffffffu, v, 1);
        uint32_t wd = pack_bf16(v, vn);
        uint32_t w0 = __shfl_sync(0xffffffffu, wd, (lane & 1) * 4);
        uint32_t w1 = __shfl_sync(0xffffffffu, wd, (lane & 1) * 4 + 2);
        if (lane < 16) st_pkt(&p.s->mod1[(lane >> 1) * 256 + bid * 2 + (lane & 1)], w0, w1, tag, 0);
      }
      uint32_t r0[4], r1[4];
      const uint4* src = &p.s->mod1[j * 256 + t];
      CK_(c6);
      spin_cycles(MOD1_DELAY);
      CK_(c7);
      int spins = 0;
      do {
        ld_pkt(src, r0);
        ld_pkt(src + 128, r1);
      } while ((r0[2] != tag || r1[2] != tag) && ++spins < SPIN_LIMIT);
      const int g = t >> 2, pp = q * 2;
      const uint32_t ad = sb + SM_TAB + (uint32_t)(g * 4 + (pp & 3)) * 16 + (pp >> 2) * 4;
      asm volatile("st.shared.b32 [%0], %1;" ::"r"(ad + 8), "r"(r0[0]) : "memory");
      asm volatile("st.shared.b32 [%0], %1;" ::"r"(ad + 24), "r"(r0[1]) : "memory");
      asm volatile("st.shared.b32 [%0], %1;" ::"r"(ad), "r"(r1[0]) : "memory");
      asm volatile("st.shared.b32 [%0], %1;" ::"r"(ad + 16), "r"(r1[1]) : "memory");
      bar_arrive(NB_TAB, 384);
      bar_arrive(NB_PROD, 160);
      CK_(c8);
      CKS(0, c0); CKS(2, c2); CKS(3, c3); CKS(4, c4); CKS(5, c5); CKS(6, c6); CKS(7, c7); CKS(8, c8);
    }
    bar_sync(NB_PASS0, 384);
    {
#pragma unroll
      for (int k = 0; k < 8; k++) a[k] = 0.f;
#pragma unroll 1
      for (int b = 0; b < 4; b++) {
        const int row = b * 128 + (t >> 1);
        const __nv_bfloat16* wp = p.wmod + (size_t)row * 3072 + 1024 + bid * 16 + (t & 1) * 8;
        const uint4 w0 = ldg128(wp), w1 = ldg128(wp + 64 * 3072);
        const uint32_t c0 = ldg16(p.c + row), c1 = ldg16(p.c + row + 64);
        fma8(a, silu_c(c0), w0.x, w0.y, w0.z, w0.w);
        fma8(a, silu_c(c1), w1.x, w1.y, w1.z, w1.w);
      }
      const float r = reduce8(a, lane);
      if ((lane & 2) == 0) red[hw * 16 + (lane & 1) * 8 + (lane >> 2)] = r;
      bar_sync(NB_HELP, 128);
      if (hw == 0) {
        const int cl = lane & 15;
        float v = round_bf16(red[cl] + red[16 + cl] + red[32 + cl] + red[48 + cl]);
        if ((bid >> 5) == 2) v = 1.f + v;
        float vn = __shfl_down_sync(0xffffffffu, v, 1);
        uint32_t wd = pack_bf16(v, vn);
        uint32_t w0 = __shfl_sync(0xffffffffu, wd, q * 2);
        uint32_t w1 = __shfl_sync(0xffffffffu, wd, q * 2 + 8);
        const int vec = (0x2130 >> ((bid >> 5) * 4)) & 3;
        if (lane < 4) st_pkt(&p.s->mod2[((bid & 31) * 4 + vec) * 4 + lane], w0, w1, tag, 0);
      }
    }
    {
      const int isv = hw & 1, kh = hw >> 1;
      if (bid < 112) {
        const int kk = lane >> 1;
        uint32_t m0[4], m1[4];
        const uint4* mp = &p.s->mod2[(kh * 16 + (lane >> 2)) * 16 + (isv ? 12 : 4) + q];
        ld_mod(mp, tag, m0);
        ld_mod(mp + 128, tag, m1);
#pragma unroll
        for (int k = 0; k < 8; k++) a[k] = 0.f;
#pragma unroll 1
        for (int g0 = 0; g0 < 16; g0 += 2) {
          uint4 w[2];
#pragma unroll
          for (int i = 0; i < 2; i++) w[i] = ldg128(p.w1 + (size_t)((kh * 16 + g0 + i) * 16 + kk) * FF + bid * 16 + (lane & 1) * 8);
#pragma unroll
          for (int i = 0; i < 2; i++) {
            const int sl = ((g0 + i) & 7) * 4 + ((kk & 7) >> 1);
            const uint32_t wa = __shfl_sync(0xffffffffu, g0 < 8 ? m0[0] : m1[0], sl), wb = __shfl_sync(0xffffffffu, g0 < 8 ? m0[1] : m1[1], sl);
            const uint32_t mw = (kk & 8) ? wb : wa;
            fma8(a, (kk & 1) ? bf_hi(mw) : bf_lo(mw), w[i].x, w[i].y, w[i].z, w[i].w);
          }
        }
        float r = reduce8(a, lane);
        bar_sync(NB_HELP, 128);
        if (kh) red[isv * 32 + lane] = r;
        bar_sync(NB_HELP, 128);
        if (!kh) {
          r = (r + red[isv * 32 + lane]) * (isv ? 0.5f : 1.f);
          const float r1 = __shfl_down_sync(0xffffffffu, r, 4), r2 = __shfl_down_sync(0xffffffffu, r, 8),
                      r3 = __shfl_down_sync(0xffffffffu, r, 12);
          if ((lane & 14) == 0)
            st_pkt(&p.s->uv[isv * 448 + bid * 4 + (lane & 1) * 2 + (lane >> 4)], (__float_as_uint(r) & ~1u) | (tag & 1u),
                   __float_as_uint(r1), __float_as_uint(r2), __float_as_uint(r3));
        }
      }
      const int i = kh * 32 + lane;
      if (i < 56) {
        uint32_t m[4];
        int spins = 0;
        while (true) {
          ld_pkt(&p.s->uv[isv * 448 + j * 56 + i], m);
          if (!((m[0] ^ tag) & 1u) || ++spins >= SPIN_LIMIT) break;
          __nanosleep(200);
        }
        const int ip = (j & 1) ? (i < 8 ? i + 48 : i - 8) : i;
        const uint32_t ad = sb + SM_TAB + ip * 32 + isv * 8;
        asm volatile("st.shared.v2.b32 [%0], {%1,%2};" ::"r"(ad), "r"(m[0]), "r"(m[1]) : "memory");
        asm volatile("st.shared.v2.b32 [%0], {%1,%2};" ::"r"(ad + 16), "r"(m[2]), "r"(m[3]) : "memory");
      }
      __syncwarp();
      warp_arrive(bars + BAR_UV);
      if (t < 8) l2_prefetch((const char*)p.wo + (size_t)bid * 32768 + t * 4096, 4096);
      else if (t < 12) l2_prefetch((const char*)p.w2 + (size_t)bid * 14336 + (t - 8) * 3584, 3584);
      else if (t < 16) l2_prefetch((const char*)p.x + (size_t)(rt * 128 + j * 16) * 1024 + (t - 12) * 4096, 4096);
      TS(9);
    }
    {
      uint32_t mga[4], mg2[4], mgb[4];
      const uint4* mp = &p.s->mod2[((lane >> 2) * 4 + hw) * 16 + q];
      ld_mod(mp, tag, mga);
      ld_mod(mp + 4, tag, mg2);
      ld_mod(mp + 8, tag, mgb);
      if (lane >= 24) asm volatile("st.shared.v2.b32 [%0], {%1,%2};" ::"r"(sb + SM_TAB + 1792 + ((((lane >> 2) & 1) * 4 + hw) * 4 + q) * 8),
                                   "r"(mgb[0]), "r"(mgb[1]) : "memory");
      const uint32_t x2s = sb + SM_PARK + SLOT + hw * 512 + lane * 16;
      const uint4* const Pown = p.s->P + (size_t)(rt * 8 + j) * 4096 + hw * 32 + lane;
      float s0 = 0.f, s1 = 0.f, v0 = 0.f, v1 = 0.f;
      bar_sync(NB_PARK, 384);
      asm volatile("setmaxnreg.inc.sync.aligned.u32 56;");
#pragma unroll 1
      for (int n = 0; n < 14; n++) {
        const int cc = n & 7;
        const bool ex1 = n < 8;
        const uint32_t lb = sb + SM_WBAR + 192 + (n & 1) * 8;
        uint32_t r[4][4];
        float y[8];
        mbar_wait(lb, (n >> 1) & 1);
#pragma unroll
        for (int i = 0; i < 4; i++) lds128(sb + SM_PARK + ((n & 1) * 4 + i) * 4096 + 2048 + hw * 512 + lane * 16, r[i]);
        verify4_rt<16384>(Pown + cc * 128, r, ex1);
        warp_arrive(lb + 16);
#pragma unroll
        for (int i = 0; i < 4; i++) add_partial(y, r[i], ex1 ? 0u : 0x10000u, i == 0);
        const int src = cc * 4 + q;
        const uint32_t ma = __shfl_sync(0xffffffffu, ex1 ? mga[0] : mgb[0], src), mb = __shfl_sync(0xffffffffu, ex1 ? mga[1] : mgb[1], src);
        if (ex1) {
          uint32_t xr[4];
          asm volatile("ldmatrix.sync.aligned.m8n8.x4.shared.b16 {%0,%1,%2,%3}, [%4];"
                       : "=r"(xr[0]), "=r"(xr[1]), "=r"(xr[2]), "=r"(xr[3])
                       : "r"(sb + SM_PARK + SLOT + hw * 512 + cc * 4096 + (lane & 15) * 32 + (lane >> 4) * 16) : "memory");
          const uint32_t mc = __shfl_sync(0xffffffffu, mg2[0], src), md = __shfl_sync(0xffffffffu, mg2[1], src);
#pragma unroll
          for (int e = 0; e < 4; e++) {
            const uint32_t m = e < 2 ? ma : mb;
            const float u = fmaf(bf_lo(m), y[2 * e], bf_lo(xr[e])), v = fmaf(bf_hi(m), y[2 * e + 1], bf_hi(xr[e]));
            y[2 * e] = u; y[2 * e + 1] = v;
            if (e & 1) { s1 += u + v; v1 = fmaf(u, u, fmaf(v, v, v1)); }
            else { s0 += u + v; v0 = fmaf(u, u, fmaf(v, v, v0)); }
          }
          st_pkt(p.s->G + ((rt * 8 + j) * 32 + cc * 4 + hw) * 32 + lane, pack_tag<0>(y[0] * bf_lo(mc), y[1] * bf_hi(mc)),
                 pack_bf16(y[2] * bf_lo(mc), y[3] * bf_hi(mc)), pack_bf16(y[4] * bf_lo(md), y[5] * bf_hi(md)),
                 pack_bf16(y[6] * bf_lo(md), y[7] * bf_hi(md)));
          sts128(x2s + cc * 4096, __float_as_uint(y[0]), __float_as_uint(y[1]), __float_as_uint(y[2]), __float_as_uint(y[3]));
          sts128(x2s + cc * 4096 + 2048, __float_as_uint(y[4]), __float_as_uint(y[5]), __float_as_uint(y[6]), __float_as_uint(y[7]));
          if (n == 7) {
            const bool o1 = lane & 1, o2 = lane & 2;
            float c0 = (o1 ? v0 : s0) + __shfl_xor_sync(0xffffffffu, o1 ? s0 : v0, 1);
            float c1 = (o1 ? v1 : s1) + __shfl_xor_sync(0xffffffffu, o1 ? s1 : v1, 1);
            c0 = (o2 ? c1 : c0) + __shfl_xor_sync(0xffffffffu, o2 ? c0 : c1, 2);
            *(float*)(smem_raw + SM_PARK + 16384 + 2048 + hw * 512 + lane * 4) = c0;
            bar_sync(NB_HELP, 128);
            if (hw == 0) {
              const float* ps = (const float*)(smem_raw + SM_PARK + 16384 + 2048) + lane;
              const float m = (c0 + ps[128] + ps[256] + ps[384]) * (1.f / 512.f);
              const float mean = __shfl_sync(0xffffffffu, m, lane & ~1), sq = __shfl_sync(0xffffffffu, m, lane | 1);
              const float rs = 0.5f * rsqrtf(fmaxf(fmaf(-mean, mean, sq), 0.f) + 1e-5f), mr = -mean * rs;
              const float rs1 = __shfl_down_sync(0xffffffffu, rs, 2), mr1 = __shfl_down_sync(0xffffffffu, mr, 2);
              if (q == 0)
                st_pkt(&p.s->stat[(rt * 8 + j) * 8 + (lane >> 2)], (__float_as_uint(rs) & ~1u) | (tag & 1u), __float_as_uint(mr),
                       __float_as_uint(rs1), __float_as_uint(mr1));
              warp_arrive(bars + BAR_X2);
            }
          }
        } else {
          store_out(p.out, (uint32_t)(rt * 128 + 16 * j + (lane >> 2)) * 256 + (cc * 4 + hw) * 8 + q, x2s + cc * 4096, ma, mb, y);
        }
      }
    }
  } else {
    const int wg = warp >> 2;
    const int q = lane & 3, gq = lane >> 2;
    const Ring ring{((sb + SM_RING) & 0x3FFFF) >> 4, bars};
    const uint32_t xoff = (uint32_t)(rt * 128 + 16 * j + warp) * 256 + gq * 8 + q;
    const uint32_t ooff = ((uint32_t)(rt * 8 + j) * 32 + gq) * 32 + warp * 4 + q;
    const uint32_t wblk = sb + SM_PARK + warp * 4096, wprv = wblk + lane * 16;
    const uint32_t wbar = sb + SM_WBAR + warp * 24;
    const uint4* const Gw = p.s->G + (rt * 8 + warp) * 1024;

    {
      const uint32_t* xo = (const uint32_t*)p.x + xoff;
      uint32_t xr[4][4];
      CK_(d0);
#pragma unroll
      for (int c = 0; c < 4; c++) {
        xr[c][0] = ldg32(xo + c * 64);
        xr[c][1] = ldg32(xo + c * 64 + 8 * 256);
        xr[c][2] = ldg32(xo + c * 64 + 4);
        xr[c][3] = ldg32(xo + c * 64 + 4 + 8 * 256);
      }
      CK_(d1);
      fence_regs(xr);
      CK_(d2);
      float s0 = 0.f, s1 = 0.f, v0 = 0.f, v1 = 0.f;
#pragma unroll
      for (int c = 0; c < 4; c++) {
#pragma unroll
        for (int e = 0; e < 4; e++) {
          const float a = bf_lo(xr[c][e]), b = bf_hi(xr[c][e]);
          if (e & 1) { s1 += a + b; v1 = fmaf(a, a, fmaf(b, b, v1)); }
          else { s0 += a + b; v0 = fmaf(a, a, fmaf(b, b, v0)); }
        }
      }
#pragma unroll
      for (int o = 16; o > 0; o >>= 1) {
        s0 += __shfl_xor_sync(0xffffffffu, s0, o);
        s1 += __shfl_xor_sync(0xffffffffu, s1, o);
        v0 += __shfl_xor_sync(0xffffffffu, v0, o);
        v1 += __shfl_xor_sync(0xffffffffu, v1, o);
      }
      const float m0 = s0 * (1.f / 512.f), m1 = s1 * (1.f / 512.f);
      const float r0 = rsqrtf(fmaxf(fmaf(-m0, m0, v0 * (1.f / 512.f)), 0.f) + 1e-5f);
      const float r1 = rsqrtf(fmaxf(fmaf(-m1, m1, v1 * (1.f / 512.f)), 0.f) + 1e-5f);
#pragma unroll
      for (int c = 0; c < 4; c++) {
        st_pkt(p.s->G + ooff + c * 256,
               pack_tag<1>((bf_lo(xr[c][0]) - m0) * r0, (bf_hi(xr[c][0]) - m0) * r0),
               pack_bf16((bf_lo(xr[c][1]) - m1) * r1, (bf_hi(xr[c][1]) - m1) * r1),
               pack_bf16((bf_lo(xr[c][2]) - m0) * r0, (bf_hi(xr[c][2]) - m0) * r0),
               pack_bf16((bf_lo(xr[c][3]) - m1) * r1, (bf_hi(xr[c][3]) - m1) * r1));
      }
      CK_(d3);
      CKS(16, d0); CKS(17, d1); CKS(18, d2); CKS(19, d3);

    }
    asm volatile("setmaxnreg.inc.sync.aligned.u32 224;");
    auto my_turn = [&]() {
      asm volatile("{\n.reg .pred p;\nsetp.ne.u32 p, %0, 0;\n@p bar.sync 3, 256;\n@!p bar.sync 2, 288;\n}\n" ::"r"(wg) : "memory");
    };
    auto your_turn = [&]() {
      asm volatile("{\n.reg .pred p;\nsetp.ne.u32 p, %0, 0;\n@p bar.arrive 2, 288;\n@!p bar.arrive 3, 256;\n}\n" ::"r"(wg) : "memory");
    };
    if (wg == 1) your_turn();
    uint32_t qf[8][4], P[8][4];
    float O[64];
    {
      uint32_t h[24][4];
      const uint4* Gin = Gw + lane;
      asm volatile("barrier.cluster.wait.acquire.aligned;" ::: "memory");
      bar_sync(NB_GATHER, 384);
      if (G_DELAY) spin_cycles(G_DELAY);
#pragma unroll
      for (int c = 0; c < 3; c++) warp_bulk_load(wblk + c * SLOT, Gw + c * 256, 4096, wbar + c * 8);
#pragma unroll
      for (int c = 0; c < 4; c++) {
        uint32_t (*const hc)[4] = c < 3 ? h + c * 8 : P;
        mbar_wait(wbar + (c % 3) * 8, c / 3);
#pragma unroll
        for (int i = 0; i < 8; i++) lds128(wprv + (c % 3) * SLOT + i * 512, hc[i]);
        verify8_tag1<512>(Gin + c * 256, hc);
        if (c == 0) {
          warp_bulk_load(wblk, Gw + 768, 4096, wbar);
          TS(1);
          bar_sync(NB_TAB, 384);
        }
#pragma unroll
        for (int i = 0; i < 8; i++) {
          uint32_t m[4];
          lds128(sb + SM_TAB + (uint32_t)((c * 8 + i) * 4 + q) * 16, m);
          uint32_t* hh = hc[i];
          hh[0] = hfma2_bf16(hh[0], m[0], m[2]);
          hh[1] = hfma2_bf16(hh[1], m[0], m[2]);
          hh[2] = hfma2_bf16(hh[2], m[1], m[3]);
          hh[3] = hfma2_bf16(hh[3], m[1], m[3]);
        }
        fence_frags<8>(hc);
        if (p.zero) bar_sync(NB_TAB, 384);
        const uint32_t b = ring.tile(c);
        if (c > 0) { wg_wait<0>(); ring.release(c - 1); }
        TRU(5);
        if (c == 0) TS(2);
        my_turn();
        wg_fence();
        static_for<0, 8>([&](auto K) { wgmma_rs_n128_tb1<LB_MN128 + K * 128, HI128>(O, hc[K], b, (c | K) != 0); });
        wg_commit();
        your_turn();
      }
      bar_arrive(NB_PASS0, 384);
      auto first_half = [&](int ps) {
        wg_wait<0>();
        ring.release(3);
        fence_regs(O);
#pragma unroll
        for (int i = 0; i < 8; i++) {
          uint32_t w[4];
          pack8(w, O + 8 * i);
          sts128(wprv + (ps == 1 ? 2 : ps - 2) * SLOT + i * 512, w[0], w[1], w[2], w[3]);
        }
        my_turn();
        wg_fence();
        static_for<0, 8>([&](auto K) { wgmma_rs_n128_tb1<LB_MN128 + K * 128, HI128>(O, h[K], ring.base16, K != 0); });
        wg_commit();
        static_for<0, 8>([&](auto K) { wgmma_rs_n128_tb1<LB_MN128 + 2048 + K * 128, HI128>(O, h[8 + K], ring.base16, 1); });
        wg_commit();
        your_turn();
        wg_wait<1>();
        TRU(6);
        ring.release(0);
        wg_wait<0>();
        ring.release(1);
        my_turn();
        wg_fence();
        static_for<0, 8>([&](auto K) { wgmma_rs_n128_tb1<LB_MN128 + 4096 + K * 128, HI128>(O, h[16 + K], ring.base16, 1); });
        wg_commit();
      };
#pragma unroll 1
      for (int ps = 1; ps < 3; ps++) {
        first_half(ps);
        static_for<0, 8>([&](auto K) { wgmma_rs_n128_tb1<LB_MN128 + 6144 + K * 128, HI128>(O, P[K], ring.base16, 1); });
        wg_commit();
        your_turn();
        wg_wait<1>();
        TRU(6);
        ring.release(2);
      }
      first_half(3);
      your_turn();
#pragma unroll
      for (int i = 0; i < 8; i++) lds128(wprv + 2 * SLOT + i * 512, qf[i]);
      wg_wait<0>();
      ring.release(2);
    }
    fence_regs(qf);
    TS(3);

    uint32_t o[24][4];
    {
      float S[64];
      const float cs = 0.08838834764831845f * 1.4426950408889634f;
      const float TAU = 16.f;
      float m0, m1, l0, l1;

      auto float_block_max = [&]() {
        float b0 = fmaxf(S[0], S[1]), b1 = fmaxf(S[2], S[3]);
#pragma unroll
        for (int i = 1; i < 16; i++) {
          b0 = fmaxf(b0, fmaxf(S[4 * i], S[4 * i + 1]));
          b1 = fmaxf(b1, fmaxf(S[4 * i + 2], S[4 * i + 3]));
        }
        b0 = fmaxf(b0, __shfl_xor_sync(0xffffffffu, b0, 1)); b1 = fmaxf(b1, __shfl_xor_sync(0xffffffffu, b1, 1));
        b0 = fmaxf(b0, __shfl_xor_sync(0xffffffffu, b0, 2)); b1 = fmaxf(b1, __shfl_xor_sync(0xffffffffu, b1, 2));
        m0 = b0 * cs; m1 = b1 * cs;
      };
      auto first_block_max = [&]() {
        int a0 = max(__float_as_int(S[0]), __float_as_int(S[1]));
        int a1 = max(__float_as_int(S[2]), __float_as_int(S[3]));
#pragma unroll
        for (int i = 1; i < 16; i++) {
          a0 = __vimax3_s32(a0, __float_as_int(S[4 * i]), __float_as_int(S[4 * i + 1]));
          a1 = __vimax3_s32(a1, __float_as_int(S[4 * i + 2]), __float_as_int(S[4 * i + 3]));
        }
        a0 = max(a0, __shfl_xor_sync(0xffffffffu, a0, 1)); a1 = max(a1, __shfl_xor_sync(0xffffffffu, a1, 1));
        a0 = max(a0, __shfl_xor_sync(0xffffffffu, a0, 2)); a1 = max(a1, __shfl_xor_sync(0xffffffffu, a1, 2));
        m0 = __int_as_float(a0) * cs; m1 = __int_as_float(a1) * cs;
        if (__any_sync(0xffffffffu, (a0 | a1) < 0)) float_block_max();
      };
      auto exps = [&](int i0, int i1) {
#pragma unroll
        for (int i = i0; i < i1; i++) {
          S[4 * i] = ex2(fmaf(S[4 * i], cs, -m0)); S[4 * i + 1] = ex2(fmaf(S[4 * i + 1], cs, -m0));
          S[4 * i + 2] = ex2(fmaf(S[4 * i + 2], cs, -m1)); S[4 * i + 3] = ex2(fmaf(S[4 * i + 3], cs, -m1));
          l0 += S[4 * i]; l1 += S[4 * i + 2]; l0 += S[4 * i + 1]; l1 += S[4 * i + 3];
        }
      };
      auto softmax8 = [&](int i) {
        exps(2 * i, 2 * i + 2);
        pack8(P[i], S + 8 * i);
      };
      m0 = m1 = 0.f;
      l0 = l1 = 0.25f;
#pragma unroll 1
      for (int n = 0; n < 16; n++) {
        const uint32_t tk = 2 * n + 3, tv = 2 * n;
        const bool newhead = (n & 3) == 0;
        const uint32_t bk = ring.tile(tk & 3);
        const uint32_t bv = ring.tile(tv & 3);
        my_turn();
        wg_fence();
        static_for<0, 8>([&](auto K) { wgmma_rs_n128_tb0<LB_K128 + (K >> 2) * 1024 + (K & 3) * 2, HI128>(S, qf[K], bk, K != 0); });
        wg_commit();
        static_for<0, 8>([&](auto K) { wgmma_rs_n128_tb1<LB_MN128 + K * 128, HI128>(O, P[K], bv, K != 0 || (n & 3) != 1); });
        wg_commit();
        your_turn();
        wg_wait<1>();
        TRU(7);
        fence_regs(S);
        ring.release(tk & 3);
        if (newhead) {
          l0 += __shfl_xor_sync(0xffffffffu, l0, 1); l1 += __shfl_xor_sync(0xffffffffu, l1, 1);
          l0 += __shfl_xor_sync(0xffffffffu, l0, 2); l1 += __shfl_xor_sync(0xffffffffu, l1, 2);
          const float f0 = rcp_hw(l0), f1 = rcp_hw(l1);
          l0 = 0.f; l1 = 0.f;
          first_block_max();
          wg_wait<0>();
          fence_regs(O);
          fence_regs(P);
          ring.release(tv & 3);
#pragma unroll
          for (int i = 0; i < 8; i++) {
            softmax8(i);
#pragma unroll
            for (int e = 0; e < 8; e++) O[8 * i + e] *= (e & 2) ? f1 : f0;
            uint32_t w[4];
            pack8(w, O + 8 * i);
            sts128(wprv + (n ? (n >> 2) - 1 : 2) * SLOT + i * 512, w[0], w[1], w[2], w[3]);
          }
        } else {
          int a0 = max(__float_as_int(S[0]), __float_as_int(S[1]));
          int a1 = max(__float_as_int(S[2]), __float_as_int(S[3]));
#pragma unroll
          for (int i = 1; i < 16; i++) {
            a0 = __vimax3_s32(a0, __float_as_int(S[4 * i]), __float_as_int(S[4 * i + 1]));
            a1 = __vimax3_s32(a1, __float_as_int(S[4 * i + 2]), __float_as_int(S[4 * i + 3]));
          }
          const bool unsafe = fmaf(__int_as_float(max(a0, 0)), cs, -m0) > TAU || fmaf(__int_as_float(max(a1, 0)), cs, -m1) > TAU;
          if (__any_sync(0xffffffffu, unsafe)) {
            const float p0 = m0, p1 = m1;
            float_block_max();
            m0 = fmaxf(m0, p0); m1 = fmaxf(m1, p1);
            const float f0 = ex2(p0 - m0), f1 = ex2(p1 - m1);
            l0 *= f0; l1 *= f1;
            wg_wait<0>();
            fence_regs(O);
#pragma unroll
            for (int i = 0; i < 16; i++) {
              O[4 * i] *= f0; O[4 * i + 1] *= f0; O[4 * i + 2] *= f1; O[4 * i + 3] *= f1;
            }
          }
          exps(0, PRE_EXP);
          if ((n & 3) == 3 && n != 15) {
            fence_regs(qf);
#pragma unroll
            for (int i = 0; i < 8; i++) lds128(wprv + (n >> 2) * SLOT + i * 512, qf[i]);
          }
          wg_wait<0>();
          fence_regs(O);
          fence_regs(P);
          ring.release(tv & 3);
          exps(PRE_EXP, 16);
#pragma unroll
          for (int i = 0; i < 8; i++) pack8(P[i], S + 8 * i);
        }
        fence_regs(P);
        fence_regs(O);
        TRU(8);
      }
      {
        const uint32_t bv = ring.tile(3);
        my_turn();
        wg_fence();
        static_for<0, 8>([&](auto K) { wgmma_rs_n128_tb1<LB_MN128 + K * 128, HI128>(O, P[K], bv, 1); });
        wg_commit();
        your_turn();
#pragma unroll
        for (int i = 0; i < 16; i++) lds128(wprv + (i >> 3) * SLOT + (i & 7) * 512, o[i]);
        l0 += __shfl_xor_sync(0xffffffffu, l0, 1); l1 += __shfl_xor_sync(0xffffffffu, l1, 1);
        l0 += __shfl_xor_sync(0xffffffffu, l0, 2); l1 += __shfl_xor_sync(0xffffffffu, l1, 2);
        const float f0 = rcp_hw(l0), f1 = rcp_hw(l1);
        wg_wait<0>();
        fence_regs(O);
        ring.release(3);
#pragma unroll
        for (int i = 0; i < 8; i++) {
          qf[i][0] = pack_bf16(O[8 * i] * f0, O[8 * i + 1] * f0); qf[i][1] = pack_bf16(O[8 * i + 2] * f1, O[8 * i + 3] * f1);
          qf[i][2] = pack_bf16(O[8 * i + 4] * f0, O[8 * i + 5] * f0); qf[i][3] = pack_bf16(O[8 * i + 6] * f1, O[8 * i + 7] * f1);
        }
      }
    }
    fence_regs(qf);
    TS(4);
    asm volatile("setmaxnreg.dec.sync.aligned.u32 216;");
    bar_arrive(NB_PARK, 384);

    uint4* const Pout = p.s->P + ((size_t)(rt * 8 + warp) * 4 + (j >> 1)) * 1024 + (j & 1) * 128 + lane;
    const uint32_t tag = *(volatile uint32_t*)(smem_raw + SM_BAR + BAR_TAG);
    const uint32_t rbar = sb + SM_DBAR + warp * 16;
    uint32_t peer_land, peer_bar;
    asm("mapa.shared::cluster.u32 %0, %1, %2;" : "=r"(peer_land) : "r"(wprv), "r"(~j & 1));
    asm("mapa.shared::cluster.u32 %0, %1, %2;" : "=r"(peer_bar) : "r"(rbar), "r"(~j & 1));
    auto arm_and_ack = [&](uint32_t dep) {
      asm volatile(
          "{\n.reg .pred p;\nelect.sync _|p, 0xffffffff;\n"
          "@p mbarrier.arrive.expect_tx.shared::cta.b64 _, [%0], 2048;\n"
          "@p mbarrier.arrive.shared::cluster.b64 _, [%1];\n}\n" ::"r"(rbar), "r"(peer_bar + 8 + (dep & p.zero)) : "memory");
    };
    auto send_chunk = [&](float (&acc)[32], int pair) {
      mbar_wait(rbar + 8, pair & 1);
#pragma unroll
      for (int i = 0; i < 4; i++)
        asm volatile("st.async.weak.shared::cluster.mbarrier::complete_tx::bytes.v4.b32 [%0], {%1,%2,%3,%4}, [%5];"
                     ::"r"(peer_land + i * 512), "r"(pack_trunc(acc[8 * i], acc[8 * i + 1])), "r"(pack_trunc(acc[8 * i + 2], acc[8 * i + 3])),
                       "r"(pack_trunc(acc[8 * i + 4], acc[8 * i + 5])), "r"(pack_trunc(acc[8 * i + 6], acc[8 * i + 7])), "r"(peer_bar)
                     : "memory");
    };
    uint32_t pk[4][4];
    auto recv_chunk = [&](int pair) {
      mbar_wait(rbar, pair & 1);
#pragma unroll
      for (int i = 0; i < 4; i++) lds128(wprv + i * 512, pk[i]);
      if (pair < 7) arm_and_ack(pk[3][0]);
    };
    auto keep_chunk = [&](float (&acc)[32], int pair) {
      const uint32_t t1 = pair < 4;
#pragma unroll
      for (int i = 0; i < 4; i++) {
#pragma unroll
        for (int e = 0; e < 4; e++)
          pk[i][e] = pack_trunc(acc[8 * i + 2 * e] + __uint_as_float(pk[i][e] * 65536u + 0x8000u),
                                acc[8 * i + 2 * e + 1] + __uint_as_float(pk[i][e]));
        st_pkt(Pout + (pair & 3) * 256 + i * 32, (pk[i][0] & ~1u) | t1, pk[i][1], pk[i][2], pk[i][3]);
      }
      if (lane == 0)
        asm volatile("st.relaxed.gpu.global.u32 [%0], %1;" ::"l"(&p.s->sent[(rt * 8 + warp) * 8 + j]), "r"(tag * 32 + pair + 1) : "memory");
    };
    const uint4* const Gin = Gw + lane;
    auto g_issue = [&](int u) { warp_bulk_load(wblk + 2 * SLOT, Gw + u * 256, 4096, wbar); };

#pragma unroll
    for (int i = 16; i < 24; i++) lds128(wprv + 2 * SLOT + (i & 7) * 512, o[i]);
    fence_regs(o);
    arm_and_ack(o[23][0]);
    warp_arrive(sb + SM_SBAR);
#pragma unroll 1
    for (int cc = 0; cc < 8; cc++) {
      float acc[32];
      const uint32_t s0 = (cc & 1) * 2, b = ring.tile(s0);
      my_turn();
      wg_fence();
      static_for<0, 16>([&](auto K) { wgmma_rs_n64_tb1<K * 128, HI128>(acc, o[K], b, K != 0); });
      wg_commit();
      static_for<0, 16>([&](auto K) { wgmma_rs_n64_tb1<2048 + K * 128, HI128>(acc, K < 8 ? o[16 + (K & 7)] : qf[K & 7], b, 1); });
      wg_commit();
      your_turn();
      wg_wait<1>();
      ring.release(s0);
      if (cc & 1) recv_chunk(cc >> 1);
      wg_wait<0>();
      TRU(4);
      ring.release(s0 + 1);
      fence_regs(acc);
      if (cc & 1) keep_chunk(acc, cc >> 1);
      else send_chunk(acc, cc >> 1);
      if (cc == 6) g_issue(0);
    }
    TS(5);

    uint32_t H[14][4];
    {
      float acca[96], accb[16];
      const uint4* const statp = &p.s->stat[(rt * 8 + warp) * 8];
#pragma unroll 1
      for (int u = 0; u < 4; u++) {
        uint32_t fa[8][4];
        const uint32_t s0 = (u & 1) * 2, b = ring.tile(s0);
        mbar_wait(wbar, u & 1);
#pragma unroll
        for (int i = 0; i < 8; i++) lds128(wprv + 2 * SLOT + i * 512, fa[i]);
        verify8_tag0<512>(Gin + u * 256, fa);
        if (u < 2) g_issue(u + 1);
        const uint32_t ba = b + (j & 1) * 512, bb = b + ((j & 1) ? 4 : 1536);
        my_turn();
        wg_fence();
        static_for<0, 4>([&](auto K) { wgmma_rs_n32_tb1<LB_W1 + K * 128, HI128>(accb, fa[K], bb, (u | K) != 0); });
        static_for<0, 4>([&](auto K) { wgmma_rs_n192_tb1<LB_W1 + K * 128, HI128>(acca, fa[K], ba, (u | K) != 0); });
        wg_commit();
        static_for<0, 4>([&](auto K) { wgmma_rs_n32_tb1<LB_W1 + 2048 + K * 128, HI128>(accb, fa[4 + K], bb, 1); });
        static_for<0, 4>([&](auto K) { wgmma_rs_n192_tb1<LB_W1 + 2048 + K * 128, HI128>(acca, fa[4 + K], ba, 1); });
        wg_commit();
        your_turn();
        wg_wait<1>();
        ring.release(s0);
        if (u == 2) g_issue(3);
        if (u == 3) warp_bulk_load(wblk + 2 * SLOT, statp, 128, wbar + 16);
        wg_wait<0>();
        TRU(4);
        ring.release(s0 + 1);
      }
      fence_regs(acca);
      fence_regs(accb);
      TS(9);
      mbar_wait(bars + BAR_UV, 0);
      uint32_t xr[4];
      mbar_wait(wbar + 16, 1);
      lds128(wblk + 2 * SLOT + gq * 16, xr);
      {
        int spins = 0;
        while (((xr[0] ^ tag) & 1u) && ++spins < SPIN_LIMIT) ld_pkt(statp + gq, xr);
      }
      const float ra0 = __uint_as_float(xr[0]), rb0 = __uint_as_float(xr[1]), ra1 = __uint_as_float(xr[2]),
                  rb1 = __uint_as_float(xr[3]);
#pragma unroll
      for (int i = 0; i < 28; i++) {
        uint32_t m[4];
        lds128(sb + SM_TAB + (i * 4 + q) * 16, m);
        const float u0 = __uint_as_float(m[0]), u1 = __uint_as_float(m[1]), w0 = __uint_as_float(m[2]), w1 = __uint_as_float(m[3]);
        const float* acc = i < 24 ? acca + 4 * i : accb + 4 * (i - 24);
        const float z0 = fmaf(acc[0], ra0, fmaf(u0, rb0, w0)), z1 = fmaf(acc[1], ra0, fmaf(u1, rb0, w1));
        const float z2 = fmaf(acc[2], ra1, fmaf(u0, rb1, w0)), z3 = fmaf(acc[3], ra1, fmaf(u1, rb1, w1));
        H[i >> 1][(i & 1) * 2] = pack_bf16(fmaf(z0, tanh_hw(z0), z0), fmaf(z1, tanh_hw(z1), z1));
        H[i >> 1][(i & 1) * 2 + 1] = pack_bf16(fmaf(z2, tanh_hw(z2), z2), fmaf(z3, tanh_hw(z3), z3));
      }
    }
    fence_regs(H);
    TS(10);
    const int go = 24 + warp;
    {
      float accs[32], acck[32];
      auto ffn2 = [&](float (&acc)[32], uint32_t b) {
        const uint32_t ba = b + (j & 1) * 256, bb = b - (j & 1) * 1536;
        static_for<0, 14>([&](auto K) { wgmma_rs_n64_tb1<K * 128, HI128>(acc, H[K], K < 12 ? ba : bb, K != 0); });
        wg_commit();
      };
      {
        const uint32_t b = ring.tile(0);
        my_turn();
        wg_fence();
        ffn2(accs, b);
        your_turn();
        wg_wait<0>();
        TRU(4);
        ring.release(0);
        fence_regs(accs);
        send_chunk(accs, 4);
      }
#pragma unroll 1
      for (int pc = 0; pc < 3; pc++) {
        const uint32_t tk = 2 * pc + 1, ts = tk + 1;
        const uint32_t bk = ring.tile(tk & 3), bs = ring.tile(ts & 3);
        my_turn();
        wg_fence();
        ffn2(acck, bk);
        ffn2(accs, bs);
        your_turn();
        wg_wait<1>();
        ring.release(tk & 3);
        recv_chunk(4 + pc);
        fence_regs(acck);
        keep_chunk(acck, 4 + pc);
        wg_wait<0>();
        TRU(4);
        ring.release(ts & 3);
        fence_regs(accs);
        send_chunk(accs, 5 + pc);
      }
      const uint32_t b = ring.tile(3);
      my_turn();
      wg_fence();
      ffn2(acck, b);
      if (wg == 0) your_turn();
      recv_chunk(7);
      wg_wait<0>();
      fence_regs(acck);
      keep_chunk(acck, 7);
    }
    TS(11);
    {
      const uint4* const Pown = p.s->P + (size_t)(rt * 8 + j) * 4096 + go * 32 + lane;
      uint32_t r[4][4];
      float y[8];
      mbar_wait(bars + BAR_X2, 0);
      issue_pkts<0, 4>(Pown, 1024, r);
      verify4_rt<16384>(Pown, r, 0);
      TS(13);
#pragma unroll
      for (int s = 0; s < 4; s++) add_partial(y, r[s], 0x10000u, s == 0);
      const uint32_t gt = sb + SM_TAB + 1792 + ((go - 24) * 4 + q) * 8;
      store_out(p.out, (uint32_t)(rt * 128 + 16 * j + gq) * 256 + go * 8 + q, sb + SM_PARK + SLOT + (go >> 2) * 4096 + (go & 3) * 512 + lane * 16,
                lds32(gt), lds32(gt + 4), y);
    }
    TS(12);
    if (bid == 0 && tid == 0) asm volatile("st.relaxed.gpu.global.u32 [%0], %1;" ::"l"(&p.s->epoch), "r"(tag) : "memory");
  }
}

typedef CUresult (*EncodeFn)(CUtensorMap*, CUtensorMapDataType, cuuint32_t, void*, const cuuint64_t*, const cuuint64_t*,
                             const cuuint32_t*, const cuuint32_t*, CUtensorMapInterleave, CUtensorMapSwizzle,
                             CUtensorMapL2promotion, CUtensorMapFloatOOBfill);

static void make_map(EncodeFn fn, CUtensorMap* tm, const void* ptr, int inner, int rows, int cols, int box_rows, int box_outer,
                     CUtensorMapSwizzle swz) {
  cuuint64_t gd[3] = {(cuuint64_t)inner, (cuuint64_t)rows, (cuuint64_t)(cols / inner)};
  cuuint64_t gs[2] = {(cuuint64_t)cols * 2, (cuuint64_t)inner * 2};
  cuuint32_t bx[3] = {(cuuint32_t)inner, (cuuint32_t)box_rows, (cuuint32_t)box_outer};
  cuuint32_t es[3] = {1, 1, 1};
  fn(tm, CU_TENSOR_MAP_DATA_TYPE_BFLOAT16, 3, const_cast<void*>(ptr), gd, gs, bx, es, CU_TENSOR_MAP_INTERLEAVE_NONE, swz,
     CU_TENSOR_MAP_L2_PROMOTION_L2_128B, CU_TENSOR_MAP_FLOAT_OOB_FILL_NONE);
}

extern "C" void kernel_launch(void* const* d_in, const int* in_sizes, int n_in, void* d_out, int out_size) {
  (void)in_sizes; (void)n_in; (void)out_size;
  void* fnp = nullptr;
  cudaDriverEntryPointQueryResult qr;
  cudaGetDriverEntryPoint("cuTensorMapEncodeTiled", &fnp, cudaEnableDefault, &qr);
  EncodeFn fn = (EncodeFn)fnp;
  CUtensorMap tmWq, tmK, tmV, tmWo, tmW1, tmW2, tmWm, tmX;
  make_map(fn, &tmWq, d_in[3], 64, 512, 4096, 128, 2, CU_TENSOR_MAP_SWIZZLE_128B);
  make_map(fn, &tmK, d_in[1], 64, 8 * SK, 128, 128, 2, CU_TENSOR_MAP_SWIZZLE_128B);
  make_map(fn, &tmV, d_in[2], 64, 8 * SK, 128, 128, 2, CU_TENSOR_MAP_SWIZZLE_128B);
  make_map(fn, &tmWo, d_in[4], 64, 4096, 512, 256, 1, CU_TENSOR_MAP_SWIZZLE_128B);
  make_map(fn, &tmW1, d_in[6], 64, 512, FF, 64, 4, CU_TENSOR_MAP_SWIZZLE_128B);
  make_map(fn, &tmW2, d_in[7], 64, FF, 512, 224, 1, CU_TENSOR_MAP_SWIZZLE_128B);
  make_map(fn, &tmWm, d_in[9], 8, 512, 3072, 256, 1, CU_TENSOR_MAP_SWIZZLE_NONE);
  make_map(fn, &tmX, d_in[0], 16, 2048, 512, 16, 4, CU_TENSOR_MAP_SWIZZLE_NONE);
  Params p;
  p.x = (const __nv_bfloat16*)d_in[0];
  p.c = (const __nv_bfloat16*)d_in[8];
  p.wmod = (const __nv_bfloat16*)d_in[9];
  p.wo = (const __nv_bfloat16*)d_in[4];
  p.w1 = (const __nv_bfloat16*)d_in[6];
  p.w2 = (const __nv_bfloat16*)d_in[7];
  p.out = (__nv_bfloat16*)d_out;
  p.zero = 0;
  cudaGetSymbolAddress((void**)&p.s, g_scratch);
  cudaFuncSetAttribute(adaln_block_kernel, cudaFuncAttributeMaxDynamicSharedMemorySize, SM_TOTAL);
  cudaLaunchConfig_t cfg = {};
  cfg.gridDim = 128; cfg.blockDim = 512; cfg.dynamicSmemBytes = SM_TOTAL; cfg.stream = cudaStreamPerThread;
  cudaLaunchAttribute at[1];
  at[0].id = cudaLaunchAttributeClusterDimension; at[0].val.clusterDim.x = 2; at[0].val.clusterDim.y = 1; at[0].val.clusterDim.z = 1;
  cfg.attrs = at; cfg.numAttrs = 1;
  cudaLaunchKernelEx(&cfg, adaln_block_kernel, tmWq, tmK, tmV, tmWo, tmW1, tmW2, tmWm, tmX, p);
}
```

```cpp
#include <cuda_runtime.h>
#include <cuda_bf16.h>
#include <cuda.h>
#include <stdint.h>

template <int OFF, uint32_t HI>
__device__ __forceinline__ void wgmma_rs_n128_tb0(float (&d)[64], const uint32_t (&a)[4], uint32_t lo, int sd) {
  asm volatile("{\n.reg .pred p;\n.reg .b32 l;\n.reg .b64 db;\nsetp.ne.b32 p, %69, 0;\n"
    "add.u32 l, %68, %70;\nmov.b64 db, {l, %71};\n"
    "wgmma.mma_async.sync.aligned.m64n128k16.f32.bf16.bf16 "
    "{%0,%1,%2,%3,%4,%5,%6,%7,%8,%9,%10,%11,%12,%13,%14,%15,"
    "%16,%17,%18,%19,%20,%21,%22,%23,%24,%25,%26,%27,%28,%29,%30,%31,"
    "%32,%33,%34,%35,%36,%37,%38,%39,%40,%41,%42,%43,%44,%45,%46,%47,"
    "%48,%49,%50,%51,%52,%53,%54,%55,%56,%57,%58,%59,%60,%61,%62,%63}, "
    "{%64,%65,%66,%67}, db, p, 1, 1, 0;\n}\n"
    : "+f"(d[0]), "+f"(d[1]), "+f"(d[2]), "+f"(d[3]), "+f"(d[4]), "+f"(d[5]), "+f"(d[6]), "+f"(d[7]),
      "+f"(d[8]), "+f"(d[9]), "+f"(d[10]), "+f"(d[11]), "+f"(d[12]), "+f"(d[13]), "+f"(d[14]), "+f"(d[15]),
      "+f"(d[16]), "+f"(d[17]), "+f"(d[18]), "+f"(d[19]), "+f"(d[20]), "+f"(d[21]), "+f"(d[22]), "+f"(d[23]),
      "+f"(d[24]), "+f"(d[25]), "+f"(d[26]), "+f"(d[27]), "+f"(d[28]), "+f"(d[29]), "+f"(d[30]), "+f"(d[31]),
      "+f"(d[32]), "+f"(d[33]), "+f"(d[34]), "+f"(d[35]), "+f"(d[36]), "+f"(d[37]), "+f"(d[38]), "+f"(d[39]),
      "+f"(d[40]), "+f"(d[41]), "+f"(d[42]), "+f"(d[43]), "+f"(d[44]), "+f"(d[45]), "+f"(d[46]), "+f"(d[47]),
      "+f"(d[48]), "+f"(d[49]), "+f"(d[50]), "+f"(d[51]), "+f"(d[52]), "+f"(d[53]), "+f"(d[54]), "+f"(d[55]),
      "+f"(d[56]), "+f"(d[57]), "+f"(d[58]), "+f"(d[59]), "+f"(d[60]), "+f"(d[61]), "+f"(d[62]), "+f"(d[63])
    : "r"(a[0]), "r"(a[1]), "r"(a[2]), "r"(a[3]), "r"(lo), "r"(sd), "n"(OFF), "n"(HI));
}

template <int OFF, uint32_t HI>
__device__ __forceinline__ void wgmma_rs_n128_tb1(float (&d)[64], const uint32_t (&a)[4], uint32_t lo, int sd) {
  asm volatile("{\n.reg .pred p;\n.reg .b32 l;\n.reg .b64 db;\nsetp.ne.b32 p, %69, 0;\n"
    "add.u32 l, %68, %70;\nmov.b64 db, {l, %71};\n"
    "wgmma.mma_async.sync.aligned.m64n128k16.f32.bf16.bf16 "
    "{%0,%1,%2,%3,%4,%5,%6,%7,%8,%9,%10,%11,%12,%13,%14,%15,"
    "%16,%17,%18,%19,%20,%21,%22,%23,%24,%25,%26,%27,%28,%29,%30,%31,"
    "%32,%33,%34,%35,%36,%37,%38,%39,%40,%41,%42,%43,%44,%45,%46,%47,"
    "%48,%49,%50,%51,%52,%53,%54,%55,%56,%57,%58,%59,%60,%61,%62,%63}, "
    "{%64,%65,%66,%67}, db, p, 1, 1, 1;\n}\n"
    : "+f"(d[0]), "+f"(d[1]), "+f"(d[2]), "+f"(d[3]), "+f"(d[4]), "+f"(d[5]), "+f"(d[6]), "+f"(d[7]),
      "+f"(d[8]), "+f"(d[9]), "+f"(d[10]), "+f"(d[11]), "+f"(d[12]), "+f"(d[13]), "+f"(d[14]), "+f"(d[15]),
      "+f"(d[16]), "+f"(d[17]), "+f"(d[18]), "+f"(d[19]), "+f"(d[20]), "+f"(d[21]), "+f"(d[22]), "+f"(d[23]),
      "+f"(d[24]), "+f"(d[25]), "+f"(d[26]), "+f"(d[27]), "+f"(d[28]), "+f"(d[29]), "+f"(d[30]), "+f"(d[31]),
      "+f"(d[32]), "+f"(d[33]), "+f"(d[34]), "+f"(d[35]), "+f"(d[36]), "+f"(d[37]), "+f"(d[38]), "+f"(d[39]),
      "+f"(d[40]), "+f"(d[41]), "+f"(d[42]), "+f"(d[43]), "+f"(d[44]), "+f"(d[45]), "+f"(d[46]), "+f"(d[47]),
      "+f"(d[48]), "+f"(d[49]), "+f"(d[50]), "+f"(d[51]), "+f"(d[52]), "+f"(d[53]), "+f"(d[54]), "+f"(d[55]),
      "+f"(d[56]), "+f"(d[57]), "+f"(d[58]), "+f"(d[59]), "+f"(d[60]), "+f"(d[61]), "+f"(d[62]), "+f"(d[63])
    : "r"(a[0]), "r"(a[1]), "r"(a[2]), "r"(a[3]), "r"(lo), "r"(sd), "n"(OFF), "n"(HI));
}

template <int OFF, uint32_t HI>
__device__ __forceinline__ void wgmma_rs_n192_tb1(float (&d)[96], const uint32_t (&a)[4], uint32_t lo, int sd) {
  asm volatile("{\n.reg .pred p;\n.reg .b32 l;\n.reg .b64 db;\nsetp.ne.b32 p, %101, 0;\n"
    "add.u32 l, %100, %102;\nmov.b64 db, {l, %103};\n"
    "wgmma.mma_async.sync.aligned.m64n192k16.f32.bf16.bf16 "
    "{%0,%1,%2,%3,%4,%5,%6,%7,%8,%9,%10,%11,%12,%13,%14,%15,"
    "%16,%17,%18,%19,%20,%21,%22,%23,%24,%25,%26,%27,%28,%29,%30,%31,"
    "%32,%33,%34,%35,%36,%37,%38,%39,%40,%41,%42,%43,%44,%45,%46,%47,"
    "%48,%49,%50,%51,%52,%53,%54,%55,%56,%57,%58,%59,%60,%61,%62,%63,"
    "%64,%65,%66,%67,%68,%69,%70,%71,%72,%73,%74,%75,%76,%77,%78,%79,"
    "%80,%81,%82,%83,%84,%85,%86,%87,%88,%89,%90,%91,%92,%93,%94,%95}, "
    "{%96,%97,%98,%99}, db, p, 1, 1, 1;\n}\n"
    : "+f"(d[0]), "+f"(d[1]), "+f"(d[2]), "+f"(d[3]), "+f"(d[4]), "+f"(d[5]), "+f"(d[6]), "+f"(d[7]),
      "+f"(d[8]), "+f"(d[9]), "+f"(d[10]), "+f"(d[11]), "+f"(d[12]), "+f"(d[13]), "+f"(d[14]), "+f"(d[15]),
      "+f"(d[16]), "+f"(d[17]), "+f"(d[18]), "+f"(d[19]), "+f"(d[20]), "+f"(d[21]), "+f"(d[22]), "+f"(d[23]),
      "+f"(d[24]), "+f"(d[25]), "+f"(d[26]), "+f"(d[27]), "+f"(d[28]), "+f"(d[29]), "+f"(d[30]), "+f"(d[31]),
      "+f"(d[32]), "+f"(d[33]), "+f"(d[34]), "+f"(d[35]), "+f"(d[36]), "+f"(d[37]), "+f"(d[38]), "+f"(d[39]),
      "+f"(d[40]), "+f"(d[41]), "+f"(d[42]), "+f"(d[43]), "+f"(d[44]), "+f"(d[45]), "+f"(d[46]), "+f"(d[47]),
      "+f"(d[48]), "+f"(d[49]), "+f"(d[50]), "+f"(d[51]), "+f"(d[52]), "+f"(d[53]), "+f"(d[54]), "+f"(d[55]),
      "+f"(d[56]), "+f"(d[57]), "+f"(d[58]), "+f"(d[59]), "+f"(d[60]), "+f"(d[61]), "+f"(d[62]), "+f"(d[63]),
      "+f"(d[64]), "+f"(d[65]), "+f"(d[66]), "+f"(d[67]), "+f"(d[68]), "+f"(d[69]), "+f"(d[70]), "+f"(d[71]),
      "+f"(d[72]), "+f"(d[73]), "+f"(d[74]), "+f"(d[75]), "+f"(d[76]), "+f"(d[77]), "+f"(d[78]), "+f"(d[79]),
      "+f"(d[80]), "+f"(d[81]), "+f"(d[82]), "+f"(d[83]), "+f"(d[84]), "+f"(d[85]), "+f"(d[86]), "+f"(d[87]),
      "+f"(d[88]), "+f"(d[89]), "+f"(d[90]), "+f"(d[91]), "+f"(d[92]), "+f"(d[93]), "+f"(d[94]), "+f"(d[95])
    : "r"(a[0]), "r"(a[1]), "r"(a[2]), "r"(a[3]), "r"(lo), "r"(sd), "n"(OFF), "n"(HI));
}

template <int OFF, uint32_t HI>
__device__ __forceinline__ void wgmma_rs_n32_tb1(float (&d)[16], const uint32_t (&a)[4], uint32_t lo, int sd) {
  asm volatile("{\n.reg .pred p;\n.reg .b32 l;\n.reg .b64 db;\nsetp.ne.b32 p, %21, 0;\n"
    "add.u32 l, %20, %22;\nmov.b64 db, {l, %23};\n"
    "wgmma.mma_async.sync.aligned.m64n32k16.f32.bf16.bf16 "
    "{%0,%1,%2,%3,%4,%5,%6,%7,%8,%9,%10,%11,%12,%13,%14,%15}, "
    "{%16,%17,%18,%19}, db, p, 1, 1, 1;\n}\n"
    : "+f"(d[0]), "+f"(d[1]), "+f"(d[2]), "+f"(d[3]), "+f"(d[4]), "+f"(d[5]), "+f"(d[6]), "+f"(d[7]),
      "+f"(d[8]), "+f"(d[9]), "+f"(d[10]), "+f"(d[11]), "+f"(d[12]), "+f"(d[13]), "+f"(d[14]), "+f"(d[15])
    : "r"(a[0]), "r"(a[1]), "r"(a[2]), "r"(a[3]), "r"(lo), "r"(sd), "n"(OFF), "n"(HI));
}

template <int OFF, uint32_t HI>
__device__ __forceinline__ void wgmma_rs_n64_tb1(float (&d)[32], const uint32_t (&a)[4], uint32_t lo, int sd) {
  asm volatile("{\n.reg .pred p;\n.reg .b32 l;\n.reg .b64 db;\nsetp.ne.b32 p, %37, 0;\n"
    "add.u32 l, %36, %38;\nmov.b64 db, {l, %39};\n"
    "wgmma.mma_async.sync.aligned.m64n64k16.f32.bf16.bf16 "
    "{%0,%1,%2,%3,%4,%5,%6,%7,%8,%9,%10,%11,%12,%13,%14,%15,"
    "%16,%17,%18,%19,%20,%21,%22,%23,%24,%25,%26,%27,%28,%29,%30,%31}, "
    "{%32,%33,%34,%35}, db, p, 1, 1, 1;\n}\n"
    : "+f"(d[0]), "+f"(d[1]), "+f"(d[2]), "+f"(d[3]), "+f"(d[4]), "+f"(d[5]), "+f"(d[6]), "+f"(d[7]),
      "+f"(d[8]), "+f"(d[9]), "+f"(d[10]), "+f"(d[11]), "+f"(d[12]), "+f"(d[13]), "+f"(d[14]), "+f"(d[15]),
      "+f"(d[16]), "+f"(d[17]), "+f"(d[18]), "+f"(d[19]), "+f"(d[20]), "+f"(d[21]), "+f"(d[22]), "+f"(d[23]),
      "+f"(d[24]), "+f"(d[25]), "+f"(d[26]), "+f"(d[27]), "+f"(d[28]), "+f"(d[29]), "+f"(d[30]), "+f"(d[31])
    : "r"(a[0]), "r"(a[1]), "r"(a[2]), "r"(a[3]), "r"(lo), "r"(sd), "n"(OFF), "n"(HI));
}

template <int STR>
__device__ __forceinline__ void verify8_tag1(const uint4* p, uint32_t (*r)[4]) {
  asm volatile("{\n.reg .pred p, q;\n.reg .b32 a, n;\nmov.u32 n, 0;\n"
    "LAB_CHK:\n"
    "and.b32 a, %0, %4;\n"
    "and.b32 a, a, %8;\n"
    "and.b32 a, a, %12;\n"
    "and.b32 a, a, %16;\n"
    "and.b32 a, a, %20;\n"
    "and.b32 a, a, %24;\n"
    "and.b32 a, a, %28;\n"
    "and.b32 a, a, 1;\nsetp.eq.u32 p, a, 1;\nvote.sync.all.pred p, p, 0xffffffff;\n"
    "@p bra.uni LAB_OK;\n"
    "and.b32 a, %0, 1;\nsetp.ne.u32 q, a, 1;\n"
    "@q ld.relaxed.gpu.global.v4.b32 {%0,%1,%2,%3}, [%32+%33];\n"
    "and.b32 a, %4, 1;\nsetp.ne.u32 q, a, 1;\n"
    "@q ld.relaxed.gpu.global.v4.b32 {%4,%5,%6,%7}, [%32+%34];\n"
    "and.b32 a, %8, 1;\nsetp.ne.u32 q, a, 1;\n"
    "@q ld.relaxed.gpu.global.v4.b32 {%8,%9,%10,%11}, [%32+%35];\n"
    "and.b32 a, %12, 1;\nsetp.ne.u32 q, a, 1;\n"
    "@q ld.relaxed.gpu.global.v4.b32 {%12,%13,%14,%15}, [%32+%36];\n"
    "and.b32 a, %16, 1;\nsetp.ne.u32 q, a, 1;\n"
    "@q ld.relaxed.gpu.global.v4.b32 {%16,%17,%18,%19}, [%32+%37];\n"
    "and.b32 a, %20, 1;\nsetp.ne.u32 q, a, 1;\n"
    "@q ld.relaxed.gpu.global.v4.b32 {%20,%21,%22,%23}, [%32+%38];\n"
    "and.b32 a, %24, 1;\nsetp.ne.u32 q, a, 1;\n"
    "@q ld.relaxed.gpu.global.v4.b32 {%24,%25,%26,%27}, [%32+%39];\n"
    "and.b32 a, %28, 1;\nsetp.ne.u32 q, a, 1;\n"
    "@q ld.relaxed.gpu.global.v4.b32 {%28,%29,%30,%31}, [%32+%40];\n"
    "add.u32 n, n, 1;\nsetp.lt.u32 q, n, 262144;\n@q bra.uni LAB_CHK;\n"
    "LAB_OK:\n"
    "}\n"
    : "+r"(r[0][0]), "+r"(r[0][1]), "+r"(r[0][2]), "+r"(r[0][3]), "+r"(r[1][0]), "+r"(r[1][1]), "+r"(r[1][2]), "+r"(r[1][3]),
      "+r"(r[2][0]), "+r"(r[2][1]), "+r"(r[2][2]), "+r"(r[2][3]), "+r"(r[3][0]), "+r"(r[3][1]), "+r"(r[3][2]), "+r"(r[3][3]),
      "+r"(r[4][0]), "+r"(r[4][1]), "+r"(r[4][2]), "+r"(r[4][3]), "+r"(r[5][0]), "+r"(r[5][1]), "+r"(r[5][2]), "+r"(r[5][3]),
      "+r"(r[6][0]), "+r"(r[6][1]), "+r"(r[6][2]), "+r"(r[6][3]), "+r"(r[7][0]), "+r"(r[7][1]), "+r"(r[7][2]), "+r"(r[7][3])
    : "l"(p), "n"(0 * STR), "n"(1 * STR), "n"(2 * STR), "n"(3 * STR), "n"(4 * STR), "n"(5 * STR), "n"(6 * STR), "n"(7 * STR)
    : "memory");
}

template <int STR>
__device__ __forceinline__ void verify4_rt(const uint4* p, uint32_t (*r)[4], uint32_t tag) {
  asm volatile("{\n.reg .pred p, q;\n.reg .b32 a, b, n;\nmov.u32 n, 0;\n"
    "LAB_CHK:\n"
    "lop3.b32 a, %0, %4, %21, 0x7e;\n"
    "lop3.b32 b, %8, %12, %21, 0x7e;\nor.b32 a, a, b;\n"
    "and.b32 a, a, 1;\nsetp.eq.u32 p, a, 0;\nvote.sync.all.pred p, p, 0xffffffff;\n"
    "@p bra.uni LAB_OK;\n"
    "and.b32 a, %0, 1;\nsetp.ne.u32 q, a, %21;\n"
    "@q ld.relaxed.gpu.global.v4.b32 {%0,%1,%2,%3}, [%16+%17];\n"
    "and.b32 a, %4, 1;\nsetp.ne.u32 q, a, %21;\n"
    "@q ld.relaxed.gpu.global.v4.b32 {%4,%5,%6,%7}, [%16+%18];\n"
    "and.b32 a, %8, 1;\nsetp.ne.u32 q, a, %21;\n"
    "@q ld.relaxed.gpu.global.v4.b32 {%8,%9,%10,%11}, [%16+%19];\n"
    "and.b32 a, %12, 1;\nsetp.ne.u32 q, a, %21;\n"
    "@q ld.relaxed.gpu.global.v4.b32 {%12,%13,%14,%15}, [%16+%20];\n"
    "add.u32 n, n, 1;\nsetp.lt.u32 q, n, 262144;\n@q bra.uni LAB_CHK;\n"
    "LAB_OK:\n}\n"
    : "+r"(r[0][0]), "+r"(r[0][1]), "+r"(r[0][2]), "+r"(r[0][3]), "+r"(r[1][0]), "+r"(r[1][1]), "+r"(r[1][2]), "+r"(r[1][3]),
      "+r"(r[2][0]), "+r"(r[2][1]), "+r"(r[2][2]), "+r"(r[2][3]), "+r"(r[3][0]), "+r"(r[3][1]), "+r"(r[3][2]), "+r"(r[3][3])
    : "l"(p), "n"(0 * STR), "n"(1 * STR), "n"(2 * STR), "n"(3 * STR), "r"(tag)
    : "memory");
}

template <int STR>
__device__ __forceinline__ void verify8_tag0(const uint4* p, uint32_t (*r)[4]) {
  asm volatile("{\n.reg .pred p, q;\n.reg .b32 a, n;\nmov.u32 n, 0;\n"
    "LAB_CHK:\n"
    "or.b32 a, %0, %4;\n"
    "or.b32 a, a, %8;\n"
    "or.b32 a, a, %12;\n"
    "or.b32 a, a, %16;\n"
    "or.b32 a, a, %20;\n"
    "or.b32 a, a, %24;\n"
    "or.b32 a, a, %28;\n"
    "and.b32 a, a, 1;\nsetp.eq.u32 p, a, 0;\nvote.sync.all.pred p, p, 0xffffffff;\n"
    "@p bra.uni LAB_OK;\n"
    "and.b32 a, %0, 1;\nsetp.ne.u32 q, a, 0;\n"
    "@q ld.relaxed.gpu.global.v4.b32 {%0,%1,%2,%3}, [%32+%33];\n"
    "and.b32 a, %4, 1;\nsetp.ne.u32 q, a, 0;\n"
    "@q ld.relaxed.gpu.global.v4.b32 {%4,%5,%6,%7}, [%32+%34];\n"
    "and.b32 a, %8, 1;\nsetp.ne.u32 q, a, 0;\n"
    "@q ld.relaxed.gpu.global.v4.b32 {%8,%9,%10,%11}, [%32+%35];\n"
    "and.b32 a, %12, 1;\nsetp.ne.u32 q, a, 0;\n"
    "@q ld.relaxed.gpu.global.v4.b32 {%12,%13,%14,%15}, [%32+%36];\n"
    "and.b32 a, %16, 1;\nsetp.ne.u32 q, a, 0;\n"
    "@q ld.relaxed.gpu.global.v4.b32 {%16,%17,%18,%19}, [%32+%37];\n"
    "and.b32 a, %20, 1;\nsetp.ne.u32 q, a, 0;\n"
    "@q ld.relaxed.gpu.global.v4.b32 {%20,%21,%22,%23}, [%32+%38];\n"
    "and.b32 a, %24, 1;\nsetp.ne.u32 q, a, 0;\n"
    "@q ld.relaxed.gpu.global.v4.b32 {%24,%25,%26,%27}, [%32+%39];\n"
    "and.b32 a, %28, 1;\nsetp.ne.u32 q, a, 0;\n"
    "@q ld.relaxed.gpu.global.v4.b32 {%28,%29,%30,%31}, [%32+%40];\n"
    "add.u32 n, n, 1;\nsetp.lt.u32 q, n, 262144;\n@q bra.uni LAB_CHK;\n"
    "LAB_OK:\n"
    "or.b32 %0, %0, 1;\n"
    "or.b32 %4, %4, 1;\n"
    "or.b32 %8, %8, 1;\n"
    "or.b32 %12, %12, 1;\n"
    "or.b32 %16, %16, 1;\n"
    "or.b32 %20, %20, 1;\n"
    "or.b32 %24, %24, 1;\n"
    "or.b32 %28, %28, 1;\n"
    "}\n"
    : "+r"(r[0][0]), "+r"(r[0][1]), "+r"(r[0][2]), "+r"(r[0][3]), "+r"(r[1][0]), "+r"(r[1][1]), "+r"(r[1][2]), "+r"(r[1][3]),
      "+r"(r[2][0]), "+r"(r[2][1]), "+r"(r[2][2]), "+r"(r[2][3]), "+r"(r[3][0]), "+r"(r[3][1]), "+r"(r[3][2]), "+r"(r[3][3]),
      "+r"(r[4][0]), "+r"(r[4][1]), "+r"(r[4][2]), "+r"(r[4][3]), "+r"(r[5][0]), "+r"(r[5][1]), "+r"(r[5][2]), "+r"(r[5][3]),
      "+r"(r[6][0]), "+r"(r[6][1]), "+r"(r[6][2]), "+r"(r[6][3]), "+r"(r[7][0]), "+r"(r[7][1]), "+r"(r[7][2]), "+r"(r[7][3])
    : "l"(p), "n"(0 * STR), "n"(1 * STR), "n"(2 * STR), "n"(3 * STR), "n"(4 * STR), "n"(5 * STR), "n"(6 * STR), "n"(7 * STR)
    : "memory");
}

#define SPIN_LIMIT (1 << 18)

__device__ __forceinline__ uint32_t smem_u32(const void* p) { return (uint32_t)__cvta_generic_to_shared(p); }
__device__ __forceinline__ void mbar_init(uint32_t a, uint32_t c) {
  asm volatile("mbarrier.init.shared::cta.b64 [%0], %1;" ::"r"(a), "r"(c) : "memory");
}
__device__ __forceinline__ void mbar_expect(uint32_t a, uint32_t b) {
  asm volatile("mbarrier.arrive.expect_tx.shared::cta.b64 _, [%0], %1;" ::"r"(a), "r"(b) : "memory");
}
__device__ __forceinline__ void mbar_arrive(uint32_t a) {
  asm volatile("mbarrier.arrive.shared::cta.b64 _, [%0];" ::"r"(a) : "memory");
}
__device__ __forceinline__ void mbar_wait(uint32_t a, uint32_t parity) {
  asm volatile(
      "{\n.reg .pred p;\n.reg .u32 n;\nmov.u32 n, 0;\n"
      "LAB_WAIT:\n"
      "mbarrier.try_wait.parity.shared::cta.b64 p, [%0], %1;\n"
      "@p bra LAB_DONE;\n"
      "add.u32 n, n, 1;\n"
      "setp.lt.u32 p, n, 262144;\n"
      "@p bra LAB_WAIT;\n"
      "LAB_DONE:\n}\n" ::"r"(a), "r"(parity) : "memory");
}
__device__ __forceinline__ bool mbar_test(uint32_t a, uint32_t parity) {
  uint32_t ok;
  asm volatile("{\n.reg .pred p;\nmbarrier.test_wait.parity.shared::cta.b64 p, [%1], %2;\nselp.u32 %0, 1, 0, p;\n}\n"
               : "=r"(ok) : "r"(a), "r"(parity) : "memory");
  return ok;
}
__device__ __forceinline__ void tma3d(uint32_t dst, const CUtensorMap* tm, uint32_t bar, int c0, int c1, int c2) {
  asm volatile(
      "cp.async.bulk.tensor.3d.shared::cluster.global.mbarrier::complete_tx::bytes [%0], [%1, {%3,%4,%5}], [%2];"
      ::"r"(dst), "l"(tm), "r"(bar), "r"(c0), "r"(c1), "r"(c2) : "memory");
}
__device__ __forceinline__ void wg_fence() { asm volatile("wgmma.fence.sync.aligned;" ::: "memory"); }
__device__ __forceinline__ void wg_commit() { asm volatile("wgmma.commit_group.sync.aligned;" ::: "memory"); }
template <int N> __device__ __forceinline__ void wg_wait() {
  asm volatile("wgmma.wait_group.sync.aligned %0;" ::"n"(N) : "memory");
}
template <int N> __device__ __forceinline__ void fence_regs(float (&d)[N]) {
#pragma unroll
  for (int i = 0; i < N; i++) asm volatile("" : "+f"(d[i])::"memory");
}
template <int N> __device__ __forceinline__ void fence_regs(uint32_t (&d)[N][4]) {
#pragma unroll
  for (int i = 0; i < N; i++) asm volatile("" : "+r"(d[i][0]), "+r"(d[i][1]), "+r"(d[i][2]), "+r"(d[i][3])::"memory");
}
template <int N> __device__ __forceinline__ void fence_frags(uint32_t (*d)[4]) {
#pragma unroll
  for (int i = 0; i < N; i++) asm volatile("" : "+r"(d[i][0]), "+r"(d[i][1]), "+r"(d[i][2]), "+r"(d[i][3])::"memory");
}
__device__ __forceinline__ void bar_sync(int id, int n) { asm volatile("bar.sync %0, %1;" ::"r"(id), "r"(n) : "memory"); }
__device__ __forceinline__ void bar_arrive(int id, int n) { asm volatile("bar.arrive %0, %1;" ::"r"(id), "r"(n) : "memory"); }

__device__ __forceinline__ uint32_t pack_bf16(float lo, float hi) {
  uint32_t r;
  asm("cvt.rn.bf16x2.f32 %0, %1, %2;" : "=r"(r) : "f"(hi), "f"(lo));
  return r;
}
__device__ __forceinline__ float bf_lo(uint32_t w) { return __uint_as_float(w << 16); }
__device__ __forceinline__ float bf_hi(uint32_t w) { return __uint_as_float(w & 0xFFFF0000u); }
__device__ __forceinline__ float round_bf16(float x) { return bf_lo(pack_bf16(x, 0.f)); }
__device__ __forceinline__ uint32_t hfma2_bf16(uint32_t a, uint32_t b, uint32_t c) {
  uint32_t r;
  asm("fma.rn.bf16x2 %0, %1, %2, %3;" : "=r"(r) : "r"(a), "r"(b), "r"(c));
  return r;
}
__device__ __forceinline__ float ex2(float x) {
  float r;
  asm("ex2.approx.ftz.f32 %0, %1;" : "=f"(r) : "f"(x));
  return r;
}
__device__ __forceinline__ float tanh_hw(float x) {
  float r;
  asm("tanh.approx.f32 %0, %1;" : "=f"(r) : "f"(x));
  return r;
}
template <int TAG> __device__ __forceinline__ uint32_t pack_tag(float lo, float hi) {
  uint32_t w = __byte_perm(__float_as_uint(lo), pack_bf16(lo, hi), 0x7632);
  return TAG ? (w | 1u) : (w & ~1u);
}
__device__ __forceinline__ void st_pkt(uint4* p, uint32_t a, uint32_t b, uint32_t c, uint32_t d) {
  asm volatile(
      "st.relaxed.gpu.global.v4.b32 [%0], {%1,%2,%3,%4};" ::"l"(p), "r"(a), "r"(b), "r"(c), "r"(d) : "memory");
}
__device__ __forceinline__ void ld_pkt(const uint4* p, uint32_t (&r)[4]) {
  asm volatile(
      "ld.relaxed.gpu.global.v4.b32 {%0,%1,%2,%3}, [%4];"
      : "=r"(r[0]), "=r"(r[1]), "=r"(r[2]), "=r"(r[3]) : "l"(p) : "memory");
}
__device__ __forceinline__ uint32_t ldg32(const void* p) {
  uint32_t r;
  asm volatile("ld.global.nc.b32 %0, [%1];" : "=r"(r) : "l"(p));
  return r;
}
__device__ __forceinline__ uint32_t ldg16(const void* p) {
  uint16_t r;
  asm volatile("ld.global.nc.b16 %0, [%1];" : "=h"(r) : "l"(p));
  return r;
}
__device__ __forceinline__ uint4 ldg128(const void* p) {
  uint4 r;
  asm volatile("ld.global.nc.v4.b32 {%0,%1,%2,%3}, [%4];" : "=r"(r.x), "=r"(r.y), "=r"(r.z), "=r"(r.w) : "l"(p));
  return r;
}
__device__ __forceinline__ void l2_prefetch(const void* p, uint32_t bytes) {
  asm volatile("cp.async.bulk.prefetch.L2.global [%0], %1;" ::"l"(p), "r"(bytes) : "memory");
}
__device__ __forceinline__ float rcp_hw(float x) {
  float r;
  asm("rcp.approx.ftz.f32 %0, %1;" : "=f"(r) : "f"(x));
  return r;
}
__device__ __forceinline__ void warp_bulk_load(uint32_t sdst, const void* gsrc, uint32_t bytes, uint32_t bar) {
  asm volatile(
      "{\n.reg .pred p;\nelect.sync _|p, 0xffffffff;\n"
      "@p mbarrier.arrive.expect_tx.shared::cta.b64 _, [%3], %2;\n"
      "@p cp.async.bulk.shared::cluster.global.mbarrier::complete_tx::bytes [%0], [%1], %2, [%3];\n}\n"
      ::"r"(sdst), "l"(gsrc), "r"(bytes), "r"(bar) : "memory");
}
__device__ __forceinline__ void warp_tma3d(uint32_t dst, const CUtensorMap* tm, uint32_t bar, uint32_t bytes, int c1, int c2) {
  asm volatile(
      "{\n.reg .pred p;\nelect.sync _|p, 0xffffffff;\n"
      "@p mbarrier.arrive.expect_tx.shared::cta.b64 _, [%2], %3;\n"
      "@p cp.async.bulk.tensor.3d.shared::cluster.global.mbarrier::complete_tx::bytes [%0], [%1, {%6,%4,%5}], [%2];\n}\n"
      ::"r"(dst), "l"(tm), "r"(bar), "r"(bytes), "r"(c1), "r"(c2), "r"(0) : "memory");
}
__device__ __forceinline__ bool elect_one() {
  uint32_t r;
  asm volatile("{\n.reg .pred p;\nelect.sync _|p, 0xffffffff;\nselp.u32 %0, 1, 0, p;\n}\n" : "=r"(r));
  return r;
}
__device__ __forceinline__ void warp_arrive(uint32_t bar) {
  asm volatile("{\n.reg .pred p;\nelect.sync _|p, 0xffffffff;\n@p mbarrier.arrive.shared::cta.b64 _, [%0];\n}\n" ::"r"(bar) : "memory");
}
__device__ __forceinline__ uint32_t pack_trunc(float lo, float hi) {
  return __byte_perm(__float_as_uint(lo), __float_as_uint(hi), 0x7632);
}
__device__ __forceinline__ void add_partial(float (&y)[8], const uint32_t (&r)[4], uint32_t c0, bool first) {
#pragma unroll
  for (int e = 0; e < 4; e++) {
    const float lo = __uint_as_float(r[e] * 65536u + (e ? 0x8000u : c0)), hi = __uint_as_float(r[e]);
    y[2 * e] = first ? lo : y[2 * e] + lo;
    y[2 * e + 1] = first ? hi : y[2 * e + 1] + hi;
  }
}
__device__ __forceinline__ void spin_cycles(uint32_t n) {
  uint32_t t0, t;
  asm volatile("mov.u32 %0, %%clock;" : "=r"(t0));
  do { asm volatile("mov.u32 %0, %%clock;" : "=r"(t)); } while (t - t0 < n);
}
__device__ __forceinline__ void sts128(uint32_t a, uint32_t x, uint32_t y, uint32_t z, uint32_t w) {
  asm volatile("st.shared.v4.b32 [%0], {%1,%2,%3,%4};" ::"r"(a), "r"(x), "r"(y), "r"(z), "r"(w) : "memory");
}
__device__ __forceinline__ void lds128(uint32_t a, uint32_t (&r)[4]) {
  asm volatile("ld.shared.v4.b32 {%0,%1,%2,%3}, [%4];" : "=r"(r[0]), "=r"(r[1]), "=r"(r[2]), "=r"(r[3]) : "r"(a) : "memory");
}

__device__ __forceinline__ uint32_t lds32(uint32_t a) {
  uint32_t r;
  asm volatile("ld.shared.b32 %0, [%1];" : "=r"(r) : "r"(a) : "memory");
  return r;
}
__device__ __forceinline__ void store_out(__nv_bfloat16* out, uint32_t woff, uint32_t x2s, uint32_t gb0, uint32_t gb1,
                                          const float (&y)[8]) {
  const uint32_t gb[2] = {gb0, gb1};
  uint32_t xa[2][4];
  lds128(x2s, xa[0]);
  lds128(x2s + 2048, xa[1]);
  uint32_t* const oo = (uint32_t*)out + woff;
#pragma unroll
  for (int e = 0; e < 4; e++)
    oo[(e >> 1) * 4 + (e & 1) * 8 * 256] =
        pack_bf16(fmaf(bf_lo(gb[e >> 1]), y[2 * e], __uint_as_float(xa[e >> 1][(e & 1) * 2])),
                  fmaf(bf_hi(gb[e >> 1]), y[2 * e + 1], __uint_as_float(xa[e >> 1][(e & 1) * 2 + 1])));
}

constexpr int SK = 2048, WIN = 512;
constexpr int FF = 1792, FSL = 224;
constexpr int NTILES = 80;
constexpr int NSLOT = 4;
constexpr uint32_t SLOT = 32768;
constexpr uint32_t SM_PARK = 0;
constexpr uint32_t SM_RING = 3 * SLOT;
constexpr uint32_t SM_TAB = 7 * SLOT;
constexpr uint32_t SM_RED = SM_TAB + 2048;
constexpr uint32_t SM_BAR = SM_RED + 256;
constexpr uint32_t SM_WBAR = SM_BAR + 128;
constexpr uint32_t SM_SBAR = SM_WBAR + 256;
constexpr uint32_t BAR_SLAB = 64, BAR_UV = 72, BAR_X2 = 80, BAR_TAG = 88, BAR_KMAX = 96;
constexpr uint32_t SM_DBAR = SM_SBAR + 16;
constexpr uint32_t SM_TOTAL = SM_DBAR + 128;

struct Scratch {
  uint4 P[16 * 8 * 4 * 1024];
  uint4 G[16 * 8 * 32 * 32];
  uint4 mod1[8 * 256];
  uint4 mod2[512];
  uint4 uv[2 * 448];
  uint4 stat[16 * 8 * 8];
  uint4 kmax[8 * 16 * 4 * 2];
  uint32_t sent[16 * 8 * 8];
  uint32_t epoch;
};
__device__ Scratch g_scratch;

#define TS(i) do { } while (0)
#define TR(code)
#define CK_(v)
#define CKS(i, v)

#define TRU(code)

struct Params {
  const __nv_bfloat16* x;
  const __nv_bfloat16* k;
  const __nv_bfloat16* c;
  const __nv_bfloat16* wmod;
  const __nv_bfloat16* wo;
  const __nv_bfloat16* w1;
  const __nv_bfloat16* w2;
  __nv_bfloat16* out;
  Scratch* s;
  uint32_t zero;
};

constexpr uint32_t HI128 = (1024 >> 4) | (1u << 30);
constexpr int LB_MN128 = (16384 >> 4) << 16;
constexpr int LB_K128 = 1 << 16;
constexpr int LB_W1 = (8192 >> 4) << 16;

template <int I> struct IC {
  __host__ __device__ constexpr operator int() const { return I; }
};
template <int I, int N, typename F> __device__ __forceinline__ void static_for(F&& f) {
  if constexpr (I < N) {
    f(IC<I>{});
    static_for<I + 1, N>(f);
  }
}

struct Ring {
  uint32_t base16, bars;
  __device__ __forceinline__ uint32_t tile(uint32_t slot) const { return base16 + slot * (SLOT >> 4); }
  __device__ __forceinline__ void release(uint32_t slot) const {
    warp_arrive(bars + 32 + slot * 8);
  }
};

__device__ __forceinline__ float silu_c(uint32_t bits) {
  float x = bf_lo(bits);
  return round_bf16(x * rcp_hw(1.f + ex2(-1.4426950408889634f * x)));
}
__device__ __forceinline__ void pack8(uint32_t (&o)[4], const float* v) {
  o[0] = pack_bf16(v[0], v[1]); o[1] = pack_bf16(v[2], v[3]); o[2] = pack_bf16(v[4], v[5]); o[3] = pack_bf16(v[6], v[7]);
}

template <int TAG, int N>
__device__ __forceinline__ void issue_pkts(const uint4* p, int stride, uint32_t (*r)[4]) {
#pragma unroll
  for (int i = 0; i < N; i++) ld_pkt(p + i * stride, r[i]);
}
__device__ __forceinline__ void wait_sent(const uint32_t* p, uint32_t tag, uint32_t step) {
#pragma unroll 1
  for (int spins = 0; spins < SPIN_LIMIT; spins++) {
    uint32_t v;
    asm volatile("ld.relaxed.gpu.global.u32 %0, [%1];" : "=r"(v) : "l"(p) : "memory");
    if (__all_sync(0xffffffffu, v - (tag * 32 + step + 1) < 16u)) break;
  }
}
__device__ __forceinline__ void ld_mod(const uint4* p, uint32_t tag, uint32_t (&r)[4]) {
  int spins = 0;
  ld_pkt(p, r);
  while (r[2] != tag && ++spins < SPIN_LIMIT) ld_pkt(p, r);
}

#define EARLY_TILES 2
#define PF_WMOD 1
#define MOD1_DELAY 500
#define RED3_UNIT 3
#define NITEM2 24
#define FIN_DELAY0 800
#define FIN_DELAY1 0
#define PRE_EXP 8
#define O_EARLY 12
#define G_DELAY 300

__device__ __forceinline__ float reduce8(float (&a)[8], int lane) {
  const bool h16 = lane & 16, h8 = lane & 8, h4 = lane & 4;
#pragma unroll
  for (int k = 0; k < 4; k++) a[k] = (h16 ? a[k + 4] : a[k]) + __shfl_xor_sync(0xffffffffu, h16 ? a[k] : a[k + 4], 16);
#pragma unroll
  for (int k = 0; k < 2; k++) a[k] = (h8 ? a[k + 2] : a[k]) + __shfl_xor_sync(0xffffffffu, h8 ? a[k] : a[k + 2], 8);
  const float r = (h4 ? a[1] : a[0]) + __shfl_xor_sync(0xffffffffu, h4 ? a[0] : a[1], 4);
  return r + __shfl_xor_sync(0xffffffffu, r, 2);
}
__device__ __forceinline__ void fma8(float (&a)[8], float s, uint32_t w0, uint32_t w1, uint32_t w2, uint32_t w3) {
  a[0] = fmaf(s, bf_lo(w0), a[0]); a[1] = fmaf(s, bf_hi(w0), a[1]);
  a[2] = fmaf(s, bf_lo(w1), a[2]); a[3] = fmaf(s, bf_hi(w1), a[3]);
  a[4] = fmaf(s, bf_lo(w2), a[4]); a[5] = fmaf(s, bf_hi(w2), a[5]);
  a[6] = fmaf(s, bf_lo(w3), a[6]); a[7] = fmaf(s, bf_hi(w3), a[7]);
}

enum { NB_TAB = 1, NB_WG0 = 2, NB_WG1 = 3, NB_HELP = 4, NB_INIT = 5, NB_PASS0 = 6, NB_GATHER = 7, NB_PARK = 8, NB_PROD = 9 };

__global__ void __launch_bounds__(512, 1)
adaln_block_kernel(const __grid_constant__ CUtensorMap tmWq, const __grid_constant__ CUtensorMap tmK,
                   const __grid_constant__ CUtensorMap tmV, const __grid_constant__ CUtensorMap tmWo,
                   const __grid_constant__ CUtensorMap tmW1, const __grid_constant__ CUtensorMap tmW2,
                   const __grid_constant__ CUtensorMap tmWm, const __grid_constant__ CUtensorMap tmX,
                   const Params p) {
  extern __shared__ __align__(1024) uint8_t smem_raw[];
  const uint32_t sb = smem_u32(smem_raw);
  const int tid = threadIdx.x, lane = tid & 31;
  const int warp = __shfl_sync(0xffffffffu, tid >> 5, 0);
  const int kp = blockIdx.x >> 1;
  const int bid = (kp < 4 ? kp : kp < 36 ? 4 + ((kp - 4) & 7) * 4 + ((kp - 4) >> 3) : 36 + ((kp - 36) % 7) * 4 + (kp - 36) / 7) * 2 +
                  (blockIdx.x & 1);
  const int j = bid & 7, rt = bid >> 3;
  const uint32_t bars = sb + SM_BAR;
  if (warp != 13) asm volatile("barrier.cluster.arrive.relaxed.aligned;" ::: "memory");

  if (warp >= 12) {
    asm volatile("setmaxnreg.dec.sync.aligned.u32 24;");
    if (warp == 13) {
      if (elect_one()) {
#pragma unroll
        for (int i = 0; i < 28; i++) mbar_init(sb + SM_WBAR + i * 8, i < 26 ? 1 : 4);
        mbar_init(sb + SM_SBAR, 8);
#pragma unroll
        for (int i = 0; i < 16; i++) mbar_init(sb + SM_DBAR + i * 8, 1);
        asm volatile("fence.mbarrier_init.release.cluster;" ::: "memory");
      }
      __syncwarp();
      asm volatile("barrier.cluster.arrive.relaxed.aligned;" ::: "memory");
      bar_arrive(NB_INIT, 224);
      mbar_wait(sb + SM_SBAR, 0);
      const uint32_t tag = *(volatile uint32_t*)(smem_raw + SM_BAR + BAR_TAG);
#pragma unroll 1
      for (int n = 0; n < 14; n++) {
        const uint32_t lb = sb + SM_WBAR + 192 + (n & 1) * 8;
        mbar_wait(lb + 16, ((n >> 1) & 1) ^ 1);
        wait_sent(&p.s->sent[(rt * 8 + j) * 8 + (lane & 6) + (n & 1)], tag, n >> 1);
        if (elect_one()) {
          mbar_expect(lb, n < 8 ? 8192 + 2048 : 8192);
#pragma unroll
          for (int m = 0; m < 4; m++)
            asm volatile("cp.async.bulk.shared::cluster.global.mbarrier::complete_tx::bytes [%0], [%1], 2048, [%2];"
                         ::"r"(sb + SM_PARK + ((n & 1) * 4 + m) * 4096 + 2048),
                           "l"(p.s->P + ((size_t)(rt * 8 + j) * 4 + m) * 1024 + (n & 7) * 128), "r"(lb) : "memory");
          if (n < 8) tma3d(sb + SM_PARK + SLOT + n * 4096, &tmX, lb, 0, rt * 128 + j * 16, n * 4);
        }
        __syncwarp();
      }
    } else if (warp == 14) {
      if (elect_one()) {
        asm volatile("prefetch.tensormap [%0];" ::"l"(&tmWq) : "memory");
        asm volatile("prefetch.tensormap [%0];" ::"l"(&tmK) : "memory");
        asm volatile("prefetch.tensormap [%0];" ::"l"(&tmV) : "memory");
        asm volatile("prefetch.tensormap [%0];" ::"l"(&tmWo) : "memory");
        asm volatile("prefetch.tensormap [%0];" ::"l"(&tmX) : "memory");
        asm volatile("prefetch.tensormap [%0];" ::"l"(&tmW1) : "memory");
        asm volatile("prefetch.tensormap [%0];" ::"l"(&tmW2) : "memory");
      }
      __syncwarp();
      bar_sync(NB_INIT, 224);
#pragma unroll 1
      for (int tt = 0; tt < NTILES; tt++) {
        mbar_wait(bars + (tt & 3) * 8, (tt >> 2) & 1);
        const bool single = tt < 4 || tt == 14 || tt == 47 || tt == 72 || tt == 79;
        const bool second = (tt > 14 && tt < 47) || tt > 72 ? !(tt & 1) : (tt & 1);
        if (single || second) bar_sync(NB_WG0, 288);
      }
    } else if (warp == 12) {
      if (elect_one()) {
        mbar_init(bars + BAR_SLAB, 1);
        asm volatile("fence.mbarrier_init.release.cluster;" ::: "memory");
        mbar_expect(bars + BAR_SLAB, 8192);
        tma3d(sb + SM_RING + 3 * SLOT, &tmWm, bars + BAR_SLAB, 0, 0, bid);
        tma3d(sb + SM_RING + 3 * SLOT + 4096, &tmWm, bars + BAR_SLAB, 0, 256, bid);
#pragma unroll
        for (int i = 0; i < 4; i++) { mbar_init(bars + i * 8, 1); mbar_init(bars + 32 + i * 8, 8); }
        mbar_init(bars + BAR_UV, 4);
        mbar_init(bars + BAR_X2, 1);
        mbar_init(bars + BAR_KMAX, 1);
        asm volatile("fence.mbarrier_init.release.cluster;" ::: "memory");
      }
      __syncwarp();
      bar_arrive(NB_INIT, 224);
      mbar_wait(bars + BAR_SLAB, 0);
      uint32_t s = 0, ph = 1;
#pragma unroll 1
      for (int tt = 0; tt < NTILES; tt++) {
        const CUtensorMap* tm;
        int c1, c2;
        uint32_t bytes = SLOT;
        if (tt < 15 || tt == 16) {
          const int u = min(tt, 15);
          tm = &tmWq; c1 = (u & 3) * 128; c2 = (j * 4 + (u >> 2)) * 2;
        } else if (tt < 48) {
          const bool isK = (tt & 1) && tt != 47;
          const int n = isK ? (tt - 15) >> 1 : (tt - 17) >> 1;
          tm = isK ? &tmK : &tmV; c1 = j * SK + (SK - WIN) + (n & 3) * 128; c2 = 0;
        } else if (tt < 64) {
          const int u = tt - 48;
          tm = &tmWo; c1 = j * 512 + (u & 1) * 256; c2 = (u >> 1) ^ (~j & 1);
        } else if (tt < 72) {
          tm = &tmW1; c1 = (tt - 64) * 64; c2 = (j * 7) >> 1;
        } else {
          tm = &tmW2; c1 = j * FSL; c2 = (tt - 72) ^ (~j & 1); bytes = 28672;
        }
        if (tt == EARLY_TILES) bar_sync(NB_PROD, 160);
        mbar_wait(bars + 32 + s * 8, ph);
        warp_tma3d(sb + SM_RING + s * SLOT, tm, bars + s * 8, bytes, c1, c2);
        if (++s == 4) { s = 0; ph ^= 1; }
      }
    }
  } else if (warp >= 8) {
    CK_(c0);
    asm volatile("setmaxnreg.dec.sync.aligned.u32 40;");
    const int t = tid - 256, hw = warp - 8, q = lane & 3;
    float* const red = (float*)(smem_raw + SM_RED);
    uint32_t tag;
    float a[8];
    {
      uint32_t cb[4];
#pragma unroll
      for (int i = 0; i < 4; i++) cb[i] = ldg16(p.c + t + 128 * i);
      asm volatile("ld.relaxed.gpu.global.u32 %0, [%1];" : "=r"(tag) : "l"(&p.s->epoch) : "memory");
      bar_sync(NB_INIT, 224);
      CK_(c2);
      tag += 1;
      float sc[4];
#pragma unroll
      for (int i = 0; i < 4; i++) sc[i] = silu_c(cb[i]);
#pragma unroll
      for (int k = 0; k < 8; k++) a[k] = 0.f;
      if (t == 0) *(uint32_t*)(smem_raw + SM_BAR + BAR_TAG) = tag;
      mbar_wait(bars + BAR_SLAB, 0);
      CK_(c3);
      bar_arrive(NB_GATHER, 384);
#pragma unroll
      for (int i = 0; i < 4; i++) {
        uint32_t w[4];
        lds128(sb + SM_RING + 3 * SLOT + (t + 128 * i) * 16, w);
        fma8(a, sc[i], w[0], w[1], w[2], w[3]);
      }
      float r = reduce8(a, lane);
      r += __shfl_xor_sync(0xffffffffu, r, 1);
      if (q == 0) red[hw * 8 + (lane >> 2)] = r;
      CK_(c4);
      bar_sync(NB_HELP, 128);
      CK_(c5);
      if (hw == 0) {
        const int cl = lane & 7;
        float v = round_bf16(red[cl] + red[8 + cl] + red[16 + cl] + red[24 + cl]);
        if (bid >= 64) v = 1.f + v;
        float vn = __shfl_down_sync(0xffffffffu, v, 1);
        uint32_t wd = pack_bf16(v, vn);
        uint32_t w0 = __shfl_sync(0xffffffffu, wd, (lane & 1) * 4);
        uint32_t w1 = __shfl_sync(0xffffffffu, wd, (lane & 1) * 4 + 2);
        if (lane < 16) st_pkt(&p.s->mod1[(lane >> 1) * 256 + bid * 2 + (lane & 1)], w0, w1, tag, 0);
      }
      uint32_t r0[4], r1[4];
      const uint4* src = &p.s->mod1[j * 256 + t];
      CK_(c6);
      spin_cycles(MOD1_DELAY);
      CK_(c7);
      int spins = 0;
      do {
        ld_pkt(src, r0);
        ld_pkt(src + 128, r1);
      } while ((r0[2] != tag || r1[2] != tag) && ++spins < SPIN_LIMIT);
      const int g = t >> 2, pp = q * 2;
      const uint32_t ad = sb + SM_TAB + (uint32_t)(g * 4 + (pp & 3)) * 16 + (pp >> 2) * 4;
      asm volatile("st.shared.b32 [%0], %1;" ::"r"(ad + 8), "r"(r0[0]) : "memory");
      asm volatile("st.shared.b32 [%0], %1;" ::"r"(ad + 24), "r"(r0[1]) : "memory");
      asm volatile("st.shared.b32 [%0], %1;" ::"r"(ad), "r"(r1[0]) : "memory");
      asm volatile("st.shared.b32 [%0], %1;" ::"r"(ad + 16), "r"(r1[1]) : "memory");
      bar_arrive(NB_TAB, 384);
      bar_arrive(NB_PROD, 160);
      CK_(c8);
      CKS(0, c0); CKS(2, c2); CKS(3, c3); CKS(4, c4); CKS(5, c5); CKS(6, c6); CKS(7, c7); CKS(8, c8);
    }
    bar_sync(NB_PASS0, 384);
    {
      const __nv_bfloat16* kp = p.k + ((size_t)j * SK + (SK - WIN) + rt * 32 + (t >> 2)) * 128 + q * 8;
      float ss = 0.f;
#pragma unroll
      for (int i = 0; i < 4; i++) {
        const uint4 w = ldg128(kp + i * 32);
        const uint32_t ww[4] = {w.x, w.y, w.z, w.w};
#pragma unroll
        for (int e = 0; e < 4; e++) ss = fmaf(bf_lo(ww[e]), bf_lo(ww[e]), fmaf(bf_hi(ww[e]), bf_hi(ww[e]), ss));
      }
      ss += __shfl_xor_sync(0xffffffffu, ss, 1);
      ss += __shfl_xor_sync(0xffffffffu, ss, 2);
      const uint32_t mx = __reduce_max_sync(0xffffffffu, __float_as_uint(ss) & 0x7fffffffu);
      if (lane < 2) st_pkt(&p.s->kmax[((j * 16 + rt) * 4 + hw) * 2 + lane], mx, 0, tag, 0);
    }
    {
#pragma unroll
      for (int k = 0; k < 8; k++) a[k] = 0.f;
#pragma unroll 1
      for (int b = 0; b < 4; b++) {
        const int row = b * 128 + (t >> 1);
        const __nv_bfloat16* wp = p.wmod + (size_t)row * 3072 + 1024 + bid * 16 + (t & 1) * 8;
        const uint4 w0 = ldg128(wp), w1 = ldg128(wp + 64 * 3072);
        const uint32_t c0 = ldg16(p.c + row), c1 = ldg16(p.c + row + 64);
        fma8(a, silu_c(c0), w0.x, w0.y, w0.z, w0.w);
        fma8(a, silu_c(c1), w1.x, w1.y, w1.z, w1.w);
      }
      const float r = reduce8(a, lane);
      if ((lane & 2) == 0) red[hw * 16 + (lane & 1) * 8 + (lane >> 2)] = r;
      bar_sync(NB_HELP, 128);
      if (hw == 0) {
        const int cl = lane & 15;
        float v = round_bf16(red[cl] + red[16 + cl] + red[32 + cl] + red[48 + cl]);
        if ((bid >> 5) == 2) v = 1.f + v;
        float vn = __shfl_down_sync(0xffffffffu, v, 1);
        uint32_t wd = pack_bf16(v, vn);
        uint32_t w0 = __shfl_sync(0xffffffffu, wd, q * 2);
        uint32_t w1 = __shfl_sync(0xffffffffu, wd, q * 2 + 8);
        const int vec = (0x2130 >> ((bid >> 5) * 4)) & 3;
        if (lane < 4) st_pkt(&p.s->mod2[((bid & 31) * 4 + vec) * 4 + lane], w0, w1, tag, 0);
      }
    }
    if (hw == 1) {
      uint32_t m0[4], m1[4];
      ld_mod(&p.s->kmax[(j * 64 + lane) * 2], tag, m0);
      ld_mod(&p.s->kmax[(j * 64 + 32 + lane) * 2], tag, m1);
      const uint32_t mx = __reduce_max_sync(0xffffffffu, max(m0[0], m1[0]));
      if (lane == 0) *(uint32_t*)(smem_raw + SM_BAR + BAR_KMAX + 8) = mx;
      __syncwarp();
      warp_arrive(bars + BAR_KMAX);
    }
    {
      const int isv = hw & 1, kh = hw >> 1;
      if (bid < 112) {
        const int kk = lane >> 1;
        uint32_t m0[4], m1[4];
        const uint4* mp = &p.s->mod2[(kh * 16 + (lane >> 2)) * 16 + (isv ? 12 : 4) + q];
        ld_mod(mp, tag, m0);
        ld_mod(mp + 128, tag, m1);
#pragma unroll
        for (int k = 0; k < 8; k++) a[k] = 0.f;
#pragma unroll 1
        for (int g0 = 0; g0 < 16; g0 += 2) {
          uint4 w[2];
#pragma unroll
          for (int i = 0; i < 2; i++) w[i] = ldg128(p.w1 + (size_t)((kh * 16 + g0 + i) * 16 + kk) * FF + bid * 16 + (lane & 1) * 8);
#pragma unroll
          for (int i = 0; i < 2; i++) {
            const int sl = ((g0 + i) & 7) * 4 + ((kk & 7) >> 1);
            const uint32_t wa = __shfl_sync(0xffffffffu, g0 < 8 ? m0[0] : m1[0], sl), wb = __shfl_sync(0xffffffffu, g0 < 8 ? m0[1] : m1[1], sl);
            const uint32_t mw = (kk & 8) ? wb : wa;
            fma8(a, (kk & 1) ? bf_hi(mw) : bf_lo(mw), w[i].x, w[i].y, w[i].z, w[i].w);
          }
        }
        float r = reduce8(a, lane);
        bar_sync(NB_HELP, 128);
        if (kh) red[isv * 32 + lane] = r;
        bar_sync(NB_HELP, 128);
        if (!kh) {
          r = (r + red[isv * 32 + lane]) * (isv ? 0.5f : 1.f);
          const float r1 = __shfl_down_sync(0xffffffffu, r, 4), r2 = __shfl_down_sync(0xffffffffu, r, 8),
                      r3 = __shfl_down_sync(0xffffffffu, r, 12);
          if ((lane & 14) == 0)
            st_pkt(&p.s->uv[isv * 448 + bid * 4 + (lane & 1) * 2 + (lane >> 4)], (__float_as_uint(r) & ~1u) | (tag & 1u),
                   __float_as_uint(r1), __float_as_uint(r2), __float_as_uint(r3));
        }
      }
      const int i = kh * 32 + lane;
      if (i < 56) {
        uint32_t m[4];
        int spins = 0;
        while (true) {
          ld_pkt(&p.s->uv[isv * 448 + j * 56 + i], m);
          if (!((m[0] ^ tag) & 1u) || ++spins >= SPIN_LIMIT) break;
          __nanosleep(200);
        }
        const int ip = (j & 1) ? (i < 8 ? i + 48 : i - 8) : i;
        const uint32_t ad = sb + SM_TAB + ip * 32 + isv * 8;
        asm volatile("st.shared.v2.b32 [%0], {%1,%2};" ::"r"(ad), "r"(m[0]), "r"(m[1]) : "memory");
        asm volatile("st.shared.v2.b32 [%0], {%1,%2};" ::"r"(ad + 16), "r"(m[2]), "r"(m[3]) : "memory");
      }
      __syncwarp();
      warp_arrive(bars + BAR_UV);
      if (t < 8) l2_prefetch((const char*)p.wo + (size_t)bid * 32768 + t * 4096, 4096);
      else if (t < 12) l2_prefetch((const char*)p.w2 + (size_t)bid * 14336 + (t - 8) * 3584, 3584);
      else if (t < 16) l2_prefetch((const char*)p.x + (size_t)(rt * 128 + j * 16) * 1024 + (t - 12) * 4096, 4096);
      TS(9);
    }
    {
      uint32_t mga[4], mg2[4], mgb[4];
      const uint4* mp = &p.s->mod2[((lane >> 2) * 4 + hw) * 16 + q];
      ld_mod(mp, tag, mga);
      ld_mod(mp + 4, tag, mg2);
      ld_mod(mp + 8, tag, mgb);
      if (lane >= 24) asm volatile("st.shared.v2.b32 [%0], {%1,%2};" ::"r"(sb + SM_TAB + 1792 + ((((lane >> 2) & 1) * 4 + hw) * 4 + q) * 8),
                                   "r"(mgb[0]), "r"(mgb[1]) : "memory");
      const uint32_t x2s = sb + SM_PARK + SLOT + hw * 512 + lane * 16;
      const uint4* const Pown = p.s->P + (size_t)(rt * 8 + j) * 4096 + hw * 32 + lane;
      float s0 = 0.f, s1 = 0.f, v0 = 0.f, v1 = 0.f;
      bar_sync(NB_PARK, 384);
      asm volatile("setmaxnreg.inc.sync.aligned.u32 56;");
#pragma unroll 1
      for (int n = 0; n < 14; n++) {
        const int cc = n & 7;
        const bool ex1 = n < 8;
        const uint32_t lb = sb + SM_WBAR + 192 + (n & 1) * 8;
        uint32_t r[4][4];
        float y[8];
        mbar_wait(lb, (n >> 1) & 1);
#pragma unroll
        for (int i = 0; i < 4; i++) lds128(sb + SM_PARK + ((n & 1) * 4 + i) * 4096 + 2048 + hw * 512 + lane * 16, r[i]);
        verify4_rt<16384>(Pown + cc * 128, r, ex1);
        warp_arrive(lb + 16);
#pragma unroll
        for (int i = 0; i < 4; i++) add_partial(y, r[i], ex1 ? 0u : 0x10000u, i == 0);
        const int src = cc * 4 + q;
        const uint32_t ma = __shfl_sync(0xffffffffu, ex1 ? mga[0] : mgb[0], src), mb = __shfl_sync(0xffffffffu, ex1 ? mga[1] : mgb[1], src);
        if (ex1) {
          uint32_t xr[4];
          asm volatile("ldmatrix.sync.aligned.m8n8.x4.shared.b16 {%0,%1,%2,%3}, [%4];"
                       : "=r"(xr[0]), "=r"(xr[1]), "=r"(xr[2]), "=r"(xr[3])
                       : "r"(sb + SM_PARK + SLOT + hw * 512 + cc * 4096 + (lane & 15) * 32 + (lane >> 4) * 16) : "memory");
          const uint32_t mc = __shfl_sync(0xffffffffu, mg2[0], src), md = __shfl_sync(0xffffffffu, mg2[1], src);
#pragma unroll
          for (int e = 0; e < 4; e++) {
            const uint32_t m = e < 2 ? ma : mb;
            const float u = fmaf(bf_lo(m), y[2 * e], bf_lo(xr[e])), v = fmaf(bf_hi(m), y[2 * e + 1], bf_hi(xr[e]));
            y[2 * e] = u; y[2 * e + 1] = v;
            if (e & 1) { s1 += u + v; v1 = fmaf(u, u, fmaf(v, v, v1)); }
            else { s0 += u + v; v0 = fmaf(u, u, fmaf(v, v, v0)); }
          }
          st_pkt(p.s->G + ((rt * 8 + j) * 32 + cc * 4 + hw) * 32 + lane, pack_tag<0>(y[0] * bf_lo(mc), y[1] * bf_hi(mc)),
                 pack_bf16(y[2] * bf_lo(mc), y[3] * bf_hi(mc)), pack_bf16(y[4] * bf_lo(md), y[5] * bf_hi(md)),
                 pack_bf16(y[6] * bf_lo(md), y[7] * bf_hi(md)));
          sts128(x2s + cc * 4096, __float_as_uint(y[0]), __float_as_uint(y[1]), __float_as_uint(y[2]), __float_as_uint(y[3]));
          sts128(x2s + cc * 4096 + 2048, __float_as_uint(y[4]), __float_as_uint(y[5]), __float_as_uint(y[6]), __float_as_uint(y[7]));
          if (n == 7) {
            const bool o1 = lane & 1, o2 = lane & 2;
            float c0 = (o1 ? v0 : s0) + __shfl_xor_sync(0xffffffffu, o1 ? s0 : v0, 1);
            float c1 = (o1 ? v1 : s1) + __shfl_xor_sync(0xffffffffu, o1 ? s1 : v1, 1);
            c0 = (o2 ? c1 : c0) + __shfl_xor_sync(0xffffffffu, o2 ? c0 : c1, 2);
            *(float*)(smem_raw + SM_PARK + 16384 + 2048 + hw * 512 + lane * 4) = c0;
            bar_sync(NB_HELP, 128);
            if (hw == 0) {
              const float* ps = (const float*)(smem_raw + SM_PARK + 16384 + 2048) + lane;
              const float m = (c0 + ps[128] + ps[256] + ps[384]) * (1.f / 512.f);
              const float mean = __shfl_sync(0xffffffffu, m, lane & ~1), sq = __shfl_sync(0xffffffffu, m, lane | 1);
              const float rs = 0.5f * rsqrtf(fmaxf(fmaf(-mean, mean, sq), 0.f) + 1e-5f), mr = -mean * rs;
              const float rs1 = __shfl_down_sync(0xffffffffu, rs, 2), mr1 = __shfl_down_sync(0xffffffffu, mr, 2);
              if (q == 0)
                st_pkt(&p.s->stat[(rt * 8 + j) * 8 + (lane >> 2)], (__float_as_uint(rs) & ~1u) | (tag & 1u), __float_as_uint(mr),
                       __float_as_uint(rs1), __float_as_uint(mr1));
              warp_arrive(bars + BAR_X2);
            }
          }
        } else {
          store_out(p.out, (uint32_t)(rt * 128 + 16 * j + (lane >> 2)) * 256 + (cc * 4 + hw) * 8 + q, x2s + cc * 4096, ma, mb, y);
        }
      }
    }
  } else {
    const int wg = warp >> 2;
    const int q = lane & 3, gq = lane >> 2;
    const Ring ring{((sb + SM_RING) & 0x3FFFF) >> 4, bars};
    const uint32_t xoff = (uint32_t)(rt * 128 + 16 * j + warp) * 256 + gq * 8 + q;
    const uint32_t ooff = ((uint32_t)(rt * 8 + j) * 32 + gq) * 32 + warp * 4 + q;
    const uint32_t wblk = sb + SM_PARK + warp * 4096;
    uint32_t wprv = wblk + lane * 16;
    asm volatile("" : "+r"(wprv));
    const uint32_t wbar = sb + SM_WBAR + warp * 24;
    const uint4* const Gw = p.s->G + (rt * 8 + warp) * 1024;

    {
      const uint32_t* xo = (const uint32_t*)p.x + xoff;
      uint32_t xr[4][4];
      CK_(d0);
#pragma unroll
      for (int c = 0; c < 4; c++) {
        xr[c][0] = ldg32(xo + c * 64);
        xr[c][1] = ldg32(xo + c * 64 + 8 * 256);
        xr[c][2] = ldg32(xo + c * 64 + 4);
        xr[c][3] = ldg32(xo + c * 64 + 4 + 8 * 256);
      }
      CK_(d1);
      fence_regs(xr);
      CK_(d2);
      float s0 = 0.f, s1 = 0.f, v0 = 0.f, v1 = 0.f;
#pragma unroll
      for (int c = 0; c < 4; c++) {
#pragma unroll
        for (int e = 0; e < 4; e++) {
          const float a = bf_lo(xr[c][e]), b = bf_hi(xr[c][e]);
          if (e & 1) { s1 += a + b; v1 = fmaf(a, a, fmaf(b, b, v1)); }
          else { s0 += a + b; v0 = fmaf(a, a, fmaf(b, b, v0)); }
        }
      }
#pragma unroll
      for (int o = 16; o > 0; o >>= 1) {
        s0 += __shfl_xor_sync(0xffffffffu, s0, o);
        s1 += __shfl_xor_sync(0xffffffffu, s1, o);
        v0 += __shfl_xor_sync(0xffffffffu, v0, o);
        v1 += __shfl_xor_sync(0xffffffffu, v1, o);
      }
      const float m0 = s0 * (1.f / 512.f), m1 = s1 * (1.f / 512.f);
      const float r0 = rsqrtf(fmaxf(fmaf(-m0, m0, v0 * (1.f / 512.f)), 0.f) + 1e-5f);
      const float r1 = rsqrtf(fmaxf(fmaf(-m1, m1, v1 * (1.f / 512.f)), 0.f) + 1e-5f);
#pragma unroll
      for (int c = 0; c < 4; c++) {
        st_pkt(p.s->G + ooff + c * 256,
               pack_tag<1>((bf_lo(xr[c][0]) - m0) * r0, (bf_hi(xr[c][0]) - m0) * r0),
               pack_bf16((bf_lo(xr[c][1]) - m1) * r1, (bf_hi(xr[c][1]) - m1) * r1),
               pack_bf16((bf_lo(xr[c][2]) - m0) * r0, (bf_hi(xr[c][2]) - m0) * r0),
               pack_bf16((bf_lo(xr[c][3]) - m1) * r1, (bf_hi(xr[c][3]) - m1) * r1));
      }
      CK_(d3);
      CKS(16, d0); CKS(17, d1); CKS(18, d2); CKS(19, d3);

    }
    asm volatile("setmaxnreg.inc.sync.aligned.u32 224;");
    auto my_turn = [&]() {
      asm volatile("{\n.reg .pred p;\nsetp.ne.u32 p, %0, 0;\n@p bar.sync 3, 256;\n@!p bar.sync 2, 288;\n}\n" ::"r"(wg) : "memory");
    };
    auto your_turn = [&]() {
      asm volatile("{\n.reg .pred p;\nsetp.ne.u32 p, %0, 0;\n@p bar.arrive 2, 288;\n@!p bar.arrive 3, 256;\n}\n" ::"r"(wg) : "memory");
    };
    if (wg == 1) your_turn();
    uint32_t qf[8][4], P[8][4];
    float O[64];
    const float cs = 0.08838834764831845f * 1.4426950408889634f;
    uint32_t qmax = 0;
    auto track_qnorm = [&](float scale) {
      float s0 = 0.f, s1 = 0.f;
#pragma unroll
      for (int i = 0; i < 16; i++) {
        s0 = fmaf(O[4 * i], O[4 * i], fmaf(O[4 * i + 1], O[4 * i + 1], s0));
        s1 = fmaf(O[4 * i + 2], O[4 * i + 2], fmaf(O[4 * i + 3], O[4 * i + 3], s1));
      }
      s0 += __shfl_xor_sync(0xffffffffu, s0, 1); s1 += __shfl_xor_sync(0xffffffffu, s1, 1);
      s0 += __shfl_xor_sync(0xffffffffu, s0, 2); s1 += __shfl_xor_sync(0xffffffffu, s1, 2);
      qmax = max(qmax, max(__float_as_uint(s0 * scale) & 0x7fffffffu, __float_as_uint(s1 * scale) & 0x7fffffffu));
      asm volatile("" : "+r"(qmax));
    };
    {
      uint32_t h[24][4];
      const uint4* Gin = Gw + lane;
      asm volatile("barrier.cluster.wait.acquire.aligned;" ::: "memory");
      bar_sync(NB_GATHER, 384);
      if (G_DELAY) spin_cycles(G_DELAY);
#pragma unroll
      for (int c = 0; c < 3; c++) warp_bulk_load(wblk + c * SLOT, Gw + c * 256, 4096, wbar + c * 8);
#pragma unroll
      for (int c = 0; c < 4; c++) {
        uint32_t (*const hc)[4] = c < 3 ? h + c * 8 : P;
        mbar_wait(wbar + (c % 3) * 8, c / 3);
#pragma unroll
        for (int i = 0; i < 8; i++) lds128(wprv + (c % 3) * SLOT + i * 512, hc[i]);
        verify8_tag1<512>(Gin + c * 256, hc);
        if (c == 0) {
          warp_bulk_load(wblk, Gw + 768, 4096, wbar);
          TS(1);
          bar_sync(NB_TAB, 384);
        }
#pragma unroll
        for (int i = 0; i < 8; i++) {
          uint32_t m[4];
          lds128(sb + SM_TAB + (uint32_t)((c * 8 + i) * 4 + q) * 16, m);
          uint32_t* hh = hc[i];
          hh[0] = hfma2_bf16(hh[0], m[0], m[2]);
          hh[1] = hfma2_bf16(hh[1], m[0], m[2]);
          hh[2] = hfma2_bf16(hh[2], m[1], m[3]);
          hh[3] = hfma2_bf16(hh[3], m[1], m[3]);
        }
        fence_frags<8>(hc);
        if (p.zero) bar_sync(NB_TAB, 384);
        const uint32_t b = ring.tile(c);
        if (c > 0) { wg_wait<0>(); ring.release(c - 1); }
        TRU(5);
        if (c == 0) TS(2);
        my_turn();
        wg_fence();
        static_for<0, 8>([&](auto K) { wgmma_rs_n128_tb1<LB_MN128 + K * 128, HI128>(O, hc[K], b, (c | K) != 0); });
        wg_commit();
        your_turn();
      }
      bar_arrive(NB_PASS0, 384);
      auto first_half = [&](int ps) {
        wg_wait<0>();
        ring.release(3);
        fence_regs(O);
        track_qnorm(cs * cs);
        fence_regs(O);
#pragma unroll
        for (int i = 0; i < 8; i++)
          sts128(wprv + (ps == 1 ? 2 : ps - 2) * SLOT + i * 512, pack_bf16(O[8 * i] * cs, O[8 * i + 1] * cs),
                 pack_bf16(O[8 * i + 2] * cs, O[8 * i + 3] * cs), pack_bf16(O[8 * i + 4] * cs, O[8 * i + 5] * cs),
                 pack_bf16(O[8 * i + 6] * cs, O[8 * i + 7] * cs));
        my_turn();
        wg_fence();
        static_for<0, 8>([&](auto K) { wgmma_rs_n128_tb1<LB_MN128 + K * 128, HI128>(O, h[K], ring.base16, K != 0); });
        wg_commit();
        static_for<0, 8>([&](auto K) { wgmma_rs_n128_tb1<LB_MN128 + 2048 + K * 128, HI128>(O, h[8 + K], ring.base16, 1); });
        wg_commit();
        your_turn();
        wg_wait<1>();
        TRU(6);
        ring.release(0);
        wg_wait<0>();
        ring.release(1);
        my_turn();
        wg_fence();
        static_for<0, 8>([&](auto K) { wgmma_rs_n128_tb1<LB_MN128 + 4096 + K * 128, HI128>(O, h[16 + K], ring.base16, 1); });
        wg_commit();
      };
#pragma unroll 1
      for (int ps = 1; ps < 3; ps++) {
        first_half(ps);
        static_for<0, 8>([&](auto K) { wgmma_rs_n128_tb1<LB_MN128 + 6144 + K * 128, HI128>(O, P[K], ring.base16, 1); });
        wg_commit();
        your_turn();
        wg_wait<1>();
        TRU(6);
        ring.release(2);
      }
      first_half(3);
      your_turn();
#pragma unroll
      for (int i = 0; i < 8; i++) lds128(wprv + 2 * SLOT + i * 512, qf[i]);
      wg_wait<0>();
      ring.release(2);
    }
    fence_regs(qf);
    TS(3);

    uint32_t o[24][4];
    {
      float S[64];
      float m0 = 0.f, m1 = 0.f;
      float l0 = 0.f, l1 = 0.f;
      float g0 = cs, g1 = cs;
      mbar_wait(bars + BAR_KMAX, 0);
      auto out_of_range = [&]() {
        const float kmax = *(volatile float*)(smem_raw + SM_BAR + BAR_KMAX + 8);
        return __any_sync(0xffffffffu, !(__uint_as_float(qmax) * kmax <= 9000.f));
      };
      bool online = out_of_range();
      auto exps = [&](int i0, int i1) {
#pragma unroll
        for (int i = i0; i < i1; i++) {
          S[4 * i] = ex2(S[4 * i]); S[4 * i + 1] = ex2(S[4 * i + 1]);
          S[4 * i + 2] = ex2(S[4 * i + 2]); S[4 * i + 3] = ex2(S[4 * i + 3]);
          l0 += S[4 * i]; l1 += S[4 * i + 2]; l0 += S[4 * i + 1]; l1 += S[4 * i + 3];
        }
      };
#pragma unroll 1
      for (int n = 0; n < 16; n++) {
        const uint32_t tk = 2 * n + 3, tv = 2 * n;
        const bool newhead = (n & 3) == 0;
        const uint32_t bk = ring.tile(tk & 3);
        const uint32_t bv = ring.tile(tv & 3);
        my_turn();
        wg_fence();
        static_for<0, 8>([&](auto K) { wgmma_rs_n128_tb0<LB_K128 + (K >> 2) * 1024 + (K & 3) * 2, HI128>(S, qf[K], bk, K != 0); });
        wg_commit();
        if ((n & 3) == 1) {
#pragma unroll
          for (int i = 0; i < 8; i++) {
#pragma unroll
            for (int e = 0; e < 8; e++) O[8 * i + e] *= (e & 2) ? g1 : g0;
            uint32_t w[4];
            pack8(w, O + 8 * i);
            sts128(wprv + (n > 1 ? (n >> 2) - 1 : 2) * SLOT + i * 512, w[0], w[1], w[2], w[3]);
          }
          fence_regs(O);
        }
        wg_fence();
        static_for<0, 8>([&](auto K) { wgmma_rs_n128_tb1<LB_MN128 + K * 128, HI128>(O, P[K], bv, K != 0 || (n & 3) != 1); });
        wg_commit();
        your_turn();
        wg_wait<1>();
        TRU(7);
        fence_regs(S);
        ring.release(tk & 3);
        float f0 = 1.f, f1 = 1.f;
        if (online) {
          float b0 = fmaxf(S[0], S[1]), b1 = fmaxf(S[2], S[3]);
#pragma unroll
          for (int i = 1; i < 16; i++) {
            b0 = fmaxf(b0, fmaxf(S[4 * i], S[4 * i + 1]));
            b1 = fmaxf(b1, fmaxf(S[4 * i + 2], S[4 * i + 3]));
          }
          b0 = fmaxf(b0, __shfl_xor_sync(0xffffffffu, b0, 1)); b1 = fmaxf(b1, __shfl_xor_sync(0xffffffffu, b1, 1));
          b0 = fmaxf(b0, __shfl_xor_sync(0xffffffffu, b0, 2)); b1 = fmaxf(b1, __shfl_xor_sync(0xffffffffu, b1, 2));
          if (!newhead) {
            b0 = fmaxf(b0, m0); b1 = fmaxf(b1, m1);
            f0 = ex2(m0 - b0); f1 = ex2(m1 - b1);
            l0 *= f0; l1 *= f1;
          }
          m0 = b0; m1 = b1;
#pragma unroll
          for (int i = 0; i < 16; i++) { S[4 * i] -= m0; S[4 * i + 1] -= m0; S[4 * i + 2] -= m1; S[4 * i + 3] -= m1; }
        }
        exps(0, PRE_EXP);
        if (p.zero) ring.release(0);
        wg_wait<0>();
        fence_regs(O);
        fence_regs(P);
        ring.release(tv & 3);
        exps(PRE_EXP, 16);
#pragma unroll
        for (int i = 0; i < 8; i++) pack8(P[i], S + 8 * i);
        if (online) {
#pragma unroll
          for (int i = 0; i < 16; i++) {
            O[4 * i] *= f0; O[4 * i + 1] *= f0; O[4 * i + 2] *= f1; O[4 * i + 3] *= f1;
          }
        }
        if ((n & 3) == 3) {
          if (n != 15) {
            fence_regs(qf);
#pragma unroll
            for (int i = 0; i < 8; i++) lds128(wprv + (n >> 2) * SLOT + i * 512, qf[i]);
          }
          l0 += __shfl_xor_sync(0xffffffffu, l0, 1); l1 += __shfl_xor_sync(0xffffffffu, l1, 1);
          l0 += __shfl_xor_sync(0xffffffffu, l0, 2); l1 += __shfl_xor_sync(0xffffffffu, l1, 2);
          g0 = rcp_hw(l0); g1 = rcp_hw(l1);
          l0 = 0.f; l1 = 0.f;
        } else if (n == 0) {
          track_qnorm(cs * cs);
          online = out_of_range();
        }
        fence_regs(P);
        fence_regs(O);
        TRU(8);
      }
      {
        const uint32_t bv = ring.tile(3);
        my_turn();
        wg_fence();
        static_for<0, 8>([&](auto K) { wgmma_rs_n128_tb1<LB_MN128 + K * 128, HI128>(O, P[K], bv, 1); });
        wg_commit();
        your_turn();
#pragma unroll
        for (int i = 0; i < O_EARLY; i++) lds128(wprv + (i >> 3) * SLOT + (i & 7) * 512, o[i]);
        const float f0 = g0, f1 = g1;
        wg_wait<0>();
        fence_regs(O);
        ring.release(3);
#pragma unroll
        for (int i = 0; i < 8; i++) {
          qf[i][0] = pack_bf16(O[8 * i] * f0, O[8 * i + 1] * f0); qf[i][1] = pack_bf16(O[8 * i + 2] * f1, O[8 * i + 3] * f1);
          qf[i][2] = pack_bf16(O[8 * i + 4] * f0, O[8 * i + 5] * f0); qf[i][3] = pack_bf16(O[8 * i + 6] * f1, O[8 * i + 7] * f1);
        }
      }
    }
    fence_regs(qf);
    TS(4);
    asm volatile("setmaxnreg.dec.sync.aligned.u32 216;");
    bar_arrive(NB_PARK, 384);

    uint4* const Pout = p.s->P + ((size_t)(rt * 8 + warp) * 4 + (j >> 1)) * 1024 + (j & 1) * 128 + lane;
    const uint32_t tag = *(volatile uint32_t*)(smem_raw + SM_BAR + BAR_TAG);
    const uint32_t rbar = sb + SM_DBAR + warp * 16;
    uint32_t peer_land, peer_bar;
    asm("mapa.shared::cluster.u32 %0, %1, %2;" : "=r"(peer_land) : "r"(wprv), "r"(~j & 1));
    asm("mapa.shared::cluster.u32 %0, %1, %2;" : "=r"(peer_bar) : "r"(rbar), "r"(~j & 1));
    auto arm_and_ack = [&](uint32_t dep) {
      asm volatile(
          "{\n.reg .pred p;\nelect.sync _|p, 0xffffffff;\n"
          "@p mbarrier.arrive.expect_tx.shared::cta.b64 _, [%0], 2048;\n"
          "@p mbarrier.arrive.shared::cluster.b64 _, [%1];\n}\n" ::"r"(rbar), "r"(peer_bar + 8 + (dep & p.zero)) : "memory");
    };
    auto send_chunk = [&](float (&acc)[32], int pair) {
      mbar_wait(rbar + 8, pair & 1);
#pragma unroll
      for (int i = 0; i < 4; i++)
        asm volatile("st.async.weak.shared::cluster.mbarrier::complete_tx::bytes.v4.b32 [%0], {%1,%2,%3,%4}, [%5];"
                     ::"r"(peer_land + i * 512), "r"(pack_trunc(acc[8 * i], acc[8 * i + 1])), "r"(pack_trunc(acc[8 * i + 2], acc[8 * i + 3])),
                       "r"(pack_trunc(acc[8 * i + 4], acc[8 * i + 5])), "r"(pack_trunc(acc[8 * i + 6], acc[8 * i + 7])), "r"(peer_bar)
                     : "memory");
    };
    uint32_t pk[4][4];
    auto recv_chunk = [&](int pair) {
      mbar_wait(rbar, pair & 1);
#pragma unroll
      for (int i = 0; i < 4; i++) lds128(wprv + i * 512, pk[i]);
      if (pair < 7) arm_and_ack(pk[3][0]);
    };
    auto keep_chunk = [&](float (&acc)[32], int pair) {
      const uint32_t t1 = pair < 4;
#pragma unroll
      for (int i = 0; i < 4; i++) {
#pragma unroll
        for (int e = 0; e < 4; e++)
          pk[i][e] = pack_trunc(acc[8 * i + 2 * e] + __uint_as_float(pk[i][e] * 65536u + 0x8000u),
                                acc[8 * i + 2 * e + 1] + __uint_as_float(pk[i][e]));
        st_pkt(Pout + (pair & 3) * 256 + i * 32, (pk[i][0] & ~1u) | t1, pk[i][1], pk[i][2], pk[i][3]);
      }
      if (lane == 0)
        asm volatile("st.relaxed.gpu.global.u32 [%0], %1;" ::"l"(&p.s->sent[(rt * 8 + warp) * 8 + j]), "r"(tag * 32 + pair + 1) : "memory");
    };
    const uint4* const Gin = Gw + lane;
    auto g_issue = [&](int u) { warp_bulk_load(wblk + 2 * SLOT, Gw + u * 256, 4096, wbar); };

#pragma unroll
    for (int i = O_EARLY; i < 24; i++) lds128(wprv + (i >> 3) * SLOT + (i & 7) * 512, o[i]);
    fence_regs(o);
    arm_and_ack(o[23][0]);
    warp_arrive(sb + SM_SBAR);
#pragma unroll 1
    for (int cc = 0; cc < 8; cc++) {
      float acc[32];
      const uint32_t s0 = (cc & 1) * 2, b = ring.tile(s0);
      my_turn();
      wg_fence();
      static_for<0, 16>([&](auto K) { wgmma_rs_n64_tb1<K * 128, HI128>(acc, o[K], b, K != 0); });
      wg_commit();
      static_for<0, 16>([&](auto K) { wgmma_rs_n64_tb1<2048 + K * 128, HI128>(acc, K < 8 ? o[16 + (K & 7)] : qf[K & 7], b, 1); });
      wg_commit();
      your_turn();
      wg_wait<1>();
      ring.release(s0);
      if (cc & 1) recv_chunk(cc >> 1);
      wg_wait<0>();
      TRU(4);
      ring.release(s0 + 1);
      fence_regs(acc);
      if (cc & 1) keep_chunk(acc, cc >> 1);
      else send_chunk(acc, cc >> 1);
      if (cc == 6) g_issue(0);
    }
    TS(5);

    uint32_t H[14][4];
    {
      float acca[96], accb[16];
      const uint4* const statp = &p.s->stat[(rt * 8 + warp) * 8];
#pragma unroll 1
      for (int u = 0; u < 4; u++) {
        uint32_t fa[8][4];
        const uint32_t s0 = (u & 1) * 2, b = ring.tile(s0);
        mbar_wait(wbar, u & 1);
#pragma unroll
        for (int i = 0; i < 8; i++) lds128(wprv + 2 * SLOT + i * 512, fa[i]);
        verify8_tag0<512>(Gin + u * 256, fa);
        if (u < 2) g_issue(u + 1);
        const uint32_t ba = b + (j & 1) * 512, bb = b + ((j & 1) ? 4 : 1536);
        my_turn();
        wg_fence();
        static_for<0, 4>([&](auto K) { wgmma_rs_n32_tb1<LB_W1 + K * 128, HI128>(accb, fa[K], bb, (u | K) != 0); });
        static_for<0, 4>([&](auto K) { wgmma_rs_n192_tb1<LB_W1 + K * 128, HI128>(acca, fa[K], ba, (u | K) != 0); });
        wg_commit();
        static_for<0, 4>([&](auto K) { wgmma_rs_n32_tb1<LB_W1 + 2048 + K * 128, HI128>(accb, fa[4 + K], bb, 1); });
        static_for<0, 4>([&](auto K) { wgmma_rs_n192_tb1<LB_W1 + 2048 + K * 128, HI128>(acca, fa[4 + K], ba, 1); });
        wg_commit();
        your_turn();
        wg_wait<1>();
        ring.release(s0);
        if (u == 2) g_issue(3);
        if (u == 3) warp_bulk_load(wblk + 2 * SLOT, statp, 128, wbar + 16);
        wg_wait<0>();
        TRU(4);
        ring.release(s0 + 1);
      }
      fence_regs(acca);
      fence_regs(accb);
      TS(9);
      mbar_wait(bars + BAR_UV, 0);
      uint32_t xr[4];
      mbar_wait(wbar + 16, 1);
      lds128(wblk + 2 * SLOT + gq * 16, xr);
      {
        int spins = 0;
        while (((xr[0] ^ tag) & 1u) && ++spins < SPIN_LIMIT) ld_pkt(statp + gq, xr);
      }
      const float ra0 = __uint_as_float(xr[0]), rb0 = __uint_as_float(xr[1]), ra1 = __uint_as_float(xr[2]),
                  rb1 = __uint_as_float(xr[3]);
#pragma unroll
      for (int i = 0; i < 28; i++) {
        uint32_t m[4];
        lds128(sb + SM_TAB + (i * 4 + q) * 16, m);
        const float u0 = __uint_as_float(m[0]), u1 = __uint_as_float(m[1]), w0 = __uint_as_float(m[2]), w1 = __uint_as_float(m[3]);
        const float* acc = i < 24 ? acca + 4 * i : accb + 4 * (i - 24);
        const float z0 = fmaf(acc[0], ra0, fmaf(u0, rb0, w0)), z1 = fmaf(acc[1], ra0, fmaf(u1, rb0, w1));
        const float z2 = fmaf(acc[2], ra1, fmaf(u0, rb1, w0)), z3 = fmaf(acc[3], ra1, fmaf(u1, rb1, w1));
        H[i >> 1][(i & 1) * 2] = pack_bf16(fmaf(z0, tanh_hw(z0), z0), fmaf(z1, tanh_hw(z1), z1));
        H[i >> 1][(i & 1) * 2 + 1] = pack_bf16(fmaf(z2, tanh_hw(z2), z2), fmaf(z3, tanh_hw(z3), z3));
      }
    }
    fence_regs(H);
    TS(10);
    const int go = 24 + warp;
    {
      float accs[32], acck[32];
      auto ffn2 = [&](float (&acc)[32], uint32_t b) {
        const uint32_t ba = b + (j & 1) * 256, bb = b - (j & 1) * 1536;
        static_for<0, 14>([&](auto K) { wgmma_rs_n64_tb1<K * 128, HI128>(acc, H[K], K < 12 ? ba : bb, K != 0); });
        wg_commit();
      };
      {
        const uint32_t b = ring.tile(0);
        my_turn();
        wg_fence();
        ffn2(accs, b);
        your_turn();
        wg_wait<0>();
        TRU(4);
        ring.release(0);
        fence_regs(accs);
        send_chunk(accs, 4);
      }
#pragma unroll 1
      for (int pc = 0; pc < 3; pc++) {
        const uint32_t tk = 2 * pc + 1, ts = tk + 1;
        const uint32_t bk = ring.tile(tk & 3), bs = ring.tile(ts & 3);
        my_turn();
        wg_fence();
        ffn2(acck, bk);
        ffn2(accs, bs);
        your_turn();
        wg_wait<1>();
        ring.release(tk & 3);
        recv_chunk(4 + pc);
        fence_regs(acck);
        keep_chunk(acck, 4 + pc);
        wg_wait<0>();
        TRU(4);
        ring.release(ts & 3);
        fence_regs(accs);
        send_chunk(accs, 5 + pc);
      }
      const uint32_t b = ring.tile(3);
      my_turn();
      wg_fence();
      ffn2(acck, b);
      if (wg == 0) your_turn();
      recv_chunk(7);
      wg_wait<0>();
      fence_regs(acck);
      keep_chunk(acck, 7);
    }
    TS(11);
    {
      const uint4* const Pown = p.s->P + (size_t)(rt * 8 + j) * 4096 + go * 32 + lane;
      uint32_t r[4][4];
      float y[8];
      mbar_wait(bars + BAR_X2, 0);
      issue_pkts<0, 4>(Pown, 1024, r);
      verify4_rt<16384>(Pown, r, 0);
      TS(13);
#pragma unroll
      for (int s = 0; s < 4; s++) add_partial(y, r[s], 0x10000u, s == 0);
      const uint32_t gt = sb + SM_TAB + 1792 + ((go - 24) * 4 + q) * 8;
      store_out(p.out, (uint32_t)(rt * 128 + 16 * j + gq) * 256 + go * 8 + q, sb + SM_PARK + SLOT + (go >> 2) * 4096 + (go & 3) * 512 + lane * 16,
                lds32(gt), lds32(gt + 4), y);
    }
    TS(12);
    if (bid == 0 && tid == 0) asm volatile("st.relaxed.gpu.global.u32 [%0], %1;" ::"l"(&p.s->epoch), "r"(tag) : "memory");
  }
}

typedef CUresult (*EncodeFn)(CUtensorMap*, CUtensorMapDataType, cuuint32_t, void*, const cuuint64_t*, const cuuint64_t*,
                             const cuuint32_t*, const cuuint32_t*, CUtensorMapInterleave, CUtensorMapSwizzle,
                             CUtensorMapL2promotion, CUtensorMapFloatOOBfill);

static void make_map(EncodeFn fn, CUtensorMap* tm, const void* ptr, int inner, int rows, int cols, int box_rows, int box_outer,
                     CUtensorMapSwizzle swz) {
  cuuint64_t gd[3] = {(cuuint64_t)inner, (cuuint64_t)rows, (cuuint64_t)(cols / inner)};
  cuuint64_t gs[2] = {(cuuint64_t)cols * 2, (cuuint64_t)inner * 2};
  cuuint32_t bx[3] = {(cuuint32_t)inner, (cuuint32_t)box_rows, (cuuint32_t)box_outer};
  cuuint32_t es[3] = {1, 1, 1};
  fn(tm, CU_TENSOR_MAP_DATA_TYPE_BFLOAT16, 3, const_cast<void*>(ptr), gd, gs, bx, es, CU_TENSOR_MAP_INTERLEAVE_NONE, swz,
     CU_TENSOR_MAP_L2_PROMOTION_L2_128B, CU_TENSOR_MAP_FLOAT_OOB_FILL_NONE);
}

extern "C" void kernel_launch(void* const* d_in, const int* in_sizes, int n_in, void* d_out, int out_size) {
  (void)in_sizes; (void)n_in; (void)out_size;
  void* fnp = nullptr;
  cudaDriverEntryPointQueryResult qr;
  cudaGetDriverEntryPoint("cuTensorMapEncodeTiled", &fnp, cudaEnableDefault, &qr);
  EncodeFn fn = (EncodeFn)fnp;
  CUtensorMap tmWq, tmK, tmV, tmWo, tmW1, tmW2, tmWm, tmX;
  make_map(fn, &tmWq, d_in[3], 64, 512, 4096, 128, 2, CU_TENSOR_MAP_SWIZZLE_128B);
  make_map(fn, &tmK, d_in[1], 64, 8 * SK, 128, 128, 2, CU_TENSOR_MAP_SWIZZLE_128B);
  make_map(fn, &tmV, d_in[2], 64, 8 * SK, 128, 128, 2, CU_TENSOR_MAP_SWIZZLE_128B);
  make_map(fn, &tmWo, d_in[4], 64, 4096, 512, 256, 1, CU_TENSOR_MAP_SWIZZLE_128B);
  make_map(fn, &tmW1, d_in[6], 64, 512, FF, 64, 4, CU_TENSOR_MAP_SWIZZLE_128B);
  make_map(fn, &tmW2, d_in[7], 64, FF, 512, 224, 1, CU_TENSOR_MAP_SWIZZLE_128B);
  make_map(fn, &tmWm, d_in[9], 8, 512, 3072, 256, 1, CU_TENSOR_MAP_SWIZZLE_NONE);
  make_map(fn, &tmX, d_in[0], 16, 2048, 512, 16, 4, CU_TENSOR_MAP_SWIZZLE_NONE);
  Params p;
  p.x = (const __nv_bfloat16*)d_in[0];
  p.k = (const __nv_bfloat16*)d_in[1];
  p.c = (const __nv_bfloat16*)d_in[8];
  p.wmod = (const __nv_bfloat16*)d_in[9];
  p.wo = (const __nv_bfloat16*)d_in[4];
  p.w1 = (const __nv_bfloat16*)d_in[6];
  p.w2 = (const __nv_bfloat16*)d_in[7];
  p.out = (__nv_bfloat16*)d_out;
  p.zero = 0;
  cudaGetSymbolAddress((void**)&p.s, g_scratch);
  cudaFuncSetAttribute(adaln_block_kernel, cudaFuncAttributeMaxDynamicSharedMemorySize, SM_TOTAL);
  cudaLaunchConfig_t cfg = {};
  cfg.gridDim = 128; cfg.blockDim = 512; cfg.dynamicSmemBytes = SM_TOTAL; cfg.stream = cudaStreamPerThread;
  cudaLaunchAttribute at[1];
  at[0].id = cudaLaunchAttributeClusterDimension; at[0].val.clusterDim.x = 2; at[0].val.clusterDim.y = 1; at[0].val.clusterDim.z = 1;
  cfg.attrs = at; cfg.numAttrs = 1;
  cudaLaunchKernelEx(&cfg, adaln_block_kernel, tmWq, tmK, tmV, tmWo, tmW1, tmW2, tmWm, tmX, p);
}
```
